```python
import torch

def _softmax(x, axis=-1):
    return torch.softmax(x, dim=axis)
def _gelu(x):
    return torch.nn.functional.gelu(x, approximate="tanh")
def _silu(x):
    return torch.nn.functional.silu(x)
def _sigmoid(x):
    return torch.sigmoid(x)
def _layernorm(x, axis=-1, eps=1e-5):
    m = x.mean(dim=axis, keepdim=True)
    v = x.var(dim=axis, keepdim=True, unbiased=False)
    return (x - m) / torch.sqrt(v + eps)
def _scatter_add(tgt, idx, src, axis=0):
    return tgt.clone().index_add_(axis, idx, src)
def _segment_sum(src, seg, n):
    out = torch.zeros((n,) + src.shape[1:], dtype=src.dtype)
    return out.index_add_(0, seg, src)
def _pad(x, pw):
    flat = tuple(v for pair in reversed(pw) for v in pair)
    return torch.nn.functional.pad(x, flat)

kernel_name = 'sequential_preLN__softmax_full_mha__geglu_ffn__prompt'

def setup_inputs():

    _w = (lambda a: (lambda t: t.to(torch.bfloat16) if t.is_floating_point() else t)(torch.as_tensor(a)))
    def _A_setup():
        B, S, D = 1, 2048, 512
        return {
            "x": _w((lambda *s: torch.randn(*s, dtype=torch.bfloat16) * 0.05)(B, S, D)),
            "wqkv": _w((lambda *s: torch.randn(*s, dtype=torch.bfloat16) * 0.05)(D, 3 * D)),
            "wo": _w((lambda *s: torch.randn(*s, dtype=torch.bfloat16) * 0.05)(D, D)),
        }
    _A_in = _A_setup()

    def _B_setup():
        B, S, D, F = 1, 2048, 512, 1792
        return {
            "x": _w((lambda *s: torch.randn(*s, dtype=torch.bfloat16) * 0.05)(B, S, D)),
            "w_gate": _w((lambda *s: torch.randn(*s, dtype=torch.bfloat16) * 0.05)(D, F)),
            "w_up": _w((lambda *s: torch.randn(*s, dtype=torch.bfloat16) * 0.05)(D, F)),
            "w_down": _w((lambda *s: torch.randn(*s, dtype=torch.bfloat16) * 0.05)(F, D)),
        }
    _B_in = _B_setup()

    return {
        "A_x": _A_in["x"],
        "A_wqkv": _A_in["wqkv"],
        "A_wo": _A_in["wo"],
        "B_x": _B_in["x"],
        "B_w_gate": _B_in["w_gate"],
        "B_w_up": _B_in["w_up"],
        "B_w_down": _B_in["w_down"],
    }

def reference(A_x, A_wqkv, A_wo, B_x, B_w_gate, B_w_up, B_w_down):
    def _A_ref(x, wqkv, wo):
        B, S, D = x.shape
        H = 32; Dh = D // H
        qkv = (lambda x, *d: x.permute(*d))((x @ wqkv).reshape(B, S, 3, H, Dh), 2, 0, 3, 1, 4)
        q, k, v = qkv[0], qkv[1], qkv[2]
        scale = Dh ** -0.5
        scores = torch.einsum("bhqd,bhkd->bhqk", q, k) * scale
        p = _softmax(scores, axis=-1)
        o = torch.einsum("bhqk,bhkd->bhqd", p, v)
        return (lambda x, *d: x.permute(*d))(o, 0, 2, 1, 3).reshape(B, S, D) @ wo

    def _B_ref(x, w_gate, w_up, w_down):
        return (_gelu(x @ w_gate) * (x @ w_up)) @ w_down

    x = A_x
    h = x + _A_ref(_layernorm(x, axis=-1), A_wqkv, A_wo)
    h2 = h + _B_ref(_layernorm(h, axis=-1), B_w_gate, B_w_up, B_w_down)
    return h2
```

```cpp
#include <cuda_runtime.h>
#include <cuda_bf16.h>
#include <cuda.h>
#include <stdint.h>

namespace {

constexpr int S_LEN = 2048, DM = 512, NH = 32, FF = 1792;

__device__ __align__(1024) __nv_bfloat16 g_qkv[3 * NH * S_LEN * 16];
__device__ __align__(1024) __nv_bfloat16 g_ao[S_LEN * DM];
__device__ __align__(1024) __nv_bfloat16 g_h[S_LEN * DM];
__device__ __align__(1024) __nv_bfloat16 g_g[S_LEN * FF];
__device__ float2 g_rowstat1[S_LEN];
__device__ float g_cs1_part[16 * 1536];
__device__ unsigned int g_cnt[32];
__device__ float g_nrm[3 * NH * 128];
__device__ float2 g_hstat[S_LEN * 8];
__device__ float g_cs2[2 * FF];

__device__ __forceinline__ uint32_t smem_u32(const void* p) { return (uint32_t)__cvta_generic_to_shared(p); }
__device__ __forceinline__ void mbar_init(uint32_t a, int c) { asm volatile("mbarrier.init.shared.b64 [%0], %1;" :: "r"(a), "r"(c)); }
__device__ __forceinline__ void mbar_expect(uint32_t a, int bytes) { asm volatile("mbarrier.arrive.expect_tx.shared.b64 _, [%0], %1;" :: "r"(a), "r"(bytes) : "memory"); }
__device__ __forceinline__ void mbar_arrive(uint32_t a) { asm volatile("mbarrier.arrive.shared.b64 _, [%0];" :: "r"(a) : "memory"); }
__device__ __forceinline__ void mbar_wait(uint32_t a, int parity) {
    uint32_t done;
    int it = 0;
    do {
        asm volatile("{\n.reg .pred p;\nmbarrier.try_wait.parity.shared.b64 p, [%1], %2;\nselp.u32 %0, 1, 0, p;\n}"
                     : "=r"(done) : "r"(a), "r"(parity) : "memory");
        if (++it > (1 << 24)) __trap();
    } while (!done);
}
__device__ __forceinline__ void bulk_g2s(uint32_t dst, const void* src, int bytes, uint32_t bar) {
    asm volatile("cp.async.bulk.shared::cluster.global.mbarrier::complete_tx::bytes [%0], [%1], %2, [%3];"
                 :: "r"(dst), "l"(src), "r"(bytes), "r"(bar) : "memory");
}
__device__ __forceinline__ void tma2d(uint32_t dst, const CUtensorMap* m, int c0, int c1, uint32_t bar) {
    asm volatile("cp.async.bulk.tensor.2d.shared::cluster.global.mbarrier::complete_tx::bytes [%0], [%1, {%3, %4}], [%2];"
                 :: "r"(dst), "l"(m), "r"(bar), "r"(c0), "r"(c1) : "memory");
}
__device__ __forceinline__ void tma3d(uint32_t dst, const CUtensorMap* m, int c0, int c1, int c2, uint32_t bar) {
    asm volatile("cp.async.bulk.tensor.3d.shared::cluster.global.mbarrier::complete_tx::bytes [%0], [%1, {%3, %4, %5}], [%2];"
                 :: "r"(dst), "l"(m), "r"(bar), "r"(c0), "r"(c1), "r"(c2) : "memory");
}
__device__ __forceinline__ void prefetch_tmap(const CUtensorMap* m) { asm volatile("prefetch.tensormap [%0];" :: "l"(m) : "memory"); }
__device__ __forceinline__ void pdl_wait() { asm volatile("griddepcontrol.wait;" ::: "memory"); }
__device__ __forceinline__ void pdl_launch() { asm volatile("griddepcontrol.launch_dependents;" ::: "memory"); }
__device__ __forceinline__ void fence_barrier_init() { asm volatile("fence.mbarrier_init.release.cluster;" ::: "memory"); }
__device__ __forceinline__ void fence_proxy_async() { asm volatile("fence.proxy.async.shared::cta;" ::: "memory"); }
__device__ __forceinline__ uint64_t make_desc(uint32_t saddr, uint32_t lbo, uint32_t sbo, uint32_t swz) {
    return (uint64_t)((saddr & 0x3FFFF) >> 4) | ((uint64_t)((lbo & 0x3FFFF) >> 4) << 16) |
           ((uint64_t)((sbo & 0x3FFFF) >> 4) << 32) | ((uint64_t)swz << 62);
}
#define WG_FENCE() asm volatile("wgmma.fence.sync.aligned;" ::: "memory")
#define WG_COMMIT() asm volatile("wgmma.commit_group.sync.aligned;" ::: "memory")
template <int N> __device__ __forceinline__ void wg_wait() { asm volatile("wgmma.wait_group.sync.aligned %0;" :: "n"(N) : "memory"); }
template <int N> __device__ __forceinline__ void fence_regs(float (&d)[N]) {
#pragma unroll
    for (int i = 0; i < N; i++) asm volatile("" : "+f"(d[i]) :: "memory");
}
__device__ __forceinline__ float ex2f(float x) { float y; asm("ex2.approx.ftz.f32 %0, %1;" : "=f"(y) : "f"(x)); return y; }
__device__ __forceinline__ float tanh_fast(float x) { float y; asm("tanh.approx.f32 %0, %1;" : "=f"(y) : "f"(x)); return y; }
__device__ __forceinline__ uint32_t pack_bf16(float lo, float hi) { uint32_t r; asm("cvt.rn.bf16x2.f32 %0, %1, %2;" : "=r"(r) : "f"(hi), "f"(lo)); return r; }
__device__ __forceinline__ float bf_lo(uint32_t u) { return __uint_as_float(u << 16); }
__device__ __forceinline__ float bf_hi(uint32_t u) { return __uint_as_float(u & 0xFFFF0000u); }
__device__ __forceinline__ uint32_t hfma2(uint32_t a, uint32_t b, uint32_t c) { uint32_t r; asm("fma.rn.f16x2 %0, %1, %2, %3;" : "=r"(r) : "r"(a), "r"(b), "r"(c)); return r; }
__device__ __forceinline__ uint32_t hmul2(uint32_t a, uint32_t b) { uint32_t r; asm("mul.rn.f16x2 %0, %1, %2;" : "=r"(r) : "r"(a), "r"(b)); return r; }
__device__ __forceinline__ unsigned int ld_acquire(const unsigned int* p) { unsigned int v; asm volatile("ld.acquire.gpu.u32 %0, [%1];" : "=r"(v) : "l"(p) : "memory"); return v; }
__device__ __forceinline__ void red_release(unsigned int* p) { asm volatile("red.release.gpu.global.add.u32 [%0], 1;" :: "l"(p) : "memory"); }
__device__ __forceinline__ float warp_sum(float v) {
#pragma unroll
    for (int o = 16; o; o >>= 1) v += __shfl_xor_sync(0xffffffffu, v, o);
    return v;
}
__device__ __forceinline__ float warp_max(float v) {
#pragma unroll
    for (int o = 16; o; o >>= 1) v = fmaxf(v, __shfl_xor_sync(0xffffffffu, v, o));
    return v;
}

__device__ __forceinline__ void wgmma_ss_n64(float (&d)[32], uint64_t adesc, uint64_t bdesc, int scale_d) {
    asm volatile("{\n.reg .pred p;\nsetp.ne.b32 p, %34, 0;\n"
      "wgmma.mma_async.sync.aligned.m64n64k16.f32.bf16.bf16 {%0,%1,%2,%3,%4,%5,%6,%7,%8,%9,%10,%11,%12,%13,%14,%15,%16,%17,%18,%19,%20,%21,%22,%23,%24,%25,%26,%27,%28,%29,%30,%31}, %32, %33, p, 1, 1, 0, 1;\n}"
      : "+f"(d[0]), "+f"(d[1]), "+f"(d[2]), "+f"(d[3]), "+f"(d[4]), "+f"(d[5]), "+f"(d[6]), "+f"(d[7]), "+f"(d[8]), "+f"(d[9]), "+f"(d[10]), "+f"(d[11]), "+f"(d[12]), "+f"(d[13]), "+f"(d[14]), "+f"(d[15]), "+f"(d[16]), "+f"(d[17]), "+f"(d[18]), "+f"(d[19]), "+f"(d[20]), "+f"(d[21]), "+f"(d[22]), "+f"(d[23]), "+f"(d[24]), "+f"(d[25]), "+f"(d[26]), "+f"(d[27]), "+f"(d[28]), "+f"(d[29]), "+f"(d[30]), "+f"(d[31])
      : "l"(adesc), "l"(bdesc), "r"(scale_d));
}
__device__ __forceinline__ void wgmma_ss_n96(float (&d)[48], uint64_t adesc, uint64_t bdesc, int scale_d) {
    asm volatile("{\n.reg .pred p;\nsetp.ne.b32 p, %50, 0;\n"
      "wgmma.mma_async.sync.aligned.m64n96k16.f32.bf16.bf16 {%0,%1,%2,%3,%4,%5,%6,%7,%8,%9,%10,%11,%12,%13,%14,%15,%16,%17,%18,%19,%20,%21,%22,%23,%24,%25,%26,%27,%28,%29,%30,%31,%32,%33,%34,%35,%36,%37,%38,%39,%40,%41,%42,%43,%44,%45,%46,%47}, %48, %49, p, 1, 1, 0, 1;\n}"
      : "+f"(d[0]), "+f"(d[1]), "+f"(d[2]), "+f"(d[3]), "+f"(d[4]), "+f"(d[5]), "+f"(d[6]), "+f"(d[7]), "+f"(d[8]), "+f"(d[9]), "+f"(d[10]), "+f"(d[11]), "+f"(d[12]), "+f"(d[13]), "+f"(d[14]), "+f"(d[15]), "+f"(d[16]), "+f"(d[17]), "+f"(d[18]), "+f"(d[19]), "+f"(d[20]), "+f"(d[21]), "+f"(d[22]), "+f"(d[23]), "+f"(d[24]), "+f"(d[25]), "+f"(d[26]), "+f"(d[27]), "+f"(d[28]), "+f"(d[29]), "+f"(d[30]), "+f"(d[31]), "+f"(d[32]), "+f"(d[33]), "+f"(d[34]), "+f"(d[35]), "+f"(d[36]), "+f"(d[37]), "+f"(d[38]), "+f"(d[39]), "+f"(d[40]), "+f"(d[41]), "+f"(d[42]), "+f"(d[43]), "+f"(d[44]), "+f"(d[45]), "+f"(d[46]), "+f"(d[47])
      : "l"(adesc), "l"(bdesc), "r"(scale_d));
}
__device__ __forceinline__ void wgmma_ss_n128(float (&d)[64], uint64_t adesc, uint64_t bdesc, int scale_d) {
    asm volatile("{\n.reg .pred p;\nsetp.ne.b32 p, %66, 0;\n"
      "wgmma.mma_async.sync.aligned.m64n128k16.f32.bf16.bf16 {%0,%1,%2,%3,%4,%5,%6,%7,%8,%9,%10,%11,%12,%13,%14,%15,%16,%17,%18,%19,%20,%21,%22,%23,%24,%25,%26,%27,%28,%29,%30,%31,%32,%33,%34,%35,%36,%37,%38,%39,%40,%41,%42,%43,%44,%45,%46,%47,%48,%49,%50,%51,%52,%53,%54,%55,%56,%57,%58,%59,%60,%61,%62,%63}, %64, %65, p, 1, 1, 0, 1;\n}"
      : "+f"(d[0]), "+f"(d[1]), "+f"(d[2]), "+f"(d[3]), "+f"(d[4]), "+f"(d[5]), "+f"(d[6]), "+f"(d[7]), "+f"(d[8]), "+f"(d[9]), "+f"(d[10]), "+f"(d[11]), "+f"(d[12]), "+f"(d[13]), "+f"(d[14]), "+f"(d[15]), "+f"(d[16]), "+f"(d[17]), "+f"(d[18]), "+f"(d[19]), "+f"(d[20]), "+f"(d[21]), "+f"(d[22]), "+f"(d[23]), "+f"(d[24]), "+f"(d[25]), "+f"(d[26]), "+f"(d[27]), "+f"(d[28]), "+f"(d[29]), "+f"(d[30]), "+f"(d[31]), "+f"(d[32]), "+f"(d[33]), "+f"(d[34]), "+f"(d[35]), "+f"(d[36]), "+f"(d[37]), "+f"(d[38]), "+f"(d[39]), "+f"(d[40]), "+f"(d[41]), "+f"(d[42]), "+f"(d[43]), "+f"(d[44]), "+f"(d[45]), "+f"(d[46]), "+f"(d[47]), "+f"(d[48]), "+f"(d[49]), "+f"(d[50]), "+f"(d[51]), "+f"(d[52]), "+f"(d[53]), "+f"(d[54]), "+f"(d[55]), "+f"(d[56]), "+f"(d[57]), "+f"(d[58]), "+f"(d[59]), "+f"(d[60]), "+f"(d[61]), "+f"(d[62]), "+f"(d[63])
      : "l"(adesc), "l"(bdesc), "r"(scale_d));
}
__device__ __forceinline__ void wgmma_ss_n192(float (&d)[96], uint64_t adesc, uint64_t bdesc, int scale_d) {
    asm volatile("{\n.reg .pred p;\nsetp.ne.b32 p, %98, 0;\n"
      "wgmma.mma_async.sync.aligned.m64n192k16.f32.bf16.bf16 {%0,%1,%2,%3,%4,%5,%6,%7,%8,%9,%10,%11,%12,%13,%14,%15,%16,%17,%18,%19,%20,%21,%22,%23,%24,%25,%26,%27,%28,%29,%30,%31,%32,%33,%34,%35,%36,%37,%38,%39,%40,%41,%42,%43,%44,%45,%46,%47,%48,%49,%50,%51,%52,%53,%54,%55,%56,%57,%58,%59,%60,%61,%62,%63,%64,%65,%66,%67,%68,%69,%70,%71,%72,%73,%74,%75,%76,%77,%78,%79,%80,%81,%82,%83,%84,%85,%86,%87,%88,%89,%90,%91,%92,%93,%94,%95}, %96, %97, p, 1, 1, 0, 1;\n}"
      : "+f"(d[0]), "+f"(d[1]), "+f"(d[2]), "+f"(d[3]), "+f"(d[4]), "+f"(d[5]), "+f"(d[6]), "+f"(d[7]), "+f"(d[8]), "+f"(d[9]), "+f"(d[10]), "+f"(d[11]), "+f"(d[12]), "+f"(d[13]), "+f"(d[14]), "+f"(d[15]), "+f"(d[16]), "+f"(d[17]), "+f"(d[18]), "+f"(d[19]), "+f"(d[20]), "+f"(d[21]), "+f"(d[22]), "+f"(d[23]), "+f"(d[24]), "+f"(d[25]), "+f"(d[26]), "+f"(d[27]), "+f"(d[28]), "+f"(d[29]), "+f"(d[30]), "+f"(d[31]), "+f"(d[32]), "+f"(d[33]), "+f"(d[34]), "+f"(d[35]), "+f"(d[36]), "+f"(d[37]), "+f"(d[38]), "+f"(d[39]), "+f"(d[40]), "+f"(d[41]), "+f"(d[42]), "+f"(d[43]), "+f"(d[44]), "+f"(d[45]), "+f"(d[46]), "+f"(d[47]), "+f"(d[48]), "+f"(d[49]), "+f"(d[50]), "+f"(d[51]), "+f"(d[52]), "+f"(d[53]), "+f"(d[54]), "+f"(d[55]), "+f"(d[56]), "+f"(d[57]), "+f"(d[58]), "+f"(d[59]), "+f"(d[60]), "+f"(d[61]), "+f"(d[62]), "+f"(d[63]), "+f"(d[64]), "+f"(d[65]), "+f"(d[66]), "+f"(d[67]), "+f"(d[68]), "+f"(d[69]), "+f"(d[70]), "+f"(d[71]), "+f"(d[72]), "+f"(d[73]), "+f"(d[74]), "+f"(d[75]), "+f"(d[76]), "+f"(d[77]), "+f"(d[78]), "+f"(d[79]), "+f"(d[80]), "+f"(d[81]), "+f"(d[82]), "+f"(d[83]), "+f"(d[84]), "+f"(d[85]), "+f"(d[86]), "+f"(d[87]), "+f"(d[88]), "+f"(d[89]), "+f"(d[90]), "+f"(d[91]), "+f"(d[92]), "+f"(d[93]), "+f"(d[94]), "+f"(d[95])
      : "l"(adesc), "l"(bdesc), "r"(scale_d));
}
__device__ __forceinline__ void qk_wgmma_n64(float (&d)[32], const uint32_t (&a)[4], uint64_t desc) {
    asm volatile("wgmma.mma_async.sync.aligned.m64n64k16.f32.bf16.bf16 {%0,%1,%2,%3,%4,%5,%6,%7,%8,%9,%10,%11,%12,%13,%14,%15,%16,%17,%18,%19,%20,%21,%22,%23,%24,%25,%26,%27,%28,%29,%30,%31}, {%32,%33,%34,%35}, %36, 0, 1, 1, 0;"
      : "=f"(d[0]), "=f"(d[1]), "=f"(d[2]), "=f"(d[3]), "=f"(d[4]), "=f"(d[5]), "=f"(d[6]), "=f"(d[7]), "=f"(d[8]), "=f"(d[9]), "=f"(d[10]), "=f"(d[11]), "=f"(d[12]), "=f"(d[13]), "=f"(d[14]), "=f"(d[15]), "=f"(d[16]), "=f"(d[17]), "=f"(d[18]), "=f"(d[19]), "=f"(d[20]), "=f"(d[21]), "=f"(d[22]), "=f"(d[23]), "=f"(d[24]), "=f"(d[25]), "=f"(d[26]), "=f"(d[27]), "=f"(d[28]), "=f"(d[29]), "=f"(d[30]), "=f"(d[31])
      : "r"(a[0]), "r"(a[1]), "r"(a[2]), "r"(a[3]), "l"(desc));
}

__device__ __forceinline__ void pv_wgmma(float (&d)[12], uint32_t a0, uint32_t a1, uint32_t a2, uint32_t a3, uint64_t desc) {
    asm volatile("wgmma.mma_async.sync.aligned.m64n24k16.f32.bf16.bf16 {%0,%1,%2,%3,%4,%5,%6,%7,%8,%9,%10,%11}, {%12,%13,%14,%15}, %16, 1, 1, 1, 1;"
      : "+f"(d[0]), "+f"(d[1]), "+f"(d[2]), "+f"(d[3]), "+f"(d[4]), "+f"(d[5]), "+f"(d[6]), "+f"(d[7]), "+f"(d[8]), "+f"(d[9]), "+f"(d[10]), "+f"(d[11])
      : "r"(a0), "r"(a1), "r"(a2), "r"(a3), "l"(desc));
}

__device__ __forceinline__ void tile_of(int bid, int& mb, int& nt) {
    int grp = bid >> 4, in = bid & 15;
    mb = (grp >> 1) * 4 + (in >> 2);
    nt = (grp & 1) * 4 + (in & 3);
}

constexpr int K1_STAGES = 5, K1_STAGE = 16384 + 24576;
constexpr int K1_BAR = K1_STAGES * K1_STAGE, K1_RS = K1_BAR + 128, K1_CS = K1_RS + 1024, K1_SMEM = K1_CS + 768;

__device__ __forceinline__ float2 row_stats_x(const __nv_bfloat16* x, int row, int lane) {
    const uint4* p = (const uint4*)(x + (size_t)row * DM);
    uint4 a = __ldg(p + lane), b = __ldg(p + 32 + lane);
    float v[16];
    v[0] = bf_lo(a.x); v[1] = bf_hi(a.x); v[2] = bf_lo(a.y); v[3] = bf_hi(a.y);
    v[4] = bf_lo(a.z); v[5] = bf_hi(a.z); v[6] = bf_lo(a.w); v[7] = bf_hi(a.w);
    v[8] = bf_lo(b.x); v[9] = bf_hi(b.x); v[10] = bf_lo(b.y); v[11] = bf_hi(b.y);
    v[12] = bf_lo(b.z); v[13] = bf_hi(b.z); v[14] = bf_lo(b.w); v[15] = bf_hi(b.w);
    float s = 0.f;
#pragma unroll
    for (int i = 0; i < 16; i++) s += v[i];
    float mean = warp_sum(s) * (1.0f / DM);
    float q = 0.f;
#pragma unroll
    for (int i = 0; i < 16; i++) { float d = v[i] - mean; q = fmaf(d, d, q); }
    float var = warp_sum(q) * (1.0f / DM);
    float rstd = rsqrtf(var + 1e-5f);
    return make_float2(rstd, -mean * rstd);
}
__device__ __forceinline__ void colsum8(const __nv_bfloat16* w, int ld, int col, int k0, int nk, float (&s)[8]) {
#pragma unroll
    for (int i = 0; i < 8; i++) s[i] = 0.f;
    for (int k = k0; k < k0 + nk; k += 8) {
        uint4 u[8];
#pragma unroll
        for (int i = 0; i < 8; i++) u[i] = __ldg((const uint4*)(w + (size_t)(k + i) * ld + col));
#pragma unroll
        for (int i = 0; i < 8; i++) {
            s[0] += bf_lo(u[i].x); s[1] += bf_hi(u[i].x); s[2] += bf_lo(u[i].y); s[3] += bf_hi(u[i].y);
            s[4] += bf_lo(u[i].z); s[5] += bf_hi(u[i].z); s[6] += bf_lo(u[i].w); s[7] += bf_hi(u[i].w);
        }
    }
}
__device__ __forceinline__ bool wait_count(const unsigned int* p, unsigned int target, int lane) {
    int ok = 1;
    if (lane == 0) {
        int it = 0;
        while (ld_acquire(p) < target) { if (++it > (1 << 16)) { ok = 0; break; } __nanosleep(20); }
    }
    ok = __shfl_sync(0xffffffffu, ok, 0);
    return ok != 0;
}

__global__ void __launch_bounds__(384, 1)
qkv_kernel(const __grid_constant__ CUtensorMap tm_x, const __grid_constant__ CUtensorMap tm_w,
           const __nv_bfloat16* __restrict__ x, const __nv_bfloat16* __restrict__ wqkv) {
    extern __shared__ __align__(1024) unsigned char smem[];
    const uint32_t sb = smem_u32(smem);
    const int tid = threadIdx.x, warp = tid >> 5, lane = tid & 31;
    int mb, nt;
    tile_of(blockIdx.x, mb, nt);
    const uint32_t full = sb + K1_BAR, empty = full + 40, auxb = full + 80;
    if (tid == 0) {
        prefetch_tmap(&tm_x); prefetch_tmap(&tm_w);
        for (int i = 0; i < K1_STAGES; i++) { mbar_init(full + 8 * i, 1); mbar_init(empty + 8 * i, 8); }
        mbar_init(auxb, 3);
        fence_barrier_init();
    }
    __syncthreads();
    pdl_launch();
    if (warp == 0) {
        if (lane == 0) {
            for (int kb = 0; kb < 8; kb++) {
                int s = kb % K1_STAGES;
                if (kb >= K1_STAGES) mbar_wait(empty + 8 * s, 0);
                mbar_expect(full + 8 * s, K1_STAGE);
                tma2d(sb + s * K1_STAGE, &tm_x, kb * 64, mb * 128, full + 8 * s);
                tma3d(sb + s * K1_STAGE + 16384, &tm_w, 0, kb * 64, nt * 3, full + 8 * s);
            }
        }
    } else if (warp < 4) {
        float2* s_rs = (float2*)(smem + K1_RS);
        float* s_cs = (float*)(smem + K1_CS);
        if (warp < 3) {
            int r0 = mb * 128 + nt * 16 + (warp - 1) * 8;
#pragma unroll 2
            for (int i = 0; i < 8; i++) {
                float2 st = row_stats_x(x, r0 + i, lane);
                if (lane == 0) g_rowstat1[r0 + i] = st;
            }
            __threadfence();
            __syncwarp();
            if (lane == 0) red_release(&g_cnt[mb]);
        } else {
            if (lane < 24) {
                float s[8];
                colsum8(wqkv, 1536, nt * 192 + lane * 8, mb * 32, 32, s);
                float4* d = (float4*)(g_cs1_part + mb * 1536 + nt * 192 + lane * 8);
                d[0] = make_float4(s[0], s[1], s[2], s[3]);
                d[1] = make_float4(s[4], s[5], s[6], s[7]);
            }
            __threadfence();
            __syncwarp();
            if (lane == 0) red_release(&g_cnt[16 + nt]);
        }
        if (warp == 1) {
            if (wait_count(&g_cnt[mb], 16, lane)) {
#pragma unroll
                for (int i = 0; i < 4; i++) s_rs[lane + 32 * i] = __ldcg(&g_rowstat1[mb * 128 + lane + 32 * i]);
            } else {
                for (int i = 0; i < 128; i++) {
                    float2 st = row_stats_x(x, mb * 128 + i, lane);
                    if (lane == 0) s_rs[i] = st;
                }
            }
        } else {
            int c0 = (warp - 2) * 96;
            if (wait_count(&g_cnt[16 + nt], 16, lane)) {
#pragma unroll
                for (int i = 0; i < 3; i++) {
                    float s = 0.f;
#pragma unroll
                    for (int p = 0; p < 16; p++) s += __ldcg(&g_cs1_part[p * 1536 + nt * 192 + c0 + lane + 32 * i]);
                    s_cs[c0 + lane + 32 * i] = s;
                }
            } else if (lane < 12) {
                float s[8];
                colsum8(wqkv, 1536, nt * 192 + c0 + lane * 8, 0, 512, s);
#pragma unroll
                for (int i = 0; i < 8; i++) s_cs[c0 + lane * 8 + i] = s[i];
            }
        }
        __syncwarp();
        if (lane == 0) mbar_arrive(auxb);
    } else {
        const int wgi = (warp >> 2) - 1, ww = warp & 3;
        float acc[96];
#pragma unroll 1
        for (int kb = 0; kb < 8; kb++) {
            int s = kb % K1_STAGES;
            mbar_wait(full + 8 * s, (kb / K1_STAGES) & 1);
            uint64_t ad = make_desc(sb + s * K1_STAGE + wgi * 8192, 16, 1024, 1);
            uint64_t bd = make_desc(sb + s * K1_STAGE + 16384, 8192, 1024, 1);
            WG_FENCE();
#pragma unroll
            for (int k = 0; k < 4; k++) wgmma_ss_n192(acc, ad + k * 2, bd + k * 128, (kb | k) != 0);
            WG_COMMIT();
            if (kb > 0) {
                wg_wait<1>();
                if (lane == 0) mbar_arrive(empty + 8 * ((kb - 1) % K1_STAGES));
            }
        }
        wg_wait<0>();
        fence_regs(acc);
        mbar_wait(auxb, 0);
        const float2* s_rs = (const float2*)(smem + K1_RS);
        const float* s_cs = (const float*)(smem + K1_CS);
        const int g = lane >> 2, t = lane & 3;
        const int rl = wgi * 64 + ww * 16 + g;
        const float2 st0 = s_rs[rl], st1 = s_rs[rl + 8];
        const float QS = 0.25f * 1.4426950408889634f;
        const int jrow = mb * 16 + wgi * 8 + ww * 2;
        const int rg16 = mb * 8 + wgi * 4 + ww;
        uint32_t* out = (uint32_t*)g_qkv;
#pragma unroll
        for (int hh = 0; hh < 12; hh++) {
            const int col0 = nt * 192 + hh * 16;
            const int which = col0 >> 9, head = (col0 & 511) >> 4;
            const float sc = (which == 0) ? QS : 1.0f;
            const float a0 = st0.x * sc, b0 = st0.y * sc, a1 = st1.x * sc, b1 = st1.y * sc;
            float n0 = 0.f, n1 = 0.f;
#pragma unroll
            for (int c = 0; c < 2; c++) {
                const int j = hh * 2 + c;
                const float2 cs = *(const float2*)(s_cs + 8 * j + 2 * t);
                float v00 = fmaf(a0, acc[4 * j], b0 * cs.x), v01 = fmaf(a0, acc[4 * j + 1], b0 * cs.y);
                float v10 = fmaf(a1, acc[4 * j + 2], b1 * cs.x), v11 = fmaf(a1, acc[4 * j + 3], b1 * cs.y);
                size_t o = ((size_t)((which * NH + head) * 2 + c) * 256 + jrow) * 32 + lane;
                out[o] = pack_bf16(v00, v01);
                out[o + 32] = pack_bf16(v10, v11);
                if (which < 2) {
                    n0 = fmaf(v00, v00, fmaf(v01, v01, n0));
                    n1 = fmaf(v10, v10, fmaf(v11, v11, n1));
                } else {
                    n0 = fmaxf(n0, fmaxf(fabsf(v00), fabsf(v01)));
                    n1 = fmaxf(n1, fmaxf(fabsf(v10), fabsf(v11)));
                    if (v00 != v00 || v01 != v01 || v10 != v10 || v11 != v11) n0 = __int_as_float(0x7f800000);
                }
            }
            float m;
            if (which < 2) {
                n0 += __shfl_xor_sync(0xffffffffu, n0, 1); n1 += __shfl_xor_sync(0xffffffffu, n1, 1);
                n0 += __shfl_xor_sync(0xffffffffu, n0, 2); n1 += __shfl_xor_sync(0xffffffffu, n1, 2);
                m = n0 + n1 - fminf(n0, n1);
                if (!(m == m)) m = __int_as_float(0x7f800000);
                m = fmaxf(m, __shfl_xor_sync(0xffffffffu, m, 4));
                m = fmaxf(m, __shfl_xor_sync(0xffffffffu, m, 8));
                m = fmaxf(m, __shfl_xor_sync(0xffffffffu, m, 16));
            } else {
                m = warp_max(fmaxf(n0, n1));
            }
            if (lane == 0) g_nrm[(which * NH + head) * 128 + rg16] = m;
        }
    }
}

constexpr int AT_K = 0, AT_V = 65536, AT_ONES = 131072, AT_BAR = 163840, AT_SMEM = AT_BAR + 128;
#define POLY_MASK 0xAD6A

__device__ __forceinline__ uint32_t exp2_pair_poly(float x0, float x1) {
    uint32_t t0 = __float_as_uint(x0 + 32895.0f);
    uint32_t t1 = __float_as_uint(x1 + 32895.0f);
    uint32_t gd = __byte_perm(t0, t1, 0x6420);
    uint32_t wm = __byte_perm(t0, t1, 0x5612);
    uint32_t v = hfma2(gd, 0x71477147u, 0x354f354fu);
    uint32_t z = hmul2(v, gd);
    return (wm >> 1) + z;
}
__device__ __forceinline__ uint32_t exp2_pair_mufu(float x0, float x1) { return pack_bf16(ex2f(x0), ex2f(x1)); }
template <uint32_t MASK>
__device__ __forceinline__ void exp_blocks(const float (&s)[32], uint32_t (&p)[16]) {
#pragma unroll
    for (int b = 0; b < 8; b++) {
        if ((MASK >> b) & 1) {
            p[2 * b] = exp2_pair_poly(s[4 * b], s[4 * b + 1]);
            p[2 * b + 1] = exp2_pair_poly(s[4 * b + 2], s[4 * b + 3]);
        } else {
            p[2 * b] = exp2_pair_mufu(s[4 * b], s[4 * b + 1]);
            p[2 * b + 1] = exp2_pair_mufu(s[4 * b + 2], s[4 * b + 3]);
        }
    }
}
#define PV4(P) _Pragma("unroll") for (int i = 0; i < 4; i++) { pv_wgmma(o, P[4 * i], P[4 * i + 1], P[4 * i + 2], P[4 * i + 3], vd); vd += 16; }

__device__ __forceinline__ void attn_store(float (&o)[12], int row0, int head, int lane) {
    float l0 = __shfl_sync(0xffffffffu, o[8], lane & 28);
    float l1 = __shfl_sync(0xffffffffu, o[10], lane & 28);
    float r0 = 1.0f / l0, r1 = 1.0f / l1;
    uint32_t* op = (uint32_t*)g_ao;
    int mb = row0 >> 7, rg = (row0 & 127) >> 3;
    int kb = head >> 2, kc = (head & 3) * 2;
    size_t base = (((size_t)(mb * 8 + kb) * 8 + kc) * 16 + rg) * 32 + lane;
    op[base] = pack_bf16(o[0] * r0, o[1] * r0);
    op[base + 32] = pack_bf16(o[2] * r1, o[3] * r1);
    op[base + 16 * 32] = pack_bf16(o[4] * r0, o[5] * r0);
    op[base + 16 * 32 + 32] = pack_bf16(o[6] * r1, o[7] * r1);
}

__device__ __forceinline__ void attn_load_q(uint32_t (&q)[4], const __nv_bfloat16* gq, int row0, int lane) {
    const uint32_t* qp = (const uint32_t*)gq;
    int j0 = row0 >> 3;
    q[0] = __ldcg(qp + (0 * 256 + j0) * 32 + lane);
    q[1] = __ldcg(qp + (0 * 256 + j0 + 1) * 32 + lane);
    q[2] = __ldcg(qp + (1 * 256 + j0) * 32 + lane);
    q[3] = __ldcg(qp + (1 * 256 + j0 + 1) * 32 + lane);
}

__device__ __forceinline__ void attn_tile_safe(const uint32_t (&q)[4], uint64_t kd, uint64_t vd, int row0, int head, int lane) {
    float o[12];
#pragma unroll
    for (int i = 0; i < 12; i++) o[i] = 0.f;
    float m0 = -INFINITY, m1 = -INFINITY;
    fence_regs(o);
#pragma unroll 1
    for (int j = 0; j < 32; j++) {
        float s[32];
        uint32_t p[16];
        WG_FENCE();
        qk_wgmma_n64(s, q, kd); kd += 64;
        WG_COMMIT();
        wg_wait<0>();
        fence_regs(s);
        fence_regs(o);
        float x0 = m0, x1 = m1;
#pragma unroll
        for (int b = 0; b < 8; b++) {
            x0 = fmaxf(x0, fmaxf(s[4 * b], s[4 * b + 1]));
            x1 = fmaxf(x1, fmaxf(s[4 * b + 2], s[4 * b + 3]));
        }
        x0 = fmaxf(x0, __shfl_xor_sync(0xffffffffu, x0, 1)); x0 = fmaxf(x0, __shfl_xor_sync(0xffffffffu, x0, 2));
        x1 = fmaxf(x1, __shfl_xor_sync(0xffffffffu, x1, 1)); x1 = fmaxf(x1, __shfl_xor_sync(0xffffffffu, x1, 2));
        float al0 = ex2f(m0 - x0), al1 = ex2f(m1 - x1);
        m0 = x0; m1 = x1;
#pragma unroll
        for (int i = 0; i < 3; i++) { o[4 * i] *= al0; o[4 * i + 1] *= al0; o[4 * i + 2] *= al1; o[4 * i + 3] *= al1; }
#pragma unroll
        for (int b = 0; b < 8; b++) {
            p[2 * b] = exp2_pair_mufu(s[4 * b] - m0, s[4 * b + 1] - m0);
            p[2 * b + 1] = exp2_pair_mufu(s[4 * b + 2] - m1, s[4 * b + 3] - m1);
        }
        fence_regs(o);
        WG_FENCE();
        PV4(p);
        WG_COMMIT();
        wg_wait<0>();
        fence_regs(o);
    }
    attn_store(o, row0, head, lane);
}

__global__ void __launch_bounds__(512, 1)
attn_kernel(const __nv_bfloat16* __restrict__ wg_, const __nv_bfloat16* __restrict__ wu_,
            const __nv_bfloat16* __restrict__ wo_, const __nv_bfloat16* __restrict__ wd_) {
    extern __shared__ __align__(1024) unsigned char smem[];
    const uint32_t sb = smem_u32(smem);
    const int tid = threadIdx.x, wg = tid >> 7, warp = (tid >> 5) & 3, lane = tid & 31;
    pdl_launch();
    if (blockIdx.x >= 128) {
        const int e = blockIdx.x - 128;
        const __nv_bfloat16* w = (e < 2) ? wg_ : wu_;
        float* red = (float*)smem;
        const int cgrp = tid & 127, kq = tid >> 7;
        if (cgrp < 112) {
            float s[8];
            colsum8(w, FF, (e & 1) * 896 + cgrp * 8, kq * 128, 128, s);
#pragma unroll
            for (int i = 0; i < 8; i++) red[kq * 896 + cgrp * 8 + i] = s[i];
        }
        __syncthreads();
        for (int c = tid; c < 896; c += 512)
            g_cs2[(e >> 1) * FF + (e & 1) * 896 + c] = red[c] + red[896 + c] + red[1792 + c] + red[2688 + c];
        if (tid < 32) {
            const char* p0 = (const char*)wo_ + e * (DM * DM * 2 / 4);
            for (int i = lane; i < 32; i += 32)
                asm volatile("cp.async.bulk.prefetch.L2.global [%0], %1;" :: "l"(p0 + i * 4096), "r"(4096) : "memory");
            const char* p1 = (const char*)wd_ + e * (FF * DM * 2 / 4);
            for (int i = lane; i < 112; i += 32)
                asm volatile("cp.async.bulk.prefetch.L2.global [%0], %1;" :: "l"(p1 + i * 4096), "r"(4096) : "memory");
        }
        return;
    }
    const int head = blockIdx.x >> 2, qq = blockIdx.x & 3;
    const __nv_bfloat16* gq = g_qkv + (size_t)head * (S_LEN * 16);
    const __nv_bfloat16* gk = g_qkv + (size_t)(NH + head) * (S_LEN * 16);
    const __nv_bfloat16* gv = g_qkv + (size_t)(2 * NH + head) * (S_LEN * 16);
    if (tid == 0) {
        for (int i = 0; i < 8; i++) mbar_init(sb + AT_BAR + 8 * i, 1);
        fence_barrier_init();
    }
    {
        uint4 one = make_uint4(0x00003F80u, 0, 0, 0);
#pragma unroll
        for (int i = 0; i < 4; i++) *(uint4*)(smem + AT_ONES + (i * 512 + tid) * 16) = one;
        fence_proxy_async();
    }
    __syncthreads();
    pdl_wait();
    if (tid == 0) {
        for (int i = 0; i < 8; i++) {
            uint32_t bar = sb + AT_BAR + 8 * i;
            mbar_expect(bar, 16384);
            bulk_g2s(sb + AT_K + i * 4096, gk + i * 2048, 4096, bar);
            bulk_g2s(sb + AT_K + 32768 + i * 4096, gk + 16384 + i * 2048, 4096, bar);
            bulk_g2s(sb + AT_V + i * 4096, gv + i * 2048, 4096, bar);
            bulk_g2s(sb + AT_V + 32768 + i * 4096, gv + 16384 + i * 2048, 4096, bar);
        }
    }
    bool fast;
    {
        const float* nq = g_nrm + (0 * NH + head) * 128 + qq * 32;
        const float* nk = g_nrm + (1 * NH + head) * 128;
        const float* nv = g_nrm + (2 * NH + head) * 128;
        float4 k4 = __ldcg((const float4*)nk + lane), v4 = __ldcg((const float4*)nv + lane);
        float qm = warp_max(__ldcg(nq + lane));
        float km = warp_max(fmaxf(fmaxf(k4.x, k4.y), fmaxf(k4.z, k4.w)));
        float vm = warp_max(fmaxf(fmaxf(v4.x, v4.y), fmaxf(v4.z, v4.w)));
        fast = (qm * km <= 3500.0f) && (vm <= 1.0e12f);
    }
    const uint64_t kdesc0 = make_desc(sb + AT_K, 32768, 128, 0);
    const uint64_t vdesc0 = make_desc(sb + AT_V, 128, 32768, 0);
    if (!fast) {
        for (int i = 0; i < 8; i++) mbar_wait(sb + AT_BAR + 8 * i, 0);
#pragma unroll 1
        for (int tile = 0; tile < 2; tile++) {
            const int row0 = qq * 512 + (tile * 4 + wg) * 64 + warp * 16;
            uint32_t q[4];
            attn_load_q(q, gq, row0, lane);
            attn_tile_safe(q, kdesc0, vdesc0, row0, head, lane);
        }
        return;
    }
#pragma unroll 1
    for (int tile = 0; tile < 2; tile++) {
        const int row0 = qq * 512 + (tile * 4 + wg) * 64 + warp * 16;
        uint32_t q[4];
        attn_load_q(q, gq, row0, lane);
        float o[12];
#pragma unroll
        for (int i = 0; i < 12; i++) o[i] = 0.f;
        fence_regs(o);
        float sa[32];
        uint32_t pa[16];
        uint64_t kd = kdesc0, vd = vdesc0;
        if (tile == 0) mbar_wait(sb + AT_BAR, 0);
        WG_FENCE();
        qk_wgmma_n64(sa, q, kd); kd += 64;
        WG_COMMIT();
#pragma unroll 1
        for (int jj = 0; jj < 8; jj++) {
            if (tile == 0 && jj < 7) mbar_wait(sb + AT_BAR + 8 * (jj + 1), 0);
#pragma unroll
            for (int j = 0; j < 4; j++) {
                wg_wait<0>();
                fence_regs(sa);
                if (j & 1) exp_blocks<(POLY_MASK >> 8)>(sa, pa); else exp_blocks<(POLY_MASK & 255)>(sa, pa);
                WG_FENCE();
                qk_wgmma_n64(sa, q, kd); kd += 64;
                PV4(pa);
                WG_COMMIT();
            }
        }
        wg_wait<0>();
        fence_regs(o);
        fence_regs(sa);
        attn_store(o, row0, head, lane);
    }
}

constexpr int K3_STAGE = 16384 + 8192, K3_BAR = 8 * K3_STAGE, K3_SMEM = K3_BAR + 128;

__global__ void __launch_bounds__(384, 1)
wo_kernel(const __grid_constant__ CUtensorMap tm_w, const __nv_bfloat16* __restrict__ x) {
    extern __shared__ __align__(1024) unsigned char smem[];
    const uint32_t sb = smem_u32(smem);
    const int tid = threadIdx.x, warp = tid >> 5, lane = tid & 31;
    int mb, nt;
    tile_of(blockIdx.x, mb, nt);
    const uint32_t full = sb + K3_BAR;
    if (tid == 0) {
        prefetch_tmap(&tm_w);
        for (int i = 0; i < 8; i++) mbar_init(full + 8 * i, 1);
        fence_barrier_init();
    }
    __syncthreads();
    pdl_launch();
    if (warp == 0) {
        if (lane == 0) {
            for (int kb = 0; kb < 8; kb++) {
                mbar_expect(full + 8 * kb, K3_STAGE);
                tma2d(sb + kb * K3_STAGE + 16384, &tm_w, nt * 64, kb * 64, full + 8 * kb);
            }
            pdl_wait();
            for (int kb = 0; kb < 8; kb++)
                bulk_g2s(sb + kb * K3_STAGE, g_ao + (size_t)(mb * 8 + kb) * 8192, 16384, full + 8 * kb);
            if (blockIdx.x == 0)
                for (int i = 0; i < 32; i++) g_cnt[i] = 0;
        }
    } else if (warp >= 4) {
        const int wgi = (warp >> 2) - 1, ww = warp & 3;
        const int g = lane >> 2, t = lane & 3;
        const int row = mb * 128 + wgi * 64 + ww * 16 + g;
        uint32_t xr[16];
        {
            const uint32_t* xp = (const uint32_t*)(x + (size_t)row * DM + nt * 64) + t;
#pragma unroll
            for (int j = 0; j < 8; j++) { xr[2 * j] = __ldg(xp + 4 * j); xr[2 * j + 1] = __ldg(xp + 8 * (DM / 2) + 4 * j); }
        }
        float acc[32];
#pragma unroll 1
        for (int kb = 0; kb < 8; kb++) {
            mbar_wait(full + 8 * kb, 0);
            uint64_t ad = make_desc(sb + kb * K3_STAGE + wgi * 1024, 2048, 128, 0);
            uint64_t bd = make_desc(sb + kb * K3_STAGE + 16384, 8192, 1024, 1);
            WG_FENCE();
#pragma unroll
            for (int k = 0; k < 4; k++) wgmma_ss_n64(acc, ad + k * 256, bd + k * 128, (kb | k) != 0);
            WG_COMMIT();
        }
        wg_wait<0>();
        fence_regs(acc);
        pdl_wait();
        uint32_t* hp = (uint32_t*)g_h + ((size_t)(mb * 8 + nt) * 8 * 16 + wgi * 8 + ww * 2) * 32 + lane;
        float v0[16], v1[16];
        float s0 = 0.f, s1 = 0.f;
#pragma unroll
        for (int j = 0; j < 8; j++) {
            uint32_t u0 = pack_bf16(bf_lo(xr[2 * j]) + acc[4 * j], bf_hi(xr[2 * j]) + acc[4 * j + 1]);
            uint32_t u1 = pack_bf16(bf_lo(xr[2 * j + 1]) + acc[4 * j + 2], bf_hi(xr[2 * j + 1]) + acc[4 * j + 3]);
            hp[j * 16 * 32] = u0;
            hp[j * 16 * 32 + 32] = u1;
            v0[2 * j] = bf_lo(u0); v0[2 * j + 1] = bf_hi(u0);
            v1[2 * j] = bf_lo(u1); v1[2 * j + 1] = bf_hi(u1);
            s0 += v0[2 * j] + v0[2 * j + 1];
            s1 += v1[2 * j] + v1[2 * j + 1];
        }
        float m0 = s0 * (1.0f / 16), m1 = s1 * (1.0f / 16), q0 = 0.f, q1 = 0.f;
#pragma unroll
        for (int i = 0; i < 16; i++) {
            float d0 = v0[i] - m0, d1 = v1[i] - m1;
            q0 = fmaf(d0, d0, q0); q1 = fmaf(d1, d1, q1);
        }
#pragma unroll
        for (int st = 0; st < 2; st++) {
            float hn = st ? 16.f : 8.f;
            float om0 = __shfl_xor_sync(0xffffffffu, m0, 1 << st), oq0 = __shfl_xor_sync(0xffffffffu, q0, 1 << st);
            float om1 = __shfl_xor_sync(0xffffffffu, m1, 1 << st), oq1 = __shfl_xor_sync(0xffffffffu, q1, 1 << st);
            float d0 = om0 - m0, d1 = om1 - m1;
            q0 = q0 + oq0 + d0 * d0 * hn; q1 = q1 + oq1 + d1 * d1 * hn;
            m0 = 0.5f * (m0 + om0); m1 = 0.5f * (m1 + om1);
        }
        if (t == 0) {
            g_hstat[row * 8 + nt] = make_float2(m0, q0);
            g_hstat[(row + 8) * 8 + nt] = make_float2(m1, q1);
        }
    }
}

constexpr int K4_STAGES = 3, K4_B = 131072, K4_BSTAGE = 32768, K4_BAR = K4_B + K4_STAGES * K4_BSTAGE;
constexpr int K4_RS = K4_BAR + 256, K4_CS = K4_RS + 1024, K4_SMEM = K4_CS + 448 * 4;

__device__ __forceinline__ float geglu(float gt, float up) {
    float u = gt * fmaf(gt * gt, 0.044715f * 0.7978845608028654f, 0.7978845608028654f);
    float hg = 0.5f * gt;
    return fmaf(hg, tanh_fast(u), hg) * up;
}
template <int NB>
__device__ __forceinline__ void k4_epilogue(const float* ag, const float* au, const float* s_cs, int cs_off, int jb0,
                                            float2 st0, float2 st1, int mb, int rgl, int lane) {
    const int t = lane & 3;
    uint32_t* gp = (uint32_t*)g_g;
#pragma unroll
    for (int j = 0; j < NB; j++) {
        const float2 cg = *(const float2*)(s_cs + cs_off + 8 * j + 2 * t);
        const float2 cu = *(const float2*)(s_cs + 224 + cs_off + 8 * j + 2 * t);
        float g00 = fmaf(st0.x, ag[4 * j], st0.y * cg.x), g01 = fmaf(st0.x, ag[4 * j + 1], st0.y * cg.y);
        float g10 = fmaf(st1.x, ag[4 * j + 2], st1.y * cg.x), g11 = fmaf(st1.x, ag[4 * j + 3], st1.y * cg.y);
        float u00 = fmaf(st0.x, au[4 * j], st0.y * cu.x), u01 = fmaf(st0.x, au[4 * j + 1], st0.y * cu.y);
        float u10 = fmaf(st1.x, au[4 * j + 2], st1.y * cu.x), u11 = fmaf(st1.x, au[4 * j + 3], st1.y * cu.y);
        const int jb = jb0 + j;
        size_t o = (((size_t)mb * 28 * 8 + jb) * 16 + rgl) * 32 + lane;
        gp[o] = pack_bf16(geglu(g00, u00), geglu(g01, u01));
        gp[o + 32] = pack_bf16(geglu(g10, u10), geglu(g11, u11));
    }
}

__global__ void __launch_bounds__(384, 1)
ffn1_kernel(const __grid_constant__ CUtensorMap tm_g, const __grid_constant__ CUtensorMap tm_u) {
    extern __shared__ __align__(1024) unsigned char smem[];
    const uint32_t sb = smem_u32(smem);
    const int tid = threadIdx.x, warp = tid >> 5, lane = tid & 31;
    int mb, nt;
    tile_of(blockIdx.x, mb, nt);
    const uint32_t afull = sb + K4_BAR, full = afull + 64, empty = full + 32, auxb = empty + 32;
    if (tid == 0) {
        prefetch_tmap(&tm_g); prefetch_tmap(&tm_u);
        for (int i = 0; i < 8; i++) mbar_init(afull + 8 * i, 1);
        for (int i = 0; i < K4_STAGES; i++) { mbar_init(full + 8 * i, 1); mbar_init(empty + 8 * i, 8); }
        mbar_init(auxb, 3);
        fence_barrier_init();
    }
    __syncthreads();
    pdl_launch();
    if (warp < 4) {
        asm volatile("setmaxnreg.dec.sync.aligned.u32 56;");
        if (warp == 0) {
            if (lane == 0) {
                for (int it = 0; it < 16; it++) {
                    const int s = it % K4_STAGES, pass = it >> 3, kb = it & 7;
                    const int ng = pass ? 3 : 4, c0 = nt * 224 + pass * 128;
                    if (it >= K4_STAGES) mbar_wait(empty + 8 * s, ((it / K4_STAGES) - 1) & 1);
                    mbar_expect(full + 8 * s, ng * 8192);
                    const uint32_t dst = sb + K4_B + s * K4_BSTAGE;
                    for (int i = 0; i < ng; i++) {
                        tma2d(dst + i * 4096, &tm_g, c0 + i * 32, kb * 64, full + 8 * s);
                        tma2d(dst + 16384 + i * 4096, &tm_u, c0 + i * 32, kb * 64, full + 8 * s);
                    }
                    if (it == K4_STAGES - 1) {
                        pdl_wait();
                        for (int k2 = 0; k2 < 8; k2++) {
                            mbar_expect(afull + 8 * k2, 16384);
                            bulk_g2s(sb + k2 * 16384, g_h + (size_t)(mb * 8 + k2) * 8192, 16384, afull + 8 * k2);
                        }
                    }
                }
            }
        } else {
            pdl_wait();
            float2* s_rs = (float2*)(smem + K4_RS);
            float* s_cs = (float*)(smem + K4_CS);
            for (int r = tid - 32; r < 128; r += 96) {
                const float4* hp = (const float4*)(g_hstat + (size_t)(mb * 128 + r) * 8);
                float4 a = __ldcg(hp), b = __ldcg(hp + 1), c = __ldcg(hp + 2), d = __ldcg(hp + 3);
                float mean = 0.125f * (a.x + a.z + b.x + b.z + c.x + c.z + d.x + d.z);
                float m2 = a.y + a.w + b.y + b.w + c.y + c.w + d.y + d.w;
                float e;
                e = a.x - mean; m2 = fmaf(64.f * e, e, m2); e = a.z - mean; m2 = fmaf(64.f * e, e, m2);
                e = b.x - mean; m2 = fmaf(64.f * e, e, m2); e = b.z - mean; m2 = fmaf(64.f * e, e, m2);
                e = c.x - mean; m2 = fmaf(64.f * e, e, m2); e = c.z - mean; m2 = fmaf(64.f * e, e, m2);
                e = d.x - mean; m2 = fmaf(64.f * e, e, m2); e = d.z - mean; m2 = fmaf(64.f * e, e, m2);
                float rstd = rsqrtf(m2 * (1.0f / DM) + 1e-5f);
                s_rs[r] = make_float2(rstd, -mean * rstd);
            }
            for (int c = tid - 32; c < 448; c += 96)
                s_cs[c] = __ldcg(&g_cs2[(c >= 224 ? FF - 224 : 0) + nt * 224 + c]);
            __syncwarp();
            if (lane == 0) mbar_arrive(auxb);
        }
    } else {
        asm volatile("setmaxnreg.inc.sync.aligned.u32 216;");
        const int wgi = (warp >> 2) - 1, ww = warp & 3;
        const int rl = wgi * 64 + ww * 16 + (lane >> 2);
        const int rgl = wgi * 8 + ww * 2;
        const float2* s_rs = (const float2*)(smem + K4_RS);
        const float* s_cs = (const float*)(smem + K4_CS);
        {
            float ag[64], au[64];
#pragma unroll 1
            for (int kb = 0; kb < 8; kb++) {
                const int s = kb % K4_STAGES;
                mbar_wait(afull + 8 * kb, 0);
                mbar_wait(full + 8 * s, (kb / K4_STAGES) & 1);
                uint64_t ad = make_desc(sb + kb * 16384 + wgi * 1024, 2048, 128, 0);
                uint64_t bd = make_desc(sb + K4_B + s * K4_BSTAGE, 4096, 512, 2);
                WG_FENCE();
#pragma unroll
                for (int k = 0; k < 4; k++) {
                    wgmma_ss_n128(ag, ad + k * 256, bd + k * 64, (kb | k) != 0);
                    wgmma_ss_n128(au, ad + k * 256, bd + 1024 + k * 64, (kb | k) != 0);
                }
                WG_COMMIT();
                if (kb > 0) {
                    wg_wait<1>();
                    if (lane == 0) mbar_arrive(empty + 8 * ((kb - 1) % K4_STAGES));
                }
            }
            wg_wait<0>();
            if (lane == 0) mbar_arrive(empty + 8 * (7 % K4_STAGES));
            fence_regs(ag); fence_regs(au);
            mbar_wait(auxb, 0);
            k4_epilogue<16>(ag, au, s_cs, 0, nt * 28, s_rs[rl], s_rs[rl + 8], mb, rgl, lane);
        }
        {
            float ag[48], au[48];
#pragma unroll 1
            for (int kb = 0; kb < 8; kb++) {
                const int it = 8 + kb, s = it % K4_STAGES;
                mbar_wait(full + 8 * s, (it / K4_STAGES) & 1);
                uint64_t ad = make_desc(sb + kb * 16384 + wgi * 1024, 2048, 128, 0);
                uint64_t bd = make_desc(sb + K4_B + s * K4_BSTAGE, 4096, 512, 2);
                WG_FENCE();
#pragma unroll
                for (int k = 0; k < 4; k++) {
                    wgmma_ss_n96(ag, ad + k * 256, bd + k * 64, (kb | k) != 0);
                    wgmma_ss_n96(au, ad + k * 256, bd + 1024 + k * 64, (kb | k) != 0);
                }
                WG_COMMIT();
                if (kb > 0) {
                    wg_wait<1>();
                    if (lane == 0) mbar_arrive(empty + 8 * ((it - 1) % K4_STAGES));
                }
            }
            wg_wait<0>();
            fence_regs(ag); fence_regs(au);
            k4_epilogue<12>(ag, au, s_cs, 128, nt * 28 + 16, s_rs[rl], s_rs[rl + 8], mb, rgl, lane);
        }
    }
}

constexpr int K5_STAGES = 8, K5_STAGE = 16384 + 8192, K5_BAR = K5_STAGES * K5_STAGE, K5_SMEM = K5_BAR + 128;

__global__ void __launch_bounds__(384, 1)
ffn2_kernel(const __grid_constant__ CUtensorMap tm_w, __nv_bfloat16* __restrict__ out) {
    extern __shared__ __align__(1024) unsigned char smem[];
    const uint32_t sb = smem_u32(smem);
    const int tid = threadIdx.x, warp = tid >> 5, lane = tid & 31;
    int mb, nt;
    tile_of(blockIdx.x, mb, nt);
    const uint32_t full = sb + K5_BAR, empty = full + 64;
    if (tid == 0) {
        prefetch_tmap(&tm_w);
        for (int i = 0; i < K5_STAGES; i++) { mbar_init(full + 8 * i, 1); mbar_init(empty + 8 * i, 8); }
        fence_barrier_init();
    }
    __syncthreads();
    if (warp == 0) {
        if (lane == 0) {
            for (int kb = 0; kb < K5_STAGES; kb++) {
                mbar_expect(full + 8 * kb, K5_STAGE);
                tma2d(sb + kb * K5_STAGE + 16384, &tm_w, nt * 64, kb * 64, full + 8 * kb);
            }
            pdl_wait();
            for (int kb = 0; kb < 28; kb++) {
                const int s = kb % K5_STAGES;
                if (kb >= K5_STAGES) {
                    mbar_wait(empty + 8 * s, ((kb / K5_STAGES) - 1) & 1);
                    mbar_expect(full + 8 * s, K5_STAGE);
                    tma2d(sb + s * K5_STAGE + 16384, &tm_w, nt * 64, kb * 64, full + 8 * s);
                }
                bulk_g2s(sb + s * K5_STAGE, g_g + (size_t)(mb * 28 + kb) * 8192, 16384, full + 8 * s);
            }
        }
    } else if (warp >= 4) {
        const int wgi = (warp >> 2) - 1, ww = warp & 3;
        const int g = lane >> 2, t = lane & 3;
        pdl_wait();
        uint32_t hr[16];
        {
            const uint32_t* hp = (const uint32_t*)g_h + ((size_t)(mb * 8 + nt) * 8 * 16 + wgi * 8 + ww * 2) * 32 + lane;
#pragma unroll
            for (int j = 0; j < 8; j++) { hr[2 * j] = __ldcg(hp + j * 16 * 32); hr[2 * j + 1] = __ldcg(hp + j * 16 * 32 + 32); }
        }
        float acc[32];
#pragma unroll 1
        for (int kb = 0; kb < 28; kb++) {
            const int s = kb % K5_STAGES;
            mbar_wait(full + 8 * s, (kb / K5_STAGES) & 1);
            uint64_t ad = make_desc(sb + s * K5_STAGE + wgi * 1024, 2048, 128, 0);
            uint64_t bd = make_desc(sb + s * K5_STAGE + 16384, 8192, 1024, 1);
            WG_FENCE();
#pragma unroll
            for (int k = 0; k < 4; k++) wgmma_ss_n64(acc, ad + k * 256, bd + k * 128, (kb | k) != 0);
            WG_COMMIT();
            if (kb > 0) {
                wg_wait<1>();
                if (lane == 0) mbar_arrive(empty + 8 * ((kb - 1) % K5_STAGES));
            }
        }
        wg_wait<0>();
        fence_regs(acc);
        const int row = mb * 128 + wgi * 64 + ww * 16 + g;
        uint32_t* op = (uint32_t*)(out + (size_t)row * DM + nt * 64) + t;
#pragma unroll
        for (int j = 0; j < 8; j++) {
            op[4 * j] = pack_bf16(bf_lo(hr[2 * j]) + acc[4 * j], bf_hi(hr[2 * j]) + acc[4 * j + 1]);
            op[8 * (DM / 2) + 4 * j] = pack_bf16(bf_lo(hr[2 * j + 1]) + acc[4 * j + 2], bf_hi(hr[2 * j + 1]) + acc[4 * j + 3]);
        }
    }
}

typedef CUresult (*EncodeFn)(CUtensorMap*, CUtensorMapDataType, cuuint32_t, void*, const cuuint64_t*, const cuuint64_t*,
                             const cuuint32_t*, const cuuint32_t*, CUtensorMapInterleave, CUtensorMapSwizzle,
                             CUtensorMapL2promotion, CUtensorMapFloatOOBfill);

void encode(EncodeFn fn, CUtensorMap* m, const void* ptr, int rank, const cuuint64_t* dims, const cuuint64_t* strides,
            const cuuint32_t* box, CUtensorMapSwizzle swz) {
    cuuint32_t es[3] = {1, 1, 1};
    fn(m, CU_TENSOR_MAP_DATA_TYPE_BFLOAT16, rank, (void*)ptr, dims, strides, box, es, CU_TENSOR_MAP_INTERLEAVE_NONE, swz,
       CU_TENSOR_MAP_L2_PROMOTION_L2_256B, CU_TENSOR_MAP_FLOAT_OOB_FILL_NONE);
}

template <typename... KArgs, typename... Args>
void launch(void (*kern)(KArgs...), int grid, int block, int smem, bool pdl, Args... args) {
    cudaLaunchConfig_t cfg = {};
    cfg.gridDim = dim3(grid); cfg.blockDim = dim3(block); cfg.dynamicSmemBytes = smem;
    cfg.stream = cudaStreamPerThread;
    cudaLaunchAttribute at[1];
    at[0].id = cudaLaunchAttributeProgrammaticStreamSerialization;
    at[0].val.programmaticStreamSerializationAllowed = 1;
    cfg.attrs = at; cfg.numAttrs = pdl ? 1 : 0;
    cudaLaunchKernelEx(&cfg, kern, KArgs(args)...);
}

}

extern "C" void kernel_launch(void* const* d_in, const int* in_sizes, int n_in, void* d_out, int out_size) {
    const __nv_bfloat16* x = (const __nv_bfloat16*)d_in[0];
    const __nv_bfloat16* wqkv = (const __nv_bfloat16*)d_in[1];
    const __nv_bfloat16* wo = (const __nv_bfloat16*)d_in[2];
    const __nv_bfloat16* wgate = (const __nv_bfloat16*)d_in[4];
    const __nv_bfloat16* wup = (const __nv_bfloat16*)d_in[5];
    const __nv_bfloat16* wdown = (const __nv_bfloat16*)d_in[6];
    __nv_bfloat16* out = (__nv_bfloat16*)d_out;

    static CUtensorMap tm_x, tm_wqkv, tm_wo, tm_wg, tm_wu, tm_wd;
    static const void* cached[6] = {nullptr, nullptr, nullptr, nullptr, nullptr, nullptr};
    if (cached[0] != x || cached[1] != wqkv || cached[2] != wo || cached[3] != wgate || cached[4] != wup || cached[5] != wdown) {
        void* fp = nullptr;
        cudaDriverEntryPointQueryResult qr;
        cudaGetDriverEntryPoint("cuTensorMapEncodeTiled", &fp, cudaEnableDefault, &qr);
        EncodeFn fn = (EncodeFn)fp;
        { cuuint64_t d[2] = {512, 2048}, s[1] = {1024}; cuuint32_t b[2] = {64, 128};
          encode(fn, &tm_x, x, 2, d, s, b, CU_TENSOR_MAP_SWIZZLE_128B); }
        { cuuint64_t d[3] = {64, 512, 24}, s[2] = {3072, 128}; cuuint32_t b[3] = {64, 64, 3};
          encode(fn, &tm_wqkv, wqkv, 3, d, s, b, CU_TENSOR_MAP_SWIZZLE_128B); }
        { cuuint64_t d[2] = {512, 512}, s[1] = {1024}; cuuint32_t b[2] = {64, 64};
          encode(fn, &tm_wo, wo, 2, d, s, b, CU_TENSOR_MAP_SWIZZLE_128B); }
        { cuuint64_t d[2] = {1792, 512}, s[1] = {3584}; cuuint32_t b[2] = {32, 64};
          encode(fn, &tm_wg, wgate, 2, d, s, b, CU_TENSOR_MAP_SWIZZLE_64B);
          encode(fn, &tm_wu, wup, 2, d, s, b, CU_TENSOR_MAP_SWIZZLE_64B); }
        { cuuint64_t d[2] = {512, 1792}, s[1] = {1024}; cuuint32_t b[2] = {64, 64};
          encode(fn, &tm_wd, wdown, 2, d, s, b, CU_TENSOR_MAP_SWIZZLE_128B); }
        cudaFuncSetAttribute(qkv_kernel, cudaFuncAttributeMaxDynamicSharedMemorySize, K1_SMEM);
        cudaFuncSetAttribute(attn_kernel, cudaFuncAttributeMaxDynamicSharedMemorySize, AT_SMEM);
        cudaFuncSetAttribute(wo_kernel, cudaFuncAttributeMaxDynamicSharedMemorySize, K3_SMEM);
        cudaFuncSetAttribute(ffn1_kernel, cudaFuncAttributeMaxDynamicSharedMemorySize, K4_SMEM);
        cudaFuncSetAttribute(ffn2_kernel, cudaFuncAttributeMaxDynamicSharedMemorySize, K5_SMEM);
        cached[0] = x; cached[1] = wqkv; cached[2] = wo; cached[3] = wgate; cached[4] = wup; cached[5] = wdown;
    }
    launch(qkv_kernel, 128, 384, K1_SMEM, false, tm_x, tm_wqkv, x, wqkv);
    launch(attn_kernel, 132, 512, AT_SMEM, true, wgate, wup, wo, wdown);
    launch(wo_kernel, 128, 384, K3_SMEM, true, tm_wo, x);
    launch(ffn1_kernel, 128, 384, K4_SMEM, true, tm_wg, tm_wu);
    launch(ffn2_kernel, 128, 384, K5_SMEM, true, tm_wd, out);
}
```

```cpp
#include <cuda_runtime.h>
#include <cuda_bf16.h>
#include <cuda.h>
#include <stdint.h>

namespace {

constexpr int S_LEN = 2048, DM = 512, NH = 32, FF = 1792;

__device__ __align__(1024) __nv_bfloat16 g_qkv[3 * NH * S_LEN * 16];
__device__ __align__(1024) __nv_bfloat16 g_ao[S_LEN * DM];
__device__ __align__(1024) __nv_bfloat16 g_h[S_LEN * DM];
__device__ __align__(1024) __nv_bfloat16 g_g[S_LEN * FF];
__device__ float2 g_rowstat1[S_LEN];
__device__ float g_cs1_part[16 * 1536];
__device__ unsigned int g_cnt[32];
__device__ float g_nrm[3 * NH * 128];
__device__ float2 g_hstat[S_LEN * 8];
__device__ float g_cs2[2 * FF];

#define TL(slot)
__device__ __forceinline__ uint32_t smem_u32(const void* p) { return (uint32_t)__cvta_generic_to_shared(p); }
__device__ __forceinline__ void mbar_init(uint32_t a, int c) { asm volatile("mbarrier.init.shared.b64 [%0], %1;" :: "r"(a), "r"(c)); }
__device__ __forceinline__ void mbar_expect(uint32_t a, int bytes) { asm volatile("mbarrier.arrive.expect_tx.shared.b64 _, [%0], %1;" :: "r"(a), "r"(bytes) : "memory"); }
__device__ __forceinline__ void mbar_arrive(uint32_t a) { asm volatile("mbarrier.arrive.shared.b64 _, [%0];" :: "r"(a) : "memory"); }
__device__ __forceinline__ void mbar_wait(uint32_t a, int parity) {
    uint32_t done;
    int it = 0;
    do {
        asm volatile("{\n.reg .pred p;\nmbarrier.try_wait.parity.shared.b64 p, [%1], %2;\nselp.u32 %0, 1, 0, p;\n}"
                     : "=r"(done) : "r"(a), "r"(parity) : "memory");
        if (++it > (1 << 24)) __trap();
    } while (!done);
}
__device__ __forceinline__ void bulk_g2s(uint32_t dst, const void* src, int bytes, uint32_t bar) {
    asm volatile("cp.async.bulk.shared::cluster.global.mbarrier::complete_tx::bytes [%0], [%1], %2, [%3];"
                 :: "r"(dst), "l"(src), "r"(bytes), "r"(bar) : "memory");
}
__device__ __forceinline__ void tma2d(uint32_t dst, const CUtensorMap* m, int c0, int c1, uint32_t bar) {
    asm volatile("cp.async.bulk.tensor.2d.shared::cluster.global.mbarrier::complete_tx::bytes [%0], [%1, {%3, %4}], [%2];"
                 :: "r"(dst), "l"(m), "r"(bar), "r"(c0), "r"(c1) : "memory");
}
__device__ __forceinline__ void tma3d(uint32_t dst, const CUtensorMap* m, int c0, int c1, int c2, uint32_t bar) {
    asm volatile("cp.async.bulk.tensor.3d.shared::cluster.global.mbarrier::complete_tx::bytes [%0], [%1, {%3, %4, %5}], [%2];"
                 :: "r"(dst), "l"(m), "r"(bar), "r"(c0), "r"(c1), "r"(c2) : "memory");
}
__device__ __forceinline__ void prefetch_tmap(const CUtensorMap* m) { asm volatile("prefetch.tensormap [%0];" :: "l"(m) : "memory"); }
__device__ __forceinline__ void pdl_wait() { asm volatile("griddepcontrol.wait;" ::: "memory"); }
__device__ __forceinline__ void pdl_launch() { asm volatile("griddepcontrol.launch_dependents;" ::: "memory"); }
__device__ __forceinline__ void fence_barrier_init() { asm volatile("fence.mbarrier_init.release.cluster;" ::: "memory"); }
__device__ __forceinline__ void fence_proxy_async() { asm volatile("fence.proxy.async.shared::cta;" ::: "memory"); }
__device__ __forceinline__ uint64_t make_desc(uint32_t saddr, uint32_t lbo, uint32_t sbo, uint32_t swz) {
    return (uint64_t)((saddr & 0x3FFFF) >> 4) | ((uint64_t)((lbo & 0x3FFFF) >> 4) << 16) |
           ((uint64_t)((sbo & 0x3FFFF) >> 4) << 32) | ((uint64_t)swz << 62);
}
#define WG_FENCE() asm volatile("wgmma.fence.sync.aligned;" ::: "memory")
#define WG_COMMIT() asm volatile("wgmma.commit_group.sync.aligned;" ::: "memory")
template <int N> __device__ __forceinline__ void wg_wait() { asm volatile("wgmma.wait_group.sync.aligned %0;" :: "n"(N) : "memory"); }
template <int N> __device__ __forceinline__ void fence_regs(float (&d)[N]) {
#pragma unroll
    for (int i = 0; i < N; i++) asm volatile("" : "+f"(d[i]) :: "memory");
}
__device__ __forceinline__ float ex2f(float x) { float y; asm("ex2.approx.ftz.f32 %0, %1;" : "=f"(y) : "f"(x)); return y; }
__device__ __forceinline__ float tanh_fast(float x) { float y; asm("tanh.approx.f32 %0, %1;" : "=f"(y) : "f"(x)); return y; }
__device__ __forceinline__ uint32_t pack_bf16(float lo, float hi) { uint32_t r; asm("cvt.rn.bf16x2.f32 %0, %1, %2;" : "=r"(r) : "f"(hi), "f"(lo)); return r; }
__device__ __forceinline__ float bf_lo(uint32_t u) { return __uint_as_float(u << 16); }
__device__ __forceinline__ float bf_hi(uint32_t u) { return __uint_as_float(u & 0xFFFF0000u); }
__device__ __forceinline__ uint32_t hfma2(uint32_t a, uint32_t b, uint32_t c) { uint32_t r; asm("fma.rn.f16x2 %0, %1, %2, %3;" : "=r"(r) : "r"(a), "r"(b), "r"(c)); return r; }
__device__ __forceinline__ uint32_t hmul2(uint32_t a, uint32_t b) { uint32_t r; asm("mul.rn.f16x2 %0, %1, %2;" : "=r"(r) : "r"(a), "r"(b)); return r; }
__device__ __forceinline__ unsigned int ld_acquire(const unsigned int* p) { unsigned int v; asm volatile("ld.acquire.gpu.u32 %0, [%1];" : "=r"(v) : "l"(p) : "memory"); return v; }
__device__ __forceinline__ void red_release(unsigned int* p) { asm volatile("red.release.gpu.global.add.u32 [%0], 1;" :: "l"(p) : "memory"); }
__device__ __forceinline__ float warp_sum(float v) {
#pragma unroll
    for (int o = 16; o; o >>= 1) v += __shfl_xor_sync(0xffffffffu, v, o);
    return v;
}
__device__ __forceinline__ float warp_max(float v) {
#pragma unroll
    for (int o = 16; o; o >>= 1) v = fmaxf(v, __shfl_xor_sync(0xffffffffu, v, o));
    return v;
}

__device__ __forceinline__ void wgmma_ss_n64(float (&d)[32], uint64_t adesc, uint64_t bdesc, int scale_d) {
    asm volatile("{\n.reg .pred p;\nsetp.ne.b32 p, %34, 0;\n"
      "wgmma.mma_async.sync.aligned.m64n64k16.f32.bf16.bf16 {%0,%1,%2,%3,%4,%5,%6,%7,%8,%9,%10,%11,%12,%13,%14,%15,%16,%17,%18,%19,%20,%21,%22,%23,%24,%25,%26,%27,%28,%29,%30,%31}, %32, %33, p, 1, 1, 0, 1;\n}"
      : "+f"(d[0]), "+f"(d[1]), "+f"(d[2]), "+f"(d[3]), "+f"(d[4]), "+f"(d[5]), "+f"(d[6]), "+f"(d[7]), "+f"(d[8]), "+f"(d[9]), "+f"(d[10]), "+f"(d[11]), "+f"(d[12]), "+f"(d[13]), "+f"(d[14]), "+f"(d[15]), "+f"(d[16]), "+f"(d[17]), "+f"(d[18]), "+f"(d[19]), "+f"(d[20]), "+f"(d[21]), "+f"(d[22]), "+f"(d[23]), "+f"(d[24]), "+f"(d[25]), "+f"(d[26]), "+f"(d[27]), "+f"(d[28]), "+f"(d[29]), "+f"(d[30]), "+f"(d[31])
      : "l"(adesc), "l"(bdesc), "r"(scale_d));
}
__device__ __forceinline__ void wgmma_ss_n96(float (&d)[48], uint64_t adesc, uint64_t bdesc, int scale_d) {
    asm volatile("{\n.reg .pred p;\nsetp.ne.b32 p, %50, 0;\n"
      "wgmma.mma_async.sync.aligned.m64n96k16.f32.bf16.bf16 {%0,%1,%2,%3,%4,%5,%6,%7,%8,%9,%10,%11,%12,%13,%14,%15,%16,%17,%18,%19,%20,%21,%22,%23,%24,%25,%26,%27,%28,%29,%30,%31,%32,%33,%34,%35,%36,%37,%38,%39,%40,%41,%42,%43,%44,%45,%46,%47}, %48, %49, p, 1, 1, 0, 1;\n}"
      : "+f"(d[0]), "+f"(d[1]), "+f"(d[2]), "+f"(d[3]), "+f"(d[4]), "+f"(d[5]), "+f"(d[6]), "+f"(d[7]), "+f"(d[8]), "+f"(d[9]), "+f"(d[10]), "+f"(d[11]), "+f"(d[12]), "+f"(d[13]), "+f"(d[14]), "+f"(d[15]), "+f"(d[16]), "+f"(d[17]), "+f"(d[18]), "+f"(d[19]), "+f"(d[20]), "+f"(d[21]), "+f"(d[22]), "+f"(d[23]), "+f"(d[24]), "+f"(d[25]), "+f"(d[26]), "+f"(d[27]), "+f"(d[28]), "+f"(d[29]), "+f"(d[30]), "+f"(d[31]), "+f"(d[32]), "+f"(d[33]), "+f"(d[34]), "+f"(d[35]), "+f"(d[36]), "+f"(d[37]), "+f"(d[38]), "+f"(d[39]), "+f"(d[40]), "+f"(d[41]), "+f"(d[42]), "+f"(d[43]), "+f"(d[44]), "+f"(d[45]), "+f"(d[46]), "+f"(d[47])
      : "l"(adesc), "l"(bdesc), "r"(scale_d));
}
__device__ __forceinline__ void wgmma_ss_n128(float (&d)[64], uint64_t adesc, uint64_t bdesc, int scale_d) {
    asm volatile("{\n.reg .pred p;\nsetp.ne.b32 p, %66, 0;\n"
      "wgmma.mma_async.sync.aligned.m64n128k16.f32.bf16.bf16 {%0,%1,%2,%3,%4,%5,%6,%7,%8,%9,%10,%11,%12,%13,%14,%15,%16,%17,%18,%19,%20,%21,%22,%23,%24,%25,%26,%27,%28,%29,%30,%31,%32,%33,%34,%35,%36,%37,%38,%39,%40,%41,%42,%43,%44,%45,%46,%47,%48,%49,%50,%51,%52,%53,%54,%55,%56,%57,%58,%59,%60,%61,%62,%63}, %64, %65, p, 1, 1, 0, 1;\n}"
      : "+f"(d[0]), "+f"(d[1]), "+f"(d[2]), "+f"(d[3]), "+f"(d[4]), "+f"(d[5]), "+f"(d[6]), "+f"(d[7]), "+f"(d[8]), "+f"(d[9]), "+f"(d[10]), "+f"(d[11]), "+f"(d[12]), "+f"(d[13]), "+f"(d[14]), "+f"(d[15]), "+f"(d[16]), "+f"(d[17]), "+f"(d[18]), "+f"(d[19]), "+f"(d[20]), "+f"(d[21]), "+f"(d[22]), "+f"(d[23]), "+f"(d[24]), "+f"(d[25]), "+f"(d[26]), "+f"(d[27]), "+f"(d[28]), "+f"(d[29]), "+f"(d[30]), "+f"(d[31]), "+f"(d[32]), "+f"(d[33]), "+f"(d[34]), "+f"(d[35]), "+f"(d[36]), "+f"(d[37]), "+f"(d[38]), "+f"(d[39]), "+f"(d[40]), "+f"(d[41]), "+f"(d[42]), "+f"(d[43]), "+f"(d[44]), "+f"(d[45]), "+f"(d[46]), "+f"(d[47]), "+f"(d[48]), "+f"(d[49]), "+f"(d[50]), "+f"(d[51]), "+f"(d[52]), "+f"(d[53]), "+f"(d[54]), "+f"(d[55]), "+f"(d[56]), "+f"(d[57]), "+f"(d[58]), "+f"(d[59]), "+f"(d[60]), "+f"(d[61]), "+f"(d[62]), "+f"(d[63])
      : "l"(adesc), "l"(bdesc), "r"(scale_d));
}
__device__ __forceinline__ void wgmma_ss_n192(float (&d)[96], uint64_t adesc, uint64_t bdesc, int scale_d) {
    asm volatile("{\n.reg .pred p;\nsetp.ne.b32 p, %98, 0;\n"
      "wgmma.mma_async.sync.aligned.m64n192k16.f32.bf16.bf16 {%0,%1,%2,%3,%4,%5,%6,%7,%8,%9,%10,%11,%12,%13,%14,%15,%16,%17,%18,%19,%20,%21,%22,%23,%24,%25,%26,%27,%28,%29,%30,%31,%32,%33,%34,%35,%36,%37,%38,%39,%40,%41,%42,%43,%44,%45,%46,%47,%48,%49,%50,%51,%52,%53,%54,%55,%56,%57,%58,%59,%60,%61,%62,%63,%64,%65,%66,%67,%68,%69,%70,%71,%72,%73,%74,%75,%76,%77,%78,%79,%80,%81,%82,%83,%84,%85,%86,%87,%88,%89,%90,%91,%92,%93,%94,%95}, %96, %97, p, 1, 1, 0, 1;\n}"
      : "+f"(d[0]), "+f"(d[1]), "+f"(d[2]), "+f"(d[3]), "+f"(d[4]), "+f"(d[5]), "+f"(d[6]), "+f"(d[7]), "+f"(d[8]), "+f"(d[9]), "+f"(d[10]), "+f"(d[11]), "+f"(d[12]), "+f"(d[13]), "+f"(d[14]), "+f"(d[15]), "+f"(d[16]), "+f"(d[17]), "+f"(d[18]), "+f"(d[19]), "+f"(d[20]), "+f"(d[21]), "+f"(d[22]), "+f"(d[23]), "+f"(d[24]), "+f"(d[25]), "+f"(d[26]), "+f"(d[27]), "+f"(d[28]), "+f"(d[29]), "+f"(d[30]), "+f"(d[31]), "+f"(d[32]), "+f"(d[33]), "+f"(d[34]), "+f"(d[35]), "+f"(d[36]), "+f"(d[37]), "+f"(d[38]), "+f"(d[39]), "+f"(d[40]), "+f"(d[41]), "+f"(d[42]), "+f"(d[43]), "+f"(d[44]), "+f"(d[45]), "+f"(d[46]), "+f"(d[47]), "+f"(d[48]), "+f"(d[49]), "+f"(d[50]), "+f"(d[51]), "+f"(d[52]), "+f"(d[53]), "+f"(d[54]), "+f"(d[55]), "+f"(d[56]), "+f"(d[57]), "+f"(d[58]), "+f"(d[59]), "+f"(d[60]), "+f"(d[61]), "+f"(d[62]), "+f"(d[63]), "+f"(d[64]), "+f"(d[65]), "+f"(d[66]), "+f"(d[67]), "+f"(d[68]), "+f"(d[69]), "+f"(d[70]), "+f"(d[71]), "+f"(d[72]), "+f"(d[73]), "+f"(d[74]), "+f"(d[75]), "+f"(d[76]), "+f"(d[77]), "+f"(d[78]), "+f"(d[79]), "+f"(d[80]), "+f"(d[81]), "+f"(d[82]), "+f"(d[83]), "+f"(d[84]), "+f"(d[85]), "+f"(d[86]), "+f"(d[87]), "+f"(d[88]), "+f"(d[89]), "+f"(d[90]), "+f"(d[91]), "+f"(d[92]), "+f"(d[93]), "+f"(d[94]), "+f"(d[95])
      : "l"(adesc), "l"(bdesc), "r"(scale_d));
}
__device__ __forceinline__ void qk_wgmma_n64(float (&d)[32], const uint32_t (&a)[4], uint64_t desc) {
    asm volatile("wgmma.mma_async.sync.aligned.m64n64k16.f32.bf16.bf16 {%0,%1,%2,%3,%4,%5,%6,%7,%8,%9,%10,%11,%12,%13,%14,%15,%16,%17,%18,%19,%20,%21,%22,%23,%24,%25,%26,%27,%28,%29,%30,%31}, {%32,%33,%34,%35}, %36, 0, 1, 1, 0;"
      : "=f"(d[0]), "=f"(d[1]), "=f"(d[2]), "=f"(d[3]), "=f"(d[4]), "=f"(d[5]), "=f"(d[6]), "=f"(d[7]), "=f"(d[8]), "=f"(d[9]), "=f"(d[10]), "=f"(d[11]), "=f"(d[12]), "=f"(d[13]), "=f"(d[14]), "=f"(d[15]), "=f"(d[16]), "=f"(d[17]), "=f"(d[18]), "=f"(d[19]), "=f"(d[20]), "=f"(d[21]), "=f"(d[22]), "=f"(d[23]), "=f"(d[24]), "=f"(d[25]), "=f"(d[26]), "=f"(d[27]), "=f"(d[28]), "=f"(d[29]), "=f"(d[30]), "=f"(d[31])
      : "r"(a[0]), "r"(a[1]), "r"(a[2]), "r"(a[3]), "l"(desc));
}

__device__ __forceinline__ void pv_wgmma(float (&d)[12], uint32_t a0, uint32_t a1, uint32_t a2, uint32_t a3, uint64_t desc) {
    asm volatile("wgmma.mma_async.sync.aligned.m64n24k16.f32.bf16.bf16 {%0,%1,%2,%3,%4,%5,%6,%7,%8,%9,%10,%11}, {%12,%13,%14,%15}, %16, 1, 1, 1, 1;"
      : "+f"(d[0]), "+f"(d[1]), "+f"(d[2]), "+f"(d[3]), "+f"(d[4]), "+f"(d[5]), "+f"(d[6]), "+f"(d[7]), "+f"(d[8]), "+f"(d[9]), "+f"(d[10]), "+f"(d[11])
      : "r"(a0), "r"(a1), "r"(a2), "r"(a3), "l"(desc));
}

__device__ __forceinline__ void tile_of(int bid, int& mb, int& nt) {
    int grp = bid >> 4, in = bid & 15;
    mb = (grp >> 1) * 4 + (in >> 2);
    nt = (grp & 1) * 4 + (in & 3);
}

constexpr int K1_STAGES = 5, K1_STAGE = 16384 + 24576;
constexpr int K1_BAR = K1_STAGES * K1_STAGE, K1_RS = K1_BAR + 128, K1_CS = K1_RS + 1024, K1_SMEM = K1_CS + 768;

__device__ __forceinline__ float2 row_stats_x(const __nv_bfloat16* x, int row, int lane) {
    const uint4* p = (const uint4*)(x + (size_t)row * DM);
    uint4 a = __ldg(p + lane), b = __ldg(p + 32 + lane);
    float v[16];
    v[0] = bf_lo(a.x); v[1] = bf_hi(a.x); v[2] = bf_lo(a.y); v[3] = bf_hi(a.y);
    v[4] = bf_lo(a.z); v[5] = bf_hi(a.z); v[6] = bf_lo(a.w); v[7] = bf_hi(a.w);
    v[8] = bf_lo(b.x); v[9] = bf_hi(b.x); v[10] = bf_lo(b.y); v[11] = bf_hi(b.y);
    v[12] = bf_lo(b.z); v[13] = bf_hi(b.z); v[14] = bf_lo(b.w); v[15] = bf_hi(b.w);
    float s = 0.f;
#pragma unroll
    for (int i = 0; i < 16; i++) s += v[i];
    float mean = warp_sum(s) * (1.0f / DM);
    float q = 0.f;
#pragma unroll
    for (int i = 0; i < 16; i++) { float d = v[i] - mean; q = fmaf(d, d, q); }
    float var = warp_sum(q) * (1.0f / DM);
    float rstd = rsqrtf(var + 1e-5f);
    return make_float2(rstd, -mean * rstd);
}
__device__ __forceinline__ void colsum8(const __nv_bfloat16* w, int ld, int col, int k0, int nk, float (&s)[8]) {
#pragma unroll
    for (int i = 0; i < 8; i++) s[i] = 0.f;
    for (int k = k0; k < k0 + nk; k += 8) {
        uint4 u[8];
#pragma unroll
        for (int i = 0; i < 8; i++) u[i] = __ldg((const uint4*)(w + (size_t)(k + i) * ld + col));
#pragma unroll
        for (int i = 0; i < 8; i++) {
            s[0] += bf_lo(u[i].x); s[1] += bf_hi(u[i].x); s[2] += bf_lo(u[i].y); s[3] += bf_hi(u[i].y);
            s[4] += bf_lo(u[i].z); s[5] += bf_hi(u[i].z); s[6] += bf_lo(u[i].w); s[7] += bf_hi(u[i].w);
        }
    }
}
__device__ __forceinline__ bool wait_count(const unsigned int* p, unsigned int target, int lane) {
    int ok = 1;
    if (lane == 0) {
        int it = 0;
        while (ld_acquire(p) < target) { if (++it > (1 << 16)) { ok = 0; break; } __nanosleep(20); }
    }
    ok = __shfl_sync(0xffffffffu, ok, 0);
    return ok != 0;
}

__global__ void __launch_bounds__(384, 1)
qkv_kernel(const __grid_constant__ CUtensorMap tm_x, const __grid_constant__ CUtensorMap tm_w,
           const __nv_bfloat16* __restrict__ x, const __nv_bfloat16* __restrict__ wqkv) {
    extern __shared__ __align__(1024) unsigned char smem[];
    const uint32_t sb = smem_u32(smem);
    const int tid = threadIdx.x, warp = tid >> 5, lane = tid & 31;
    TL(0);
    int mb, nt;
    tile_of(blockIdx.x, mb, nt);
    const uint32_t full = sb + K1_BAR, empty = full + 40, auxb = full + 80;
    if (tid == 0) {
        prefetch_tmap(&tm_x); prefetch_tmap(&tm_w);
        for (int i = 0; i < K1_STAGES; i++) { mbar_init(full + 8 * i, 1); mbar_init(empty + 8 * i, 8); }
        mbar_init(auxb, 3);
        fence_barrier_init();
    }
    __syncthreads();
    pdl_launch();
    if (warp == 0) {
        if (lane == 0) {
            for (int kb = 0; kb < 8; kb++) {
                int s = kb % K1_STAGES;
                if (kb >= K1_STAGES) mbar_wait(empty + 8 * s, 0);
                mbar_expect(full + 8 * s, K1_STAGE);
                tma2d(sb + s * K1_STAGE, &tm_x, kb * 64, mb * 128, full + 8 * s);
                tma3d(sb + s * K1_STAGE + 16384, &tm_w, 0, kb * 64, nt * 3, full + 8 * s);
            }
        }
    } else if (warp < 4) {
        float2* s_rs = (float2*)(smem + K1_RS);
        float* s_cs = (float*)(smem + K1_CS);
        if (warp < 3) {
            int r0 = mb * 128 + nt * 16 + (warp - 1) * 8;
#pragma unroll 2
            for (int i = 0; i < 8; i++) {
                float2 st = row_stats_x(x, r0 + i, lane);
                if (lane == 0) g_rowstat1[r0 + i] = st;
            }
            __threadfence();
            __syncwarp();
            if (lane == 0) red_release(&g_cnt[mb]);
        } else {
            if (lane < 24) {
                float s[8];
                colsum8(wqkv, 1536, nt * 192 + lane * 8, mb * 32, 32, s);
                float4* d = (float4*)(g_cs1_part + mb * 1536 + nt * 192 + lane * 8);
                d[0] = make_float4(s[0], s[1], s[2], s[3]);
                d[1] = make_float4(s[4], s[5], s[6], s[7]);
            }
            __threadfence();
            __syncwarp();
            if (lane == 0) red_release(&g_cnt[16 + nt]);
        }
        if (warp == 1) {
            if (wait_count(&g_cnt[mb], 16, lane)) {
#pragma unroll
                for (int i = 0; i < 4; i++) s_rs[lane + 32 * i] = __ldcg(&g_rowstat1[mb * 128 + lane + 32 * i]);
            } else {
                for (int i = 0; i < 128; i++) {
                    float2 st = row_stats_x(x, mb * 128 + i, lane);
                    if (lane == 0) s_rs[i] = st;
                }
            }
        } else {
            int c0 = (warp - 2) * 96;
            if (wait_count(&g_cnt[16 + nt], 16, lane)) {
#pragma unroll
                for (int i = 0; i < 3; i++) {
                    float s = 0.f;
#pragma unroll
                    for (int p = 0; p < 16; p++) s += __ldcg(&g_cs1_part[p * 1536 + nt * 192 + c0 + lane + 32 * i]);
                    s_cs[c0 + lane + 32 * i] = s;
                }
            } else if (lane < 12) {
                float s[8];
                colsum8(wqkv, 1536, nt * 192 + c0 + lane * 8, 0, 512, s);
#pragma unroll
                for (int i = 0; i < 8; i++) s_cs[c0 + lane * 8 + i] = s[i];
            }
        }
        __syncwarp();
        if (lane == 0) mbar_arrive(auxb);
    } else {
        const int wgi = (warp >> 2) - 1, ww = warp & 3;
        float acc[96];
#pragma unroll 1
        for (int kb = 0; kb < 8; kb++) {
            int s = kb % K1_STAGES;
            mbar_wait(full + 8 * s, (kb / K1_STAGES) & 1);
            uint64_t ad = make_desc(sb + s * K1_STAGE + wgi * 8192, 16, 1024, 1);
            uint64_t bd = make_desc(sb + s * K1_STAGE + 16384, 8192, 1024, 1);
            WG_FENCE();
#pragma unroll
            for (int k = 0; k < 4; k++) wgmma_ss_n192(acc, ad + k * 2, bd + k * 128, (kb | k) != 0);
            WG_COMMIT();
            if (kb > 0) {
                wg_wait<1>();
                if (lane == 0) mbar_arrive(empty + 8 * ((kb - 1) % K1_STAGES));
            }
        }
        wg_wait<0>();
        fence_regs(acc);
        TL(1);
        mbar_wait(auxb, 0);
        const float2* s_rs = (const float2*)(smem + K1_RS);
        const float* s_cs = (const float*)(smem + K1_CS);
        const int g = lane >> 2, t = lane & 3;
        const int rl = wgi * 64 + ww * 16 + g;
        const float2 st0 = s_rs[rl], st1 = s_rs[rl + 8];
        const float QS = 0.25f * 1.4426950408889634f;
        const int jrow = mb * 16 + wgi * 8 + ww * 2;
        const int rg16 = mb * 8 + wgi * 4 + ww;
        uint32_t* out = (uint32_t*)g_qkv;
#pragma unroll
        for (int hh = 0; hh < 12; hh++) {
            const int col0 = nt * 192 + hh * 16;
            const int which = col0 >> 9, head = (col0 & 511) >> 4;
            const float sc = (which == 0) ? QS : 1.0f;
            const float a0 = st0.x * sc, b0 = st0.y * sc, a1 = st1.x * sc, b1 = st1.y * sc;
            float n0 = 0.f, n1 = 0.f;
#pragma unroll
            for (int c = 0; c < 2; c++) {
                const int j = hh * 2 + c;
                const float2 cs = *(const float2*)(s_cs + 8 * j + 2 * t);
                float v00 = fmaf(a0, acc[4 * j], b0 * cs.x), v01 = fmaf(a0, acc[4 * j + 1], b0 * cs.y);
                float v10 = fmaf(a1, acc[4 * j + 2], b1 * cs.x), v11 = fmaf(a1, acc[4 * j + 3], b1 * cs.y);
                size_t o = ((size_t)((which * NH + head) * 2 + c) * 256 + jrow) * 32 + lane;
                out[o] = pack_bf16(v00, v01);
                out[o + 32] = pack_bf16(v10, v11);
                if (which < 2) {
                    n0 = fmaf(v00, v00, fmaf(v01, v01, n0));
                    n1 = fmaf(v10, v10, fmaf(v11, v11, n1));
                } else {
                    n0 = fmaxf(n0, fmaxf(fabsf(v00), fabsf(v01)));
                    n1 = fmaxf(n1, fmaxf(fabsf(v10), fabsf(v11)));
                    if (v00 != v00 || v01 != v01 || v10 != v10 || v11 != v11) n0 = __int_as_float(0x7f800000);
                }
            }
            float m;
            if (which < 2) {
                n0 += __shfl_xor_sync(0xffffffffu, n0, 1); n1 += __shfl_xor_sync(0xffffffffu, n1, 1);
                n0 += __shfl_xor_sync(0xffffffffu, n0, 2); n1 += __shfl_xor_sync(0xffffffffu, n1, 2);
                m = n0 + n1 - fminf(n0, n1);
                if (!(m == m)) m = __int_as_float(0x7f800000);
                m = fmaxf(m, __shfl_xor_sync(0xffffffffu, m, 4));
                m = fmaxf(m, __shfl_xor_sync(0xffffffffu, m, 8));
                m = fmaxf(m, __shfl_xor_sync(0xffffffffu, m, 16));
            } else {
                m = warp_max(fmaxf(n0, n1));
            }
            if (lane == 0) g_nrm[(which * NH + head) * 128 + rg16] = m;
        }
        TL(2);
    }
}

constexpr int AT_K = 0, AT_V = 65536, AT_ONES = 131072, AT_BAR = 163840, AT_SMEM = AT_BAR + 128;
#define POLY_MASK 0xAD6A

__device__ __forceinline__ uint32_t exp2_pair_poly(float x0, float x1) {
    uint32_t t0 = __float_as_uint(x0 + 32895.0f);
    uint32_t t1 = __float_as_uint(x1 + 32895.0f);
    uint32_t gd = __byte_perm(t0, t1, 0x6420);
    uint32_t wm = __byte_perm(t0, t1, 0x5612);
    uint32_t v = hfma2(gd, 0x71477147u, 0x354f354fu);
    uint32_t z = hmul2(v, gd);
    return (wm >> 1) + z;
}
__device__ __forceinline__ uint32_t exp2_pair_mufu(float x0, float x1) { return pack_bf16(ex2f(x0), ex2f(x1)); }
template <uint32_t MASK>
__device__ __forceinline__ void exp_blocks(const float (&s)[32], uint32_t (&p)[16]) {
#pragma unroll
    for (int b = 0; b < 8; b++) {
        if ((MASK >> b) & 1) {
            p[2 * b] = exp2_pair_poly(s[4 * b], s[4 * b + 1]);
            p[2 * b + 1] = exp2_pair_poly(s[4 * b + 2], s[4 * b + 3]);
        } else {
            p[2 * b] = exp2_pair_mufu(s[4 * b], s[4 * b + 1]);
            p[2 * b + 1] = exp2_pair_mufu(s[4 * b + 2], s[4 * b + 3]);
        }
    }
}
#define PV4(P) _Pragma("unroll") for (int i = 0; i < 4; i++) { pv_wgmma(o, P[4 * i], P[4 * i + 1], P[4 * i + 2], P[4 * i + 3], vd); vd += 16; }

__device__ __forceinline__ void attn_store(float (&o)[12], int row0, int head, int lane) {
    float l0 = __shfl_sync(0xffffffffu, o[8], lane & 28);
    float l1 = __shfl_sync(0xffffffffu, o[10], lane & 28);
    float r0 = 1.0f / l0, r1 = 1.0f / l1;
    uint32_t* op = (uint32_t*)g_ao;
    int mb = row0 >> 7, rg = (row0 & 127) >> 3;
    int kb = head >> 2, kc = (head & 3) * 2;
    size_t base = (((size_t)(mb * 8 + kb) * 8 + kc) * 16 + rg) * 32 + lane;
    op[base] = pack_bf16(o[0] * r0, o[1] * r0);
    op[base + 32] = pack_bf16(o[2] * r1, o[3] * r1);
    op[base + 16 * 32] = pack_bf16(o[4] * r0, o[5] * r0);
    op[base + 16 * 32 + 32] = pack_bf16(o[6] * r1, o[7] * r1);
}

__device__ __forceinline__ void attn_load_q(uint32_t (&q)[4], const __nv_bfloat16* gq, int row0, int lane) {
    const uint32_t* qp = (const uint32_t*)gq;
    int j0 = row0 >> 3;
    q[0] = __ldcg(qp + (0 * 256 + j0) * 32 + lane);
    q[1] = __ldcg(qp + (0 * 256 + j0 + 1) * 32 + lane);
    q[2] = __ldcg(qp + (1 * 256 + j0) * 32 + lane);
    q[3] = __ldcg(qp + (1 * 256 + j0 + 1) * 32 + lane);
}

__device__ __forceinline__ void attn_tile_safe(const uint32_t (&q)[4], uint64_t kd, uint64_t vd, int row0, int head, int lane) {
    float o[12];
#pragma unroll
    for (int i = 0; i < 12; i++) o[i] = 0.f;
    float m0 = -INFINITY, m1 = -INFINITY;
    fence_regs(o);
#pragma unroll 1
    for (int j = 0; j < 32; j++) {
        float s[32];
        uint32_t p[16];
        WG_FENCE();
        qk_wgmma_n64(s, q, kd); kd += 64;
        WG_COMMIT();
        wg_wait<0>();
        fence_regs(s);
        fence_regs(o);
        float x0 = m0, x1 = m1;
#pragma unroll
        for (int b = 0; b < 8; b++) {
            x0 = fmaxf(x0, fmaxf(s[4 * b], s[4 * b + 1]));
            x1 = fmaxf(x1, fmaxf(s[4 * b + 2], s[4 * b + 3]));
        }
        x0 = fmaxf(x0, __shfl_xor_sync(0xffffffffu, x0, 1)); x0 = fmaxf(x0, __shfl_xor_sync(0xffffffffu, x0, 2));
        x1 = fmaxf(x1, __shfl_xor_sync(0xffffffffu, x1, 1)); x1 = fmaxf(x1, __shfl_xor_sync(0xffffffffu, x1, 2));
        float al0 = ex2f(m0 - x0), al1 = ex2f(m1 - x1);
        m0 = x0; m1 = x1;
#pragma unroll
        for (int i = 0; i < 3; i++) { o[4 * i] *= al0; o[4 * i + 1] *= al0; o[4 * i + 2] *= al1; o[4 * i + 3] *= al1; }
#pragma unroll
        for (int b = 0; b < 8; b++) {
            p[2 * b] = exp2_pair_mufu(s[4 * b] - m0, s[4 * b + 1] - m0);
            p[2 * b + 1] = exp2_pair_mufu(s[4 * b + 2] - m1, s[4 * b + 3] - m1);
        }
        fence_regs(o);
        WG_FENCE();
        PV4(p);
        WG_COMMIT();
        wg_wait<0>();
        fence_regs(o);
    }
    attn_store(o, row0, head, lane);
}

__global__ void __launch_bounds__(512, 1)
attn_kernel(const __nv_bfloat16* __restrict__ wg_, const __nv_bfloat16* __restrict__ wu_,
            const __nv_bfloat16* __restrict__ wo_, const __nv_bfloat16* __restrict__ wd_) {
    extern __shared__ __align__(1024) unsigned char smem[];
    const uint32_t sb = smem_u32(smem);
    const int tid = threadIdx.x, wg = tid >> 7, warp = (tid >> 5) & 3, lane = tid & 31;
    pdl_launch();
    if (blockIdx.x >= 128) {
        const int e = blockIdx.x - 128;
        const __nv_bfloat16* w = (e < 2) ? wg_ : wu_;
        float* red = (float*)smem;
        const int cgrp = tid & 127, kq = tid >> 7;
        if (cgrp < 112) {
            float s[8];
            colsum8(w, FF, (e & 1) * 896 + cgrp * 8, kq * 128, 128, s);
#pragma unroll
            for (int i = 0; i < 8; i++) red[kq * 896 + cgrp * 8 + i] = s[i];
        }
        __syncthreads();
        for (int c = tid; c < 896; c += 512)
            g_cs2[(e >> 1) * FF + (e & 1) * 896 + c] = red[c] + red[896 + c] + red[1792 + c] + red[2688 + c];
        if (tid < 32) {
            const char* p0 = (const char*)wo_ + e * (DM * DM * 2 / 4);
            for (int i = lane; i < 32; i += 32)
                asm volatile("cp.async.bulk.prefetch.L2.global [%0], %1;" :: "l"(p0 + i * 4096), "r"(4096) : "memory");
            const char* p1 = (const char*)wd_ + e * (FF * DM * 2 / 4);
            for (int i = lane; i < 112; i += 32)
                asm volatile("cp.async.bulk.prefetch.L2.global [%0], %1;" :: "l"(p1 + i * 4096), "r"(4096) : "memory");
        }
        return;
    }
    const int head = blockIdx.x >> 2, qq = blockIdx.x & 3;
    const __nv_bfloat16* gq = g_qkv + (size_t)head * (S_LEN * 16);
    const __nv_bfloat16* gk = g_qkv + (size_t)(NH + head) * (S_LEN * 16);
    const __nv_bfloat16* gv = g_qkv + (size_t)(2 * NH + head) * (S_LEN * 16);
    if (tid == 0) {
        for (int i = 0; i < 8; i++) mbar_init(sb + AT_BAR + 8 * i, 1);
        fence_barrier_init();
    }
    {
        uint4 one = make_uint4(0x00003F80u, 0, 0, 0);
#pragma unroll
        for (int i = 0; i < 4; i++) *(uint4*)(smem + AT_ONES + (i * 512 + tid) * 16) = one;
        fence_proxy_async();
    }
    __syncthreads();
    TL(3);
    pdl_wait();
    TL(4);
    if (tid == 0) {
        for (int i = 0; i < 8; i++) {
            uint32_t bar = sb + AT_BAR + 8 * i;
            mbar_expect(bar, 16384);
            bulk_g2s(sb + AT_K + i * 4096, gk + i * 2048, 4096, bar);
            bulk_g2s(sb + AT_K + 32768 + i * 4096, gk + 16384 + i * 2048, 4096, bar);
            bulk_g2s(sb + AT_V + i * 4096, gv + i * 2048, 4096, bar);
            bulk_g2s(sb + AT_V + 32768 + i * 4096, gv + 16384 + i * 2048, 4096, bar);
        }
    }
    bool fast;
    {
        const float* nq = g_nrm + (0 * NH + head) * 128 + qq * 32;
        const float* nk = g_nrm + (1 * NH + head) * 128;
        const float* nv = g_nrm + (2 * NH + head) * 128;
        float4 k4 = __ldcg((const float4*)nk + lane), v4 = __ldcg((const float4*)nv + lane);
        float qm = warp_max(__ldcg(nq + lane));
        float km = warp_max(fmaxf(fmaxf(k4.x, k4.y), fmaxf(k4.z, k4.w)));
        float vm = warp_max(fmaxf(fmaxf(v4.x, v4.y), fmaxf(v4.z, v4.w)));
        fast = (qm * km <= 3500.0f) && (vm <= 1.0e12f);
    }
    const uint64_t kdesc0 = make_desc(sb + AT_K, 32768, 128, 0);
    const uint64_t vdesc0 = make_desc(sb + AT_V, 128, 32768, 0);
    if (!fast) {
        for (int i = 0; i < 8; i++) mbar_wait(sb + AT_BAR + 8 * i, 0);
#pragma unroll 1
        for (int tile = 0; tile < 2; tile++) {
            const int row0 = qq * 512 + (tile * 4 + wg) * 64 + warp * 16;
            uint32_t q[4];
            attn_load_q(q, gq, row0, lane);
            attn_tile_safe(q, kdesc0, vdesc0, row0, head, lane);
        }
        return;
    }
#pragma unroll 1
    for (int tile = 0; tile < 2; tile++) {
        const int row0 = qq * 512 + (tile * 4 + wg) * 64 + warp * 16;
        uint32_t q[4];
        attn_load_q(q, gq, row0, lane);
        float o[12];
#pragma unroll
        for (int i = 0; i < 12; i++) o[i] = 0.f;
        fence_regs(o);
        float sa[32];
        uint32_t pa[16];
        uint64_t kd = kdesc0, vd = vdesc0;
        if (tile == 0) mbar_wait(sb + AT_BAR, 0);
        WG_FENCE();
        qk_wgmma_n64(sa, q, kd); kd += 64;
        WG_COMMIT();
#pragma unroll 1
        for (int jj = 0; jj < 8; jj++) {
            if (tile == 0 && jj < 7) mbar_wait(sb + AT_BAR + 8 * (jj + 1), 0);
#pragma unroll
            for (int j = 0; j < 4; j++) {
                wg_wait<0>();
                fence_regs(sa);
                if (j & 1) exp_blocks<(POLY_MASK >> 8)>(sa, pa); else exp_blocks<(POLY_MASK & 255)>(sa, pa);
                WG_FENCE();
                qk_wgmma_n64(sa, q, kd); kd += 64;
                PV4(pa);
                WG_COMMIT();
            }
        }
        wg_wait<0>();
        fence_regs(o);
        fence_regs(sa);
        attn_store(o, row0, head, lane);
    }
    TL(5);
}

constexpr int K3_STAGE = 16384 + 8192, K3_BAR = 8 * K3_STAGE, K3_SMEM = K3_BAR + 128;

__global__ void __launch_bounds__(384, 1)
wo_kernel(const __grid_constant__ CUtensorMap tm_w, const __nv_bfloat16* __restrict__ x) {
    extern __shared__ __align__(1024) unsigned char smem[];
    const uint32_t sb = smem_u32(smem);
    const int tid = threadIdx.x, warp = tid >> 5, lane = tid & 31;
    int mb, nt;
    tile_of(blockIdx.x, mb, nt);
    TL(6);
    const uint32_t full = sb + K3_BAR;
    if (tid == 0) {
        prefetch_tmap(&tm_w);
        for (int i = 0; i < 8; i++) mbar_init(full + 8 * i, 1);
        fence_barrier_init();
    }
    __syncthreads();
    pdl_launch();
    if (warp == 0) {
        if (lane == 0) {
            for (int kb = 0; kb < 8; kb++) {
                mbar_expect(full + 8 * kb, K3_STAGE);
                tma2d(sb + kb * K3_STAGE + 16384, &tm_w, nt * 64, kb * 64, full + 8 * kb);
            }
            pdl_wait();
            for (int kb = 0; kb < 8; kb++)
                bulk_g2s(sb + kb * K3_STAGE, g_ao + (size_t)(mb * 8 + kb) * 8192, 16384, full + 8 * kb);
            if (blockIdx.x == 0)
                for (int i = 0; i < 32; i++) g_cnt[i] = 0;
        }
    } else if (warp >= 4) {
        const int wgi = (warp >> 2) - 1, ww = warp & 3;
        const int g = lane >> 2, t = lane & 3;
        const int row = mb * 128 + wgi * 64 + ww * 16 + g;
        uint32_t xr[16];
        {
            const uint32_t* xp = (const uint32_t*)(x + (size_t)row * DM + nt * 64) + t;
#pragma unroll
            for (int j = 0; j < 8; j++) { xr[2 * j] = __ldg(xp + 4 * j); xr[2 * j + 1] = __ldg(xp + 8 * (DM / 2) + 4 * j); }
        }
        float acc[32];
#pragma unroll 1
        for (int kb = 0; kb < 8; kb++) {
            mbar_wait(full + 8 * kb, 0);
            uint64_t ad = make_desc(sb + kb * K3_STAGE + wgi * 1024, 2048, 128, 0);
            uint64_t bd = make_desc(sb + kb * K3_STAGE + 16384, 8192, 1024, 1);
            WG_FENCE();
#pragma unroll
            for (int k = 0; k < 4; k++) wgmma_ss_n64(acc, ad + k * 256, bd + k * 128, (kb | k) != 0);
            WG_COMMIT();
        }
        wg_wait<0>();
        fence_regs(acc);
        TL(7);
        pdl_wait();
        uint32_t* hp = (uint32_t*)g_h + ((size_t)(mb * 8 + nt) * 8 * 16 + wgi * 8 + ww * 2) * 32 + lane;
        float v0[16], v1[16];
        float s0 = 0.f, s1 = 0.f;
#pragma unroll
        for (int j = 0; j < 8; j++) {
            uint32_t u0 = pack_bf16(bf_lo(xr[2 * j]) + acc[4 * j], bf_hi(xr[2 * j]) + acc[4 * j + 1]);
            uint32_t u1 = pack_bf16(bf_lo(xr[2 * j + 1]) + acc[4 * j + 2], bf_hi(xr[2 * j + 1]) + acc[4 * j + 3]);
            hp[j * 16 * 32] = u0;
            hp[j * 16 * 32 + 32] = u1;
            v0[2 * j] = bf_lo(u0); v0[2 * j + 1] = bf_hi(u0);
            v1[2 * j] = bf_lo(u1); v1[2 * j + 1] = bf_hi(u1);
            s0 += v0[2 * j] + v0[2 * j + 1];
            s1 += v1[2 * j] + v1[2 * j + 1];
        }
        float m0 = s0 * (1.0f / 16), m1 = s1 * (1.0f / 16), q0 = 0.f, q1 = 0.f;
#pragma unroll
        for (int i = 0; i < 16; i++) {
            float d0 = v0[i] - m0, d1 = v1[i] - m1;
            q0 = fmaf(d0, d0, q0); q1 = fmaf(d1, d1, q1);
        }
#pragma unroll
        for (int st = 0; st < 2; st++) {
            float hn = st ? 16.f : 8.f;
            float om0 = __shfl_xor_sync(0xffffffffu, m0, 1 << st), oq0 = __shfl_xor_sync(0xffffffffu, q0, 1 << st);
            float om1 = __shfl_xor_sync(0xffffffffu, m1, 1 << st), oq1 = __shfl_xor_sync(0xffffffffu, q1, 1 << st);
            float d0 = om0 - m0, d1 = om1 - m1;
            q0 = q0 + oq0 + d0 * d0 * hn; q1 = q1 + oq1 + d1 * d1 * hn;
            m0 = 0.5f * (m0 + om0); m1 = 0.5f * (m1 + om1);
        }
        if (t == 0) {
            g_hstat[row * 8 + nt] = make_float2(m0, q0);
            g_hstat[(row + 8) * 8 + nt] = make_float2(m1, q1);
        }
        TL(8);
    }
}

constexpr int K4_STAGES = 3, K4_B = 131072, K4_BSTAGE = 32768, K4_BAR = K4_B + K4_STAGES * K4_BSTAGE;
constexpr int K4_RS = K4_BAR + 256, K4_CS = K4_RS + 1024, K4_SMEM = K4_CS + 448 * 4;

__device__ __forceinline__ float geglu(float gt, float up) {
    float u = gt * fmaf(gt * gt, 0.044715f * 0.7978845608028654f, 0.7978845608028654f);
    float hg = 0.5f * gt;
    return fmaf(hg, tanh_fast(u), hg) * up;
}
template <int NB>
__device__ __forceinline__ void k4_epilogue(const float* ag, const float* au, const float* s_cs, int cs_off, int jb0,
                                            float2 st0, float2 st1, int mb, int rgl, int lane) {
    const int t = lane & 3;
    uint32_t* gp = (uint32_t*)g_g;
#pragma unroll
    for (int j = 0; j < NB; j++) {
        const float2 cg = *(const float2*)(s_cs + cs_off + 8 * j + 2 * t);
        const float2 cu = *(const float2*)(s_cs + 224 + cs_off + 8 * j + 2 * t);
        float g00 = fmaf(st0.x, ag[4 * j], st0.y * cg.x), g01 = fmaf(st0.x, ag[4 * j + 1], st0.y * cg.y);
        float g10 = fmaf(st1.x, ag[4 * j + 2], st1.y * cg.x), g11 = fmaf(st1.x, ag[4 * j + 3], st1.y * cg.y);
        float u00 = fmaf(st0.x, au[4 * j], st0.y * cu.x), u01 = fmaf(st0.x, au[4 * j + 1], st0.y * cu.y);
        float u10 = fmaf(st1.x, au[4 * j + 2], st1.y * cu.x), u11 = fmaf(st1.x, au[4 * j + 3], st1.y * cu.y);
        const int jb = jb0 + j;
        size_t o = (((size_t)mb * 28 * 8 + jb) * 16 + rgl) * 32 + lane;
        gp[o] = pack_bf16(geglu(g00, u00), geglu(g01, u01));
        gp[o + 32] = pack_bf16(geglu(g10, u10), geglu(g11, u11));
    }
}

__global__ void __launch_bounds__(384, 1)
ffn1_kernel(const __grid_constant__ CUtensorMap tm_g, const __grid_constant__ CUtensorMap tm_u) {
    extern __shared__ __align__(1024) unsigned char smem[];
    const uint32_t sb = smem_u32(smem);
    const int tid = threadIdx.x, warp = tid >> 5, lane = tid & 31;
    int mb, nt;
    tile_of(blockIdx.x, mb, nt);
    TL(9);
    const uint32_t afull = sb + K4_BAR, full = afull + 64, empty = full + 32, auxb = empty + 32;
    if (tid == 0) {
        prefetch_tmap(&tm_g); prefetch_tmap(&tm_u);
        for (int i = 0; i < 8; i++) mbar_init(afull + 8 * i, 1);
        for (int i = 0; i < K4_STAGES; i++) { mbar_init(full + 8 * i, 1); mbar_init(empty + 8 * i, 8); }
        mbar_init(auxb, 3);
        fence_barrier_init();
    }
    __syncthreads();
    pdl_launch();
    if (warp < 4) {
        asm volatile("setmaxnreg.dec.sync.aligned.u32 56;");
        if (warp == 0) {
            if (lane == 0) {
                for (int it = 0; it < 16; it++) {
                    const int s = it % K4_STAGES, pass = it >> 3, kb = it & 7;
                    const int ng = pass ? 3 : 4, c0 = nt * 224 + pass * 128;
                    if (it >= K4_STAGES) mbar_wait(empty + 8 * s, ((it / K4_STAGES) - 1) & 1);
                    mbar_expect(full + 8 * s, ng * 8192);
                    const uint32_t dst = sb + K4_B + s * K4_BSTAGE;
                    for (int i = 0; i < ng; i++) {
                        tma2d(dst + i * 4096, &tm_g, c0 + i * 32, kb * 64, full + 8 * s);
                        tma2d(dst + 16384 + i * 4096, &tm_u, c0 + i * 32, kb * 64, full + 8 * s);
                    }
                    if (it == K4_STAGES - 1) {
                        pdl_wait();
                        for (int k2 = 0; k2 < 8; k2++) {
                            mbar_expect(afull + 8 * k2, 16384);
                            bulk_g2s(sb + k2 * 16384, g_h + (size_t)(mb * 8 + k2) * 8192, 16384, afull + 8 * k2);
                        }
                    }
                }
            }
        } else {
            pdl_wait();
            float2* s_rs = (float2*)(smem + K4_RS);
            float* s_cs = (float*)(smem + K4_CS);
            for (int r = tid - 32; r < 128; r += 96) {
                const float4* hp = (const float4*)(g_hstat + (size_t)(mb * 128 + r) * 8);
                float4 a = __ldcg(hp), b = __ldcg(hp + 1), c = __ldcg(hp + 2), d = __ldcg(hp + 3);
                float mean = 0.125f * (a.x + a.z + b.x + b.z + c.x + c.z + d.x + d.z);
                float m2 = a.y + a.w + b.y + b.w + c.y + c.w + d.y + d.w;
                float e;
                e = a.x - mean; m2 = fmaf(64.f * e, e, m2); e = a.z - mean; m2 = fmaf(64.f * e, e, m2);
                e = b.x - mean; m2 = fmaf(64.f * e, e, m2); e = b.z - mean; m2 = fmaf(64.f * e, e, m2);
                e = c.x - mean; m2 = fmaf(64.f * e, e, m2); e = c.z - mean; m2 = fmaf(64.f * e, e, m2);
                e = d.x - mean; m2 = fmaf(64.f * e, e, m2); e = d.z - mean; m2 = fmaf(64.f * e, e, m2);
                float rstd = rsqrtf(m2 * (1.0f / DM) + 1e-5f);
                s_rs[r] = make_float2(rstd, -mean * rstd);
            }
            for (int c = tid - 32; c < 448; c += 96)
                s_cs[c] = __ldcg(&g_cs2[(c >= 224 ? FF - 224 : 0) + nt * 224 + c]);
            __syncwarp();
            if (lane == 0) mbar_arrive(auxb);
        }
    } else {
        asm volatile("setmaxnreg.inc.sync.aligned.u32 216;");
        const int wgi = (warp >> 2) - 1, ww = warp & 3;
        const int rl = wgi * 64 + ww * 16 + (lane >> 2);
        const int rgl = wgi * 8 + ww * 2;
        const float2* s_rs = (const float2*)(smem + K4_RS);
        const float* s_cs = (const float*)(smem + K4_CS);
        {
            float ag[64], au[64];
#pragma unroll 1
            for (int kb = 0; kb < 8; kb++) {
                const int s = kb % K4_STAGES;
                mbar_wait(afull + 8 * kb, 0);
                mbar_wait(full + 8 * s, (kb / K4_STAGES) & 1);
                uint64_t ad = make_desc(sb + kb * 16384 + wgi * 1024, 2048, 128, 0);
                uint64_t bd = make_desc(sb + K4_B + s * K4_BSTAGE, 4096, 512, 2);
                WG_FENCE();
#pragma unroll
                for (int k = 0; k < 4; k++) {
                    wgmma_ss_n128(ag, ad + k * 256, bd + k * 64, (kb | k) != 0);
                    wgmma_ss_n128(au, ad + k * 256, bd + 1024 + k * 64, (kb | k) != 0);
                }
                WG_COMMIT();
                if (kb > 0) {
                    wg_wait<1>();
                    if (lane == 0) mbar_arrive(empty + 8 * ((kb - 1) % K4_STAGES));
                }
            }
            wg_wait<0>();
            if (lane == 0) mbar_arrive(empty + 8 * (7 % K4_STAGES));
            fence_regs(ag); fence_regs(au);
            TL(10);
            mbar_wait(auxb, 0);
            k4_epilogue<16>(ag, au, s_cs, 0, nt * 28, s_rs[rl], s_rs[rl + 8], mb, rgl, lane);
        }
        {
            float ag[48], au[48];
#pragma unroll 1
            for (int kb = 0; kb < 8; kb++) {
                const int it = 8 + kb, s = it % K4_STAGES;
                mbar_wait(full + 8 * s, (it / K4_STAGES) & 1);
                uint64_t ad = make_desc(sb + kb * 16384 + wgi * 1024, 2048, 128, 0);
                uint64_t bd = make_desc(sb + K4_B + s * K4_BSTAGE, 4096, 512, 2);
                WG_FENCE();
#pragma unroll
                for (int k = 0; k < 4; k++) {
                    wgmma_ss_n96(ag, ad + k * 256, bd + k * 64, (kb | k) != 0);
                    wgmma_ss_n96(au, ad + k * 256, bd + 1024 + k * 64, (kb | k) != 0);
                }
                WG_COMMIT();
                if (kb > 0) {
                    wg_wait<1>();
                    if (lane == 0) mbar_arrive(empty + 8 * ((it - 1) % K4_STAGES));
                }
            }
            wg_wait<0>();
            fence_regs(ag); fence_regs(au);
            TL(11);
            k4_epilogue<12>(ag, au, s_cs, 128, nt * 28 + 16, s_rs[rl], s_rs[rl + 8], mb, rgl, lane);
            TL(12);
        }
    }
}

constexpr int K5_STAGES = 8, K5_STAGE = 16384 + 8192, K5_BAR = K5_STAGES * K5_STAGE, K5_SMEM = K5_BAR + 128;

__global__ void __launch_bounds__(384, 1)
ffn2_kernel(const __grid_constant__ CUtensorMap tm_w, __nv_bfloat16* __restrict__ out) {
    extern __shared__ __align__(1024) unsigned char smem[];
    const uint32_t sb = smem_u32(smem);
    const int tid = threadIdx.x, warp = tid >> 5, lane = tid & 31;
    int mb, nt;
    tile_of(blockIdx.x, mb, nt);
    TL(13);
    const uint32_t full = sb + K5_BAR, empty = full + 64;
    if (tid == 0) {
        prefetch_tmap(&tm_w);
        for (int i = 0; i < K5_STAGES; i++) { mbar_init(full + 8 * i, 1); mbar_init(empty + 8 * i, 8); }
        fence_barrier_init();
    }
    __syncthreads();
    if (warp == 0) {
        if (lane == 0) {
            for (int kb = 0; kb < K5_STAGES; kb++) {
                mbar_expect(full + 8 * kb, K5_STAGE);
                tma2d(sb + kb * K5_STAGE + 16384, &tm_w, nt * 64, kb * 64, full + 8 * kb);
            }
            pdl_wait();
            for (int kb = 0; kb < 28; kb++) {
                const int s = kb % K5_STAGES;
                if (kb >= K5_STAGES) {
                    mbar_wait(empty + 8 * s, ((kb / K5_STAGES) - 1) & 1);
                    mbar_expect(full + 8 * s, K5_STAGE);
                    tma2d(sb + s * K5_STAGE + 16384, &tm_w, nt * 64, kb * 64, full + 8 * s);
                }
                bulk_g2s(sb + s * K5_STAGE, g_g + (size_t)(mb * 28 + kb) * 8192, 16384, full + 8 * s);
            }
        }
    } else if (warp >= 4) {
        const int wgi = (warp >> 2) - 1, ww = warp & 3;
        const int g = lane >> 2, t = lane & 3;
        pdl_wait();
        uint32_t hr[16];
        {
            const uint32_t* hp = (const uint32_t*)g_h + ((size_t)(mb * 8 + nt) * 8 * 16 + wgi * 8 + ww * 2) * 32 + lane;
#pragma unroll
            for (int j = 0; j < 8; j++) { hr[2 * j] = __ldcg(hp + j * 16 * 32); hr[2 * j + 1] = __ldcg(hp + j * 16 * 32 + 32); }
        }
        float acc[32];
#pragma unroll 1
        for (int kb = 0; kb < 28; kb++) {
            const int s = kb % K5_STAGES;
            mbar_wait(full + 8 * s, (kb / K5_STAGES) & 1);
            uint64_t ad = make_desc(sb + s * K5_STAGE + wgi * 1024, 2048, 128, 0);
            uint64_t bd = make_desc(sb + s * K5_STAGE + 16384, 8192, 1024, 1);
            WG_FENCE();
#pragma unroll
            for (int k = 0; k < 4; k++) wgmma_ss_n64(acc, ad + k * 256, bd + k * 128, (kb | k) != 0);
            WG_COMMIT();
            if (kb > 0) {
                wg_wait<1>();
                if (lane == 0) mbar_arrive(empty + 8 * ((kb - 1) % K5_STAGES));
            }
        }
        wg_wait<0>();
        fence_regs(acc);
        TL(14);
        const int row = mb * 128 + wgi * 64 + ww * 16 + g;
        uint32_t* op = (uint32_t*)(out + (size_t)row * DM + nt * 64) + t;
#pragma unroll
        for (int j = 0; j < 8; j++) {
            op[4 * j] = pack_bf16(bf_lo(hr[2 * j]) + acc[4 * j], bf_hi(hr[2 * j]) + acc[4 * j + 1]);
            op[8 * (DM / 2) + 4 * j] = pack_bf16(bf_lo(hr[2 * j + 1]) + acc[4 * j + 2], bf_hi(hr[2 * j + 1]) + acc[4 * j + 3]);
        }
        TL(15);
    }
}

typedef CUresult (*EncodeFn)(CUtensorMap*, CUtensorMapDataType, cuuint32_t, void*, const cuuint64_t*, const cuuint64_t*,
                             const cuuint32_t*, const cuuint32_t*, CUtensorMapInterleave, CUtensorMapSwizzle,
                             CUtensorMapL2promotion, CUtensorMapFloatOOBfill);

void encode(EncodeFn fn, CUtensorMap* m, const void* ptr, int rank, const cuuint64_t* dims, const cuuint64_t* strides,
            const cuuint32_t* box, CUtensorMapSwizzle swz) {
    cuuint32_t es[3] = {1, 1, 1};
    fn(m, CU_TENSOR_MAP_DATA_TYPE_BFLOAT16, rank, (void*)ptr, dims, strides, box, es, CU_TENSOR_MAP_INTERLEAVE_NONE, swz,
       CU_TENSOR_MAP_L2_PROMOTION_L2_256B, CU_TENSOR_MAP_FLOAT_OOB_FILL_NONE);
}

template <typename... KArgs, typename... Args>
void launch(void (*kern)(KArgs...), int grid, int block, int smem, bool pdl, Args... args) {
    cudaLaunchConfig_t cfg = {};
    cfg.gridDim = dim3(grid); cfg.blockDim = dim3(block); cfg.dynamicSmemBytes = smem;
    cfg.stream = cudaStreamPerThread;
    cudaLaunchAttribute at[1];
    at[0].id = cudaLaunchAttributeProgrammaticStreamSerialization;
    at[0].val.programmaticStreamSerializationAllowed = 1;
    cfg.attrs = at; cfg.numAttrs = pdl ? 1 : 0;
    cudaLaunchKernelEx(&cfg, kern, KArgs(args)...);
}

}

extern "C" void kernel_launch(void* const* d_in, const int* in_sizes, int n_in, void* d_out, int out_size) {
    const __nv_bfloat16* x = (const __nv_bfloat16*)d_in[0];
    const __nv_bfloat16* wqkv = (const __nv_bfloat16*)d_in[1];
    const __nv_bfloat16* wo = (const __nv_bfloat16*)d_in[2];
    const __nv_bfloat16* wgate = (const __nv_bfloat16*)d_in[4];
    const __nv_bfloat16* wup = (const __nv_bfloat16*)d_in[5];
    const __nv_bfloat16* wdown = (const __nv_bfloat16*)d_in[6];
    __nv_bfloat16* out = (__nv_bfloat16*)d_out;

    static CUtensorMap tm_x, tm_wqkv, tm_wo, tm_wg, tm_wu, tm_wd;
    static const void* cached[6] = {nullptr, nullptr, nullptr, nullptr, nullptr, nullptr};
    if (cached[0] != x || cached[1] != wqkv || cached[2] != wo || cached[3] != wgate || cached[4] != wup || cached[5] != wdown) {
        void* fp = nullptr;
        cudaDriverEntryPointQueryResult qr;
        cudaGetDriverEntryPoint("cuTensorMapEncodeTiled", &fp, cudaEnableDefault, &qr);
        EncodeFn fn = (EncodeFn)fp;
        { cuuint64_t d[2] = {512, 2048}, s[1] = {1024}; cuuint32_t b[2] = {64, 128};
          encode(fn, &tm_x, x, 2, d, s, b, CU_TENSOR_MAP_SWIZZLE_128B); }
        { cuuint64_t d[3] = {64, 512, 24}, s[2] = {3072, 128}; cuuint32_t b[3] = {64, 64, 3};
          encode(fn, &tm_wqkv, wqkv, 3, d, s, b, CU_TENSOR_MAP_SWIZZLE_128B); }
        { cuuint64_t d[2] = {512, 512}, s[1] = {1024}; cuuint32_t b[2] = {64, 64};
          encode(fn, &tm_wo, wo, 2, d, s, b, CU_TENSOR_MAP_SWIZZLE_128B); }
        { cuuint64_t d[2] = {1792, 512}, s[1] = {3584}; cuuint32_t b[2] = {32, 64};
          encode(fn, &tm_wg, wgate, 2, d, s, b, CU_TENSOR_MAP_SWIZZLE_64B);
          encode(fn, &tm_wu, wup, 2, d, s, b, CU_TENSOR_MAP_SWIZZLE_64B); }
        { cuuint64_t d[2] = {512, 1792}, s[1] = {1024}; cuuint32_t b[2] = {64, 64};
          encode(fn, &tm_wd, wdown, 2, d, s, b, CU_TENSOR_MAP_SWIZZLE_128B); }
        cudaFuncSetAttribute(qkv_kernel, cudaFuncAttributeMaxDynamicSharedMemorySize, K1_SMEM);
        cudaFuncSetAttribute(attn_kernel, cudaFuncAttributeMaxDynamicSharedMemorySize, AT_SMEM);
        cudaFuncSetAttribute(wo_kernel, cudaFuncAttributeMaxDynamicSharedMemorySize, K3_SMEM);
        cudaFuncSetAttribute(ffn1_kernel, cudaFuncAttributeMaxDynamicSharedMemorySize, K4_SMEM);
        cudaFuncSetAttribute(ffn2_kernel, cudaFuncAttributeMaxDynamicSharedMemorySize, K5_SMEM);
        cached[0] = x; cached[1] = wqkv; cached[2] = wo; cached[3] = wgate; cached[4] = wup; cached[5] = wdown;
    }
    launch(qkv_kernel, 128, 384, K1_SMEM, false, tm_x, tm_wqkv, x, wqkv);
    launch(attn_kernel, 132, 512, AT_SMEM, true, wgate, wup, wo, wdown);
    launch(wo_kernel, 128, 384, K3_SMEM, true, tm_wo, x);
    launch(ffn1_kernel, 128, 384, K4_SMEM, true, tm_wg, tm_wu);
    launch(ffn2_kernel, 128, 384, K5_SMEM, true, tm_wd, out);
}
```

```cpp
#include <cuda_runtime.h>
#include <cuda_bf16.h>
#include <cuda.h>
#include <stdint.h>

#define TAILMAP 1
namespace {

constexpr int S_LEN = 2048, DM = 512, NH = 32, FF = 1792;

__device__ __align__(1024) __nv_bfloat16 g_qkv[3 * NH * S_LEN * 16];
__device__ __align__(1024) __nv_bfloat16 g_ao[S_LEN * DM];
__device__ __align__(1024) __nv_bfloat16 g_h[S_LEN * DM];
__device__ __align__(1024) __nv_bfloat16 g_g[S_LEN * FF];
__device__ __align__(16) float2 g_rowstat1[S_LEN];
__device__ float g_cs1_part[16 * 1536];
__device__ unsigned int g_cnt[32];
__device__ unsigned int g_cnt2[64];
__device__ float g_nrm[3 * NH * 128];
__device__ float2 g_hstat[S_LEN * 8];
__device__ float g_cs2[2 * FF];

#define TL(slot)
#define TX(slot)
__device__ __forceinline__ uint32_t smem_u32(const void* p) { return (uint32_t)__cvta_generic_to_shared(p); }
__device__ __forceinline__ void mbar_init(uint32_t a, int c) { asm volatile("mbarrier.init.shared.b64 [%0], %1;" :: "r"(a), "r"(c)); }
__device__ __forceinline__ void mbar_expect(uint32_t a, int bytes) { asm volatile("mbarrier.arrive.expect_tx.shared.b64 _, [%0], %1;" :: "r"(a), "r"(bytes) : "memory"); }
__device__ __forceinline__ void mbar_arrive(uint32_t a) { asm volatile("mbarrier.arrive.shared.b64 _, [%0];" :: "r"(a) : "memory"); }
__device__ __forceinline__ void mbar_wait(uint32_t a, int parity) {
    uint32_t done;
    int it = 0;
    do {
        asm volatile("{\n.reg .pred p;\nmbarrier.try_wait.parity.shared.b64 p, [%1], %2;\nselp.u32 %0, 1, 0, p;\n}"
                     : "=r"(done) : "r"(a), "r"(parity) : "memory");
        if (++it > (1 << 24)) __trap();
    } while (!done);
}
__device__ __forceinline__ void bulk_g2s(uint32_t dst, const void* src, int bytes, uint32_t bar) {
    asm volatile("cp.async.bulk.shared::cluster.global.mbarrier::complete_tx::bytes [%0], [%1], %2, [%3];"
                 :: "r"(dst), "l"(src), "r"(bytes), "r"(bar) : "memory");
}
__device__ __forceinline__ void tma2d(uint32_t dst, const CUtensorMap* m, int c0, int c1, uint32_t bar) {
    asm volatile("cp.async.bulk.tensor.2d.shared::cluster.global.mbarrier::complete_tx::bytes [%0], [%1, {%3, %4}], [%2];"
                 :: "r"(dst), "l"(m), "r"(bar), "r"(c0), "r"(c1) : "memory");
}
__device__ __forceinline__ void tma3d(uint32_t dst, const CUtensorMap* m, int c0, int c1, int c2, uint32_t bar) {
    asm volatile("cp.async.bulk.tensor.3d.shared::cluster.global.mbarrier::complete_tx::bytes [%0], [%1, {%3, %4, %5}], [%2];"
                 :: "r"(dst), "l"(m), "r"(bar), "r"(c0), "r"(c1), "r"(c2) : "memory");
}
__device__ __forceinline__ void prefetch_tmap(const CUtensorMap* m) { asm volatile("prefetch.tensormap [%0];" :: "l"(m) : "memory"); }
__device__ __forceinline__ void pdl_wait() { asm volatile("griddepcontrol.wait;" ::: "memory"); }
__device__ __forceinline__ void pdl_launch() { asm volatile("griddepcontrol.launch_dependents;" ::: "memory"); }
__device__ __forceinline__ void fence_barrier_init() { asm volatile("fence.mbarrier_init.release.cluster;" ::: "memory"); }
__device__ __forceinline__ void fence_proxy_async() { asm volatile("fence.proxy.async.shared::cta;" ::: "memory"); }
__device__ __forceinline__ uint64_t make_desc(uint32_t saddr, uint32_t lbo, uint32_t sbo, uint32_t swz) {
    return (uint64_t)((saddr & 0x3FFFF) >> 4) | ((uint64_t)((lbo & 0x3FFFF) >> 4) << 16) |
           ((uint64_t)((sbo & 0x3FFFF) >> 4) << 32) | ((uint64_t)swz << 62);
}
#define WG_FENCE() asm volatile("wgmma.fence.sync.aligned;" ::: "memory")
#define WG_COMMIT() asm volatile("wgmma.commit_group.sync.aligned;" ::: "memory")
template <int N> __device__ __forceinline__ void wg_wait() { asm volatile("wgmma.wait_group.sync.aligned %0;" :: "n"(N) : "memory"); }
template <int N> __device__ __forceinline__ void fence_regs(float (&d)[N]) {
#pragma unroll
    for (int i = 0; i < N; i++) asm volatile("" : "+f"(d[i]) :: "memory");
}
__device__ __forceinline__ float ex2f(float x) { float y; asm("ex2.approx.ftz.f32 %0, %1;" : "=f"(y) : "f"(x)); return y; }
__device__ __forceinline__ float tanh_fast(float x) { float y; asm("tanh.approx.f32 %0, %1;" : "=f"(y) : "f"(x)); return y; }
__device__ __forceinline__ uint32_t pack_bf16(float lo, float hi) { uint32_t r; asm("cvt.rn.bf16x2.f32 %0, %1, %2;" : "=r"(r) : "f"(hi), "f"(lo)); return r; }
__device__ __forceinline__ float bf_lo(uint32_t u) { return __uint_as_float(u << 16); }
__device__ __forceinline__ float bf_hi(uint32_t u) { return __uint_as_float(u & 0xFFFF0000u); }
__device__ __forceinline__ uint32_t hfma2(uint32_t a, uint32_t b, uint32_t c) { uint32_t r; asm("fma.rn.f16x2 %0, %1, %2, %3;" : "=r"(r) : "r"(a), "r"(b), "r"(c)); return r; }
__device__ __forceinline__ uint32_t hmul2(uint32_t a, uint32_t b) { uint32_t r; asm("mul.rn.f16x2 %0, %1, %2;" : "=r"(r) : "r"(a), "r"(b)); return r; }
__device__ __forceinline__ unsigned int ld_acquire(const unsigned int* p) { unsigned int v; asm volatile("ld.acquire.gpu.u32 %0, [%1];" : "=r"(v) : "l"(p) : "memory"); return v; }
__device__ __forceinline__ void red_release(unsigned int* p) { asm volatile("red.release.gpu.global.add.u32 [%0], 1;" :: "l"(p) : "memory"); }
__device__ __forceinline__ float warp_sum(float v) {
#pragma unroll
    for (int o = 16; o; o >>= 1) v += __shfl_xor_sync(0xffffffffu, v, o);
    return v;
}
__device__ __forceinline__ float warp_max(float v) {
#pragma unroll
    for (int o = 16; o; o >>= 1) v = fmaxf(v, __shfl_xor_sync(0xffffffffu, v, o));
    return v;
}

__device__ __forceinline__ void wgmma_ss_n64(float (&d)[32], uint64_t adesc, uint64_t bdesc, int scale_d) {
    asm volatile("{\n.reg .pred p;\nsetp.ne.b32 p, %34, 0;\n"
      "wgmma.mma_async.sync.aligned.m64n64k16.f32.bf16.bf16 {%0,%1,%2,%3,%4,%5,%6,%7,%8,%9,%10,%11,%12,%13,%14,%15,%16,%17,%18,%19,%20,%21,%22,%23,%24,%25,%26,%27,%28,%29,%30,%31}, %32, %33, p, 1, 1, 0, 1;\n}"
      : "+f"(d[0]), "+f"(d[1]), "+f"(d[2]), "+f"(d[3]), "+f"(d[4]), "+f"(d[5]), "+f"(d[6]), "+f"(d[7]), "+f"(d[8]), "+f"(d[9]), "+f"(d[10]), "+f"(d[11]), "+f"(d[12]), "+f"(d[13]), "+f"(d[14]), "+f"(d[15]), "+f"(d[16]), "+f"(d[17]), "+f"(d[18]), "+f"(d[19]), "+f"(d[20]), "+f"(d[21]), "+f"(d[22]), "+f"(d[23]), "+f"(d[24]), "+f"(d[25]), "+f"(d[26]), "+f"(d[27]), "+f"(d[28]), "+f"(d[29]), "+f"(d[30]), "+f"(d[31])
      : "l"(adesc), "l"(bdesc), "r"(scale_d));
}
__device__ __forceinline__ void wgmma_ss_n96(float (&d)[48], uint64_t adesc, uint64_t bdesc, int scale_d) {
    asm volatile("{\n.reg .pred p;\nsetp.ne.b32 p, %50, 0;\n"
      "wgmma.mma_async.sync.aligned.m64n96k16.f32.bf16.bf16 {%0,%1,%2,%3,%4,%5,%6,%7,%8,%9,%10,%11,%12,%13,%14,%15,%16,%17,%18,%19,%20,%21,%22,%23,%24,%25,%26,%27,%28,%29,%30,%31,%32,%33,%34,%35,%36,%37,%38,%39,%40,%41,%42,%43,%44,%45,%46,%47}, %48, %49, p, 1, 1, 0, 1;\n}"
      : "+f"(d[0]), "+f"(d[1]), "+f"(d[2]), "+f"(d[3]), "+f"(d[4]), "+f"(d[5]), "+f"(d[6]), "+f"(d[7]), "+f"(d[8]), "+f"(d[9]), "+f"(d[10]), "+f"(d[11]), "+f"(d[12]), "+f"(d[13]), "+f"(d[14]), "+f"(d[15]), "+f"(d[16]), "+f"(d[17]), "+f"(d[18]), "+f"(d[19]), "+f"(d[20]), "+f"(d[21]), "+f"(d[22]), "+f"(d[23]), "+f"(d[24]), "+f"(d[25]), "+f"(d[26]), "+f"(d[27]), "+f"(d[28]), "+f"(d[29]), "+f"(d[30]), "+f"(d[31]), "+f"(d[32]), "+f"(d[33]), "+f"(d[34]), "+f"(d[35]), "+f"(d[36]), "+f"(d[37]), "+f"(d[38]), "+f"(d[39]), "+f"(d[40]), "+f"(d[41]), "+f"(d[42]), "+f"(d[43]), "+f"(d[44]), "+f"(d[45]), "+f"(d[46]), "+f"(d[47])
      : "l"(adesc), "l"(bdesc), "r"(scale_d));
}
__device__ __forceinline__ void wgmma_ss_n128(float (&d)[64], uint64_t adesc, uint64_t bdesc, int scale_d) {
    asm volatile("{\n.reg .pred p;\nsetp.ne.b32 p, %66, 0;\n"
      "wgmma.mma_async.sync.aligned.m64n128k16.f32.bf16.bf16 {%0,%1,%2,%3,%4,%5,%6,%7,%8,%9,%10,%11,%12,%13,%14,%15,%16,%17,%18,%19,%20,%21,%22,%23,%24,%25,%26,%27,%28,%29,%30,%31,%32,%33,%34,%35,%36,%37,%38,%39,%40,%41,%42,%43,%44,%45,%46,%47,%48,%49,%50,%51,%52,%53,%54,%55,%56,%57,%58,%59,%60,%61,%62,%63}, %64, %65, p, 1, 1, 0, 1;\n}"
      : "+f"(d[0]), "+f"(d[1]), "+f"(d[2]), "+f"(d[3]), "+f"(d[4]), "+f"(d[5]), "+f"(d[6]), "+f"(d[7]), "+f"(d[8]), "+f"(d[9]), "+f"(d[10]), "+f"(d[11]), "+f"(d[12]), "+f"(d[13]), "+f"(d[14]), "+f"(d[15]), "+f"(d[16]), "+f"(d[17]), "+f"(d[18]), "+f"(d[19]), "+f"(d[20]), "+f"(d[21]), "+f"(d[22]), "+f"(d[23]), "+f"(d[24]), "+f"(d[25]), "+f"(d[26]), "+f"(d[27]), "+f"(d[28]), "+f"(d[29]), "+f"(d[30]), "+f"(d[31]), "+f"(d[32]), "+f"(d[33]), "+f"(d[34]), "+f"(d[35]), "+f"(d[36]), "+f"(d[37]), "+f"(d[38]), "+f"(d[39]), "+f"(d[40]), "+f"(d[41]), "+f"(d[42]), "+f"(d[43]), "+f"(d[44]), "+f"(d[45]), "+f"(d[46]), "+f"(d[47]), "+f"(d[48]), "+f"(d[49]), "+f"(d[50]), "+f"(d[51]), "+f"(d[52]), "+f"(d[53]), "+f"(d[54]), "+f"(d[55]), "+f"(d[56]), "+f"(d[57]), "+f"(d[58]), "+f"(d[59]), "+f"(d[60]), "+f"(d[61]), "+f"(d[62]), "+f"(d[63])
      : "l"(adesc), "l"(bdesc), "r"(scale_d));
}
__device__ __forceinline__ void wgmma_ss_n192(float (&d)[96], uint64_t adesc, uint64_t bdesc, int scale_d) {
    asm volatile("{\n.reg .pred p;\nsetp.ne.b32 p, %98, 0;\n"
      "wgmma.mma_async.sync.aligned.m64n192k16.f32.bf16.bf16 {%0,%1,%2,%3,%4,%5,%6,%7,%8,%9,%10,%11,%12,%13,%14,%15,%16,%17,%18,%19,%20,%21,%22,%23,%24,%25,%26,%27,%28,%29,%30,%31,%32,%33,%34,%35,%36,%37,%38,%39,%40,%41,%42,%43,%44,%45,%46,%47,%48,%49,%50,%51,%52,%53,%54,%55,%56,%57,%58,%59,%60,%61,%62,%63,%64,%65,%66,%67,%68,%69,%70,%71,%72,%73,%74,%75,%76,%77,%78,%79,%80,%81,%82,%83,%84,%85,%86,%87,%88,%89,%90,%91,%92,%93,%94,%95}, %96, %97, p, 1, 1, 0, 1;\n}"
      : "+f"(d[0]), "+f"(d[1]), "+f"(d[2]), "+f"(d[3]), "+f"(d[4]), "+f"(d[5]), "+f"(d[6]), "+f"(d[7]), "+f"(d[8]), "+f"(d[9]), "+f"(d[10]), "+f"(d[11]), "+f"(d[12]), "+f"(d[13]), "+f"(d[14]), "+f"(d[15]), "+f"(d[16]), "+f"(d[17]), "+f"(d[18]), "+f"(d[19]), "+f"(d[20]), "+f"(d[21]), "+f"(d[22]), "+f"(d[23]), "+f"(d[24]), "+f"(d[25]), "+f"(d[26]), "+f"(d[27]), "+f"(d[28]), "+f"(d[29]), "+f"(d[30]), "+f"(d[31]), "+f"(d[32]), "+f"(d[33]), "+f"(d[34]), "+f"(d[35]), "+f"(d[36]), "+f"(d[37]), "+f"(d[38]), "+f"(d[39]), "+f"(d[40]), "+f"(d[41]), "+f"(d[42]), "+f"(d[43]), "+f"(d[44]), "+f"(d[45]), "+f"(d[46]), "+f"(d[47]), "+f"(d[48]), "+f"(d[49]), "+f"(d[50]), "+f"(d[51]), "+f"(d[52]), "+f"(d[53]), "+f"(d[54]), "+f"(d[55]), "+f"(d[56]), "+f"(d[57]), "+f"(d[58]), "+f"(d[59]), "+f"(d[60]), "+f"(d[61]), "+f"(d[62]), "+f"(d[63]), "+f"(d[64]), "+f"(d[65]), "+f"(d[66]), "+f"(d[67]), "+f"(d[68]), "+f"(d[69]), "+f"(d[70]), "+f"(d[71]), "+f"(d[72]), "+f"(d[73]), "+f"(d[74]), "+f"(d[75]), "+f"(d[76]), "+f"(d[77]), "+f"(d[78]), "+f"(d[79]), "+f"(d[80]), "+f"(d[81]), "+f"(d[82]), "+f"(d[83]), "+f"(d[84]), "+f"(d[85]), "+f"(d[86]), "+f"(d[87]), "+f"(d[88]), "+f"(d[89]), "+f"(d[90]), "+f"(d[91]), "+f"(d[92]), "+f"(d[93]), "+f"(d[94]), "+f"(d[95])
      : "l"(adesc), "l"(bdesc), "r"(scale_d));
}
__device__ __forceinline__ void qk_wgmma_n64(float (&d)[32], const uint32_t (&a)[4], uint64_t desc) {
    asm volatile("wgmma.mma_async.sync.aligned.m64n64k16.f32.bf16.bf16 {%0,%1,%2,%3,%4,%5,%6,%7,%8,%9,%10,%11,%12,%13,%14,%15,%16,%17,%18,%19,%20,%21,%22,%23,%24,%25,%26,%27,%28,%29,%30,%31}, {%32,%33,%34,%35}, %36, 0, 1, 1, 0;"
      : "=f"(d[0]), "=f"(d[1]), "=f"(d[2]), "=f"(d[3]), "=f"(d[4]), "=f"(d[5]), "=f"(d[6]), "=f"(d[7]), "=f"(d[8]), "=f"(d[9]), "=f"(d[10]), "=f"(d[11]), "=f"(d[12]), "=f"(d[13]), "=f"(d[14]), "=f"(d[15]), "=f"(d[16]), "=f"(d[17]), "=f"(d[18]), "=f"(d[19]), "=f"(d[20]), "=f"(d[21]), "=f"(d[22]), "=f"(d[23]), "=f"(d[24]), "=f"(d[25]), "=f"(d[26]), "=f"(d[27]), "=f"(d[28]), "=f"(d[29]), "=f"(d[30]), "=f"(d[31])
      : "r"(a[0]), "r"(a[1]), "r"(a[2]), "r"(a[3]), "l"(desc));
}

__device__ __forceinline__ void pv_wgmma(float (&d)[12], uint32_t a0, uint32_t a1, uint32_t a2, uint32_t a3, uint64_t desc) {
    asm volatile("wgmma.mma_async.sync.aligned.m64n24k16.f32.bf16.bf16 {%0,%1,%2,%3,%4,%5,%6,%7,%8,%9,%10,%11}, {%12,%13,%14,%15}, %16, 1, 1, 1, 1;"
      : "+f"(d[0]), "+f"(d[1]), "+f"(d[2]), "+f"(d[3]), "+f"(d[4]), "+f"(d[5]), "+f"(d[6]), "+f"(d[7]), "+f"(d[8]), "+f"(d[9]), "+f"(d[10]), "+f"(d[11])
      : "r"(a0), "r"(a1), "r"(a2), "r"(a3), "l"(desc));
}

__device__ __forceinline__ void tile_of(int bid, int& mb, int& nt) {
    int grp = bid >> 4, in = bid & 15;
    mb = (grp >> 1) * 4 + (in >> 2);
    nt = (grp & 1) * 4 + (in & 3);
}

constexpr int K1_STAGES = 5, K1_STAGE = 16384 + 24576;
constexpr int K1_BAR = K1_STAGES * K1_STAGE, K1_RS = K1_BAR + 128, K1_CS = K1_RS + 1024, K1_SMEM = K1_CS + 768;

__device__ __forceinline__ float2 row_stats_x(const __nv_bfloat16* x, int row, int lane) {
    const uint4* p = (const uint4*)(x + (size_t)row * DM);
    uint4 a = __ldg(p + lane), b = __ldg(p + 32 + lane);
    float v[16];
    v[0] = bf_lo(a.x); v[1] = bf_hi(a.x); v[2] = bf_lo(a.y); v[3] = bf_hi(a.y);
    v[4] = bf_lo(a.z); v[5] = bf_hi(a.z); v[6] = bf_lo(a.w); v[7] = bf_hi(a.w);
    v[8] = bf_lo(b.x); v[9] = bf_hi(b.x); v[10] = bf_lo(b.y); v[11] = bf_hi(b.y);
    v[12] = bf_lo(b.z); v[13] = bf_hi(b.z); v[14] = bf_lo(b.w); v[15] = bf_hi(b.w);
    float s = 0.f;
#pragma unroll
    for (int i = 0; i < 16; i++) s += v[i];
    float mean = warp_sum(s) * (1.0f / DM);
    float q = 0.f;
#pragma unroll
    for (int i = 0; i < 16; i++) { float d = v[i] - mean; q = fmaf(d, d, q); }
    float var = warp_sum(q) * (1.0f / DM);
    float rstd = rsqrtf(var + 1e-5f);
    return make_float2(rstd, -mean * rstd);
}
__device__ __forceinline__ void colsum8(const __nv_bfloat16* w, int ld, int col, int k0, int nk, float (&s)[8]) {
#pragma unroll
    for (int i = 0; i < 8; i++) s[i] = 0.f;
    for (int k = k0; k < k0 + nk; k += 8) {
        uint4 u[8];
#pragma unroll
        for (int i = 0; i < 8; i++) u[i] = __ldg((const uint4*)(w + (size_t)(k + i) * ld + col));
#pragma unroll
        for (int i = 0; i < 8; i++) {
            s[0] += bf_lo(u[i].x); s[1] += bf_hi(u[i].x); s[2] += bf_lo(u[i].y); s[3] += bf_hi(u[i].y);
            s[4] += bf_lo(u[i].z); s[5] += bf_hi(u[i].z); s[6] += bf_lo(u[i].w); s[7] += bf_hi(u[i].w);
        }
    }
}
__device__ __forceinline__ bool wait_count(const unsigned int* p, unsigned int target, int lane) {
    int ok = 1;
    if (lane == 0) {
        int it = 0;
        while (ld_acquire(p) < target) { if (++it > (1 << 16)) { ok = 0; break; } __nanosleep(20); }
    }
    ok = __shfl_sync(0xffffffffu, ok, 0);
    return ok != 0;
}

__global__ void __launch_bounds__(384, 1)
qkv_kernel(const __grid_constant__ CUtensorMap tm_x, const __grid_constant__ CUtensorMap tm_w,
           const __nv_bfloat16* __restrict__ x, const __nv_bfloat16* __restrict__ wqkv) {
    extern __shared__ __align__(1024) unsigned char smem[];
    const uint32_t sb = smem_u32(smem);
    const int tid = threadIdx.x, warp = tid >> 5, lane = tid & 31;
    TL(0);
    int mb, nt;
    tile_of(blockIdx.x, mb, nt);
    const uint32_t full = sb + K1_BAR, empty = full + 40, auxb = full + 80;
    if (tid == 0) {
        prefetch_tmap(&tm_x); prefetch_tmap(&tm_w);
        for (int i = 0; i < K1_STAGES; i++) { mbar_init(full + 8 * i, 1); mbar_init(empty + 8 * i, 8); }
        mbar_init(auxb, 3);
        fence_barrier_init();
    }
    __syncthreads();
    pdl_launch();
    if (warp == 0) {
        if (blockIdx.x == 0) { g_cnt2[lane] = 0; g_cnt2[32 + lane] = 0; }
        if (lane == 0) {
            for (int kb = 0; kb < 8; kb++) {
                int s = kb % K1_STAGES;
                if (kb >= K1_STAGES) mbar_wait(empty + 8 * s, 0);
                mbar_expect(full + 8 * s, K1_STAGE);
                tma2d(sb + s * K1_STAGE, &tm_x, kb * 64, mb * 128, full + 8 * s);
                tma3d(sb + s * K1_STAGE + 16384, &tm_w, 0, kb * 64, nt * 3, full + 8 * s);
            }
        }
    } else if (warp < 4) {
        float2* s_rs = (float2*)(smem + K1_RS);
        float* s_cs = (float*)(smem + K1_CS);
        {
            float cs[8];
            const int cg = (warp - 1) * 8 + (lane & 7);
            colsum8(wqkv, 1536, nt * 192 + cg * 8, mb * 32 + (lane >> 3) * 8, 8, cs);
#pragma unroll
            for (int i = 0; i < 8; i++) {
                cs[i] += __shfl_xor_sync(0xffffffffu, cs[i], 8);
                cs[i] += __shfl_xor_sync(0xffffffffu, cs[i], 16);
            }
            if (lane < 8) {
                float4* d = (float4*)(g_cs1_part + mb * 1536 + nt * 192 + cg * 8);
                d[0] = make_float4(cs[0], cs[1], cs[2], cs[3]);
                d[1] = make_float4(cs[4], cs[5], cs[6], cs[7]);
            }
            __syncwarp();
            if (lane == 0) { __threadfence(); red_release(&g_cnt[16 + nt]); }
        }
        TX(8 + warp);
        if (warp == 1) {
            if (wait_count(&g_cnt[mb], 64, lane)) {
#pragma unroll
                for (int i = 0; i < 4; i++) s_rs[lane + 32 * i] = __ldcg(&g_rowstat1[mb * 128 + lane + 32 * i]);
            } else {
                for (int i = 0; i < 128; i++) {
                    float2 st = row_stats_x(x, mb * 128 + i, lane);
                    if (lane == 0) s_rs[i] = st;
                }
            }
        } else {
            int c0 = (warp - 2) * 96;
            if (wait_count(&g_cnt[16 + nt], 48, lane)) {
#pragma unroll
                for (int i = 0; i < 3; i++) {
                    float s = 0.f;
#pragma unroll
                    for (int p = 0; p < 16; p++) s += __ldcg(&g_cs1_part[p * 1536 + nt * 192 + c0 + lane + 32 * i]);
                    s_cs[c0 + lane + 32 * i] = s;
                }
            } else if (lane < 12) {
                float s[8];
                colsum8(wqkv, 1536, nt * 192 + c0 + lane * 8, 0, 512, s);
#pragma unroll
                for (int i = 0; i < 8; i++) s_cs[c0 + lane * 8 + i] = s[i];
            }
        }
        __syncwarp();
        TX(12 + warp);
        if (lane == 0) mbar_arrive(auxb);
    } else {
        const int wgi = (warp >> 2) - 1, ww = warp & 3;
        {
            const int r0 = mb * 128 + nt * 16 + (warp - 4) * 2;
            float2 sa = row_stats_x(x, r0, lane), sb2 = row_stats_x(x, r0 + 1, lane);
            if (lane == 0) {
                *(float4*)(g_rowstat1 + r0) = make_float4(sa.x, sa.y, sb2.x, sb2.y);
                __threadfence();
                red_release(&g_cnt[mb]);
            }
        }
        float acc[96];
#pragma unroll 1
        for (int kb = 0; kb < 8; kb++) {
            int s = kb % K1_STAGES;
            mbar_wait(full + 8 * s, (kb / K1_STAGES) & 1);
            if (warp == 4) TX(kb);
            uint64_t ad = make_desc(sb + s * K1_STAGE + wgi * 8192, 16, 1024, 1);
            uint64_t bd = make_desc(sb + s * K1_STAGE + 16384, 8192, 1024, 1);
            WG_FENCE();
#pragma unroll
            for (int k = 0; k < 4; k++) wgmma_ss_n192(acc, ad + k * 2, bd + k * 128, (kb | k) != 0);
            WG_COMMIT();
            if (kb > 0) {
                wg_wait<1>();
                if (lane == 0) mbar_arrive(empty + 8 * ((kb - 1) % K1_STAGES));
            }
        }
        wg_wait<0>();
        fence_regs(acc);
        TL(1);
        if (warp == 4) TX(16);
        mbar_wait(auxb, 0);
        if (warp == 4) TX(17);
        const float2* s_rs = (const float2*)(smem + K1_RS);
        const float* s_cs = (const float*)(smem + K1_CS);
        const int g = lane >> 2, t = lane & 3;
        const int rl = wgi * 64 + ww * 16 + g;
        const float2 st0 = s_rs[rl], st1 = s_rs[rl + 8];
        const float QS = 0.25f * 1.4426950408889634f;
        const int jrow = mb * 16 + wgi * 8 + ww * 2;
        const int rg16 = mb * 8 + wgi * 4 + ww;
        uint32_t* out = (uint32_t*)g_qkv;
#pragma unroll
        for (int hh = 0; hh < 12; hh++) {
            const int col0 = nt * 192 + hh * 16;
            const int which = col0 >> 9, head = (col0 & 511) >> 4;
            const float sc = (which == 0) ? QS : 1.0f;
            const float a0 = st0.x * sc, b0 = st0.y * sc, a1 = st1.x * sc, b1 = st1.y * sc;
            float n0 = 0.f, n1 = 0.f;
#pragma unroll
            for (int c = 0; c < 2; c++) {
                const int j = hh * 2 + c;
                const float2 cs = *(const float2*)(s_cs + 8 * j + 2 * t);
                float v00 = fmaf(a0, acc[4 * j], b0 * cs.x), v01 = fmaf(a0, acc[4 * j + 1], b0 * cs.y);
                float v10 = fmaf(a1, acc[4 * j + 2], b1 * cs.x), v11 = fmaf(a1, acc[4 * j + 3], b1 * cs.y);
                size_t o = ((size_t)((which * NH + head) * 2 + c) * 256 + jrow) * 32 + lane;
                out[o] = pack_bf16(v00, v01);
                out[o + 32] = pack_bf16(v10, v11);
                if (which < 2) {
                    n0 = fmaf(v00, v00, fmaf(v01, v01, n0));
                    n1 = fmaf(v10, v10, fmaf(v11, v11, n1));
                } else {
                    n0 = fmaxf(n0, fmaxf(fabsf(v00), fabsf(v01)));
                    n1 = fmaxf(n1, fmaxf(fabsf(v10), fabsf(v11)));
                    if (v00 != v00 || v01 != v01 || v10 != v10 || v11 != v11) n0 = __int_as_float(0x7f800000);
                }
            }
            float m;
            if (which < 2) {
                n0 += __shfl_xor_sync(0xffffffffu, n0, 1); n1 += __shfl_xor_sync(0xffffffffu, n1, 1);
                n0 += __shfl_xor_sync(0xffffffffu, n0, 2); n1 += __shfl_xor_sync(0xffffffffu, n1, 2);
                m = n0 + n1 - fminf(n0, n1);
                if (!(m == m)) m = __int_as_float(0x7f800000);
                m = fmaxf(m, __shfl_xor_sync(0xffffffffu, m, 4));
                m = fmaxf(m, __shfl_xor_sync(0xffffffffu, m, 8));
                m = fmaxf(m, __shfl_xor_sync(0xffffffffu, m, 16));
            } else {
                m = warp_max(fmaxf(n0, n1));
            }
            if (lane == 0) g_nrm[(which * NH + head) * 128 + rg16] = m;
        }
        TL(2);
        if (warp == 4) TX(18);
    }
}

constexpr int AT_K = 0, AT_V = 65536, AT_ONES = 131072, AT_BAR = 163840, AT_SMEM = AT_BAR + 128;
#define POLY_MASK 0xAD6A

__device__ __forceinline__ uint32_t exp2_pair_poly(float x0, float x1) {
    uint32_t t0 = __float_as_uint(x0 + 32895.0f);
    uint32_t t1 = __float_as_uint(x1 + 32895.0f);
    uint32_t gd = __byte_perm(t0, t1, 0x6420);
    uint32_t wm = __byte_perm(t0, t1, 0x5612);
    uint32_t v = hfma2(gd, 0x71477147u, 0x354f354fu);
    uint32_t z = hmul2(v, gd);
    return (wm >> 1) + z;
}
__device__ __forceinline__ uint32_t exp2_pair_mufu(float x0, float x1) { return pack_bf16(ex2f(x0), ex2f(x1)); }
template <uint32_t MASK>
__device__ __forceinline__ void exp_blocks(const float (&s)[32], uint32_t (&p)[16]) {
#pragma unroll
    for (int b = 0; b < 8; b++) {
        if ((MASK >> b) & 1) {
            p[2 * b] = exp2_pair_poly(s[4 * b], s[4 * b + 1]);
            p[2 * b + 1] = exp2_pair_poly(s[4 * b + 2], s[4 * b + 3]);
        } else {
            p[2 * b] = exp2_pair_mufu(s[4 * b], s[4 * b + 1]);
            p[2 * b + 1] = exp2_pair_mufu(s[4 * b + 2], s[4 * b + 3]);
        }
    }
}
#define PV4(P) _Pragma("unroll") for (int i = 0; i < 4; i++) { pv_wgmma(o, P[4 * i], P[4 * i + 1], P[4 * i + 2], P[4 * i + 3], vd); vd += 16; }

__device__ __forceinline__ void attn_store(float (&o)[12], int row0, int head, int lane) {
    float l0 = __shfl_sync(0xffffffffu, o[8], lane & 28);
    float l1 = __shfl_sync(0xffffffffu, o[10], lane & 28);
    float r0 = 1.0f / l0, r1 = 1.0f / l1;
    uint32_t* op = (uint32_t*)g_ao;
    int mb = row0 >> 7, rg = (row0 & 127) >> 3;
    int kb = head >> 2, kc = (head & 3) * 2;
    size_t base = (((size_t)(mb * 8 + kb) * 8 + kc) * 16 + rg) * 32 + lane;
    op[base] = pack_bf16(o[0] * r0, o[1] * r0);
    op[base + 32] = pack_bf16(o[2] * r1, o[3] * r1);
    op[base + 16 * 32] = pack_bf16(o[4] * r0, o[5] * r0);
    op[base + 16 * 32 + 32] = pack_bf16(o[6] * r1, o[7] * r1);
}

__device__ __forceinline__ void attn_load_q(uint32_t (&q)[4], const __nv_bfloat16* gq, int row0, int lane) {
    const uint32_t* qp = (const uint32_t*)gq;
    int j0 = row0 >> 3;
    q[0] = __ldcg(qp + (0 * 256 + j0) * 32 + lane);
    q[1] = __ldcg(qp + (0 * 256 + j0 + 1) * 32 + lane);
    q[2] = __ldcg(qp + (1 * 256 + j0) * 32 + lane);
    q[3] = __ldcg(qp + (1 * 256 + j0 + 1) * 32 + lane);
}

__device__ __forceinline__ void attn_tile_safe(const uint32_t (&q)[4], uint64_t kd, uint64_t vd, int row0, int head, int lane) {
    float o[12];
#pragma unroll
    for (int i = 0; i < 12; i++) o[i] = 0.f;
    float m0 = -INFINITY, m1 = -INFINITY;
    fence_regs(o);
#pragma unroll 1
    for (int j = 0; j < 32; j++) {
        float s[32];
        uint32_t p[16];
        WG_FENCE();
        qk_wgmma_n64(s, q, kd); kd += 64;
        WG_COMMIT();
        wg_wait<0>();
        fence_regs(s);
        fence_regs(o);
        float x0 = m0, x1 = m1;
#pragma unroll
        for (int b = 0; b < 8; b++) {
            x0 = fmaxf(x0, fmaxf(s[4 * b], s[4 * b + 1]));
            x1 = fmaxf(x1, fmaxf(s[4 * b + 2], s[4 * b + 3]));
        }
        x0 = fmaxf(x0, __shfl_xor_sync(0xffffffffu, x0, 1)); x0 = fmaxf(x0, __shfl_xor_sync(0xffffffffu, x0, 2));
        x1 = fmaxf(x1, __shfl_xor_sync(0xffffffffu, x1, 1)); x1 = fmaxf(x1, __shfl_xor_sync(0xffffffffu, x1, 2));
        float al0 = ex2f(m0 - x0), al1 = ex2f(m1 - x1);
        m0 = x0; m1 = x1;
#pragma unroll
        for (int i = 0; i < 3; i++) { o[4 * i] *= al0; o[4 * i + 1] *= al0; o[4 * i + 2] *= al1; o[4 * i + 3] *= al1; }
#pragma unroll
        for (int b = 0; b < 8; b++) {
            p[2 * b] = exp2_pair_mufu(s[4 * b] - m0, s[4 * b + 1] - m0);
            p[2 * b + 1] = exp2_pair_mufu(s[4 * b + 2] - m1, s[4 * b + 3] - m1);
        }
        fence_regs(o);
        WG_FENCE();
        PV4(p);
        WG_COMMIT();
        wg_wait<0>();
        fence_regs(o);
    }
    attn_store(o, row0, head, lane);
}

__global__ void __launch_bounds__(512, 1)
attn_kernel(const __nv_bfloat16* __restrict__ wg_, const __nv_bfloat16* __restrict__ wu_,
            const __nv_bfloat16* __restrict__ wo_, const __nv_bfloat16* __restrict__ wd_) {
    extern __shared__ __align__(1024) unsigned char smem[];
    const uint32_t sb = smem_u32(smem);
    const int tid = threadIdx.x, wg = tid >> 7, warp = (tid >> 5) & 3, lane = tid & 31;
    pdl_launch();
    if (blockIdx.x >= 128) {
        const int e = blockIdx.x - 128;
        const __nv_bfloat16* w = (e < 2) ? wg_ : wu_;
        float* red = (float*)smem;
        const int cgrp = tid & 127, kq = tid >> 7;
        if (cgrp < 112) {
            float s[8];
            colsum8(w, FF, (e & 1) * 896 + cgrp * 8, kq * 128, 128, s);
#pragma unroll
            for (int i = 0; i < 8; i++) red[kq * 896 + cgrp * 8 + i] = s[i];
        }
        __syncthreads();
        for (int c = tid; c < 896; c += 512)
            g_cs2[(e >> 1) * FF + (e & 1) * 896 + c] = red[c] + red[896 + c] + red[1792 + c] + red[2688 + c];
        if (tid < 32) {
            const char* p0 = (const char*)wo_ + e * (DM * DM * 2 / 4);
            for (int i = lane; i < 32; i += 32)
                asm volatile("cp.async.bulk.prefetch.L2.global [%0], %1;" :: "l"(p0 + i * 4096), "r"(4096) : "memory");
            const char* p1 = (const char*)wd_ + e * (FF * DM * 2 / 4);
            for (int i = lane; i < 112; i += 32)
                asm volatile("cp.async.bulk.prefetch.L2.global [%0], %1;" :: "l"(p1 + i * 4096), "r"(4096) : "memory");
        }
        return;
    }
    const int head = blockIdx.x >> 2, qq = blockIdx.x & 3;
    const __nv_bfloat16* gq = g_qkv + (size_t)head * (S_LEN * 16);
    const __nv_bfloat16* gk = g_qkv + (size_t)(NH + head) * (S_LEN * 16);
    const __nv_bfloat16* gv = g_qkv + (size_t)(2 * NH + head) * (S_LEN * 16);
    if (tid == 0) {
        for (int i = 0; i < 8; i++) mbar_init(sb + AT_BAR + 8 * i, 1);
        fence_barrier_init();
    }
    {
        uint4 one = make_uint4(0x00003F80u, 0, 0, 0);
#pragma unroll
        for (int i = 0; i < 4; i++) *(uint4*)(smem + AT_ONES + (i * 512 + tid) * 16) = one;
        fence_proxy_async();
    }
    __syncthreads();
    TL(3);
    pdl_wait();
    TL(4);
    if (tid == 0) {
        for (int i = 0; i < 8; i++) {
            uint32_t bar = sb + AT_BAR + 8 * i;
            mbar_expect(bar, 16384);
            bulk_g2s(sb + AT_K + i * 4096, gk + i * 2048, 4096, bar);
            bulk_g2s(sb + AT_K + 32768 + i * 4096, gk + 16384 + i * 2048, 4096, bar);
            bulk_g2s(sb + AT_V + i * 4096, gv + i * 2048, 4096, bar);
            bulk_g2s(sb + AT_V + 32768 + i * 4096, gv + 16384 + i * 2048, 4096, bar);
        }
    }
    bool fast;
    {
        const float* nq = g_nrm + (0 * NH + head) * 128 + qq * 32;
        const float* nk = g_nrm + (1 * NH + head) * 128;
        const float* nv = g_nrm + (2 * NH + head) * 128;
        float4 k4 = __ldcg((const float4*)nk + lane), v4 = __ldcg((const float4*)nv + lane);
        float qm = warp_max(__ldcg(nq + lane));
        float km = warp_max(fmaxf(fmaxf(k4.x, k4.y), fmaxf(k4.z, k4.w)));
        float vm = warp_max(fmaxf(fmaxf(v4.x, v4.y), fmaxf(v4.z, v4.w)));
        fast = (qm * km <= 3500.0f) && (vm <= 1.0e12f);
    }
    const uint64_t kdesc0 = make_desc(sb + AT_K, 32768, 128, 0);
    const uint64_t vdesc0 = make_desc(sb + AT_V, 128, 32768, 0);
    if (!fast) {
        for (int i = 0; i < 8; i++) mbar_wait(sb + AT_BAR + 8 * i, 0);
#pragma unroll 1
        for (int tile = 0; tile < 2; tile++) {
            const int row0 = qq * 512 + (tile * 4 + wg) * 64 + warp * 16;
            uint32_t q[4];
            attn_load_q(q, gq, row0, lane);
            attn_tile_safe(q, kdesc0, vdesc0, row0, head, lane);
        }
        return;
    }
#pragma unroll 1
    for (int tile = 0; tile < 2; tile++) {
        const int row0 = qq * 512 + (tile * 4 + wg) * 64 + warp * 16;
        uint32_t q[4];
        attn_load_q(q, gq, row0, lane);
        float o[12];
#pragma unroll
        for (int i = 0; i < 12; i++) o[i] = 0.f;
        fence_regs(o);
        float sa[32];
        uint32_t pa[16];
        uint64_t kd = kdesc0, vd = vdesc0;
        if (tile == 0) mbar_wait(sb + AT_BAR, 0);
        WG_FENCE();
        qk_wgmma_n64(sa, q, kd); kd += 64;
        WG_COMMIT();
#pragma unroll 1
        for (int jj = 0; jj < 8; jj++) {
            if (tile == 0 && jj < 7) mbar_wait(sb + AT_BAR + 8 * (jj + 1), 0);
#pragma unroll
            for (int j = 0; j < 4; j++) {
                wg_wait<0>();
                fence_regs(sa);
                if (j & 1) exp_blocks<(POLY_MASK >> 8)>(sa, pa); else exp_blocks<(POLY_MASK & 255)>(sa, pa);
                WG_FENCE();
                qk_wgmma_n64(sa, q, kd); kd += 64;
                PV4(pa);
                WG_COMMIT();
            }
        }
        wg_wait<0>();
        fence_regs(o);
        fence_regs(sa);
        attn_store(o, row0, head, lane);
    }
    TL(5);
}

constexpr int F_R2 = 131072, F_X = 196608, F_BAR = 229376;
constexpr int F_RS = F_BAR + 256, F_CS = F_RS + 1024, F_SMEM = F_CS + 1792;
enum { B_FA = 0, B_HF = 2, B_BF = 6, B_BE = 9, B_CF = 12, B_CE = 18, B_ADONE = 24, B_BDONE = 25, B_XA = 26, B_XC = 27, B_PRDY = 28, B_AUX = 29 };

__device__ __forceinline__ uint32_t mapa(uint32_t a, uint32_t rank) { uint32_t r; asm("mapa.shared::cluster.u32 %0, %1, %2;" : "=r"(r) : "r"(a), "r"(rank)); return r; }
__device__ __forceinline__ void st_async4(uint32_t dst, float a, float b, float c, float d, uint32_t bar) {
    asm volatile("st.async.weak.shared::cluster.mbarrier::complete_tx::bytes.v4.f32 [%0], {%1,%2,%3,%4}, [%5];"
                 :: "r"(dst), "f"(a), "f"(b), "f"(c), "f"(d), "r"(bar) : "memory");
}
__device__ __forceinline__ void mbar_arrive_remote(uint32_t a) { asm volatile("mbarrier.arrive.release.cluster.shared::cluster.b64 _, [%0];" :: "r"(a) : "memory"); }
__device__ __forceinline__ void mbar_wait_cluster(uint32_t a, int parity) {
    uint32_t done;
    int it = 0;
    do {
        asm volatile("{\n.reg .pred p;\nmbarrier.try_wait.parity.acquire.cluster.shared::cta.b64 p, [%1], %2;\nselp.u32 %0, 1, 0, p;\n}"
                     : "=r"(done) : "r"(a), "r"(parity) : "memory");
        if (++it > (1 << 24)) __trap();
    } while (!done);
}
__device__ __forceinline__ void poll_count(const unsigned int* p, unsigned int target) {
    int it = 0;
    while (ld_acquire(p) < target) { if (++it > (1 << 22)) __trap(); }
    asm volatile("fence.proxy.async.global;" ::: "memory");
}
__device__ __forceinline__ void publish(unsigned int* p, int lane) {
    asm volatile("fence.proxy.async.global;" ::: "memory");
    __syncwarp();
    if (lane == 0) { __threadfence(); red_release(p); }
}
template <int R>
__device__ __forceinline__ void xchg(float (&acc)[64], float (&o)[32], uint32_t sb, unsigned char* smem, int bar, int ctid) {
    const uint32_t dst = mapa(sb + F_X + ctid * 16, 1 - R), rb = mapa(sb + F_BAR + 8 * bar, 1 - R);
#pragma unroll
    for (int q = 0; q < 8; q++) {
        const int j = (1 - R) * 32 + 4 * q;
        st_async4(dst + q * 4096, acc[j], acc[j + 1], acc[j + 2], acc[j + 3], rb);
    }
    mbar_wait_cluster(sb + F_BAR + 8 * bar, 0);
#pragma unroll
    for (int q = 0; q < 8; q++) {
        float4 v = *(const float4*)(smem + F_X + q * 4096 + ctid * 16);
        const int j = R * 32 + 4 * q;
        o[4 * q] = acc[j] + v.x; o[4 * q + 1] = acc[j + 1] + v.y; o[4 * q + 2] = acc[j + 2] + v.z; o[4 * q + 3] = acc[j + 3] + v.w;
    }
}

template <int NB>
__device__ __forceinline__ void ffn_epilogue(const float* ag, const float* au, const float* s_cs, int cs_off, int jb0,
                                             float2 st0, float2 st1, int mb, int rgl, int lane) {
    const int t = lane & 3;
    uint32_t* gp = (uint32_t*)g_g;
    const float C1 = 0.7978845608028654f, C2 = 0.044715f * 0.7978845608028654f;
    const float k10 = st0.x * C1, k20 = st0.x * st0.x * st0.x * C2, k11 = st1.x * C1, k21 = st1.x * st1.x * st1.x * C2;
#pragma unroll
    for (int j = 0; j < NB; j++) {
        const float2 cg = *(const float2*)(s_cs + cs_off + 8 * j + 2 * t);
        const float2 cu = *(const float2*)(s_cs + 224 + cs_off + 8 * j + 2 * t);
        float r[4];
#pragma unroll
        for (int e = 0; e < 4; e++) {
            const float nm = (e < 2) ? st0.y : st1.y, k1 = (e < 2) ? k10 : k11, k2 = (e < 2) ? k20 : k21;
            const float tg = fmaf(nm, (e & 1) ? cg.y : cg.x, ag[4 * j + e]);
            const float tu = fmaf(nm, (e & 1) ? cu.y : cu.x, au[4 * j + e]);
            const float th = tanh_fast(tg * fmaf(tg * tg, k2, k1));
            const float p = tg * tu;
            r[e] = fmaf(p, th, p);
        }
        const int jb = jb0 + j;
        size_t o = (((size_t)mb * 28 * 8 + jb) * 16 + rgl) * 32 + lane;
        gp[o] = pack_bf16(r[0], r[1]);
        gp[o + 32] = pack_bf16(r[2], r[3]);
    }
}

__global__ void __cluster_dims__(2, 1, 1) __launch_bounds__(384, 1)
tail_kernel(const __grid_constant__ CUtensorMap tm_o, const __grid_constant__ CUtensorMap tm_g,
            const __grid_constant__ CUtensorMap tm_u, const __grid_constant__ CUtensorMap tm_d,
            const __nv_bfloat16* __restrict__ x, __nv_bfloat16* __restrict__ out) {
    extern __shared__ __align__(1024) unsigned char smem[];
    const uint32_t sb = smem_u32(smem);
    const uint32_t bars = sb + F_BAR;
    const int tid = threadIdx.x, warp = tid >> 5, lane = tid & 31;
    TL(6);
    const int cl = blockIdx.x >> 1, r = blockIdx.x & 1;
    const int mb = ((cl & 7) >> 1) * 4 + (cl >> 4), ntA = (cl & 1) * 2 + ((cl >> 3) & 1);
    const int nt = ntA * 2 + r;
    if (tid == 0) {
        prefetch_tmap(&tm_o); prefetch_tmap(&tm_g); prefetch_tmap(&tm_u); prefetch_tmap(&tm_d);
        for (int i = 0; i < 30; i++) {
            int cnt = 1;
            if ((i >= B_BE && i < B_BE + 3) || (i >= B_CE && i < B_CE + 6) || i == B_ADONE || i == B_BDONE || i == B_PRDY) cnt = 8;
            if (i == B_AUX) cnt = 3;
            mbar_init(bars + 8 * i, cnt);
        }
        mbar_expect(bars + 8 * B_XA, 32768);
        mbar_expect(bars + 8 * B_XC, 32768);
        fence_barrier_init();
    }
    __syncthreads();
    asm volatile("barrier.cluster.arrive.release.aligned;\nbarrier.cluster.wait.acquire.aligned;" ::: "memory");
    if (warp < 4) {
        asm volatile("setmaxnreg.dec.sync.aligned.u32 56;");
        if (warp == 0) {
            if (lane == 0) {
                auto load_b = [&](int it) {
                    const int s = it % 3, pass = it >> 3, kb = it & 7;
                    const int ng = pass ? 3 : 4, c0 = nt * 224 + pass * 128;
                    const uint32_t bar = bars + 8 * (B_BF + s), dst = sb + F_R2 + s * 32768;
                    mbar_expect(bar, ng * 8192);
                    for (int i = 0; i < ng; i++) {
                        tma2d(dst + i * 4096, &tm_g, c0 + i * 32, kb * 64, bar);
                        tma2d(dst + 16384 + i * 4096, &tm_u, c0 + i * 32, kb * 64, bar);
                    }
                };
                for (int i = 0; i < 4; i++) {
                    const uint32_t bar = bars + 8 * (B_FA + (i >> 1));
                    if (!(i & 1)) mbar_expect(bar, 65536);
                    tma2d(sb + i * 32768 + 16384, &tm_o, ntA * 128, (4 * r + i) * 64, bar);
                    tma2d(sb + i * 32768 + 24576, &tm_o, ntA * 128 + 64, (4 * r + i) * 64, bar);
                }
                load_b(0); load_b(1);
                pdl_wait();
                for (int i = 0; i < 4; i++)
                    bulk_g2s(sb + i * 32768, g_ao + (size_t)(mb * 8 + 4 * r + i) * 8192, 16384, bars + 8 * (B_FA + (i >> 1)));
                if (blockIdx.x == 0)
                    for (int i = 0; i < 32; i++) g_cnt[i] = 0;
                mbar_wait(bars + 8 * B_ADONE, 0);
                poll_count(&g_cnt2[mb], 64);
                TX(48);
                for (int kb = 0; kb < 8; kb++) {
                    const uint32_t bar = bars + 8 * (B_HF + (kb >> 1));
                    if (!(kb & 1)) mbar_expect(bar, 32768);
                    bulk_g2s(sb + kb * 16384, g_h + (size_t)(mb * 8 + kb) * 8192, 16384, bar);
                }
                for (int it = 2; it < 16; it++) {
                    const int s = it % 3, n = it / 3;
                    mbar_wait(bars + 8 * (B_BE + s), (s == 2 ? n : n - 1) & 1);
                    load_b(it);
                }
                mbar_wait(bars + 8 * B_BDONE, 0);
                for (int i = 0; i < 6; i++) {
                    const uint32_t bar = bars + 8 * (B_CF + i);
                    mbar_expect(bar, 32768);
                    tma2d(sb + i * 32768 + 16384, &tm_d, ntA * 128, (14 * r + i) * 64, bar);
                    tma2d(sb + i * 32768 + 24576, &tm_d, ntA * 128 + 64, (14 * r + i) * 64, bar);
                }
                poll_count(&g_cnt2[16 + mb * 2 + r], 32);
                TX(53);
                for (int kb = 0; kb < 14; kb++) {
                    const int s = kb % 6;
                    const uint32_t bar = bars + 8 * (B_CF + s);
                    if (kb >= 6) {
                        mbar_wait(bars + 8 * (B_CE + s), ((kb / 6) - 1) & 1);
                        mbar_expect(bar, 32768);
                        tma2d(sb + s * 32768 + 16384, &tm_d, ntA * 128, (14 * r + kb) * 64, bar);
                        tma2d(sb + s * 32768 + 24576, &tm_d, ntA * 128 + 64, (14 * r + kb) * 64, bar);
                    }
                    bulk_g2s(sb + s * 32768, g_g + (size_t)(mb * 28 + 14 * r + kb) * 8192, 16384, bar);
                }
            }
        } else {
            pdl_wait();
            float2* s_rs = (float2*)(smem + F_RS);
            float* s_cs = (float*)(smem + F_CS);
            for (int c = tid - 32; c < 448; c += 96)
                s_cs[c] = __ldcg(&g_cs2[(c >= 224 ? FF - 224 : 0) + nt * 224 + c]);
            if (lane == 0) poll_count(&g_cnt2[mb], 64);
            __syncwarp();
            for (int rr = tid - 32; rr < 128; rr += 96) {
                const float4* hp = (const float4*)(g_hstat + (size_t)(mb * 128 + rr) * 8);
                float4 a = __ldcg(hp), b = __ldcg(hp + 1), c = __ldcg(hp + 2), d = __ldcg(hp + 3);
                float mean = 0.125f * (a.x + a.z + b.x + b.z + c.x + c.z + d.x + d.z);
                float m2 = a.y + a.w + b.y + b.w + c.y + c.w + d.y + d.w;
                float e;
                e = a.x - mean; m2 = fmaf(64.f * e, e, m2); e = a.z - mean; m2 = fmaf(64.f * e, e, m2);
                e = b.x - mean; m2 = fmaf(64.f * e, e, m2); e = b.z - mean; m2 = fmaf(64.f * e, e, m2);
                e = c.x - mean; m2 = fmaf(64.f * e, e, m2); e = c.z - mean; m2 = fmaf(64.f * e, e, m2);
                e = d.x - mean; m2 = fmaf(64.f * e, e, m2); e = d.z - mean; m2 = fmaf(64.f * e, e, m2);
                s_rs[rr] = make_float2(rsqrtf(m2 * (1.0f / DM) + 1e-5f), -mean);
            }
            __syncwarp();
            if (lane == 0) mbar_arrive(bars + 8 * B_AUX);
        }
    } else {
        asm volatile("setmaxnreg.inc.sync.aligned.u32 216;");
        const int wgi = (warp >> 2) - 1, ww = warp & 3, ctid = tid - 128;
        const int g = lane >> 2, t = lane & 3;
        const int rl = wgi * 64 + ww * 16 + g, row = mb * 128 + rl;
        const int rgl = wgi * 8 + ww * 2;
        const float2* s_rs = (const float2*)(smem + F_RS);
        const float* s_cs = (const float*)(smem + F_CS);
        uint32_t* hp = (uint32_t*)g_h + ((size_t)(mb * 8 + nt) * 8 * 16 + rgl) * 32 + lane;
        {
            uint32_t xr[16];
            const uint32_t* xp = (const uint32_t*)(x + (size_t)row * DM + nt * 64) + t;
#pragma unroll
            for (int j = 0; j < 8; j++) { xr[2 * j] = __ldg(xp + 4 * j); xr[2 * j + 1] = __ldg(xp + 8 * (DM / 2) + 4 * j); }
            float acc[64];
#pragma unroll 1
            for (int i = 0; i < 4; i++) {
                if (!(i & 1)) mbar_wait(bars + 8 * (B_FA + (i >> 1)), 0);
                uint64_t ad = make_desc(sb + i * 32768 + wgi * 1024, 2048, 128, 0);
                uint64_t bd = make_desc(sb + i * 32768 + 16384, 8192, 1024, 1);
                WG_FENCE();
#pragma unroll
                for (int k = 0; k < 4; k++) wgmma_ss_n128(acc, ad + k * 256, bd + k * 128, (i | k) != 0);
                WG_COMMIT();
            }
            wg_wait<0>();
            fence_regs(acc);
            TL(7);
            if (lane == 0) mbar_arrive(bars + 8 * B_ADONE);
            float o[32];
            if (r == 0) xchg<0>(acc, o, sb, smem, B_XA, ctid); else xchg<1>(acc, o, sb, smem, B_XA, ctid);
            fence_proxy_async();
            __syncwarp();
            if (lane == 0) mbar_arrive(bars + 8 * (B_BE + 2));
            float v0[16], v1[16];
            float s0 = 0.f, s1 = 0.f;
#pragma unroll
            for (int j = 0; j < 8; j++) {
                uint32_t u0 = pack_bf16(bf_lo(xr[2 * j]) + o[4 * j], bf_hi(xr[2 * j]) + o[4 * j + 1]);
                uint32_t u1 = pack_bf16(bf_lo(xr[2 * j + 1]) + o[4 * j + 2], bf_hi(xr[2 * j + 1]) + o[4 * j + 3]);
                hp[j * 16 * 32] = u0;
                hp[j * 16 * 32 + 32] = u1;
                v0[2 * j] = bf_lo(u0); v0[2 * j + 1] = bf_hi(u0);
                v1[2 * j] = bf_lo(u1); v1[2 * j + 1] = bf_hi(u1);
                s0 += v0[2 * j] + v0[2 * j + 1];
                s1 += v1[2 * j] + v1[2 * j + 1];
            }
            float m0 = s0 * (1.0f / 16), m1 = s1 * (1.0f / 16), q0 = 0.f, q1 = 0.f;
#pragma unroll
            for (int i = 0; i < 16; i++) {
                float d0 = v0[i] - m0, d1 = v1[i] - m1;
                q0 = fmaf(d0, d0, q0); q1 = fmaf(d1, d1, q1);
            }
#pragma unroll
            for (int st = 0; st < 2; st++) {
                float hn = st ? 16.f : 8.f;
                float om0 = __shfl_xor_sync(0xffffffffu, m0, 1 << st), oq0 = __shfl_xor_sync(0xffffffffu, q0, 1 << st);
                float om1 = __shfl_xor_sync(0xffffffffu, m1, 1 << st), oq1 = __shfl_xor_sync(0xffffffffu, q1, 1 << st);
                float d0 = om0 - m0, d1 = om1 - m1;
                q0 = q0 + oq0 + d0 * d0 * hn; q1 = q1 + oq1 + d1 * d1 * hn;
                m0 = 0.5f * (m0 + om0); m1 = 0.5f * (m1 + om1);
            }
            if (t == 0) {
                g_hstat[row * 8 + nt] = make_float2(m0, q0);
                g_hstat[(row + 8) * 8 + nt] = make_float2(m1, q1);
            }
            publish(&g_cnt2[mb], lane);
            TL(8);
        }
        {
            float ag[64], au[64];
#pragma unroll 1
            for (int kb = 0; kb < 8; kb++) {
                const int s = kb % 3;
                if (!(kb & 1)) mbar_wait(bars + 8 * (B_HF + (kb >> 1)), 0);
                mbar_wait(bars + 8 * (B_BF + s), (kb / 3) & 1);
                if (warp == 4) TX(32 + kb);
                uint64_t ad = make_desc(sb + kb * 16384 + wgi * 1024, 2048, 128, 0);
                uint64_t bd = make_desc(sb + F_R2 + s * 32768, 4096, 512, 2);
                WG_FENCE();
#pragma unroll
                for (int k = 0; k < 4; k++) {
                    wgmma_ss_n128(ag, ad + k * 256, bd + k * 64, (kb | k) != 0);
                    wgmma_ss_n128(au, ad + k * 256, bd + 1024 + k * 64, (kb | k) != 0);
                }
                WG_COMMIT();
                if (kb > 0) {
                    wg_wait<1>();
                    if (lane == 0) mbar_arrive(bars + 8 * (B_BE + (kb - 1) % 3));
                }
            }
            wg_wait<0>();
            if (lane == 0) mbar_arrive(bars + 8 * (B_BE + 7 % 3));
            fence_regs(ag); fence_regs(au);
            TL(10);
            mbar_wait(bars + 8 * B_AUX, 0);
            ffn_epilogue<16>(ag, au, s_cs, 0, nt * 28, s_rs[rl], s_rs[rl + 8], mb, rgl, lane);
        }
        {
            float ag[48], au[48];
#pragma unroll 1
            for (int kb = 0; kb < 8; kb++) {
                const int it = 8 + kb, s = it % 3;
                mbar_wait(bars + 8 * (B_BF + s), (it / 3) & 1);
                if (warp == 4) TX(32 + it);
                uint64_t ad = make_desc(sb + kb * 16384 + wgi * 1024, 2048, 128, 0);
                uint64_t bd = make_desc(sb + F_R2 + s * 32768, 4096, 512, 2);
                WG_FENCE();
#pragma unroll
                for (int k = 0; k < 4; k++) {
                    wgmma_ss_n96(ag, ad + k * 256, bd + k * 64, (kb | k) != 0);
                    wgmma_ss_n96(au, ad + k * 256, bd + 1024 + k * 64, (kb | k) != 0);
                }
                WG_COMMIT();
                if (kb > 0) {
                    wg_wait<1>();
                    if (lane == 0) mbar_arrive(bars + 8 * (B_BE + (it - 1) % 3));
                }
            }
            wg_wait<0>();
            if (lane == 0) {
                mbar_arrive(bars + 8 * B_BDONE);
                mbar_arrive_remote(mapa(bars + 8 * B_PRDY, 1 - r));
            }
            fence_regs(ag); fence_regs(au);
            TL(11);
            ffn_epilogue<12>(ag, au, s_cs, 128, nt * 28 + 16, s_rs[rl], s_rs[rl + 8], mb, rgl, lane);
            publish(&g_cnt2[16 + mb * 2 + (nt >> 2)], lane);
            TL(12);
        }
        {
            uint32_t hr[16];
#pragma unroll
            for (int j = 0; j < 8; j++) { hr[2 * j] = __ldcg(hp + j * 16 * 32); hr[2 * j + 1] = __ldcg(hp + j * 16 * 32 + 32); }
            float acc[64];
#pragma unroll 1
            for (int kb = 0; kb < 14; kb++) {
                const int s = kb % 6;
                mbar_wait(bars + 8 * (B_CF + s), (kb / 6) & 1);
                if (warp == 4) TX(96 + kb);
                uint64_t ad = make_desc(sb + s * 32768 + wgi * 1024, 2048, 128, 0);
                uint64_t bd = make_desc(sb + s * 32768 + 16384, 8192, 1024, 1);
                WG_FENCE();
#pragma unroll
                for (int k = 0; k < 4; k++) wgmma_ss_n128(acc, ad + k * 256, bd + k * 128, (kb | k) != 0);
                WG_COMMIT();
                if (kb > 0) {
                    wg_wait<1>();
                    if (lane == 0) mbar_arrive(bars + 8 * (B_CE + (kb - 1) % 6));
                }
            }
            wg_wait<0>();
            fence_regs(acc);
            TL(14);
            mbar_wait_cluster(bars + 8 * B_PRDY, 0);
            float o[32];
            if (r == 0) xchg<0>(acc, o, sb, smem, B_XC, ctid); else xchg<1>(acc, o, sb, smem, B_XC, ctid);
            const float a0 = s_rs[rl].x, a1 = s_rs[rl + 8].x;
            const float k0 = 0.5f * a0 * a0, k1 = 0.5f * a1 * a1;
            uint32_t* op = (uint32_t*)(out + (size_t)row * DM + nt * 64) + t;
#pragma unroll
            for (int j = 0; j < 8; j++) {
                op[4 * j] = pack_bf16(fmaf(k0, o[4 * j], bf_lo(hr[2 * j])), fmaf(k0, o[4 * j + 1], bf_hi(hr[2 * j])));
                op[8 * (DM / 2) + 4 * j] = pack_bf16(fmaf(k1, o[4 * j + 2], bf_lo(hr[2 * j + 1])), fmaf(k1, o[4 * j + 3], bf_hi(hr[2 * j + 1])));
            }
            TL(15);
        }
    }
}

typedef CUresult (*EncodeFn)(CUtensorMap*, CUtensorMapDataType, cuuint32_t, void*, const cuuint64_t*, const cuuint64_t*,
                             const cuuint32_t*, const cuuint32_t*, CUtensorMapInterleave, CUtensorMapSwizzle,
                             CUtensorMapL2promotion, CUtensorMapFloatOOBfill);

void encode(EncodeFn fn, CUtensorMap* m, const void* ptr, int rank, const cuuint64_t* dims, const cuuint64_t* strides,
            const cuuint32_t* box, CUtensorMapSwizzle swz) {
    cuuint32_t es[3] = {1, 1, 1};
    fn(m, CU_TENSOR_MAP_DATA_TYPE_BFLOAT16, rank, (void*)ptr, dims, strides, box, es, CU_TENSOR_MAP_INTERLEAVE_NONE, swz,
       CU_TENSOR_MAP_L2_PROMOTION_L2_256B, CU_TENSOR_MAP_FLOAT_OOB_FILL_NONE);
}

template <typename... KArgs, typename... Args>
void launch(void (*kern)(KArgs...), int grid, int block, int smem, bool pdl, Args... args) {
    cudaLaunchConfig_t cfg = {};
    cfg.gridDim = dim3(grid); cfg.blockDim = dim3(block); cfg.dynamicSmemBytes = smem;
    cfg.stream = cudaStreamPerThread;
    cudaLaunchAttribute at[1];
    at[0].id = cudaLaunchAttributeProgrammaticStreamSerialization;
    at[0].val.programmaticStreamSerializationAllowed = 1;
    cfg.attrs = at; cfg.numAttrs = pdl ? 1 : 0;
    cudaLaunchKernelEx(&cfg, kern, KArgs(args)...);
}

}

extern "C" void kernel_launch(void* const* d_in, const int* in_sizes, int n_in, void* d_out, int out_size) {
    const __nv_bfloat16* x = (const __nv_bfloat16*)d_in[0];
    const __nv_bfloat16* wqkv = (const __nv_bfloat16*)d_in[1];
    const __nv_bfloat16* wo = (const __nv_bfloat16*)d_in[2];
    const __nv_bfloat16* wgate = (const __nv_bfloat16*)d_in[4];
    const __nv_bfloat16* wup = (const __nv_bfloat16*)d_in[5];
    const __nv_bfloat16* wdown = (const __nv_bfloat16*)d_in[6];
    __nv_bfloat16* out = (__nv_bfloat16*)d_out;

    static CUtensorMap tm_x, tm_wqkv, tm_wo, tm_wg, tm_wu, tm_wd;
    static const void* cached[6] = {nullptr, nullptr, nullptr, nullptr, nullptr, nullptr};
    if (cached[0] != x || cached[1] != wqkv || cached[2] != wo || cached[3] != wgate || cached[4] != wup || cached[5] != wdown) {
        void* fp = nullptr;
        cudaDriverEntryPointQueryResult qr;
        cudaGetDriverEntryPoint("cuTensorMapEncodeTiled", &fp, cudaEnableDefault, &qr);
        EncodeFn fn = (EncodeFn)fp;
        { cuuint64_t d[2] = {512, 2048}, s[1] = {1024}; cuuint32_t b[2] = {64, 128};
          encode(fn, &tm_x, x, 2, d, s, b, CU_TENSOR_MAP_SWIZZLE_128B); }
        { cuuint64_t d[3] = {64, 512, 24}, s[2] = {3072, 128}; cuuint32_t b[3] = {64, 64, 3};
          encode(fn, &tm_wqkv, wqkv, 3, d, s, b, CU_TENSOR_MAP_SWIZZLE_128B); }
        { cuuint64_t d[2] = {512, 512}, s[1] = {1024}; cuuint32_t b[2] = {64, 64};
          encode(fn, &tm_wo, wo, 2, d, s, b, CU_TENSOR_MAP_SWIZZLE_128B); }
        { cuuint64_t d[2] = {1792, 512}, s[1] = {3584}; cuuint32_t b[2] = {32, 64};
          encode(fn, &tm_wg, wgate, 2, d, s, b, CU_TENSOR_MAP_SWIZZLE_64B);
          encode(fn, &tm_wu, wup, 2, d, s, b, CU_TENSOR_MAP_SWIZZLE_64B); }
        { cuuint64_t d[2] = {512, 1792}, s[1] = {1024}; cuuint32_t b[2] = {64, 64};
          encode(fn, &tm_wd, wdown, 2, d, s, b, CU_TENSOR_MAP_SWIZZLE_128B); }
        cudaFuncSetAttribute(qkv_kernel, cudaFuncAttributeMaxDynamicSharedMemorySize, K1_SMEM);
        cudaFuncSetAttribute(attn_kernel, cudaFuncAttributeMaxDynamicSharedMemorySize, AT_SMEM);
        cudaFuncSetAttribute(tail_kernel, cudaFuncAttributeMaxDynamicSharedMemorySize, F_SMEM);
        cached[0] = x; cached[1] = wqkv; cached[2] = wo; cached[3] = wgate; cached[4] = wup; cached[5] = wdown;
    }
    launch(qkv_kernel, 128, 384, K1_SMEM, false, tm_x, tm_wqkv, x, wqkv);
    launch(attn_kernel, 132, 512, AT_SMEM, true, wgate, wup, wo, wdown);
    launch(tail_kernel, 128, 384, F_SMEM, true, tm_wo, tm_wg, tm_wu, tm_wd, x, out);
}
```

```cpp
#include <cuda_runtime.h>
#include <cuda_bf16.h>
#include <cuda.h>
#include <stdint.h>

#define TAILMAP 1
namespace {

constexpr int S_LEN = 2048, DM = 512, NH = 32, FF = 1792;

__device__ __align__(1024) __nv_bfloat16 g_qkv[3 * NH * S_LEN * 16];
__device__ __align__(1024) __nv_bfloat16 g_ao[S_LEN * DM];
__device__ __align__(1024) __nv_bfloat16 g_h[S_LEN * DM];
__device__ __align__(1024) __nv_bfloat16 g_g[S_LEN * FF];
__device__ __align__(16) float2 g_rowstat1[S_LEN];
__device__ float g_cs1_part[16 * 1536];
__device__ unsigned int g_cnt[32];
__device__ unsigned int g_cnt2[64];
__device__ float g_nrm[3 * NH * 128];
__device__ float2 g_hstat[S_LEN * 8];
__device__ float g_cs2[2 * FF];

#define TL(slot)
#define TX(slot)
__device__ __forceinline__ uint32_t smem_u32(const void* p) { return (uint32_t)__cvta_generic_to_shared(p); }
__device__ __forceinline__ void mbar_init(uint32_t a, int c) { asm volatile("mbarrier.init.shared.b64 [%0], %1;" :: "r"(a), "r"(c)); }
__device__ __forceinline__ void mbar_expect(uint32_t a, int bytes) { asm volatile("mbarrier.arrive.expect_tx.shared.b64 _, [%0], %1;" :: "r"(a), "r"(bytes) : "memory"); }
__device__ __forceinline__ void mbar_arrive(uint32_t a) { asm volatile("mbarrier.arrive.shared.b64 _, [%0];" :: "r"(a) : "memory"); }
__device__ __forceinline__ void mbar_wait(uint32_t a, int parity) {
    uint32_t done;
    int it = 0;
    do {
        asm volatile("{\n.reg .pred p;\nmbarrier.try_wait.parity.shared.b64 p, [%1], %2;\nselp.u32 %0, 1, 0, p;\n}"
                     : "=r"(done) : "r"(a), "r"(parity) : "memory");
        if (++it > (1 << 24)) __trap();
    } while (!done);
}
__device__ __forceinline__ void bulk_g2s(uint32_t dst, const void* src, int bytes, uint32_t bar) {
    asm volatile("cp.async.bulk.shared::cluster.global.mbarrier::complete_tx::bytes [%0], [%1], %2, [%3];"
                 :: "r"(dst), "l"(src), "r"(bytes), "r"(bar) : "memory");
}
__device__ __forceinline__ void tma2d(uint32_t dst, const CUtensorMap* m, int c0, int c1, uint32_t bar) {
    asm volatile("cp.async.bulk.tensor.2d.shared::cluster.global.mbarrier::complete_tx::bytes [%0], [%1, {%3, %4}], [%2];"
                 :: "r"(dst), "l"(m), "r"(bar), "r"(c0), "r"(c1) : "memory");
}
__device__ __forceinline__ void tma3d(uint32_t dst, const CUtensorMap* m, int c0, int c1, int c2, uint32_t bar) {
    asm volatile("cp.async.bulk.tensor.3d.shared::cluster.global.mbarrier::complete_tx::bytes [%0], [%1, {%3, %4, %5}], [%2];"
                 :: "r"(dst), "l"(m), "r"(bar), "r"(c0), "r"(c1), "r"(c2) : "memory");
}
__device__ __forceinline__ void prefetch_tmap(const CUtensorMap* m) { asm volatile("prefetch.tensormap [%0];" :: "l"(m) : "memory"); }
__device__ __forceinline__ void pdl_wait() { asm volatile("griddepcontrol.wait;" ::: "memory"); }
__device__ __forceinline__ void pdl_launch() { asm volatile("griddepcontrol.launch_dependents;" ::: "memory"); }
__device__ __forceinline__ void fence_barrier_init() { asm volatile("fence.mbarrier_init.release.cluster;" ::: "memory"); }
__device__ __forceinline__ void fence_proxy_async() { asm volatile("fence.proxy.async.shared::cta;" ::: "memory"); }
__device__ __forceinline__ uint64_t make_desc(uint32_t saddr, uint32_t lbo, uint32_t sbo, uint32_t swz) {
    return (uint64_t)((saddr & 0x3FFFF) >> 4) | ((uint64_t)((lbo & 0x3FFFF) >> 4) << 16) |
           ((uint64_t)((sbo & 0x3FFFF) >> 4) << 32) | ((uint64_t)swz << 62);
}
#define WG_FENCE() asm volatile("wgmma.fence.sync.aligned;" ::: "memory")
#define WG_COMMIT() asm volatile("wgmma.commit_group.sync.aligned;" ::: "memory")
template <int N> __device__ __forceinline__ void wg_wait() { asm volatile("wgmma.wait_group.sync.aligned %0;" :: "n"(N) : "memory"); }
template <int N> __device__ __forceinline__ void fence_regs(float (&d)[N]) {
#pragma unroll
    for (int i = 0; i < N; i++) asm volatile("" : "+f"(d[i]) :: "memory");
}
__device__ __forceinline__ float ex2f(float x) { float y; asm("ex2.approx.ftz.f32 %0, %1;" : "=f"(y) : "f"(x)); return y; }
__device__ __forceinline__ float tanh_fast(float x) { float y; asm("tanh.approx.f32 %0, %1;" : "=f"(y) : "f"(x)); return y; }
__device__ __forceinline__ uint32_t pack_bf16(float lo, float hi) { uint32_t r; asm("cvt.rn.bf16x2.f32 %0, %1, %2;" : "=r"(r) : "f"(hi), "f"(lo)); return r; }
__device__ __forceinline__ float bf_lo(uint32_t u) { return __uint_as_float(u << 16); }
__device__ __forceinline__ float bf_hi(uint32_t u) { return __uint_as_float(u & 0xFFFF0000u); }
__device__ __forceinline__ uint32_t hfma2(uint32_t a, uint32_t b, uint32_t c) { uint32_t r; asm("fma.rn.f16x2 %0, %1, %2, %3;" : "=r"(r) : "r"(a), "r"(b), "r"(c)); return r; }
__device__ __forceinline__ uint32_t hmul2(uint32_t a, uint32_t b) { uint32_t r; asm("mul.rn.f16x2 %0, %1, %2;" : "=r"(r) : "r"(a), "r"(b)); return r; }
__device__ __forceinline__ unsigned int ld_acquire(const unsigned int* p) { unsigned int v; asm volatile("ld.acquire.gpu.u32 %0, [%1];" : "=r"(v) : "l"(p) : "memory"); return v; }
__device__ __forceinline__ void red_release(unsigned int* p) { asm volatile("red.release.gpu.global.add.u32 [%0], 1;" :: "l"(p) : "memory"); }
__device__ __forceinline__ float warp_sum(float v) {
#pragma unroll
    for (int o = 16; o; o >>= 1) v += __shfl_xor_sync(0xffffffffu, v, o);
    return v;
}
__device__ __forceinline__ float warp_max(float v) {
#pragma unroll
    for (int o = 16; o; o >>= 1) v = fmaxf(v, __shfl_xor_sync(0xffffffffu, v, o));
    return v;
}

__device__ __forceinline__ void wgmma_ss_n64(float (&d)[32], uint64_t adesc, uint64_t bdesc, int scale_d) {
    asm volatile("{\n.reg .pred p;\nsetp.ne.b32 p, %34, 0;\n"
      "wgmma.mma_async.sync.aligned.m64n64k16.f32.bf16.bf16 {%0,%1,%2,%3,%4,%5,%6,%7,%8,%9,%10,%11,%12,%13,%14,%15,%16,%17,%18,%19,%20,%21,%22,%23,%24,%25,%26,%27,%28,%29,%30,%31}, %32, %33, p, 1, 1, 0, 1;\n}"
      : "+f"(d[0]), "+f"(d[1]), "+f"(d[2]), "+f"(d[3]), "+f"(d[4]), "+f"(d[5]), "+f"(d[6]), "+f"(d[7]), "+f"(d[8]), "+f"(d[9]), "+f"(d[10]), "+f"(d[11]), "+f"(d[12]), "+f"(d[13]), "+f"(d[14]), "+f"(d[15]), "+f"(d[16]), "+f"(d[17]), "+f"(d[18]), "+f"(d[19]), "+f"(d[20]), "+f"(d[21]), "+f"(d[22]), "+f"(d[23]), "+f"(d[24]), "+f"(d[25]), "+f"(d[26]), "+f"(d[27]), "+f"(d[28]), "+f"(d[29]), "+f"(d[30]), "+f"(d[31])
      : "l"(adesc), "l"(bdesc), "r"(scale_d));
}
__device__ __forceinline__ void wgmma_ss_n96(float (&d)[48], uint64_t adesc, uint64_t bdesc, int scale_d) {
    asm volatile("{\n.reg .pred p;\nsetp.ne.b32 p, %50, 0;\n"
      "wgmma.mma_async.sync.aligned.m64n96k16.f32.bf16.bf16 {%0,%1,%2,%3,%4,%5,%6,%7,%8,%9,%10,%11,%12,%13,%14,%15,%16,%17,%18,%19,%20,%21,%22,%23,%24,%25,%26,%27,%28,%29,%30,%31,%32,%33,%34,%35,%36,%37,%38,%39,%40,%41,%42,%43,%44,%45,%46,%47}, %48, %49, p, 1, 1, 0, 1;\n}"
      : "+f"(d[0]), "+f"(d[1]), "+f"(d[2]), "+f"(d[3]), "+f"(d[4]), "+f"(d[5]), "+f"(d[6]), "+f"(d[7]), "+f"(d[8]), "+f"(d[9]), "+f"(d[10]), "+f"(d[11]), "+f"(d[12]), "+f"(d[13]), "+f"(d[14]), "+f"(d[15]), "+f"(d[16]), "+f"(d[17]), "+f"(d[18]), "+f"(d[19]), "+f"(d[20]), "+f"(d[21]), "+f"(d[22]), "+f"(d[23]), "+f"(d[24]), "+f"(d[25]), "+f"(d[26]), "+f"(d[27]), "+f"(d[28]), "+f"(d[29]), "+f"(d[30]), "+f"(d[31]), "+f"(d[32]), "+f"(d[33]), "+f"(d[34]), "+f"(d[35]), "+f"(d[36]), "+f"(d[37]), "+f"(d[38]), "+f"(d[39]), "+f"(d[40]), "+f"(d[41]), "+f"(d[42]), "+f"(d[43]), "+f"(d[44]), "+f"(d[45]), "+f"(d[46]), "+f"(d[47])
      : "l"(adesc), "l"(bdesc), "r"(scale_d));
}
__device__ __forceinline__ void wgmma_ss_n128(float (&d)[64], uint64_t adesc, uint64_t bdesc, int scale_d) {
    asm volatile("{\n.reg .pred p;\nsetp.ne.b32 p, %66, 0;\n"
      "wgmma.mma_async.sync.aligned.m64n128k16.f32.bf16.bf16 {%0,%1,%2,%3,%4,%5,%6,%7,%8,%9,%10,%11,%12,%13,%14,%15,%16,%17,%18,%19,%20,%21,%22,%23,%24,%25,%26,%27,%28,%29,%30,%31,%32,%33,%34,%35,%36,%37,%38,%39,%40,%41,%42,%43,%44,%45,%46,%47,%48,%49,%50,%51,%52,%53,%54,%55,%56,%57,%58,%59,%60,%61,%62,%63}, %64, %65, p, 1, 1, 0, 1;\n}"
      : "+f"(d[0]), "+f"(d[1]), "+f"(d[2]), "+f"(d[3]), "+f"(d[4]), "+f"(d[5]), "+f"(d[6]), "+f"(d[7]), "+f"(d[8]), "+f"(d[9]), "+f"(d[10]), "+f"(d[11]), "+f"(d[12]), "+f"(d[13]), "+f"(d[14]), "+f"(d[15]), "+f"(d[16]), "+f"(d[17]), "+f"(d[18]), "+f"(d[19]), "+f"(d[20]), "+f"(d[21]), "+f"(d[22]), "+f"(d[23]), "+f"(d[24]), "+f"(d[25]), "+f"(d[26]), "+f"(d[27]), "+f"(d[28]), "+f"(d[29]), "+f"(d[30]), "+f"(d[31]), "+f"(d[32]), "+f"(d[33]), "+f"(d[34]), "+f"(d[35]), "+f"(d[36]), "+f"(d[37]), "+f"(d[38]), "+f"(d[39]), "+f"(d[40]), "+f"(d[41]), "+f"(d[42]), "+f"(d[43]), "+f"(d[44]), "+f"(d[45]), "+f"(d[46]), "+f"(d[47]), "+f"(d[48]), "+f"(d[49]), "+f"(d[50]), "+f"(d[51]), "+f"(d[52]), "+f"(d[53]), "+f"(d[54]), "+f"(d[55]), "+f"(d[56]), "+f"(d[57]), "+f"(d[58]), "+f"(d[59]), "+f"(d[60]), "+f"(d[61]), "+f"(d[62]), "+f"(d[63])
      : "l"(adesc), "l"(bdesc), "r"(scale_d));
}
__device__ __forceinline__ void wgmma_ss_n192(float (&d)[96], uint64_t adesc, uint64_t bdesc, int scale_d) {
    asm volatile("{\n.reg .pred p;\nsetp.ne.b32 p, %98, 0;\n"
      "wgmma.mma_async.sync.aligned.m64n192k16.f32.bf16.bf16 {%0,%1,%2,%3,%4,%5,%6,%7,%8,%9,%10,%11,%12,%13,%14,%15,%16,%17,%18,%19,%20,%21,%22,%23,%24,%25,%26,%27,%28,%29,%30,%31,%32,%33,%34,%35,%36,%37,%38,%39,%40,%41,%42,%43,%44,%45,%46,%47,%48,%49,%50,%51,%52,%53,%54,%55,%56,%57,%58,%59,%60,%61,%62,%63,%64,%65,%66,%67,%68,%69,%70,%71,%72,%73,%74,%75,%76,%77,%78,%79,%80,%81,%82,%83,%84,%85,%86,%87,%88,%89,%90,%91,%92,%93,%94,%95}, %96, %97, p, 1, 1, 0, 1;\n}"
      : "+f"(d[0]), "+f"(d[1]), "+f"(d[2]), "+f"(d[3]), "+f"(d[4]), "+f"(d[5]), "+f"(d[6]), "+f"(d[7]), "+f"(d[8]), "+f"(d[9]), "+f"(d[10]), "+f"(d[11]), "+f"(d[12]), "+f"(d[13]), "+f"(d[14]), "+f"(d[15]), "+f"(d[16]), "+f"(d[17]), "+f"(d[18]), "+f"(d[19]), "+f"(d[20]), "+f"(d[21]), "+f"(d[22]), "+f"(d[23]), "+f"(d[24]), "+f"(d[25]), "+f"(d[26]), "+f"(d[27]), "+f"(d[28]), "+f"(d[29]), "+f"(d[30]), "+f"(d[31]), "+f"(d[32]), "+f"(d[33]), "+f"(d[34]), "+f"(d[35]), "+f"(d[36]), "+f"(d[37]), "+f"(d[38]), "+f"(d[39]), "+f"(d[40]), "+f"(d[41]), "+f"(d[42]), "+f"(d[43]), "+f"(d[44]), "+f"(d[45]), "+f"(d[46]), "+f"(d[47]), "+f"(d[48]), "+f"(d[49]), "+f"(d[50]), "+f"(d[51]), "+f"(d[52]), "+f"(d[53]), "+f"(d[54]), "+f"(d[55]), "+f"(d[56]), "+f"(d[57]), "+f"(d[58]), "+f"(d[59]), "+f"(d[60]), "+f"(d[61]), "+f"(d[62]), "+f"(d[63]), "+f"(d[64]), "+f"(d[65]), "+f"(d[66]), "+f"(d[67]), "+f"(d[68]), "+f"(d[69]), "+f"(d[70]), "+f"(d[71]), "+f"(d[72]), "+f"(d[73]), "+f"(d[74]), "+f"(d[75]), "+f"(d[76]), "+f"(d[77]), "+f"(d[78]), "+f"(d[79]), "+f"(d[80]), "+f"(d[81]), "+f"(d[82]), "+f"(d[83]), "+f"(d[84]), "+f"(d[85]), "+f"(d[86]), "+f"(d[87]), "+f"(d[88]), "+f"(d[89]), "+f"(d[90]), "+f"(d[91]), "+f"(d[92]), "+f"(d[93]), "+f"(d[94]), "+f"(d[95])
      : "l"(adesc), "l"(bdesc), "r"(scale_d));
}
__device__ __forceinline__ void qk_wgmma_n64(float (&d)[32], const uint32_t (&a)[4], uint64_t desc) {
    asm volatile("wgmma.mma_async.sync.aligned.m64n64k16.f32.bf16.bf16 {%0,%1,%2,%3,%4,%5,%6,%7,%8,%9,%10,%11,%12,%13,%14,%15,%16,%17,%18,%19,%20,%21,%22,%23,%24,%25,%26,%27,%28,%29,%30,%31}, {%32,%33,%34,%35}, %36, 0, 1, 1, 0;"
      : "=f"(d[0]), "=f"(d[1]), "=f"(d[2]), "=f"(d[3]), "=f"(d[4]), "=f"(d[5]), "=f"(d[6]), "=f"(d[7]), "=f"(d[8]), "=f"(d[9]), "=f"(d[10]), "=f"(d[11]), "=f"(d[12]), "=f"(d[13]), "=f"(d[14]), "=f"(d[15]), "=f"(d[16]), "=f"(d[17]), "=f"(d[18]), "=f"(d[19]), "=f"(d[20]), "=f"(d[21]), "=f"(d[22]), "=f"(d[23]), "=f"(d[24]), "=f"(d[25]), "=f"(d[26]), "=f"(d[27]), "=f"(d[28]), "=f"(d[29]), "=f"(d[30]), "=f"(d[31])
      : "r"(a[0]), "r"(a[1]), "r"(a[2]), "r"(a[3]), "l"(desc));
}

__device__ __forceinline__ void pv_wgmma(float (&d)[12], uint32_t a0, uint32_t a1, uint32_t a2, uint32_t a3, uint64_t desc) {
    asm volatile("wgmma.mma_async.sync.aligned.m64n24k16.f32.bf16.bf16 {%0,%1,%2,%3,%4,%5,%6,%7,%8,%9,%10,%11}, {%12,%13,%14,%15}, %16, 1, 1, 1, 1;"
      : "+f"(d[0]), "+f"(d[1]), "+f"(d[2]), "+f"(d[3]), "+f"(d[4]), "+f"(d[5]), "+f"(d[6]), "+f"(d[7]), "+f"(d[8]), "+f"(d[9]), "+f"(d[10]), "+f"(d[11])
      : "r"(a0), "r"(a1), "r"(a2), "r"(a3), "l"(desc));
}

__device__ __forceinline__ void tile_of(int bid, int& mb, int& nt) {
    int grp = bid >> 4, in = bid & 15;
    mb = (grp >> 1) * 4 + (in >> 2);
    nt = (grp & 1) * 4 + (in & 3);
}

constexpr int K1_STAGES = 5, K1_STAGE = 16384 + 24576;
constexpr int K1_BAR = K1_STAGES * K1_STAGE, K1_RS = K1_BAR + 128, K1_CS = K1_RS + 1024, K1_SMEM = K1_CS + 768;

__device__ __forceinline__ float2 row_stats_x(const __nv_bfloat16* x, int row, int lane) {
    const uint4* p = (const uint4*)(x + (size_t)row * DM);
    uint4 a = __ldg(p + lane), b = __ldg(p + 32 + lane);
    float v[16];
    v[0] = bf_lo(a.x); v[1] = bf_hi(a.x); v[2] = bf_lo(a.y); v[3] = bf_hi(a.y);
    v[4] = bf_lo(a.z); v[5] = bf_hi(a.z); v[6] = bf_lo(a.w); v[7] = bf_hi(a.w);
    v[8] = bf_lo(b.x); v[9] = bf_hi(b.x); v[10] = bf_lo(b.y); v[11] = bf_hi(b.y);
    v[12] = bf_lo(b.z); v[13] = bf_hi(b.z); v[14] = bf_lo(b.w); v[15] = bf_hi(b.w);
    float s = 0.f;
#pragma unroll
    for (int i = 0; i < 16; i++) s += v[i];
    float mean = warp_sum(s) * (1.0f / DM);
    float q = 0.f;
#pragma unroll
    for (int i = 0; i < 16; i++) { float d = v[i] - mean; q = fmaf(d, d, q); }
    float var = warp_sum(q) * (1.0f / DM);
    float rstd = rsqrtf(var + 1e-5f);
    return make_float2(rstd, -mean * rstd);
}
__device__ __forceinline__ void colsum8(const __nv_bfloat16* w, int ld, int col, int k0, int nk, float (&s)[8]) {
#pragma unroll
    for (int i = 0; i < 8; i++) s[i] = 0.f;
    for (int k = k0; k < k0 + nk; k += 8) {
        uint4 u[8];
#pragma unroll
        for (int i = 0; i < 8; i++) u[i] = __ldg((const uint4*)(w + (size_t)(k + i) * ld + col));
#pragma unroll
        for (int i = 0; i < 8; i++) {
            s[0] += bf_lo(u[i].x); s[1] += bf_hi(u[i].x); s[2] += bf_lo(u[i].y); s[3] += bf_hi(u[i].y);
            s[4] += bf_lo(u[i].z); s[5] += bf_hi(u[i].z); s[6] += bf_lo(u[i].w); s[7] += bf_hi(u[i].w);
        }
    }
}
__device__ __forceinline__ bool wait_count(const unsigned int* p, unsigned int target, int lane) {
    int ok = 1;
    if (lane == 0) {
        int it = 0;
        while (ld_acquire(p) < target) { if (++it > (1 << 16)) { ok = 0; break; } __nanosleep(20); }
    }
    ok = __shfl_sync(0xffffffffu, ok, 0);
    return ok != 0;
}

__global__ void __launch_bounds__(384, 1)
qkv_kernel(const __grid_constant__ CUtensorMap tm_x, const __grid_constant__ CUtensorMap tm_w,
           const __nv_bfloat16* __restrict__ x, const __nv_bfloat16* __restrict__ wqkv) {
    extern __shared__ __align__(1024) unsigned char smem[];
    const uint32_t sb = smem_u32(smem);
    const int tid = threadIdx.x, warp = tid >> 5, lane = tid & 31;
    TL(0);
    int mb, nt;
    tile_of(blockIdx.x, mb, nt);
    const uint32_t full = sb + K1_BAR, empty = full + 40, auxb = full + 80;
    if (tid == 0) {
        prefetch_tmap(&tm_x); prefetch_tmap(&tm_w);
        for (int i = 0; i < K1_STAGES; i++) { mbar_init(full + 8 * i, 1); mbar_init(empty + 8 * i, 8); }
        mbar_init(auxb, 3);
        fence_barrier_init();
    }
    __syncthreads();
    pdl_launch();
    if (warp == 0) {
        if (blockIdx.x == 0) { g_cnt2[lane] = 0; g_cnt2[32 + lane] = 0; }
        if (lane == 0) {
            for (int kb = 0; kb < 8; kb++) {
                int s = kb % K1_STAGES;
                if (kb >= K1_STAGES) mbar_wait(empty + 8 * s, 0);
                mbar_expect(full + 8 * s, K1_STAGE);
                tma2d(sb + s * K1_STAGE, &tm_x, kb * 64, mb * 128, full + 8 * s);
                tma3d(sb + s * K1_STAGE + 16384, &tm_w, 0, kb * 64, nt * 3, full + 8 * s);
            }
        }
    } else if (warp < 4) {
        float2* s_rs = (float2*)(smem + K1_RS);
        float* s_cs = (float*)(smem + K1_CS);
        {
            float cs[8];
            const int cg = (warp - 1) * 8 + (lane & 7);
            colsum8(wqkv, 1536, nt * 192 + cg * 8, mb * 32 + (lane >> 3) * 8, 8, cs);
#pragma unroll
            for (int i = 0; i < 8; i++) {
                cs[i] += __shfl_xor_sync(0xffffffffu, cs[i], 8);
                cs[i] += __shfl_xor_sync(0xffffffffu, cs[i], 16);
            }
            if (lane < 8) {
                float4* d = (float4*)(g_cs1_part + mb * 1536 + nt * 192 + cg * 8);
                d[0] = make_float4(cs[0], cs[1], cs[2], cs[3]);
                d[1] = make_float4(cs[4], cs[5], cs[6], cs[7]);
            }
            __syncwarp();
            if (lane == 0) red_release(&g_cnt[16 + nt]);
        }
        if (warp == 1) {
            asm volatile("bar.sync 1, 288;" ::: "memory");
            if (lane == 0) red_release(&g_cnt[mb]);
        }
        TX(8 + warp);
        if (warp == 1) {
            if (wait_count(&g_cnt[mb], 8, lane)) {
#pragma unroll
                for (int i = 0; i < 4; i++) s_rs[lane + 32 * i] = __ldcg(&g_rowstat1[mb * 128 + lane + 32 * i]);
            } else {
                for (int i = 0; i < 128; i++) {
                    float2 st = row_stats_x(x, mb * 128 + i, lane);
                    if (lane == 0) s_rs[i] = st;
                }
            }
        } else {
            int c0 = (warp - 2) * 96;
            if (wait_count(&g_cnt[16 + nt], 48, lane)) {
#pragma unroll
                for (int i = 0; i < 3; i++) {
                    float s = 0.f;
#pragma unroll
                    for (int p = 0; p < 16; p++) s += __ldcg(&g_cs1_part[p * 1536 + nt * 192 + c0 + lane + 32 * i]);
                    s_cs[c0 + lane + 32 * i] = s;
                }
            } else if (lane < 12) {
                float s[8];
                colsum8(wqkv, 1536, nt * 192 + c0 + lane * 8, 0, 512, s);
#pragma unroll
                for (int i = 0; i < 8; i++) s_cs[c0 + lane * 8 + i] = s[i];
            }
        }
        __syncwarp();
        TX(12 + warp);
        if (lane == 0) mbar_arrive(auxb);
    } else {
        const int wgi = (warp >> 2) - 1, ww = warp & 3;
        {
            const int r0 = mb * 128 + nt * 16 + (warp - 4) * 2;
            float2 sa = row_stats_x(x, r0, lane), sb2 = row_stats_x(x, r0 + 1, lane);
            if (lane == 0) *(float4*)(g_rowstat1 + r0) = make_float4(sa.x, sa.y, sb2.x, sb2.y);
            asm volatile("bar.arrive 1, 288;" ::: "memory");
        }
        float acc[96];
#pragma unroll 1
        for (int kb = 0; kb < 8; kb++) {
            int s = kb % K1_STAGES;
            mbar_wait(full + 8 * s, (kb / K1_STAGES) & 1);
            if (warp == 4) TX(kb);
            uint64_t ad = make_desc(sb + s * K1_STAGE + wgi * 8192, 16, 1024, 1);
            uint64_t bd = make_desc(sb + s * K1_STAGE + 16384, 8192, 1024, 1);
            WG_FENCE();
#pragma unroll
            for (int k = 0; k < 4; k++) wgmma_ss_n192(acc, ad + k * 2, bd + k * 128, (kb | k) != 0);
            WG_COMMIT();
            if (kb > 0) {
                wg_wait<1>();
                if (lane == 0) mbar_arrive(empty + 8 * ((kb - 1) % K1_STAGES));
            }
        }
        wg_wait<0>();
        fence_regs(acc);
        TL(1);
        if (warp == 4) TX(16);
        mbar_wait(auxb, 0);
        if (warp == 4) TX(17);
        const float2* s_rs = (const float2*)(smem + K1_RS);
        const float* s_cs = (const float*)(smem + K1_CS);
        const int g = lane >> 2, t = lane & 3;
        const int rl = wgi * 64 + ww * 16 + g;
        const float2 st0 = s_rs[rl], st1 = s_rs[rl + 8];
        const float QS = 0.25f * 1.4426950408889634f;
        const int jrow = mb * 16 + wgi * 8 + ww * 2;
        const int rg16 = mb * 8 + wgi * 4 + ww;
        uint32_t* out = (uint32_t*)g_qkv;
#pragma unroll
        for (int hh = 0; hh < 12; hh++) {
            const int col0 = nt * 192 + hh * 16;
            const int which = col0 >> 9, head = (col0 & 511) >> 4;
            const float sc = (which == 0) ? QS : 1.0f;
            const float a0 = st0.x * sc, b0 = st0.y * sc, a1 = st1.x * sc, b1 = st1.y * sc;
            float n0 = 0.f, n1 = 0.f;
#pragma unroll
            for (int c = 0; c < 2; c++) {
                const int j = hh * 2 + c;
                const float2 cs = *(const float2*)(s_cs + 8 * j + 2 * t);
                float v00 = fmaf(a0, acc[4 * j], b0 * cs.x), v01 = fmaf(a0, acc[4 * j + 1], b0 * cs.y);
                float v10 = fmaf(a1, acc[4 * j + 2], b1 * cs.x), v11 = fmaf(a1, acc[4 * j + 3], b1 * cs.y);
                size_t o = ((size_t)((which * NH + head) * 2 + c) * 256 + jrow) * 32 + lane;
                out[o] = pack_bf16(v00, v01);
                out[o + 32] = pack_bf16(v10, v11);
                if (which < 2) {
                    n0 = fmaf(v00, v00, fmaf(v01, v01, n0));
                    n1 = fmaf(v10, v10, fmaf(v11, v11, n1));
                } else {
                    n0 = fmaxf(n0, fmaxf(fabsf(v00), fabsf(v01)));
                    n1 = fmaxf(n1, fmaxf(fabsf(v10), fabsf(v11)));
                    if (v00 != v00 || v01 != v01 || v10 != v10 || v11 != v11) n0 = __int_as_float(0x7f800000);
                }
            }
            float m;
            if (which < 2) {
                n0 += __shfl_xor_sync(0xffffffffu, n0, 1); n1 += __shfl_xor_sync(0xffffffffu, n1, 1);
                n0 += __shfl_xor_sync(0xffffffffu, n0, 2); n1 += __shfl_xor_sync(0xffffffffu, n1, 2);
                m = n0 + n1 - fminf(n0, n1);
                if (!(m == m)) m = __int_as_float(0x7f800000);
                m = fmaxf(m, __shfl_xor_sync(0xffffffffu, m, 4));
                m = fmaxf(m, __shfl_xor_sync(0xffffffffu, m, 8));
                m = fmaxf(m, __shfl_xor_sync(0xffffffffu, m, 16));
            } else {
                m = warp_max(fmaxf(n0, n1));
            }
            if (lane == 0) g_nrm[(which * NH + head) * 128 + rg16] = m;
        }
        TL(2);
        if (warp == 4) TX(18);
    }
}

constexpr int AT_K = 0, AT_V = 65536, AT_ONES = 131072, AT_BAR = 163840, AT_SMEM = AT_BAR + 128;
#define POLY_MASK 0xAD6A

__device__ __forceinline__ uint32_t exp2_pair_poly(float x0, float x1) {
    uint32_t t0 = __float_as_uint(x0 + 32895.0f);
    uint32_t t1 = __float_as_uint(x1 + 32895.0f);
    uint32_t gd = __byte_perm(t0, t1, 0x6420);
    uint32_t wm = __byte_perm(t0, t1, 0x5612);
    uint32_t v = hfma2(gd, 0x71477147u, 0x354f354fu);
    uint32_t z = hmul2(v, gd);
    return (wm >> 1) + z;
}
__device__ __forceinline__ uint32_t exp2_pair_mufu(float x0, float x1) { return pack_bf16(ex2f(x0), ex2f(x1)); }
template <uint32_t MASK>
__device__ __forceinline__ void exp_blocks(const float (&s)[32], uint32_t (&p)[16]) {
#pragma unroll
    for (int b = 0; b < 8; b++) {
        if ((MASK >> b) & 1) {
            p[2 * b] = exp2_pair_poly(s[4 * b], s[4 * b + 1]);
            p[2 * b + 1] = exp2_pair_poly(s[4 * b + 2], s[4 * b + 3]);
        } else {
            p[2 * b] = exp2_pair_mufu(s[4 * b], s[4 * b + 1]);
            p[2 * b + 1] = exp2_pair_mufu(s[4 * b + 2], s[4 * b + 3]);
        }
    }
}
#define PV4(P) _Pragma("unroll") for (int i = 0; i < 4; i++) { pv_wgmma(o, P[4 * i], P[4 * i + 1], P[4 * i + 2], P[4 * i + 3], vd); vd += 16; }

__device__ __forceinline__ void attn_store(float (&o)[12], int row0, int head, int lane) {
    float l0 = __shfl_sync(0xffffffffu, o[8], lane & 28);
    float l1 = __shfl_sync(0xffffffffu, o[10], lane & 28);
    float r0 = 1.0f / l0, r1 = 1.0f / l1;
    uint32_t* op = (uint32_t*)g_ao;
    int mb = row0 >> 7, rg = (row0 & 127) >> 3;
    int kb = head >> 2, kc = (head & 3) * 2;
    size_t base = (((size_t)(mb * 8 + kb) * 8 + kc) * 16 + rg) * 32 + lane;
    op[base] = pack_bf16(o[0] * r0, o[1] * r0);
    op[base + 32] = pack_bf16(o[2] * r1, o[3] * r1);
    op[base + 16 * 32] = pack_bf16(o[4] * r0, o[5] * r0);
    op[base + 16 * 32 + 32] = pack_bf16(o[6] * r1, o[7] * r1);
}

__device__ __forceinline__ void attn_load_q(uint32_t (&q)[4], const __nv_bfloat16* gq, int row0, int lane) {
    const uint32_t* qp = (const uint32_t*)gq;
    int j0 = row0 >> 3;
    q[0] = __ldcg(qp + (0 * 256 + j0) * 32 + lane);
    q[1] = __ldcg(qp + (0 * 256 + j0 + 1) * 32 + lane);
    q[2] = __ldcg(qp + (1 * 256 + j0) * 32 + lane);
    q[3] = __ldcg(qp + (1 * 256 + j0 + 1) * 32 + lane);
}

__device__ __forceinline__ void attn_tile_safe(const uint32_t (&q)[4], uint64_t kd, uint64_t vd, int row0, int head, int lane) {
    float o[12];
#pragma unroll
    for (int i = 0; i < 12; i++) o[i] = 0.f;
    float m0 = -INFINITY, m1 = -INFINITY;
    fence_regs(o);
#pragma unroll 1
    for (int j = 0; j < 32; j++) {
        float s[32];
        uint32_t p[16];
        WG_FENCE();
        qk_wgmma_n64(s, q, kd); kd += 64;
        WG_COMMIT();
        wg_wait<0>();
        fence_regs(s);
        fence_regs(o);
        float x0 = m0, x1 = m1;
#pragma unroll
        for (int b = 0; b < 8; b++) {
            x0 = fmaxf(x0, fmaxf(s[4 * b], s[4 * b + 1]));
            x1 = fmaxf(x1, fmaxf(s[4 * b + 2], s[4 * b + 3]));
        }
        x0 = fmaxf(x0, __shfl_xor_sync(0xffffffffu, x0, 1)); x0 = fmaxf(x0, __shfl_xor_sync(0xffffffffu, x0, 2));
        x1 = fmaxf(x1, __shfl_xor_sync(0xffffffffu, x1, 1)); x1 = fmaxf(x1, __shfl_xor_sync(0xffffffffu, x1, 2));
        float al0 = ex2f(m0 - x0), al1 = ex2f(m1 - x1);
        m0 = x0; m1 = x1;
#pragma unroll
        for (int i = 0; i < 3; i++) { o[4 * i] *= al0; o[4 * i + 1] *= al0; o[4 * i + 2] *= al1; o[4 * i + 3] *= al1; }
#pragma unroll
        for (int b = 0; b < 8; b++) {
            p[2 * b] = exp2_pair_mufu(s[4 * b] - m0, s[4 * b + 1] - m0);
            p[2 * b + 1] = exp2_pair_mufu(s[4 * b + 2] - m1, s[4 * b + 3] - m1);
        }
        fence_regs(o);
        WG_FENCE();
        PV4(p);
        WG_COMMIT();
        wg_wait<0>();
        fence_regs(o);
    }
    attn_store(o, row0, head, lane);
}

__global__ void __launch_bounds__(512, 1)
attn_kernel(const __nv_bfloat16* __restrict__ wg_, const __nv_bfloat16* __restrict__ wu_,
            const __nv_bfloat16* __restrict__ wo_, const __nv_bfloat16* __restrict__ wd_) {
    extern __shared__ __align__(1024) unsigned char smem[];
    const uint32_t sb = smem_u32(smem);
    const int tid = threadIdx.x, wg = tid >> 7, warp = (tid >> 5) & 3, lane = tid & 31;
    pdl_launch();
    if (blockIdx.x >= 128) {
        const int e = blockIdx.x - 128;
        const __nv_bfloat16* w = (e < 2) ? wg_ : wu_;
        float* red = (float*)smem;
        const int cgrp = tid & 127, kq = tid >> 7;
        if (cgrp < 112) {
            float s[8];
            colsum8(w, FF, (e & 1) * 896 + cgrp * 8, kq * 128, 128, s);
#pragma unroll
            for (int i = 0; i < 8; i++) red[kq * 896 + cgrp * 8 + i] = s[i];
        }
        __syncthreads();
        for (int c = tid; c < 896; c += 512)
            g_cs2[(e >> 1) * FF + (e & 1) * 896 + c] = red[c] + red[896 + c] + red[1792 + c] + red[2688 + c];
        if (tid < 32) {
            const char* p0 = (const char*)wo_ + e * (DM * DM * 2 / 4);
            for (int i = lane; i < 32; i += 32)
                asm volatile("cp.async.bulk.prefetch.L2.global [%0], %1;" :: "l"(p0 + i * 4096), "r"(4096) : "memory");
            const char* p1 = (const char*)wd_ + e * (FF * DM * 2 / 4);
            for (int i = lane; i < 112; i += 32)
                asm volatile("cp.async.bulk.prefetch.L2.global [%0], %1;" :: "l"(p1 + i * 4096), "r"(4096) : "memory");
        }
        return;
    }
    const int head = blockIdx.x >> 2, qq = blockIdx.x & 3;
    const __nv_bfloat16* gq = g_qkv + (size_t)head * (S_LEN * 16);
    const __nv_bfloat16* gk = g_qkv + (size_t)(NH + head) * (S_LEN * 16);
    const __nv_bfloat16* gv = g_qkv + (size_t)(2 * NH + head) * (S_LEN * 16);
    if (tid == 0) {
        for (int i = 0; i < 8; i++) mbar_init(sb + AT_BAR + 8 * i, 1);
        fence_barrier_init();
    }
    {
        uint4 one = make_uint4(0x00003F80u, 0, 0, 0);
#pragma unroll
        for (int i = 0; i < 4; i++) *(uint4*)(smem + AT_ONES + (i * 512 + tid) * 16) = one;
        fence_proxy_async();
    }
    __syncthreads();
    TL(3);
    pdl_wait();
    TL(4);
    if (tid == 0) {
        for (int i = 0; i < 8; i++) {
            uint32_t bar = sb + AT_BAR + 8 * i;
            mbar_expect(bar, 16384);
            bulk_g2s(sb + AT_K + i * 4096, gk + i * 2048, 4096, bar);
            bulk_g2s(sb + AT_K + 32768 + i * 4096, gk + 16384 + i * 2048, 4096, bar);
            bulk_g2s(sb + AT_V + i * 4096, gv + i * 2048, 4096, bar);
            bulk_g2s(sb + AT_V + 32768 + i * 4096, gv + 16384 + i * 2048, 4096, bar);
        }
    }
    bool fast;
    {
        const float* nq = g_nrm + (0 * NH + head) * 128 + qq * 32;
        const float* nk = g_nrm + (1 * NH + head) * 128;
        const float* nv = g_nrm + (2 * NH + head) * 128;
        float4 k4 = __ldcg((const float4*)nk + lane), v4 = __ldcg((const float4*)nv + lane);
        float qm = warp_max(__ldcg(nq + lane));
        float km = warp_max(fmaxf(fmaxf(k4.x, k4.y), fmaxf(k4.z, k4.w)));
        float vm = warp_max(fmaxf(fmaxf(v4.x, v4.y), fmaxf(v4.z, v4.w)));
        fast = (qm * km <= 3500.0f) && (vm <= 1.0e12f);
    }
    const uint64_t kdesc0 = make_desc(sb + AT_K, 32768, 128, 0);
    const uint64_t vdesc0 = make_desc(sb + AT_V, 128, 32768, 0);
    if (!fast) {
        for (int i = 0; i < 8; i++) mbar_wait(sb + AT_BAR + 8 * i, 0);
#pragma unroll 1
        for (int tile = 0; tile < 2; tile++) {
            const int row0 = qq * 512 + (tile * 4 + wg) * 64 + warp * 16;
            uint32_t q[4];
            attn_load_q(q, gq, row0, lane);
            attn_tile_safe(q, kdesc0, vdesc0, row0, head, lane);
        }
        return;
    }
#pragma unroll 1
    for (int tile = 0; tile < 2; tile++) {
        const int row0 = qq * 512 + (tile * 4 + wg) * 64 + warp * 16;
        uint32_t q[4];
        attn_load_q(q, gq, row0, lane);
        float o[12];
#pragma unroll
        for (int i = 0; i < 12; i++) o[i] = 0.f;
        fence_regs(o);
        float sa[32];
        uint32_t pa[16];
        uint64_t kd = kdesc0, vd = vdesc0;
        if (tile == 0) mbar_wait(sb + AT_BAR, 0);
        WG_FENCE();
        qk_wgmma_n64(sa, q, kd); kd += 64;
        WG_COMMIT();
#pragma unroll 1
        for (int jj = 0; jj < 8; jj++) {
            if (tile == 0 && jj < 7) mbar_wait(sb + AT_BAR + 8 * (jj + 1), 0);
#pragma unroll
            for (int j = 0; j < 4; j++) {
                wg_wait<0>();
                fence_regs(sa);
                if (j & 1) exp_blocks<(POLY_MASK >> 8)>(sa, pa); else exp_blocks<(POLY_MASK & 255)>(sa, pa);
                WG_FENCE();
                qk_wgmma_n64(sa, q, kd); kd += 64;
                PV4(pa);
                WG_COMMIT();
            }
        }
        wg_wait<0>();
        fence_regs(o);
        fence_regs(sa);
        attn_store(o, row0, head, lane);
    }
    TL(5);
}

constexpr int F_R2 = 131072, F_X = 196608, F_BAR = 229376;
constexpr int F_RS = F_BAR + 256, F_CS = F_RS + 1024, F_SMEM = F_CS + 1792;
enum { B_FA = 0, B_HF = 2, B_BF = 6, B_BE = 9, B_CF = 12, B_CE = 18, B_ADONE = 24, B_BDONE = 25, B_XA = 26, B_XC = 27, B_PRDY = 28, B_AUX = 29 };

__device__ __forceinline__ uint32_t mapa(uint32_t a, uint32_t rank) { uint32_t r; asm("mapa.shared::cluster.u32 %0, %1, %2;" : "=r"(r) : "r"(a), "r"(rank)); return r; }
__device__ __forceinline__ void st_async4(uint32_t dst, float a, float b, float c, float d, uint32_t bar) {
    asm volatile("st.async.weak.shared::cluster.mbarrier::complete_tx::bytes.v4.f32 [%0], {%1,%2,%3,%4}, [%5];"
                 :: "r"(dst), "f"(a), "f"(b), "f"(c), "f"(d), "r"(bar) : "memory");
}
__device__ __forceinline__ void mbar_arrive_remote(uint32_t a) { asm volatile("mbarrier.arrive.release.cluster.shared::cluster.b64 _, [%0];" :: "r"(a) : "memory"); }
__device__ __forceinline__ void mbar_wait_cluster(uint32_t a, int parity) {
    uint32_t done;
    int it = 0;
    do {
        asm volatile("{\n.reg .pred p;\nmbarrier.try_wait.parity.acquire.cluster.shared::cta.b64 p, [%1], %2;\nselp.u32 %0, 1, 0, p;\n}"
                     : "=r"(done) : "r"(a), "r"(parity) : "memory");
        if (++it > (1 << 24)) __trap();
    } while (!done);
}
__device__ __forceinline__ void poll_count(const unsigned int* p, unsigned int target) {
    int it = 0;
    while (ld_acquire(p) < target) { if (++it > (1 << 22)) __trap(); }
    asm volatile("fence.proxy.async.global;" ::: "memory");
}
__device__ __forceinline__ void publish_arrive(int id) { asm volatile("bar.arrive %0, 288;" :: "r"(id) : "memory"); }
__device__ __forceinline__ void publish_sync(int id, unsigned int* p, int lane) {
    asm volatile("bar.sync %0, 288;" :: "r"(id) : "memory");
    if (lane == 0) red_release(p);
}
template <int R>
__device__ __forceinline__ void xchg(float (&acc)[64], float (&o)[32], uint32_t sb, unsigned char* smem, int bar, int ctid) {
    const uint32_t dst = mapa(sb + F_X + ctid * 16, 1 - R), rb = mapa(sb + F_BAR + 8 * bar, 1 - R);
#pragma unroll
    for (int q = 0; q < 8; q++) {
        const int j = (1 - R) * 32 + 4 * q;
        st_async4(dst + q * 4096, acc[j], acc[j + 1], acc[j + 2], acc[j + 3], rb);
    }
    mbar_wait_cluster(sb + F_BAR + 8 * bar, 0);
#pragma unroll
    for (int q = 0; q < 8; q++) {
        float4 v = *(const float4*)(smem + F_X + q * 4096 + ctid * 16);
        const int j = R * 32 + 4 * q;
        o[4 * q] = acc[j] + v.x; o[4 * q + 1] = acc[j + 1] + v.y; o[4 * q + 2] = acc[j + 2] + v.z; o[4 * q + 3] = acc[j + 3] + v.w;
    }
}

template <int NB>
__device__ __forceinline__ void ffn_epilogue(const float* ag, const float* au, const float* s_cs, int cs_off, int jb0,
                                             float2 st0, float2 st1, int mb, int rgl, int lane) {
    const int t = lane & 3;
    uint32_t* gp = (uint32_t*)g_g;
    const float C1 = 0.7978845608028654f, C2 = 0.044715f * 0.7978845608028654f;
    const float k10 = st0.x * C1, k20 = st0.x * st0.x * st0.x * C2, k11 = st1.x * C1, k21 = st1.x * st1.x * st1.x * C2;
#pragma unroll
    for (int j = 0; j < NB; j++) {
        const float2 cg = *(const float2*)(s_cs + cs_off + 8 * j + 2 * t);
        const float2 cu = *(const float2*)(s_cs + 224 + cs_off + 8 * j + 2 * t);
        float r[4];
#pragma unroll
        for (int e = 0; e < 4; e++) {
            const float nm = (e < 2) ? st0.y : st1.y, k1 = (e < 2) ? k10 : k11, k2 = (e < 2) ? k20 : k21;
            const float tg = fmaf(nm, (e & 1) ? cg.y : cg.x, ag[4 * j + e]);
            const float tu = fmaf(nm, (e & 1) ? cu.y : cu.x, au[4 * j + e]);
            const float th = tanh_fast(tg * fmaf(tg * tg, k2, k1));
            const float p = tg * tu;
            r[e] = fmaf(p, th, p);
        }
        const int jb = jb0 + j;
        size_t o = (((size_t)mb * 28 * 8 + jb) * 16 + rgl) * 32 + lane;
        gp[o] = pack_bf16(r[0], r[1]);
        gp[o + 32] = pack_bf16(r[2], r[3]);
    }
}

__global__ void __cluster_dims__(2, 1, 1) __launch_bounds__(384, 1)
tail_kernel(const __grid_constant__ CUtensorMap tm_o, const __grid_constant__ CUtensorMap tm_g,
            const __grid_constant__ CUtensorMap tm_u, const __grid_constant__ CUtensorMap tm_d,
            const __nv_bfloat16* __restrict__ x, __nv_bfloat16* __restrict__ out) {
    extern __shared__ __align__(1024) unsigned char smem[];
    const uint32_t sb = smem_u32(smem);
    const uint32_t bars = sb + F_BAR;
    const int tid = threadIdx.x, warp = tid >> 5, lane = tid & 31;
    TL(6);
    const int cl = blockIdx.x >> 1, r = blockIdx.x & 1;
    const int mb = ((cl & 7) >> 1) * 4 + (cl >> 4), ntA = (cl & 1) * 2 + ((cl >> 3) & 1);
    const int nt = ntA * 2 + r;
    if (tid == 0) {
        prefetch_tmap(&tm_o); prefetch_tmap(&tm_g); prefetch_tmap(&tm_u); prefetch_tmap(&tm_d);
        for (int i = 0; i < 30; i++) {
            int cnt = 1;
            if ((i >= B_BE && i < B_BE + 3) || (i >= B_CE && i < B_CE + 6) || i == B_ADONE || i == B_BDONE || i == B_PRDY) cnt = 8;
            if (i == B_AUX) cnt = 3;
            mbar_init(bars + 8 * i, cnt);
        }
        mbar_expect(bars + 8 * B_XA, 32768);
        mbar_expect(bars + 8 * B_XC, 32768);
        fence_barrier_init();
    }
    __syncthreads();
    asm volatile("barrier.cluster.arrive.release.aligned;\nbarrier.cluster.wait.acquire.aligned;" ::: "memory");
    if (warp < 4) {
        asm volatile("setmaxnreg.dec.sync.aligned.u32 56;");
        if (warp == 0) {
            if (lane == 0) {
                auto load_b = [&](int it) {
                    const int s = it % 3, pass = it >> 3, kb = it & 7;
                    const int ng = pass ? 3 : 4, c0 = nt * 224 + pass * 128;
                    const uint32_t bar = bars + 8 * (B_BF + s), dst = sb + F_R2 + s * 32768;
                    mbar_expect(bar, ng * 8192);
                    for (int i = 0; i < ng; i++) {
                        tma2d(dst + i * 4096, &tm_g, c0 + i * 32, kb * 64, bar);
                        tma2d(dst + 16384 + i * 4096, &tm_u, c0 + i * 32, kb * 64, bar);
                    }
                };
                for (int i = 0; i < 4; i++) {
                    const uint32_t bar = bars + 8 * (B_FA + (i >> 1));
                    if (!(i & 1)) mbar_expect(bar, 65536);
                    tma2d(sb + i * 32768 + 16384, &tm_o, ntA * 128, (4 * r + i) * 64, bar);
                    tma2d(sb + i * 32768 + 24576, &tm_o, ntA * 128 + 64, (4 * r + i) * 64, bar);
                }
                load_b(0); load_b(1);
                pdl_wait();
                TL(16);
                for (int i = 0; i < 4; i++)
                    bulk_g2s(sb + i * 32768, g_ao + (size_t)(mb * 8 + 4 * r + i) * 8192, 16384, bars + 8 * (B_FA + (i >> 1)));
                if (blockIdx.x == 0)
                    for (int i = 0; i < 32; i++) g_cnt[i] = 0;
                mbar_wait(bars + 8 * B_ADONE, 0);
                poll_count(&g_cnt2[mb], 8);
                TL(17);
                for (int kb = 0; kb < 8; kb++) {
                    const uint32_t bar = bars + 8 * (B_HF + (kb >> 1));
                    if (!(kb & 1)) mbar_expect(bar, 32768);
                    bulk_g2s(sb + kb * 16384, g_h + (size_t)(mb * 8 + kb) * 8192, 16384, bar);
                }
                for (int it = 2; it < 16; it++) {
                    const int s = it % 3, n = it / 3;
                    mbar_wait(bars + 8 * (B_BE + s), (s == 2 ? n : n - 1) & 1);
                    load_b(it);
                }
                mbar_wait(bars + 8 * B_BDONE, 0);
                for (int i = 0; i < 6; i++) {
                    const uint32_t bar = bars + 8 * (B_CF + i);
                    mbar_expect(bar, 32768);
                    tma2d(sb + i * 32768 + 16384, &tm_d, ntA * 128, (14 * r + i) * 64, bar);
                    tma2d(sb + i * 32768 + 24576, &tm_d, ntA * 128 + 64, (14 * r + i) * 64, bar);
                }
                poll_count(&g_cnt2[16 + mb * 2 + r], 4);
                TL(18);
                for (int kb = 0; kb < 14; kb++) {
                    const int s = kb % 6;
                    const uint32_t bar = bars + 8 * (B_CF + s);
                    if (kb >= 6) {
                        mbar_wait(bars + 8 * (B_CE + s), ((kb / 6) - 1) & 1);
                        mbar_expect(bar, 32768);
                        tma2d(sb + s * 32768 + 16384, &tm_d, ntA * 128, (14 * r + kb) * 64, bar);
                        tma2d(sb + s * 32768 + 24576, &tm_d, ntA * 128 + 64, (14 * r + kb) * 64, bar);
                    }
                    bulk_g2s(sb + s * 32768, g_g + (size_t)(mb * 28 + 14 * r + kb) * 8192, 16384, bar);
                }
            }
        } else {
            pdl_wait();
            float2* s_rs = (float2*)(smem + F_RS);
            float* s_cs = (float*)(smem + F_CS);
            for (int c = tid - 32; c < 448; c += 96)
                s_cs[c] = __ldcg(&g_cs2[(c >= 224 ? FF - 224 : 0) + nt * 224 + c]);
            if (warp == 1) { publish_sync(1, &g_cnt2[mb], lane); TL(9); }
            if (lane == 0) poll_count(&g_cnt2[mb], 8);
            __syncwarp();
            for (int rr = tid - 32; rr < 128; rr += 96) {
                const float4* hp = (const float4*)(g_hstat + (size_t)(mb * 128 + rr) * 8);
                float4 a = __ldcg(hp), b = __ldcg(hp + 1), c = __ldcg(hp + 2), d = __ldcg(hp + 3);
                float mean = 0.125f * (a.x + a.z + b.x + b.z + c.x + c.z + d.x + d.z);
                float m2 = a.y + a.w + b.y + b.w + c.y + c.w + d.y + d.w;
                float e;
                e = a.x - mean; m2 = fmaf(64.f * e, e, m2); e = a.z - mean; m2 = fmaf(64.f * e, e, m2);
                e = b.x - mean; m2 = fmaf(64.f * e, e, m2); e = b.z - mean; m2 = fmaf(64.f * e, e, m2);
                e = c.x - mean; m2 = fmaf(64.f * e, e, m2); e = c.z - mean; m2 = fmaf(64.f * e, e, m2);
                e = d.x - mean; m2 = fmaf(64.f * e, e, m2); e = d.z - mean; m2 = fmaf(64.f * e, e, m2);
                s_rs[rr] = make_float2(rsqrtf(m2 * (1.0f / DM) + 1e-5f), -mean);
            }
            __syncwarp();
            if (lane == 0) mbar_arrive(bars + 8 * B_AUX);
            if (warp == 1) { publish_sync(2, &g_cnt2[16 + mb * 2 + (nt >> 2)], lane); TL(13); }
        }
    } else {
        asm volatile("setmaxnreg.inc.sync.aligned.u32 216;");
        const int wgi = (warp >> 2) - 1, ww = warp & 3, ctid = tid - 128;
        const int g = lane >> 2, t = lane & 3;
        const int rl = wgi * 64 + ww * 16 + g, row = mb * 128 + rl;
        const int rgl = wgi * 8 + ww * 2;
        const float2* s_rs = (const float2*)(smem + F_RS);
        const float* s_cs = (const float*)(smem + F_CS);
        uint32_t* hp = (uint32_t*)g_h + ((size_t)(mb * 8 + nt) * 8 * 16 + rgl) * 32 + lane;
        {
            uint32_t xr[16];
            const uint32_t* xp = (const uint32_t*)(x + (size_t)row * DM + nt * 64) + t;
#pragma unroll
            for (int j = 0; j < 8; j++) { xr[2 * j] = __ldg(xp + 4 * j); xr[2 * j + 1] = __ldg(xp + 8 * (DM / 2) + 4 * j); }
            float acc[64];
#pragma unroll 1
            for (int i = 0; i < 4; i++) {
                if (!(i & 1)) mbar_wait(bars + 8 * (B_FA + (i >> 1)), 0);
                uint64_t ad = make_desc(sb + i * 32768 + wgi * 1024, 2048, 128, 0);
                uint64_t bd = make_desc(sb + i * 32768 + 16384, 8192, 1024, 1);
                WG_FENCE();
#pragma unroll
                for (int k = 0; k < 4; k++) wgmma_ss_n128(acc, ad + k * 256, bd + k * 128, (i | k) != 0);
                WG_COMMIT();
            }
            wg_wait<0>();
            fence_regs(acc);
            TL(7);
            if (lane == 0) mbar_arrive(bars + 8 * B_ADONE);
            float o[32];
            if (r == 0) xchg<0>(acc, o, sb, smem, B_XA, ctid); else xchg<1>(acc, o, sb, smem, B_XA, ctid);
            fence_proxy_async();
            __syncwarp();
            if (lane == 0) mbar_arrive(bars + 8 * (B_BE + 2));
            float v0[16], v1[16];
            float s0 = 0.f, s1 = 0.f;
#pragma unroll
            for (int j = 0; j < 8; j++) {
                uint32_t u0 = pack_bf16(bf_lo(xr[2 * j]) + o[4 * j], bf_hi(xr[2 * j]) + o[4 * j + 1]);
                uint32_t u1 = pack_bf16(bf_lo(xr[2 * j + 1]) + o[4 * j + 2], bf_hi(xr[2 * j + 1]) + o[4 * j + 3]);
                hp[j * 16 * 32] = u0;
                hp[j * 16 * 32 + 32] = u1;
                v0[2 * j] = bf_lo(u0); v0[2 * j + 1] = bf_hi(u0);
                v1[2 * j] = bf_lo(u1); v1[2 * j + 1] = bf_hi(u1);
                s0 += v0[2 * j] + v0[2 * j + 1];
                s1 += v1[2 * j] + v1[2 * j + 1];
            }
            float m0 = s0 * (1.0f / 16), m1 = s1 * (1.0f / 16), q0 = 0.f, q1 = 0.f;
#pragma unroll
            for (int i = 0; i < 16; i++) {
                float d0 = v0[i] - m0, d1 = v1[i] - m1;
                q0 = fmaf(d0, d0, q0); q1 = fmaf(d1, d1, q1);
            }
#pragma unroll
            for (int st = 0; st < 2; st++) {
                float hn = st ? 16.f : 8.f;
                float om0 = __shfl_xor_sync(0xffffffffu, m0, 1 << st), oq0 = __shfl_xor_sync(0xffffffffu, q0, 1 << st);
                float om1 = __shfl_xor_sync(0xffffffffu, m1, 1 << st), oq1 = __shfl_xor_sync(0xffffffffu, q1, 1 << st);
                float d0 = om0 - m0, d1 = om1 - m1;
                q0 = q0 + oq0 + d0 * d0 * hn; q1 = q1 + oq1 + d1 * d1 * hn;
                m0 = 0.5f * (m0 + om0); m1 = 0.5f * (m1 + om1);
            }
            if (t == 0) {
                g_hstat[row * 8 + nt] = make_float2(m0, q0);
                g_hstat[(row + 8) * 8 + nt] = make_float2(m1, q1);
            }
            publish_arrive(1);
            TL(8);
        }
        {
            float ag[64], au[64];
#pragma unroll 1
            for (int kb = 0; kb < 8; kb++) {
                const int s = kb % 3;
                if (!(kb & 1)) mbar_wait(bars + 8 * (B_HF + (kb >> 1)), 0);
                mbar_wait(bars + 8 * (B_BF + s), (kb / 3) & 1);
                if (warp == 4) TX(32 + kb);
                uint64_t ad = make_desc(sb + kb * 16384 + wgi * 1024, 2048, 128, 0);
                uint64_t bd = make_desc(sb + F_R2 + s * 32768, 4096, 512, 2);
                WG_FENCE();
#pragma unroll
                for (int k = 0; k < 4; k++) {
                    wgmma_ss_n128(ag, ad + k * 256, bd + k * 64, (kb | k) != 0);
                    wgmma_ss_n128(au, ad + k * 256, bd + 1024 + k * 64, (kb | k) != 0);
                }
                WG_COMMIT();
                if (kb > 0) {
                    wg_wait<1>();
                    if (lane == 0) mbar_arrive(bars + 8 * (B_BE + (kb - 1) % 3));
                }
            }
            wg_wait<0>();
            if (lane == 0) mbar_arrive(bars + 8 * (B_BE + 7 % 3));
            fence_regs(ag); fence_regs(au);
            TL(10);
            mbar_wait(bars + 8 * B_AUX, 0);
            ffn_epilogue<16>(ag, au, s_cs, 0, nt * 28, s_rs[rl], s_rs[rl + 8], mb, rgl, lane);
        }
        {
            float ag[48], au[48];
#pragma unroll 1
            for (int kb = 0; kb < 8; kb++) {
                const int it = 8 + kb, s = it % 3;
                mbar_wait(bars + 8 * (B_BF + s), (it / 3) & 1);
                if (warp == 4) TX(32 + it);
                uint64_t ad = make_desc(sb + kb * 16384 + wgi * 1024, 2048, 128, 0);
                uint64_t bd = make_desc(sb + F_R2 + s * 32768, 4096, 512, 2);
                WG_FENCE();
#pragma unroll
                for (int k = 0; k < 4; k++) {
                    wgmma_ss_n96(ag, ad + k * 256, bd + k * 64, (kb | k) != 0);
                    wgmma_ss_n96(au, ad + k * 256, bd + 1024 + k * 64, (kb | k) != 0);
                }
                WG_COMMIT();
                if (kb > 0) {
                    wg_wait<1>();
                    if (lane == 0) mbar_arrive(bars + 8 * (B_BE + (it - 1) % 3));
                }
            }
            wg_wait<0>();
            if (lane == 0) {
                mbar_arrive(bars + 8 * B_BDONE);
                mbar_arrive_remote(mapa(bars + 8 * B_PRDY, 1 - r));
            }
            fence_regs(ag); fence_regs(au);
            TL(11);
            ffn_epilogue<12>(ag, au, s_cs, 128, nt * 28 + 16, s_rs[rl], s_rs[rl + 8], mb, rgl, lane);
            publish_arrive(2);
            TL(12);
        }
        {
            uint32_t hr[16];
#pragma unroll
            for (int j = 0; j < 8; j++) { hr[2 * j] = __ldcg(hp + j * 16 * 32); hr[2 * j + 1] = __ldcg(hp + j * 16 * 32 + 32); }
            float acc[64];
#pragma unroll 1
            for (int kb = 0; kb < 14; kb++) {
                const int s = kb % 6;
                mbar_wait(bars + 8 * (B_CF + s), (kb / 6) & 1);
                if (warp == 4) TX(96 + kb);
                uint64_t ad = make_desc(sb + s * 32768 + wgi * 1024, 2048, 128, 0);
                uint64_t bd = make_desc(sb + s * 32768 + 16384, 8192, 1024, 1);
                WG_FENCE();
#pragma unroll
                for (int k = 0; k < 4; k++) wgmma_ss_n128(acc, ad + k * 256, bd + k * 128, (kb | k) != 0);
                WG_COMMIT();
                if (kb > 0) {
                    wg_wait<1>();
                    if (lane == 0) mbar_arrive(bars + 8 * (B_CE + (kb - 1) % 6));
                }
            }
            wg_wait<0>();
            fence_regs(acc);
            TL(14);
            mbar_wait_cluster(bars + 8 * B_PRDY, 0);
            float o[32];
            if (r == 0) xchg<0>(acc, o, sb, smem, B_XC, ctid); else xchg<1>(acc, o, sb, smem, B_XC, ctid);
            const float a0 = s_rs[rl].x, a1 = s_rs[rl + 8].x;
            const float k0 = 0.5f * a0 * a0, k1 = 0.5f * a1 * a1;
            uint32_t* op = (uint32_t*)(out + (size_t)row * DM + nt * 64) + t;
#pragma unroll
            for (int j = 0; j < 8; j++) {
                op[4 * j] = pack_bf16(fmaf(k0, o[4 * j], bf_lo(hr[2 * j])), fmaf(k0, o[4 * j + 1], bf_hi(hr[2 * j])));
                op[8 * (DM / 2) + 4 * j] = pack_bf16(fmaf(k1, o[4 * j + 2], bf_lo(hr[2 * j + 1])), fmaf(k1, o[4 * j + 3], bf_hi(hr[2 * j + 1])));
            }
            TL(15);
        }
    }
}

typedef CUresult (*EncodeFn)(CUtensorMap*, CUtensorMapDataType, cuuint32_t, void*, const cuuint64_t*, const cuuint64_t*,
                             const cuuint32_t*, const cuuint32_t*, CUtensorMapInterleave, CUtensorMapSwizzle,
                             CUtensorMapL2promotion, CUtensorMapFloatOOBfill);

void encode(EncodeFn fn, CUtensorMap* m, const void* ptr, int rank, const cuuint64_t* dims, const cuuint64_t* strides,
            const cuuint32_t* box, CUtensorMapSwizzle swz) {
    cuuint32_t es[3] = {1, 1, 1};
    fn(m, CU_TENSOR_MAP_DATA_TYPE_BFLOAT16, rank, (void*)ptr, dims, strides, box, es, CU_TENSOR_MAP_INTERLEAVE_NONE, swz,
       CU_TENSOR_MAP_L2_PROMOTION_L2_256B, CU_TENSOR_MAP_FLOAT_OOB_FILL_NONE);
}

template <typename... KArgs, typename... Args>
void launch(void (*kern)(KArgs...), int grid, int block, int smem, bool pdl, Args... args) {
    cudaLaunchConfig_t cfg = {};
    cfg.gridDim = dim3(grid); cfg.blockDim = dim3(block); cfg.dynamicSmemBytes = smem;
    cfg.stream = cudaStreamPerThread;
    cudaLaunchAttribute at[1];
    at[0].id = cudaLaunchAttributeProgrammaticStreamSerialization;
    at[0].val.programmaticStreamSerializationAllowed = 1;
    cfg.attrs = at; cfg.numAttrs = pdl ? 1 : 0;
    cudaLaunchKernelEx(&cfg, kern, KArgs(args)...);
}

}

extern "C" void kernel_launch(void* const* d_in, const int* in_sizes, int n_in, void* d_out, int out_size) {
    const __nv_bfloat16* x = (const __nv_bfloat16*)d_in[0];
    const __nv_bfloat16* wqkv = (const __nv_bfloat16*)d_in[1];
    const __nv_bfloat16* wo = (const __nv_bfloat16*)d_in[2];
    const __nv_bfloat16* wgate = (const __nv_bfloat16*)d_in[4];
    const __nv_bfloat16* wup = (const __nv_bfloat16*)d_in[5];
    const __nv_bfloat16* wdown = (const __nv_bfloat16*)d_in[6];
    __nv_bfloat16* out = (__nv_bfloat16*)d_out;

    static CUtensorMap tm_x, tm_wqkv, tm_wo, tm_wg, tm_wu, tm_wd;
    static const void* cached[6] = {nullptr, nullptr, nullptr, nullptr, nullptr, nullptr};
    if (cached[0] != x || cached[1] != wqkv || cached[2] != wo || cached[3] != wgate || cached[4] != wup || cached[5] != wdown) {
        void* fp = nullptr;
        cudaDriverEntryPointQueryResult qr;
        cudaGetDriverEntryPoint("cuTensorMapEncodeTiled", &fp, cudaEnableDefault, &qr);
        EncodeFn fn = (EncodeFn)fp;
        { cuuint64_t d[2] = {512, 2048}, s[1] = {1024}; cuuint32_t b[2] = {64, 128};
          encode(fn, &tm_x, x, 2, d, s, b, CU_TENSOR_MAP_SWIZZLE_128B); }
        { cuuint64_t d[3] = {64, 512, 24}, s[2] = {3072, 128}; cuuint32_t b[3] = {64, 64, 3};
          encode(fn, &tm_wqkv, wqkv, 3, d, s, b, CU_TENSOR_MAP_SWIZZLE_128B); }
        { cuuint64_t d[2] = {512, 512}, s[1] = {1024}; cuuint32_t b[2] = {64, 64};
          encode(fn, &tm_wo, wo, 2, d, s, b, CU_TENSOR_MAP_SWIZZLE_128B); }
        { cuuint64_t d[2] = {1792, 512}, s[1] = {3584}; cuuint32_t b[2] = {32, 64};
          encode(fn, &tm_wg, wgate, 2, d, s, b, CU_TENSOR_MAP_SWIZZLE_64B);
          encode(fn, &tm_wu, wup, 2, d, s, b, CU_TENSOR_MAP_SWIZZLE_64B); }
        { cuuint64_t d[2] = {512, 1792}, s[1] = {1024}; cuuint32_t b[2] = {64, 64};
          encode(fn, &tm_wd, wdown, 2, d, s, b, CU_TENSOR_MAP_SWIZZLE_128B); }
        cudaFuncSetAttribute(qkv_kernel, cudaFuncAttributeMaxDynamicSharedMemorySize, K1_SMEM);
        cudaFuncSetAttribute(attn_kernel, cudaFuncAttributeMaxDynamicSharedMemorySize, AT_SMEM);
        cudaFuncSetAttribute(tail_kernel, cudaFuncAttributeMaxDynamicSharedMemorySize, F_SMEM);
        cached[0] = x; cached[1] = wqkv; cached[2] = wo; cached[3] = wgate; cached[4] = wup; cached[5] = wdown;
    }
    launch(qkv_kernel, 128, 384, K1_SMEM, false, tm_x, tm_wqkv, x, wqkv);
    launch(attn_kernel, 132, 512, AT_SMEM, true, wgate, wup, wo, wdown);
    launch(tail_kernel, 128, 384, F_SMEM, true, tm_wo, tm_wg, tm_wu, tm_wd, x, out);
}
```

```cpp
#include <cuda_runtime.h>
#include <cuda_bf16.h>
#include <cuda.h>
#include <stdint.h>

#define TAILMAP 1
namespace {

constexpr int S_LEN = 2048, DM = 512, NH = 32, FF = 1792;

__device__ __align__(1024) __nv_bfloat16 g_qkv[3 * NH * S_LEN * 16];
__device__ __align__(1024) __nv_bfloat16 g_ao[S_LEN * DM];
__device__ __align__(1024) __nv_bfloat16 g_h[S_LEN * DM];
__device__ __align__(1024) __nv_bfloat16 g_g[S_LEN * FF];
__device__ __align__(16) float2 g_rowstat1[S_LEN];
__device__ float g_cs1_part[16 * 1536];
__device__ unsigned int g_cnt[32];
__device__ unsigned int g_cnt2[64];
__device__ float g_nrm[3 * NH * 128];
__device__ float2 g_hstat[S_LEN * 8];
__device__ float g_cs2[2 * FF];

#define TL(slot)
#define TX(slot)
__device__ __forceinline__ uint32_t smem_u32(const void* p) { return (uint32_t)__cvta_generic_to_shared(p); }
__device__ __forceinline__ void mbar_init(uint32_t a, int c) { asm volatile("mbarrier.init.shared.b64 [%0], %1;" :: "r"(a), "r"(c)); }
__device__ __forceinline__ void mbar_expect(uint32_t a, int bytes) { asm volatile("mbarrier.arrive.expect_tx.shared.b64 _, [%0], %1;" :: "r"(a), "r"(bytes) : "memory"); }
__device__ __forceinline__ void mbar_arrive(uint32_t a) { asm volatile("mbarrier.arrive.shared.b64 _, [%0];" :: "r"(a) : "memory"); }
__device__ __forceinline__ void mbar_wait(uint32_t a, int parity) {
    uint32_t done;
    int it = 0;
    do {
        asm volatile("{\n.reg .pred p;\nmbarrier.try_wait.parity.shared.b64 p, [%1], %2;\nselp.u32 %0, 1, 0, p;\n}"
                     : "=r"(done) : "r"(a), "r"(parity) : "memory");
        if (++it > (1 << 24)) __trap();
    } while (!done);
}
__device__ __forceinline__ void bulk_g2s(uint32_t dst, const void* src, int bytes, uint32_t bar) {
    asm volatile("cp.async.bulk.shared::cluster.global.mbarrier::complete_tx::bytes [%0], [%1], %2, [%3];"
                 :: "r"(dst), "l"(src), "r"(bytes), "r"(bar) : "memory");
}
__device__ __forceinline__ void tma2d(uint32_t dst, const CUtensorMap* m, int c0, int c1, uint32_t bar) {
    asm volatile("cp.async.bulk.tensor.2d.shared::cluster.global.mbarrier::complete_tx::bytes [%0], [%1, {%3, %4}], [%2];"
                 :: "r"(dst), "l"(m), "r"(bar), "r"(c0), "r"(c1) : "memory");
}
__device__ __forceinline__ void tma3d(uint32_t dst, const CUtensorMap* m, int c0, int c1, int c2, uint32_t bar) {
    asm volatile("cp.async.bulk.tensor.3d.shared::cluster.global.mbarrier::complete_tx::bytes [%0], [%1, {%3, %4, %5}], [%2];"
                 :: "r"(dst), "l"(m), "r"(bar), "r"(c0), "r"(c1), "r"(c2) : "memory");
}
__device__ __forceinline__ void prefetch_tmap(const CUtensorMap* m) { asm volatile("prefetch.tensormap [%0];" :: "l"(m) : "memory"); }
__device__ __forceinline__ void pdl_wait() { asm volatile("griddepcontrol.wait;" ::: "memory"); }
__device__ __forceinline__ void pdl_launch() { asm volatile("griddepcontrol.launch_dependents;" ::: "memory"); }
__device__ __forceinline__ void fence_barrier_init() { asm volatile("fence.mbarrier_init.release.cluster;" ::: "memory"); }
__device__ __forceinline__ void fence_proxy_async() { asm volatile("fence.proxy.async.shared::cta;" ::: "memory"); }
__device__ __forceinline__ uint64_t make_desc(uint32_t saddr, uint32_t lbo, uint32_t sbo, uint32_t swz) {
    return (uint64_t)((saddr & 0x3FFFF) >> 4) | ((uint64_t)((lbo & 0x3FFFF) >> 4) << 16) |
           ((uint64_t)((sbo & 0x3FFFF) >> 4) << 32) | ((uint64_t)swz << 62);
}
#define WG_FENCE() asm volatile("wgmma.fence.sync.aligned;" ::: "memory")
#define WG_COMMIT() asm volatile("wgmma.commit_group.sync.aligned;" ::: "memory")
template <int N> __device__ __forceinline__ void wg_wait() { asm volatile("wgmma.wait_group.sync.aligned %0;" :: "n"(N) : "memory"); }
template <int N> __device__ __forceinline__ void fence_regs(float (&d)[N]) {
#pragma unroll
    for (int i = 0; i < N; i++) asm volatile("" : "+f"(d[i]) :: "memory");
}
__device__ __forceinline__ float ex2f(float x) { float y; asm("ex2.approx.ftz.f32 %0, %1;" : "=f"(y) : "f"(x)); return y; }
__device__ __forceinline__ float tanh_fast(float x) { float y; asm("tanh.approx.f32 %0, %1;" : "=f"(y) : "f"(x)); return y; }
__device__ __forceinline__ uint32_t pack_bf16(float lo, float hi) { uint32_t r; asm("cvt.rn.bf16x2.f32 %0, %1, %2;" : "=r"(r) : "f"(hi), "f"(lo)); return r; }
__device__ __forceinline__ float bf_lo(uint32_t u) { return __uint_as_float(u << 16); }
__device__ __forceinline__ float bf_hi(uint32_t u) { return __uint_as_float(u & 0xFFFF0000u); }
__device__ __forceinline__ uint32_t hfma2(uint32_t a, uint32_t b, uint32_t c) { uint32_t r; asm("fma.rn.f16x2 %0, %1, %2, %3;" : "=r"(r) : "r"(a), "r"(b), "r"(c)); return r; }
__device__ __forceinline__ uint32_t hmul2(uint32_t a, uint32_t b) { uint32_t r; asm("mul.rn.f16x2 %0, %1, %2;" : "=r"(r) : "r"(a), "r"(b)); return r; }
__device__ __forceinline__ unsigned int ld_acquire(const unsigned int* p) { unsigned int v; asm volatile("ld.acquire.gpu.u32 %0, [%1];" : "=r"(v) : "l"(p) : "memory"); return v; }
__device__ __forceinline__ void red_release(unsigned int* p) { asm volatile("red.release.gpu.global.add.u32 [%0], 1;" :: "l"(p) : "memory"); }
__device__ __forceinline__ float warp_sum(float v) {
#pragma unroll
    for (int o = 16; o; o >>= 1) v += __shfl_xor_sync(0xffffffffu, v, o);
    return v;
}
__device__ __forceinline__ float warp_max(float v) {
#pragma unroll
    for (int o = 16; o; o >>= 1) v = fmaxf(v, __shfl_xor_sync(0xffffffffu, v, o));
    return v;
}

__device__ __forceinline__ void wgmma_ss_n64(float (&d)[32], uint64_t adesc, uint64_t bdesc, int scale_d) {
    asm volatile("{\n.reg .pred p;\nsetp.ne.b32 p, %34, 0;\n"
      "wgmma.mma_async.sync.aligned.m64n64k16.f32.bf16.bf16 {%0,%1,%2,%3,%4,%5,%6,%7,%8,%9,%10,%11,%12,%13,%14,%15,%16,%17,%18,%19,%20,%21,%22,%23,%24,%25,%26,%27,%28,%29,%30,%31}, %32, %33, p, 1, 1, 0, 1;\n}"
      : "+f"(d[0]), "+f"(d[1]), "+f"(d[2]), "+f"(d[3]), "+f"(d[4]), "+f"(d[5]), "+f"(d[6]), "+f"(d[7]), "+f"(d[8]), "+f"(d[9]), "+f"(d[10]), "+f"(d[11]), "+f"(d[12]), "+f"(d[13]), "+f"(d[14]), "+f"(d[15]), "+f"(d[16]), "+f"(d[17]), "+f"(d[18]), "+f"(d[19]), "+f"(d[20]), "+f"(d[21]), "+f"(d[22]), "+f"(d[23]), "+f"(d[24]), "+f"(d[25]), "+f"(d[26]), "+f"(d[27]), "+f"(d[28]), "+f"(d[29]), "+f"(d[30]), "+f"(d[31])
      : "l"(adesc), "l"(bdesc), "r"(scale_d));
}
__device__ __forceinline__ void wgmma_ss_n96(float (&d)[48], uint64_t adesc, uint64_t bdesc, int scale_d) {
    asm volatile("{\n.reg .pred p;\nsetp.ne.b32 p, %50, 0;\n"
      "wgmma.mma_async.sync.aligned.m64n96k16.f32.bf16.bf16 {%0,%1,%2,%3,%4,%5,%6,%7,%8,%9,%10,%11,%12,%13,%14,%15,%16,%17,%18,%19,%20,%21,%22,%23,%24,%25,%26,%27,%28,%29,%30,%31,%32,%33,%34,%35,%36,%37,%38,%39,%40,%41,%42,%43,%44,%45,%46,%47}, %48, %49, p, 1, 1, 0, 1;\n}"
      : "+f"(d[0]), "+f"(d[1]), "+f"(d[2]), "+f"(d[3]), "+f"(d[4]), "+f"(d[5]), "+f"(d[6]), "+f"(d[7]), "+f"(d[8]), "+f"(d[9]), "+f"(d[10]), "+f"(d[11]), "+f"(d[12]), "+f"(d[13]), "+f"(d[14]), "+f"(d[15]), "+f"(d[16]), "+f"(d[17]), "+f"(d[18]), "+f"(d[19]), "+f"(d[20]), "+f"(d[21]), "+f"(d[22]), "+f"(d[23]), "+f"(d[24]), "+f"(d[25]), "+f"(d[26]), "+f"(d[27]), "+f"(d[28]), "+f"(d[29]), "+f"(d[30]), "+f"(d[31]), "+f"(d[32]), "+f"(d[33]), "+f"(d[34]), "+f"(d[35]), "+f"(d[36]), "+f"(d[37]), "+f"(d[38]), "+f"(d[39]), "+f"(d[40]), "+f"(d[41]), "+f"(d[42]), "+f"(d[43]), "+f"(d[44]), "+f"(d[45]), "+f"(d[46]), "+f"(d[47])
      : "l"(adesc), "l"(bdesc), "r"(scale_d));
}
__device__ __forceinline__ void wgmma_ss_n128(float (&d)[64], uint64_t adesc, uint64_t bdesc, int scale_d) {
    asm volatile("{\n.reg .pred p;\nsetp.ne.b32 p, %66, 0;\n"
      "wgmma.mma_async.sync.aligned.m64n128k16.f32.bf16.bf16 {%0,%1,%2,%3,%4,%5,%6,%7,%8,%9,%10,%11,%12,%13,%14,%15,%16,%17,%18,%19,%20,%21,%22,%23,%24,%25,%26,%27,%28,%29,%30,%31,%32,%33,%34,%35,%36,%37,%38,%39,%40,%41,%42,%43,%44,%45,%46,%47,%48,%49,%50,%51,%52,%53,%54,%55,%56,%57,%58,%59,%60,%61,%62,%63}, %64, %65, p, 1, 1, 0, 1;\n}"
      : "+f"(d[0]), "+f"(d[1]), "+f"(d[2]), "+f"(d[3]), "+f"(d[4]), "+f"(d[5]), "+f"(d[6]), "+f"(d[7]), "+f"(d[8]), "+f"(d[9]), "+f"(d[10]), "+f"(d[11]), "+f"(d[12]), "+f"(d[13]), "+f"(d[14]), "+f"(d[15]), "+f"(d[16]), "+f"(d[17]), "+f"(d[18]), "+f"(d[19]), "+f"(d[20]), "+f"(d[21]), "+f"(d[22]), "+f"(d[23]), "+f"(d[24]), "+f"(d[25]), "+f"(d[26]), "+f"(d[27]), "+f"(d[28]), "+f"(d[29]), "+f"(d[30]), "+f"(d[31]), "+f"(d[32]), "+f"(d[33]), "+f"(d[34]), "+f"(d[35]), "+f"(d[36]), "+f"(d[37]), "+f"(d[38]), "+f"(d[39]), "+f"(d[40]), "+f"(d[41]), "+f"(d[42]), "+f"(d[43]), "+f"(d[44]), "+f"(d[45]), "+f"(d[46]), "+f"(d[47]), "+f"(d[48]), "+f"(d[49]), "+f"(d[50]), "+f"(d[51]), "+f"(d[52]), "+f"(d[53]), "+f"(d[54]), "+f"(d[55]), "+f"(d[56]), "+f"(d[57]), "+f"(d[58]), "+f"(d[59]), "+f"(d[60]), "+f"(d[61]), "+f"(d[62]), "+f"(d[63])
      : "l"(adesc), "l"(bdesc), "r"(scale_d));
}
__device__ __forceinline__ void wgmma_ss_n192(float (&d)[96], uint64_t adesc, uint64_t bdesc, int scale_d) {
    asm volatile("{\n.reg .pred p;\nsetp.ne.b32 p, %98, 0;\n"
      "wgmma.mma_async.sync.aligned.m64n192k16.f32.bf16.bf16 {%0,%1,%2,%3,%4,%5,%6,%7,%8,%9,%10,%11,%12,%13,%14,%15,%16,%17,%18,%19,%20,%21,%22,%23,%24,%25,%26,%27,%28,%29,%30,%31,%32,%33,%34,%35,%36,%37,%38,%39,%40,%41,%42,%43,%44,%45,%46,%47,%48,%49,%50,%51,%52,%53,%54,%55,%56,%57,%58,%59,%60,%61,%62,%63,%64,%65,%66,%67,%68,%69,%70,%71,%72,%73,%74,%75,%76,%77,%78,%79,%80,%81,%82,%83,%84,%85,%86,%87,%88,%89,%90,%91,%92,%93,%94,%95}, %96, %97, p, 1, 1, 0, 1;\n}"
      : "+f"(d[0]), "+f"(d[1]), "+f"(d[2]), "+f"(d[3]), "+f"(d[4]), "+f"(d[5]), "+f"(d[6]), "+f"(d[7]), "+f"(d[8]), "+f"(d[9]), "+f"(d[10]), "+f"(d[11]), "+f"(d[12]), "+f"(d[13]), "+f"(d[14]), "+f"(d[15]), "+f"(d[16]), "+f"(d[17]), "+f"(d[18]), "+f"(d[19]), "+f"(d[20]), "+f"(d[21]), "+f"(d[22]), "+f"(d[23]), "+f"(d[24]), "+f"(d[25]), "+f"(d[26]), "+f"(d[27]), "+f"(d[28]), "+f"(d[29]), "+f"(d[30]), "+f"(d[31]), "+f"(d[32]), "+f"(d[33]), "+f"(d[34]), "+f"(d[35]), "+f"(d[36]), "+f"(d[37]), "+f"(d[38]), "+f"(d[39]), "+f"(d[40]), "+f"(d[41]), "+f"(d[42]), "+f"(d[43]), "+f"(d[44]), "+f"(d[45]), "+f"(d[46]), "+f"(d[47]), "+f"(d[48]), "+f"(d[49]), "+f"(d[50]), "+f"(d[51]), "+f"(d[52]), "+f"(d[53]), "+f"(d[54]), "+f"(d[55]), "+f"(d[56]), "+f"(d[57]), "+f"(d[58]), "+f"(d[59]), "+f"(d[60]), "+f"(d[61]), "+f"(d[62]), "+f"(d[63]), "+f"(d[64]), "+f"(d[65]), "+f"(d[66]), "+f"(d[67]), "+f"(d[68]), "+f"(d[69]), "+f"(d[70]), "+f"(d[71]), "+f"(d[72]), "+f"(d[73]), "+f"(d[74]), "+f"(d[75]), "+f"(d[76]), "+f"(d[77]), "+f"(d[78]), "+f"(d[79]), "+f"(d[80]), "+f"(d[81]), "+f"(d[82]), "+f"(d[83]), "+f"(d[84]), "+f"(d[85]), "+f"(d[86]), "+f"(d[87]), "+f"(d[88]), "+f"(d[89]), "+f"(d[90]), "+f"(d[91]), "+f"(d[92]), "+f"(d[93]), "+f"(d[94]), "+f"(d[95])
      : "l"(adesc), "l"(bdesc), "r"(scale_d));
}
__device__ __forceinline__ void qk_wgmma_n64(float (&d)[32], const uint32_t (&a)[4], uint64_t desc) {
    asm volatile("wgmma.mma_async.sync.aligned.m64n64k16.f32.bf16.bf16 {%0,%1,%2,%3,%4,%5,%6,%7,%8,%9,%10,%11,%12,%13,%14,%15,%16,%17,%18,%19,%20,%21,%22,%23,%24,%25,%26,%27,%28,%29,%30,%31}, {%32,%33,%34,%35}, %36, 0, 1, 1, 0;"
      : "=f"(d[0]), "=f"(d[1]), "=f"(d[2]), "=f"(d[3]), "=f"(d[4]), "=f"(d[5]), "=f"(d[6]), "=f"(d[7]), "=f"(d[8]), "=f"(d[9]), "=f"(d[10]), "=f"(d[11]), "=f"(d[12]), "=f"(d[13]), "=f"(d[14]), "=f"(d[15]), "=f"(d[16]), "=f"(d[17]), "=f"(d[18]), "=f"(d[19]), "=f"(d[20]), "=f"(d[21]), "=f"(d[22]), "=f"(d[23]), "=f"(d[24]), "=f"(d[25]), "=f"(d[26]), "=f"(d[27]), "=f"(d[28]), "=f"(d[29]), "=f"(d[30]), "=f"(d[31])
      : "r"(a[0]), "r"(a[1]), "r"(a[2]), "r"(a[3]), "l"(desc));
}

__device__ __forceinline__ void pv_wgmma(float (&d)[12], uint32_t a0, uint32_t a1, uint32_t a2, uint32_t a3, uint64_t desc) {
    asm volatile("wgmma.mma_async.sync.aligned.m64n24k16.f32.bf16.bf16 {%0,%1,%2,%3,%4,%5,%6,%7,%8,%9,%10,%11}, {%12,%13,%14,%15}, %16, 1, 1, 1, 1;"
      : "+f"(d[0]), "+f"(d[1]), "+f"(d[2]), "+f"(d[3]), "+f"(d[4]), "+f"(d[5]), "+f"(d[6]), "+f"(d[7]), "+f"(d[8]), "+f"(d[9]), "+f"(d[10]), "+f"(d[11])
      : "r"(a0), "r"(a1), "r"(a2), "r"(a3), "l"(desc));
}

__device__ __forceinline__ void tile_of(int bid, int& mb, int& nt) {
    int grp = bid >> 4, in = bid & 15;
    mb = (grp >> 1) * 4 + (in >> 2);
    nt = (grp & 1) * 4 + (in & 3);
}

constexpr int K1_STAGES = 5, K1_STAGE = 16384 + 24576;
constexpr int K1_BAR = K1_STAGES * K1_STAGE, K1_RS = K1_BAR + 128, K1_CS = K1_RS + 1024, K1_SMEM = K1_CS + 768;

__device__ __forceinline__ float2 row_stats_regs(uint4 a, uint4 b) {
    float v[16];
    v[0] = bf_lo(a.x); v[1] = bf_hi(a.x); v[2] = bf_lo(a.y); v[3] = bf_hi(a.y);
    v[4] = bf_lo(a.z); v[5] = bf_hi(a.z); v[6] = bf_lo(a.w); v[7] = bf_hi(a.w);
    v[8] = bf_lo(b.x); v[9] = bf_hi(b.x); v[10] = bf_lo(b.y); v[11] = bf_hi(b.y);
    v[12] = bf_lo(b.z); v[13] = bf_hi(b.z); v[14] = bf_lo(b.w); v[15] = bf_hi(b.w);
    float s = 0.f;
#pragma unroll
    for (int i = 0; i < 16; i++) s += v[i];
    float mean = warp_sum(s) * (1.0f / DM);
    float q = 0.f;
#pragma unroll
    for (int i = 0; i < 16; i++) { float d = v[i] - mean; q = fmaf(d, d, q); }
    float var = warp_sum(q) * (1.0f / DM);
    float rstd = rsqrtf(var + 1e-5f);
    return make_float2(rstd, -mean * rstd);
}
__device__ __forceinline__ float2 row_stats_x(const __nv_bfloat16* x, int row, int lane) {
    const uint4* p = (const uint4*)(x + (size_t)row * DM);
    return row_stats_regs(__ldg(p + lane), __ldg(p + 32 + lane));
}
__device__ __forceinline__ void colsum8(const __nv_bfloat16* w, int ld, int col, int k0, int nk, float (&s)[8]) {
#pragma unroll
    for (int i = 0; i < 8; i++) s[i] = 0.f;
    for (int k = k0; k < k0 + nk; k += 8) {
        uint4 u[8];
#pragma unroll
        for (int i = 0; i < 8; i++) u[i] = __ldg((const uint4*)(w + (size_t)(k + i) * ld + col));
#pragma unroll
        for (int i = 0; i < 8; i++) {
            s[0] += bf_lo(u[i].x); s[1] += bf_hi(u[i].x); s[2] += bf_lo(u[i].y); s[3] += bf_hi(u[i].y);
            s[4] += bf_lo(u[i].z); s[5] += bf_hi(u[i].z); s[6] += bf_lo(u[i].w); s[7] += bf_hi(u[i].w);
        }
    }
}
__device__ __forceinline__ bool wait_count(const unsigned int* p, unsigned int target, int lane) {
    int ok = 1;
    if (lane == 0) {
        int it = 0;
        while (ld_acquire(p) < target) { if (++it > (1 << 18)) { ok = 0; break; } }
    }
    ok = __shfl_sync(0xffffffffu, ok, 0);
    return ok != 0;
}

__global__ void __launch_bounds__(384, 1)
qkv_kernel(const __grid_constant__ CUtensorMap tm_x, const __grid_constant__ CUtensorMap tm_w,
           const __nv_bfloat16* __restrict__ x, const __nv_bfloat16* __restrict__ wqkv) {
    extern __shared__ __align__(1024) unsigned char smem[];
    const uint32_t sb = smem_u32(smem);
    const int tid = threadIdx.x, warp = tid >> 5, lane = tid & 31;
    TL(0);
    int mb, nt;
    tile_of(blockIdx.x, mb, nt);
    const uint32_t full = sb + K1_BAR, empty = full + 40, auxb = full + 80;
    if (tid == 0) {
        prefetch_tmap(&tm_x); prefetch_tmap(&tm_w);
        for (int i = 0; i < K1_STAGES; i++) { mbar_init(full + 8 * i, 1); mbar_init(empty + 8 * i, 8); }
        mbar_init(auxb, 3);
        fence_barrier_init();
    }
    __syncthreads();
    pdl_launch();
    if (warp == 0) {
        if (blockIdx.x == 0) { g_cnt2[lane] = 0; g_cnt2[32 + lane] = 0; }
        if (lane == 0) {
            for (int kb = 0; kb < 8; kb++) {
                int s = kb % K1_STAGES;
                if (kb >= K1_STAGES) mbar_wait(empty + 8 * s, 0);
                mbar_expect(full + 8 * s, K1_STAGE);
                tma2d(sb + s * K1_STAGE, &tm_x, kb * 64, mb * 128, full + 8 * s);
                tma3d(sb + s * K1_STAGE + 16384, &tm_w, 0, kb * 64, nt * 3, full + 8 * s);
            }
        }
    } else if (warp < 4) {
        float2* s_rs = (float2*)(smem + K1_RS);
        float* s_cs = (float*)(smem + K1_CS);
        if (warp < 3) {
            const int r0 = mb * 128 + nt * 16 + (warp - 1) * 8;
            uint4 u[16];
#pragma unroll
            for (int i = 0; i < 8; i++) {
                const uint4* p = (const uint4*)(x + (size_t)(r0 + i) * DM);
                u[2 * i] = __ldg(p + lane); u[2 * i + 1] = __ldg(p + 32 + lane);
            }
            float2 mine = make_float2(0.f, 0.f);
#pragma unroll
            for (int i = 0; i < 8; i++) {
                float2 st = row_stats_regs(u[2 * i], u[2 * i + 1]);
                if (lane == i) mine = st;
            }
            if (lane < 8) g_rowstat1[r0 + lane] = mine;
            __syncwarp();
            if (lane == 0) red_release(&g_cnt[mb]);
        } else {
            uint4 u[24];
#pragma unroll
            for (int c = 0; c < 3; c++)
#pragma unroll
                for (int i = 0; i < 8; i++)
                    u[c * 8 + i] = __ldg((const uint4*)(wqkv + (size_t)(mb * 32 + (lane >> 3) * 8 + i) * 1536 + nt * 192 + (c * 8 + (lane & 7)) * 8));
#pragma unroll
            for (int c = 0; c < 3; c++) {
                float cs[8];
#pragma unroll
                for (int i = 0; i < 8; i++) cs[i] = 0.f;
#pragma unroll
                for (int i = 0; i < 8; i++) {
                    const uint4 w = u[c * 8 + i];
                    cs[0] += bf_lo(w.x); cs[1] += bf_hi(w.x); cs[2] += bf_lo(w.y); cs[3] += bf_hi(w.y);
                    cs[4] += bf_lo(w.z); cs[5] += bf_hi(w.z); cs[6] += bf_lo(w.w); cs[7] += bf_hi(w.w);
                }
#pragma unroll
                for (int i = 0; i < 8; i++) {
                    cs[i] += __shfl_xor_sync(0xffffffffu, cs[i], 8);
                    cs[i] += __shfl_xor_sync(0xffffffffu, cs[i], 16);
                }
                if (lane < 8) {
                    float4* d = (float4*)(g_cs1_part + mb * 1536 + nt * 192 + (c * 8 + lane) * 8);
                    d[0] = make_float4(cs[0], cs[1], cs[2], cs[3]);
                    d[1] = make_float4(cs[4], cs[5], cs[6], cs[7]);
                }
            }
            __syncwarp();
            if (lane == 0) red_release(&g_cnt[16 + nt]);
        }
        TX(8 + warp);
        if (warp == 1) {
            if (wait_count(&g_cnt[mb], 16, lane)) {
#pragma unroll
                for (int i = 0; i < 4; i++) s_rs[lane + 32 * i] = __ldcg(&g_rowstat1[mb * 128 + lane + 32 * i]);
            } else {
                for (int i = 0; i < 128; i++) {
                    float2 st = row_stats_x(x, mb * 128 + i, lane);
                    if (lane == 0) s_rs[i] = st;
                }
            }
        } else {
            int c0 = (warp - 2) * 96;
            if (wait_count(&g_cnt[16 + nt], 16, lane)) {
#pragma unroll
                for (int i = 0; i < 3; i++) {
                    float s = 0.f;
#pragma unroll
                    for (int p = 0; p < 16; p++) s += __ldcg(&g_cs1_part[p * 1536 + nt * 192 + c0 + lane + 32 * i]);
                    s_cs[c0 + lane + 32 * i] = s;
                }
            } else if (lane < 12) {
                float s[8];
                colsum8(wqkv, 1536, nt * 192 + c0 + lane * 8, 0, 512, s);
#pragma unroll
                for (int i = 0; i < 8; i++) s_cs[c0 + lane * 8 + i] = s[i];
            }
        }
        __syncwarp();
        TX(12 + warp);
        if (lane == 0) mbar_arrive(auxb);
    } else {
        const int wgi = (warp >> 2) - 1, ww = warp & 3;
        float acc[96];
#pragma unroll 1
        for (int kb = 0; kb < 8; kb++) {
            int s = kb % K1_STAGES;
            mbar_wait(full + 8 * s, (kb / K1_STAGES) & 1);
            if (warp == 4) TX(kb);
            uint64_t ad = make_desc(sb + s * K1_STAGE + wgi * 8192, 16, 1024, 1);
            uint64_t bd = make_desc(sb + s * K1_STAGE + 16384, 8192, 1024, 1);
            WG_FENCE();
#pragma unroll
            for (int k = 0; k < 4; k++) wgmma_ss_n192(acc, ad + k * 2, bd + k * 128, (kb | k) != 0);
            WG_COMMIT();
            if (kb > 0) {
                wg_wait<1>();
                if (lane == 0) mbar_arrive(empty + 8 * ((kb - 1) % K1_STAGES));
            }
        }
        wg_wait<0>();
        fence_regs(acc);
        TL(1);
        if (warp == 4) TX(16);
        mbar_wait(auxb, 0);
        if (warp == 4) TX(17);
        const float2* s_rs = (const float2*)(smem + K1_RS);
        const float* s_cs = (const float*)(smem + K1_CS);
        const int g = lane >> 2, t = lane & 3;
        const int rl = wgi * 64 + ww * 16 + g;
        const float2 st0 = s_rs[rl], st1 = s_rs[rl + 8];
        const float QS = 0.25f * 1.4426950408889634f;
        const int jrow = mb * 16 + wgi * 8 + ww * 2;
        const int rg16 = mb * 8 + wgi * 4 + ww;
        uint32_t* out = (uint32_t*)g_qkv;
#pragma unroll
        for (int hh = 0; hh < 12; hh++) {
            const int col0 = nt * 192 + hh * 16;
            const int which = col0 >> 9, head = (col0 & 511) >> 4;
            const float sc = (which == 0) ? QS : 1.0f;
            const float a0 = st0.x * sc, b0 = st0.y * sc, a1 = st1.x * sc, b1 = st1.y * sc;
            float n0 = 0.f, n1 = 0.f;
#pragma unroll
            for (int c = 0; c < 2; c++) {
                const int j = hh * 2 + c;
                const float2 cs = *(const float2*)(s_cs + 8 * j + 2 * t);
                float v00 = fmaf(a0, acc[4 * j], b0 * cs.x), v01 = fmaf(a0, acc[4 * j + 1], b0 * cs.y);
                float v10 = fmaf(a1, acc[4 * j + 2], b1 * cs.x), v11 = fmaf(a1, acc[4 * j + 3], b1 * cs.y);
                size_t o = ((size_t)((which * NH + head) * 2 + c) * 256 + jrow) * 32 + lane;
                out[o] = pack_bf16(v00, v01);
                out[o + 32] = pack_bf16(v10, v11);
                if (which < 2) {
                    n0 = fmaf(v00, v00, fmaf(v01, v01, n0));
                    n1 = fmaf(v10, v10, fmaf(v11, v11, n1));
                } else {
                    n0 = fmaxf(n0, fmaxf(fabsf(v00), fabsf(v01)));
                    n1 = fmaxf(n1, fmaxf(fabsf(v10), fabsf(v11)));
                    if (v00 != v00 || v01 != v01 || v10 != v10 || v11 != v11) n0 = __int_as_float(0x7f800000);
                }
            }
            float m;
            if (which < 2) {
                n0 += __shfl_xor_sync(0xffffffffu, n0, 1); n1 += __shfl_xor_sync(0xffffffffu, n1, 1);
                n0 += __shfl_xor_sync(0xffffffffu, n0, 2); n1 += __shfl_xor_sync(0xffffffffu, n1, 2);
                m = n0 + n1 - fminf(n0, n1);
                if (!(m == m)) m = __int_as_float(0x7f800000);
                m = fmaxf(m, __shfl_xor_sync(0xffffffffu, m, 4));
                m = fmaxf(m, __shfl_xor_sync(0xffffffffu, m, 8));
                m = fmaxf(m, __shfl_xor_sync(0xffffffffu, m, 16));
            } else {
                m = warp_max(fmaxf(n0, n1));
            }
            if (lane == 0) g_nrm[(which * NH + head) * 128 + rg16] = m;
        }
        TL(2);
        if (warp == 4) TX(18);
    }
}

constexpr int AT_K = 0, AT_V = 65536, AT_ONES = 131072, AT_BAR = 163840, AT_SMEM = AT_BAR + 128;
#define POLY_MASK 0xAD6A

__device__ __forceinline__ uint32_t exp2_pair_poly(float x0, float x1) {
    uint32_t t0 = __float_as_uint(x0 + 32895.0f);
    uint32_t t1 = __float_as_uint(x1 + 32895.0f);
    uint32_t gd = __byte_perm(t0, t1, 0x6420);
    uint32_t wm = __byte_perm(t0, t1, 0x5612);
    uint32_t v = hfma2(gd, 0x71477147u, 0x354f354fu);
    uint32_t z = hmul2(v, gd);
    return (wm >> 1) + z;
}
__device__ __forceinline__ uint32_t exp2_pair_mufu(float x0, float x1) { return pack_bf16(ex2f(x0), ex2f(x1)); }
template <uint32_t MASK>
__device__ __forceinline__ void exp_blocks(const float (&s)[32], uint32_t (&p)[16]) {
#pragma unroll
    for (int b = 0; b < 8; b++) {
        if ((MASK >> b) & 1) {
            p[2 * b] = exp2_pair_poly(s[4 * b], s[4 * b + 1]);
            p[2 * b + 1] = exp2_pair_poly(s[4 * b + 2], s[4 * b + 3]);
        } else {
            p[2 * b] = exp2_pair_mufu(s[4 * b], s[4 * b + 1]);
            p[2 * b + 1] = exp2_pair_mufu(s[4 * b + 2], s[4 * b + 3]);
        }
    }
}
#define PV4(P) _Pragma("unroll") for (int i = 0; i < 4; i++) { pv_wgmma(o, P[4 * i], P[4 * i + 1], P[4 * i + 2], P[4 * i + 3], vd); vd += 16; }

__device__ __forceinline__ void attn_store(float (&o)[12], int row0, int head, int lane) {
    float l0 = __shfl_sync(0xffffffffu, o[8], lane & 28);
    float l1 = __shfl_sync(0xffffffffu, o[10], lane & 28);
    float r0 = 1.0f / l0, r1 = 1.0f / l1;
    uint32_t* op = (uint32_t*)g_ao;
    int mb = row0 >> 7, rg = (row0 & 127) >> 3;
    int kb = head >> 2, kc = (head & 3) * 2;
    size_t base = (((size_t)(mb * 8 + kb) * 8 + kc) * 16 + rg) * 32 + lane;
    op[base] = pack_bf16(o[0] * r0, o[1] * r0);
    op[base + 32] = pack_bf16(o[2] * r1, o[3] * r1);
    op[base + 16 * 32] = pack_bf16(o[4] * r0, o[5] * r0);
    op[base + 16 * 32 + 32] = pack_bf16(o[6] * r1, o[7] * r1);
}

__device__ __forceinline__ void attn_load_q(uint32_t (&q)[4], const __nv_bfloat16* gq, int row0, int lane) {
    const uint32_t* qp = (const uint32_t*)gq;
    int j0 = row0 >> 3;
    q[0] = __ldcg(qp + (0 * 256 + j0) * 32 + lane);
    q[1] = __ldcg(qp + (0 * 256 + j0 + 1) * 32 + lane);
    q[2] = __ldcg(qp + (1 * 256 + j0) * 32 + lane);
    q[3] = __ldcg(qp + (1 * 256 + j0 + 1) * 32 + lane);
}

__device__ __forceinline__ void attn_tile_safe(const uint32_t (&q)[4], uint64_t kd, uint64_t vd, int row0, int head, int lane) {
    float o[12];
#pragma unroll
    for (int i = 0; i < 12; i++) o[i] = 0.f;
    float m0 = -INFINITY, m1 = -INFINITY;
    fence_regs(o);
#pragma unroll 1
    for (int j = 0; j < 32; j++) {
        float s[32];
        uint32_t p[16];
        WG_FENCE();
        qk_wgmma_n64(s, q, kd); kd += 64;
        WG_COMMIT();
        wg_wait<0>();
        fence_regs(s);
        fence_regs(o);
        float x0 = m0, x1 = m1;
#pragma unroll
        for (int b = 0; b < 8; b++) {
            x0 = fmaxf(x0, fmaxf(s[4 * b], s[4 * b + 1]));
            x1 = fmaxf(x1, fmaxf(s[4 * b + 2], s[4 * b + 3]));
        }
        x0 = fmaxf(x0, __shfl_xor_sync(0xffffffffu, x0, 1)); x0 = fmaxf(x0, __shfl_xor_sync(0xffffffffu, x0, 2));
        x1 = fmaxf(x1, __shfl_xor_sync(0xffffffffu, x1, 1)); x1 = fmaxf(x1, __shfl_xor_sync(0xffffffffu, x1, 2));
        float al0 = ex2f(m0 - x0), al1 = ex2f(m1 - x1);
        m0 = x0; m1 = x1;
#pragma unroll
        for (int i = 0; i < 3; i++) { o[4 * i] *= al0; o[4 * i + 1] *= al0; o[4 * i + 2] *= al1; o[4 * i + 3] *= al1; }
#pragma unroll
        for (int b = 0; b < 8; b++) {
            p[2 * b] = exp2_pair_mufu(s[4 * b] - m0, s[4 * b + 1] - m0);
            p[2 * b + 1] = exp2_pair_mufu(s[4 * b + 2] - m1, s[4 * b + 3] - m1);
        }
        fence_regs(o);
        WG_FENCE();
        PV4(p);
        WG_COMMIT();
        wg_wait<0>();
        fence_regs(o);
    }
    attn_store(o, row0, head, lane);
}

__global__ void __launch_bounds__(512, 1)
attn_kernel(const __nv_bfloat16* __restrict__ wg_, const __nv_bfloat16* __restrict__ wu_,
            const __nv_bfloat16* __restrict__ wo_, const __nv_bfloat16* __restrict__ wd_) {
    extern __shared__ __align__(1024) unsigned char smem[];
    const uint32_t sb = smem_u32(smem);
    const int tid = threadIdx.x, wg = tid >> 7, warp = (tid >> 5) & 3, lane = tid & 31;
    pdl_launch();
    if (blockIdx.x >= 128) {
        const int e = blockIdx.x - 128;
        const __nv_bfloat16* w = (e < 2) ? wg_ : wu_;
        float* red = (float*)smem;
        const int cgrp = tid & 127, kq = tid >> 7;
        if (cgrp < 112) {
            float s[8];
            colsum8(w, FF, (e & 1) * 896 + cgrp * 8, kq * 128, 128, s);
#pragma unroll
            for (int i = 0; i < 8; i++) red[kq * 896 + cgrp * 8 + i] = s[i];
        }
        __syncthreads();
        for (int c = tid; c < 896; c += 512)
            g_cs2[(e >> 1) * FF + (e & 1) * 896 + c] = red[c] + red[896 + c] + red[1792 + c] + red[2688 + c];
        if (tid < 32) {
            const char* p0 = (const char*)wo_ + e * (DM * DM * 2 / 4);
            for (int i = lane; i < 32; i += 32)
                asm volatile("cp.async.bulk.prefetch.L2.global [%0], %1;" :: "l"(p0 + i * 4096), "r"(4096) : "memory");
            const char* p1 = (const char*)wd_ + e * (FF * DM * 2 / 4);
            for (int i = lane; i < 112; i += 32)
                asm volatile("cp.async.bulk.prefetch.L2.global [%0], %1;" :: "l"(p1 + i * 4096), "r"(4096) : "memory");
        }
        return;
    }
    const int head = blockIdx.x >> 2, qq = blockIdx.x & 3;
    const __nv_bfloat16* gq = g_qkv + (size_t)head * (S_LEN * 16);
    const __nv_bfloat16* gk = g_qkv + (size_t)(NH + head) * (S_LEN * 16);
    const __nv_bfloat16* gv = g_qkv + (size_t)(2 * NH + head) * (S_LEN * 16);
    if (tid == 0) {
        for (int i = 0; i < 8; i++) mbar_init(sb + AT_BAR + 8 * i, 1);
        fence_barrier_init();
    }
    {
        uint4 one = make_uint4(0x00003F80u, 0, 0, 0);
#pragma unroll
        for (int i = 0; i < 4; i++) *(uint4*)(smem + AT_ONES + (i * 512 + tid) * 16) = one;
        fence_proxy_async();
    }
    __syncthreads();
    TL(3);
    pdl_wait();
    TL(4);
    if (tid == 0) {
        for (int i = 0; i < 8; i++) {
            uint32_t bar = sb + AT_BAR + 8 * i;
            mbar_expect(bar, 16384);
            bulk_g2s(sb + AT_K + i * 4096, gk + i * 2048, 4096, bar);
            bulk_g2s(sb + AT_K + 32768 + i * 4096, gk + 16384 + i * 2048, 4096, bar);
            bulk_g2s(sb + AT_V + i * 4096, gv + i * 2048, 4096, bar);
            bulk_g2s(sb + AT_V + 32768 + i * 4096, gv + 16384 + i * 2048, 4096, bar);
        }
    }
    bool fast;
    {
        const float* nq = g_nrm + (0 * NH + head) * 128 + qq * 32;
        const float* nk = g_nrm + (1 * NH + head) * 128;
        const float* nv = g_nrm + (2 * NH + head) * 128;
        float4 k4 = __ldcg((const float4*)nk + lane), v4 = __ldcg((const float4*)nv + lane);
        float qm = warp_max(__ldcg(nq + lane));
        float km = warp_max(fmaxf(fmaxf(k4.x, k4.y), fmaxf(k4.z, k4.w)));
        float vm = warp_max(fmaxf(fmaxf(v4.x, v4.y), fmaxf(v4.z, v4.w)));
        fast = (qm * km <= 3500.0f) && (vm <= 1.0e12f);
    }
    const uint64_t kdesc0 = make_desc(sb + AT_K, 32768, 128, 0);
    const uint64_t vdesc0 = make_desc(sb + AT_V, 128, 32768, 0);
    if (!fast) {
        for (int i = 0; i < 8; i++) mbar_wait(sb + AT_BAR + 8 * i, 0);
#pragma unroll 1
        for (int tile = 0; tile < 2; tile++) {
            const int row0 = qq * 512 + (tile * 4 + wg) * 64 + warp * 16;
            uint32_t q[4];
            attn_load_q(q, gq, row0, lane);
            attn_tile_safe(q, kdesc0, vdesc0, row0, head, lane);
        }
        return;
    }
#pragma unroll 1
    for (int tile = 0; tile < 2; tile++) {
        const int row0 = qq * 512 + (tile * 4 + wg) * 64 + warp * 16;
        uint32_t q[4];
        attn_load_q(q, gq, row0, lane);
        float o[12];
#pragma unroll
        for (int i = 0; i < 12; i++) o[i] = 0.f;
        fence_regs(o);
        float sa[32];
        uint32_t pa[16];
        uint64_t kd = kdesc0, vd = vdesc0;
        if (tile == 0) mbar_wait(sb + AT_BAR, 0);
        WG_FENCE();
        qk_wgmma_n64(sa, q, kd); kd += 64;
        WG_COMMIT();
#pragma unroll 1
        for (int jj = 0; jj < 8; jj++) {
            if (tile == 0 && jj < 7) mbar_wait(sb + AT_BAR + 8 * (jj + 1), 0);
#pragma unroll
            for (int j = 0; j < 4; j++) {
                wg_wait<0>();
                fence_regs(sa);
                if (j & 1) exp_blocks<(POLY_MASK >> 8)>(sa, pa); else exp_blocks<(POLY_MASK & 255)>(sa, pa);
                WG_FENCE();
                qk_wgmma_n64(sa, q, kd); kd += 64;
                PV4(pa);
                WG_COMMIT();
            }
        }
        wg_wait<0>();
        fence_regs(o);
        fence_regs(sa);
        attn_store(o, row0, head, lane);
    }
    TL(5);
}

constexpr int F_R2 = 131072, F_X = 196608, F_BAR = 229376;
constexpr int F_RS = F_BAR + 256, F_CS = F_RS + 1024, F_SMEM = F_CS + 1792;
enum { B_FA = 0, B_HF = 2, B_BF = 6, B_BE = 9, B_CF = 12, B_CE = 18, B_ADONE = 24, B_BDONE = 25, B_XA = 26, B_XC = 27, B_PRDY = 28, B_AUX = 29 };

__device__ __forceinline__ uint32_t mapa(uint32_t a, uint32_t rank) { uint32_t r; asm("mapa.shared::cluster.u32 %0, %1, %2;" : "=r"(r) : "r"(a), "r"(rank)); return r; }
__device__ __forceinline__ void st_async4(uint32_t dst, float a, float b, float c, float d, uint32_t bar) {
    asm volatile("st.async.weak.shared::cluster.mbarrier::complete_tx::bytes.v4.f32 [%0], {%1,%2,%3,%4}, [%5];"
                 :: "r"(dst), "f"(a), "f"(b), "f"(c), "f"(d), "r"(bar) : "memory");
}
__device__ __forceinline__ void mbar_arrive_remote(uint32_t a) { asm volatile("mbarrier.arrive.release.cluster.shared::cluster.b64 _, [%0];" :: "r"(a) : "memory"); }
__device__ __forceinline__ void mbar_wait_cluster(uint32_t a, int parity) {
    uint32_t done;
    int it = 0;
    do {
        asm volatile("{\n.reg .pred p;\nmbarrier.try_wait.parity.acquire.cluster.shared::cta.b64 p, [%1], %2;\nselp.u32 %0, 1, 0, p;\n}"
                     : "=r"(done) : "r"(a), "r"(parity) : "memory");
        if (++it > (1 << 24)) __trap();
    } while (!done);
}
__device__ __forceinline__ void poll_count(const unsigned int* p, unsigned int target) {
    int it = 0;
    while (ld_acquire(p) < target) { if (++it > (1 << 22)) __trap(); }
    asm volatile("fence.proxy.async.global;" ::: "memory");
}
__device__ __forceinline__ void publish_arrive(int id) { asm volatile("bar.arrive %0, 288;" :: "r"(id) : "memory"); }
__device__ __forceinline__ void publish_sync(int id, unsigned int* p, int lane) {
    asm volatile("bar.sync %0, 288;" :: "r"(id) : "memory");
    if (lane == 0) red_release(p);
}
template <int R>
__device__ __forceinline__ void xchg(float (&acc)[64], float (&o)[32], uint32_t sb, unsigned char* smem, int bar, int ctid) {
    const uint32_t dst = mapa(sb + F_X + ctid * 16, 1 - R), rb = mapa(sb + F_BAR + 8 * bar, 1 - R);
#pragma unroll
    for (int q = 0; q < 8; q++) {
        const int j = (1 - R) * 32 + 4 * q;
        st_async4(dst + q * 4096, acc[j], acc[j + 1], acc[j + 2], acc[j + 3], rb);
    }
    mbar_wait_cluster(sb + F_BAR + 8 * bar, 0);
#pragma unroll
    for (int q = 0; q < 8; q++) {
        float4 v = *(const float4*)(smem + F_X + q * 4096 + ctid * 16);
        const int j = R * 32 + 4 * q;
        o[4 * q] = acc[j] + v.x; o[4 * q + 1] = acc[j + 1] + v.y; o[4 * q + 2] = acc[j + 2] + v.z; o[4 * q + 3] = acc[j + 3] + v.w;
    }
}

template <int NB>
__device__ __forceinline__ void ffn_epilogue(const float* ag, const float* au, const float* s_cs, int cs_off, int jb0,
                                             float2 st0, float2 st1, int mb, int rgl, int lane) {
    const int t = lane & 3;
    uint32_t* gp = (uint32_t*)g_g;
    const float C1 = 0.7978845608028654f, C2 = 0.044715f * 0.7978845608028654f;
    const float k10 = st0.x * C1, k20 = st0.x * st0.x * st0.x * C2, k11 = st1.x * C1, k21 = st1.x * st1.x * st1.x * C2;
#pragma unroll
    for (int j = 0; j < NB; j++) {
        const float2 cg = *(const float2*)(s_cs + cs_off + 8 * j + 2 * t);
        const float2 cu = *(const float2*)(s_cs + 224 + cs_off + 8 * j + 2 * t);
        float r[4];
#pragma unroll
        for (int e = 0; e < 4; e++) {
            const float nm = (e < 2) ? st0.y : st1.y, k1 = (e < 2) ? k10 : k11, k2 = (e < 2) ? k20 : k21;
            const float tg = fmaf(nm, (e & 1) ? cg.y : cg.x, ag[4 * j + e]);
            const float tu = fmaf(nm, (e & 1) ? cu.y : cu.x, au[4 * j + e]);
            const float th = tanh_fast(tg * fmaf(tg * tg, k2, k1));
            const float p = tg * tu;
            r[e] = fmaf(p, th, p);
        }
        const int jb = jb0 + j;
        size_t o = (((size_t)mb * 28 * 8 + jb) * 16 + rgl) * 32 + lane;
        gp[o] = pack_bf16(r[0], r[1]);
        gp[o + 32] = pack_bf16(r[2], r[3]);
    }
}

__global__ void __cluster_dims__(2, 1, 1) __launch_bounds__(384, 1)
tail_kernel(const __grid_constant__ CUtensorMap tm_o, const __grid_constant__ CUtensorMap tm_g,
            const __grid_constant__ CUtensorMap tm_u, const __grid_constant__ CUtensorMap tm_d,
            const __nv_bfloat16* __restrict__ x, __nv_bfloat16* __restrict__ out) {
    extern __shared__ __align__(1024) unsigned char smem[];
    const uint32_t sb = smem_u32(smem);
    const uint32_t bars = sb + F_BAR;
    const int tid = threadIdx.x, warp = tid >> 5, lane = tid & 31;
    TL(6);
    const int cl = blockIdx.x >> 1, r = blockIdx.x & 1;
    const int mb = ((cl & 7) >> 1) * 4 + (cl >> 4), ntA = (cl & 1) * 2 + ((cl >> 3) & 1);
    const int nt = ntA * 2 + r;
    if (tid == 0) {
        prefetch_tmap(&tm_o); prefetch_tmap(&tm_g); prefetch_tmap(&tm_u); prefetch_tmap(&tm_d);
        for (int i = 0; i < 30; i++) {
            int cnt = 1;
            if ((i >= B_BE && i < B_BE + 3) || (i >= B_CE && i < B_CE + 6) || i == B_ADONE || i == B_BDONE || i == B_PRDY) cnt = 8;
            if (i == B_AUX) cnt = 3;
            mbar_init(bars + 8 * i, cnt);
        }
        mbar_expect(bars + 8 * B_XA, 32768);
        mbar_expect(bars + 8 * B_XC, 32768);
        fence_barrier_init();
    }
    __syncthreads();
    asm volatile("barrier.cluster.arrive.release.aligned;" ::: "memory");
    if (warp < 4) {
        asm volatile("setmaxnreg.dec.sync.aligned.u32 56;");
        if (warp == 0) {
            if (lane == 0) {
                auto load_b = [&](int it) {
                    const int s = it % 3, pass = it >> 3, kb = it & 7;
                    const int ng = pass ? 3 : 4, c0 = nt * 224 + pass * 128;
                    const uint32_t bar = bars + 8 * (B_BF + s), dst = sb + F_R2 + s * 32768;
                    mbar_expect(bar, ng * 8192);
                    for (int i = 0; i < ng; i++) {
                        tma2d(dst + i * 4096, &tm_g, c0 + i * 32, kb * 64, bar);
                        tma2d(dst + 16384 + i * 4096, &tm_u, c0 + i * 32, kb * 64, bar);
                    }
                };
                for (int i = 0; i < 4; i++) {
                    const uint32_t bar = bars + 8 * (B_FA + (i >> 1));
                    if (!(i & 1)) mbar_expect(bar, 65536);
                    tma2d(sb + i * 32768 + 16384, &tm_o, ntA * 128, (4 * r + i) * 64, bar);
                    tma2d(sb + i * 32768 + 24576, &tm_o, ntA * 128 + 64, (4 * r + i) * 64, bar);
                }
                pdl_wait();
                TL(16);
                for (int i = 0; i < 4; i++)
                    bulk_g2s(sb + i * 32768, g_ao + (size_t)(mb * 8 + 4 * r + i) * 8192, 16384, bars + 8 * (B_FA + (i >> 1)));
                load_b(0); load_b(1);
                if (blockIdx.x == 0)
                    for (int i = 0; i < 32; i++) g_cnt[i] = 0;
                mbar_wait(bars + 8 * (B_BE + 2), 0);
                load_b(2);
                poll_count(&g_cnt2[mb], 8);
                TL(17);
                for (int kb = 0; kb < 8; kb++) {
                    const uint32_t bar = bars + 8 * (B_HF + (kb >> 1));
                    if (!(kb & 1)) mbar_expect(bar, 32768);
                    bulk_g2s(sb + kb * 16384, g_h + (size_t)(mb * 8 + kb) * 8192, 16384, bar);
                }
                for (int it = 3; it < 16; it++) {
                    const int s = it % 3, n = it / 3;
                    mbar_wait(bars + 8 * (B_BE + s), (s == 2 ? n : n - 1) & 1);
                    load_b(it);
                }
                mbar_wait(bars + 8 * B_BDONE, 0);
                for (int i = 0; i < 6; i++) {
                    const uint32_t bar = bars + 8 * (B_CF + i);
                    mbar_expect(bar, 32768);
                    tma2d(sb + i * 32768 + 16384, &tm_d, ntA * 128, (2 * i + r) * 64, bar);
                    tma2d(sb + i * 32768 + 24576, &tm_d, ntA * 128 + 64, (2 * i + r) * 64, bar);
                }
                poll_count(&g_cnt2[16 + mb], 8);
                TL(18);
                for (int kb = 0; kb < 14; kb++) {
                    const int s = kb % 6;
                    const uint32_t bar = bars + 8 * (B_CF + s);
                    if (kb >= 6) {
                        mbar_wait(bars + 8 * (B_CE + s), ((kb / 6) - 1) & 1);
                        mbar_expect(bar, 32768);
                        tma2d(sb + s * 32768 + 16384, &tm_d, ntA * 128, (2 * kb + r) * 64, bar);
                        tma2d(sb + s * 32768 + 24576, &tm_d, ntA * 128 + 64, (2 * kb + r) * 64, bar);
                    }
                    bulk_g2s(sb + s * 32768, g_g + (size_t)(mb * 28 + 2 * kb + r) * 8192, 16384, bar);
                }
            }
        } else {
            pdl_wait();
            float2* s_rs = (float2*)(smem + F_RS);
            float* s_cs = (float*)(smem + F_CS);
            for (int c = tid - 32; c < 448; c += 96)
                s_cs[c] = __ldcg(&g_cs2[(c >= 224 ? FF - 224 : 0) + nt * 224 + c]);
            if (warp == 1) { publish_sync(1, &g_cnt2[mb], lane); TL(9); }
            if (lane == 0) poll_count(&g_cnt2[mb], 8);
            __syncwarp();
            for (int rr = tid - 32; rr < 128; rr += 96) {
                const float4* hp = (const float4*)(g_hstat + (size_t)(mb * 128 + rr) * 8);
                float4 a = __ldcg(hp), b = __ldcg(hp + 1), c = __ldcg(hp + 2), d = __ldcg(hp + 3);
                float mean = 0.125f * (a.x + a.z + b.x + b.z + c.x + c.z + d.x + d.z);
                float m2 = a.y + a.w + b.y + b.w + c.y + c.w + d.y + d.w;
                float e;
                e = a.x - mean; m2 = fmaf(64.f * e, e, m2); e = a.z - mean; m2 = fmaf(64.f * e, e, m2);
                e = b.x - mean; m2 = fmaf(64.f * e, e, m2); e = b.z - mean; m2 = fmaf(64.f * e, e, m2);
                e = c.x - mean; m2 = fmaf(64.f * e, e, m2); e = c.z - mean; m2 = fmaf(64.f * e, e, m2);
                e = d.x - mean; m2 = fmaf(64.f * e, e, m2); e = d.z - mean; m2 = fmaf(64.f * e, e, m2);
                s_rs[rr] = make_float2(rsqrtf(m2 * (1.0f / DM) + 1e-5f), -mean);
            }
            __syncwarp();
            if (lane == 0) mbar_arrive(bars + 8 * B_AUX);
            if (warp == 1) { publish_sync(2, &g_cnt2[16 + mb], lane); TL(13); }
        }
        __syncwarp();
        asm volatile("barrier.cluster.wait.acquire.aligned;" ::: "memory");
    } else {
        asm volatile("setmaxnreg.inc.sync.aligned.u32 216;");
        const int wgi = (warp >> 2) - 1, ww = warp & 3, ctid = tid - 128;
        const int g = lane >> 2, t = lane & 3;
        const int rl = wgi * 64 + ww * 16 + g, row = mb * 128 + rl;
        const int rgl = wgi * 8 + ww * 2;
        const float2* s_rs = (const float2*)(smem + F_RS);
        const float* s_cs = (const float*)(smem + F_CS);
        uint32_t* hp = (uint32_t*)g_h + ((size_t)(mb * 8 + nt) * 8 * 16 + rgl) * 32 + lane;
        TL(23);
        {
            uint32_t xr[16];
            const uint32_t* xp = (const uint32_t*)(x + (size_t)row * DM + nt * 64) + t;
#pragma unroll
            for (int j = 0; j < 8; j++) { xr[2 * j] = __ldg(xp + 4 * j); xr[2 * j + 1] = __ldg(xp + 8 * (DM / 2) + 4 * j); }
            float acc[64];
#pragma unroll 1
            for (int i = 0; i < 4; i++) {
                if (!(i & 1)) { mbar_wait(bars + 8 * (B_FA + (i >> 1)), 0); TL(19 + (i >> 1)); }
                uint64_t ad = make_desc(sb + i * 32768 + wgi * 1024, 2048, 128, 0);
                uint64_t bd = make_desc(sb + i * 32768 + 16384, 8192, 1024, 1);
                WG_FENCE();
#pragma unroll
                for (int k = 0; k < 4; k++) wgmma_ss_n128(acc, ad + k * 256, bd + k * 128, (i | k) != 0);
                WG_COMMIT();
            }
            wg_wait<0>();
            fence_regs(acc);
            TL(7);
            asm volatile("barrier.cluster.wait.acquire.aligned;" ::: "memory");
            float o[32];
            if (r == 0) xchg<0>(acc, o, sb, smem, B_XA, ctid); else xchg<1>(acc, o, sb, smem, B_XA, ctid);
            TL(21);
            fence_proxy_async();
            __syncwarp();
            if (lane == 0) mbar_arrive(bars + 8 * (B_BE + 2));
            float v0[16], v1[16];
            float s0 = 0.f, s1 = 0.f;
#pragma unroll
            for (int j = 0; j < 8; j++) {
                uint32_t u0 = pack_bf16(bf_lo(xr[2 * j]) + o[4 * j], bf_hi(xr[2 * j]) + o[4 * j + 1]);
                uint32_t u1 = pack_bf16(bf_lo(xr[2 * j + 1]) + o[4 * j + 2], bf_hi(xr[2 * j + 1]) + o[4 * j + 3]);
                hp[j * 16 * 32] = u0;
                hp[j * 16 * 32 + 32] = u1;
                v0[2 * j] = bf_lo(u0); v0[2 * j + 1] = bf_hi(u0);
                v1[2 * j] = bf_lo(u1); v1[2 * j + 1] = bf_hi(u1);
                s0 += v0[2 * j] + v0[2 * j + 1];
                s1 += v1[2 * j] + v1[2 * j + 1];
            }
            float m0 = s0 * (1.0f / 16), m1 = s1 * (1.0f / 16), q0 = 0.f, q1 = 0.f;
#pragma unroll
            for (int i = 0; i < 16; i++) {
                float d0 = v0[i] - m0, d1 = v1[i] - m1;
                q0 = fmaf(d0, d0, q0); q1 = fmaf(d1, d1, q1);
            }
#pragma unroll
            for (int st = 0; st < 2; st++) {
                float hn = st ? 16.f : 8.f;
                float om0 = __shfl_xor_sync(0xffffffffu, m0, 1 << st), oq0 = __shfl_xor_sync(0xffffffffu, q0, 1 << st);
                float om1 = __shfl_xor_sync(0xffffffffu, m1, 1 << st), oq1 = __shfl_xor_sync(0xffffffffu, q1, 1 << st);
                float d0 = om0 - m0, d1 = om1 - m1;
                q0 = q0 + oq0 + d0 * d0 * hn; q1 = q1 + oq1 + d1 * d1 * hn;
                m0 = 0.5f * (m0 + om0); m1 = 0.5f * (m1 + om1);
            }
            if (t == 0) {
                g_hstat[row * 8 + nt] = make_float2(m0, q0);
                g_hstat[(row + 8) * 8 + nt] = make_float2(m1, q1);
            }
            publish_arrive(1);
            TL(8);
        }
        {
            float ag[64], au[64];
#pragma unroll 1
            for (int kb = 0; kb < 8; kb++) {
                const int s = kb % 3;
                if (!(kb & 1)) mbar_wait(bars + 8 * (B_HF + (kb >> 1)), 0);
                mbar_wait(bars + 8 * (B_BF + s), (kb / 3) & 1);
                if (warp == 4) TX(32 + kb);
                uint64_t ad = make_desc(sb + kb * 16384 + wgi * 1024, 2048, 128, 0);
                uint64_t bd = make_desc(sb + F_R2 + s * 32768, 4096, 512, 2);
                WG_FENCE();
#pragma unroll
                for (int k = 0; k < 4; k++) {
                    wgmma_ss_n128(ag, ad + k * 256, bd + k * 64, (kb | k) != 0);
                    wgmma_ss_n128(au, ad + k * 256, bd + 1024 + k * 64, (kb | k) != 0);
                }
                WG_COMMIT();
                if (kb > 0) {
                    wg_wait<1>();
                    if (lane == 0) mbar_arrive(bars + 8 * (B_BE + (kb - 1) % 3));
                }
            }
            wg_wait<0>();
            if (lane == 0) mbar_arrive(bars + 8 * (B_BE + 7 % 3));
            fence_regs(ag); fence_regs(au);
            TL(10);
            mbar_wait(bars + 8 * B_AUX, 0);
            ffn_epilogue<16>(ag, au, s_cs, 0, nt * 28, s_rs[rl], s_rs[rl + 8], mb, rgl, lane);
        }
        {
            float ag[48], au[48];
#pragma unroll 1
            for (int kb = 0; kb < 8; kb++) {
                const int it = 8 + kb, s = it % 3;
                mbar_wait(bars + 8 * (B_BF + s), (it / 3) & 1);
                if (warp == 4) TX(32 + it);
                uint64_t ad = make_desc(sb + kb * 16384 + wgi * 1024, 2048, 128, 0);
                uint64_t bd = make_desc(sb + F_R2 + s * 32768, 4096, 512, 2);
                WG_FENCE();
#pragma unroll
                for (int k = 0; k < 4; k++) {
                    wgmma_ss_n96(ag, ad + k * 256, bd + k * 64, (kb | k) != 0);
                    wgmma_ss_n96(au, ad + k * 256, bd + 1024 + k * 64, (kb | k) != 0);
                }
                WG_COMMIT();
                if (kb > 0) {
                    wg_wait<1>();
                    if (lane == 0) mbar_arrive(bars + 8 * (B_BE + (it - 1) % 3));
                }
            }
            wg_wait<0>();
            if (lane == 0) {
                mbar_arrive(bars + 8 * B_BDONE);
                mbar_arrive_remote(mapa(bars + 8 * B_PRDY, 1 - r));
            }
            fence_regs(ag); fence_regs(au);
            TL(11);
            ffn_epilogue<12>(ag, au, s_cs, 128, nt * 28 + 16, s_rs[rl], s_rs[rl + 8], mb, rgl, lane);
            publish_arrive(2);
            TL(12);
        }
        {
            uint32_t hr[16];
#pragma unroll
            for (int j = 0; j < 8; j++) { hr[2 * j] = __ldcg(hp + j * 16 * 32); hr[2 * j + 1] = __ldcg(hp + j * 16 * 32 + 32); }
            float acc[64];
#pragma unroll 1
            for (int kb = 0; kb < 14; kb++) {
                const int s = kb % 6;
                mbar_wait(bars + 8 * (B_CF + s), (kb / 6) & 1);
                if (warp == 4) TX(96 + kb);
                uint64_t ad = make_desc(sb + s * 32768 + wgi * 1024, 2048, 128, 0);
                uint64_t bd = make_desc(sb + s * 32768 + 16384, 8192, 1024, 1);
                WG_FENCE();
#pragma unroll
                for (int k = 0; k < 4; k++) wgmma_ss_n128(acc, ad + k * 256, bd + k * 128, (kb | k) != 0);
                WG_COMMIT();
                if (kb > 0) {
                    wg_wait<1>();
                    if (lane == 0) mbar_arrive(bars + 8 * (B_CE + (kb - 1) % 6));
                }
            }
            wg_wait<0>();
            fence_regs(acc);
            TL(14);
            mbar_wait_cluster(bars + 8 * B_PRDY, 0);
            float o[32];
            if (r == 0) xchg<0>(acc, o, sb, smem, B_XC, ctid); else xchg<1>(acc, o, sb, smem, B_XC, ctid);
            TL(22);
            const float a0 = s_rs[rl].x, a1 = s_rs[rl + 8].x;
            const float k0 = 0.5f * a0 * a0, k1 = 0.5f * a1 * a1;
            uint32_t* op = (uint32_t*)(out + (size_t)row * DM + nt * 64) + t;
#pragma unroll
            for (int j = 0; j < 8; j++) {
                op[4 * j] = pack_bf16(fmaf(k0, o[4 * j], bf_lo(hr[2 * j])), fmaf(k0, o[4 * j + 1], bf_hi(hr[2 * j])));
                op[8 * (DM / 2) + 4 * j] = pack_bf16(fmaf(k1, o[4 * j + 2], bf_lo(hr[2 * j + 1])), fmaf(k1, o[4 * j + 3], bf_hi(hr[2 * j + 1])));
            }
            TL(15);
        }
    }
}

typedef CUresult (*EncodeFn)(CUtensorMap*, CUtensorMapDataType, cuuint32_t, void*, const cuuint64_t*, const cuuint64_t*,
                             const cuuint32_t*, const cuuint32_t*, CUtensorMapInterleave, CUtensorMapSwizzle,
                             CUtensorMapL2promotion, CUtensorMapFloatOOBfill);

void encode(EncodeFn fn, CUtensorMap* m, const void* ptr, int rank, const cuuint64_t* dims, const cuuint64_t* strides,
            const cuuint32_t* box, CUtensorMapSwizzle swz) {
    cuuint32_t es[3] = {1, 1, 1};
    fn(m, CU_TENSOR_MAP_DATA_TYPE_BFLOAT16, rank, (void*)ptr, dims, strides, box, es, CU_TENSOR_MAP_INTERLEAVE_NONE, swz,
       CU_TENSOR_MAP_L2_PROMOTION_L2_256B, CU_TENSOR_MAP_FLOAT_OOB_FILL_NONE);
}

template <typename... KArgs, typename... Args>
void launch(void (*kern)(KArgs...), int grid, int block, int smem, bool pdl, Args... args) {
    cudaLaunchConfig_t cfg = {};
    cfg.gridDim = dim3(grid); cfg.blockDim = dim3(block); cfg.dynamicSmemBytes = smem;
    cfg.stream = cudaStreamPerThread;
    cudaLaunchAttribute at[1];
    at[0].id = cudaLaunchAttributeProgrammaticStreamSerialization;
    at[0].val.programmaticStreamSerializationAllowed = 1;
    cfg.attrs = at; cfg.numAttrs = pdl ? 1 : 0;
    cudaLaunchKernelEx(&cfg, kern, KArgs(args)...);
}

}

extern "C" void kernel_launch(void* const* d_in, const int* in_sizes, int n_in, void* d_out, int out_size) {
    const __nv_bfloat16* x = (const __nv_bfloat16*)d_in[0];
    const __nv_bfloat16* wqkv = (const __nv_bfloat16*)d_in[1];
    const __nv_bfloat16* wo = (const __nv_bfloat16*)d_in[2];
    const __nv_bfloat16* wgate = (const __nv_bfloat16*)d_in[4];
    const __nv_bfloat16* wup = (const __nv_bfloat16*)d_in[5];
    const __nv_bfloat16* wdown = (const __nv_bfloat16*)d_in[6];
    __nv_bfloat16* out = (__nv_bfloat16*)d_out;

    static CUtensorMap tm_x, tm_wqkv, tm_wo, tm_wg, tm_wu, tm_wd;
    static const void* cached[6] = {nullptr, nullptr, nullptr, nullptr, nullptr, nullptr};
    if (cached[0] != x || cached[1] != wqkv || cached[2] != wo || cached[3] != wgate || cached[4] != wup || cached[5] != wdown) {
        void* fp = nullptr;
        cudaDriverEntryPointQueryResult qr;
        cudaGetDriverEntryPoint("cuTensorMapEncodeTiled", &fp, cudaEnableDefault, &qr);
        EncodeFn fn = (EncodeFn)fp;
        { cuuint64_t d[2] = {512, 2048}, s[1] = {1024}; cuuint32_t b[2] = {64, 128};
          encode(fn, &tm_x, x, 2, d, s, b, CU_TENSOR_MAP_SWIZZLE_128B); }
        { cuuint64_t d[3] = {64, 512, 24}, s[2] = {3072, 128}; cuuint32_t b[3] = {64, 64, 3};
          encode(fn, &tm_wqkv, wqkv, 3, d, s, b, CU_TENSOR_MAP_SWIZZLE_128B); }
        { cuuint64_t d[2] = {512, 512}, s[1] = {1024}; cuuint32_t b[2] = {64, 64};
          encode(fn, &tm_wo, wo, 2, d, s, b, CU_TENSOR_MAP_SWIZZLE_128B); }
        { cuuint64_t d[2] = {1792, 512}, s[1] = {3584}; cuuint32_t b[2] = {32, 64};
          encode(fn, &tm_wg, wgate, 2, d, s, b, CU_TENSOR_MAP_SWIZZLE_64B);
          encode(fn, &tm_wu, wup, 2, d, s, b, CU_TENSOR_MAP_SWIZZLE_64B); }
        { cuuint64_t d[2] = {512, 1792}, s[1] = {1024}; cuuint32_t b[2] = {64, 64};
          encode(fn, &tm_wd, wdown, 2, d, s, b, CU_TENSOR_MAP_SWIZZLE_128B); }
        cudaFuncSetAttribute(qkv_kernel, cudaFuncAttributeMaxDynamicSharedMemorySize, K1_SMEM);
        cudaFuncSetAttribute(attn_kernel, cudaFuncAttributeMaxDynamicSharedMemorySize, AT_SMEM);
        cudaFuncSetAttribute(tail_kernel, cudaFuncAttributeMaxDynamicSharedMemorySize, F_SMEM);
        cached[0] = x; cached[1] = wqkv; cached[2] = wo; cached[3] = wgate; cached[4] = wup; cached[5] = wdown;
    }
    launch(qkv_kernel, 128, 384, K1_SMEM, false, tm_x, tm_wqkv, x, wqkv);
    launch(attn_kernel, 132, 512, AT_SMEM, true, wgate, wup, wo, wdown);
    launch(tail_kernel, 128, 384, F_SMEM, true, tm_wo, tm_wg, tm_wu, tm_wd, x, out);
}
```

```cpp
#include <cuda_runtime.h>
#include <cuda_bf16.h>
#include <cuda.h>
#include <stdint.h>

#define TAILMAP 1
namespace {

constexpr int S_LEN = 2048, DM = 512, NH = 32, FF = 1792;

__device__ __align__(1024) __nv_bfloat16 g_qkv[3 * NH * S_LEN * 16];
__device__ __align__(1024) __nv_bfloat16 g_ao[S_LEN * DM];
__device__ __align__(1024) __nv_bfloat16 g_h[S_LEN * DM];
__device__ __align__(1024) __nv_bfloat16 g_g[S_LEN * FF];
__device__ __align__(16) float2 g_rowstat1[S_LEN];
__device__ float g_cs1_part[16 * 1536];
__device__ unsigned int g_cnt[32];
__device__ unsigned int g_cnt2[64];
__device__ float g_nrm[3 * NH * 128];
__device__ float2 g_hstat[S_LEN * 8];
__device__ float g_cs2[2 * FF];

#define TL(slot)
#define TX(slot)
__device__ __forceinline__ uint32_t smem_u32(const void* p) { return (uint32_t)__cvta_generic_to_shared(p); }
__device__ __forceinline__ void mbar_init(uint32_t a, int c) { asm volatile("mbarrier.init.shared.b64 [%0], %1;" :: "r"(a), "r"(c)); }
__device__ __forceinline__ void mbar_expect(uint32_t a, int bytes) { asm volatile("mbarrier.arrive.expect_tx.shared.b64 _, [%0], %1;" :: "r"(a), "r"(bytes) : "memory"); }
__device__ __forceinline__ void mbar_arrive(uint32_t a) { asm volatile("mbarrier.arrive.shared.b64 _, [%0];" :: "r"(a) : "memory"); }
__device__ __forceinline__ void mbar_wait(uint32_t a, int parity) {
    uint32_t done;
    int it = 0;
    do {
        asm volatile("{\n.reg .pred p;\nmbarrier.try_wait.parity.shared.b64 p, [%1], %2;\nselp.u32 %0, 1, 0, p;\n}"
                     : "=r"(done) : "r"(a), "r"(parity) : "memory");
        if (++it > (1 << 24)) __trap();
    } while (!done);
}
__device__ __forceinline__ void bulk_g2s(uint32_t dst, const void* src, int bytes, uint32_t bar) {
    asm volatile("cp.async.bulk.shared::cluster.global.mbarrier::complete_tx::bytes [%0], [%1], %2, [%3];"
                 :: "r"(dst), "l"(src), "r"(bytes), "r"(bar) : "memory");
}
__device__ __forceinline__ void tma2d(uint32_t dst, const CUtensorMap* m, int c0, int c1, uint32_t bar) {
    asm volatile("cp.async.bulk.tensor.2d.shared::cluster.global.mbarrier::complete_tx::bytes [%0], [%1, {%3, %4}], [%2];"
                 :: "r"(dst), "l"(m), "r"(bar), "r"(c0), "r"(c1) : "memory");
}
__device__ __forceinline__ void tma3d(uint32_t dst, const CUtensorMap* m, int c0, int c1, int c2, uint32_t bar) {
    asm volatile("cp.async.bulk.tensor.3d.shared::cluster.global.mbarrier::complete_tx::bytes [%0], [%1, {%3, %4, %5}], [%2];"
                 :: "r"(dst), "l"(m), "r"(bar), "r"(c0), "r"(c1), "r"(c2) : "memory");
}
__device__ __forceinline__ void prefetch_tmap(const CUtensorMap* m) { asm volatile("prefetch.tensormap [%0];" :: "l"(m) : "memory"); }
__device__ __forceinline__ void pdl_wait() { asm volatile("griddepcontrol.wait;" ::: "memory"); }
__device__ __forceinline__ void pdl_launch() { asm volatile("griddepcontrol.launch_dependents;" ::: "memory"); }
__device__ __forceinline__ void fence_barrier_init() { asm volatile("fence.mbarrier_init.release.cluster;" ::: "memory"); }
__device__ __forceinline__ void fence_proxy_async() { asm volatile("fence.proxy.async.shared::cta;" ::: "memory"); }
__device__ __forceinline__ uint64_t make_desc(uint32_t saddr, uint32_t lbo, uint32_t sbo, uint32_t swz) {
    return (uint64_t)((saddr & 0x3FFFF) >> 4) | ((uint64_t)((lbo & 0x3FFFF) >> 4) << 16) |
           ((uint64_t)((sbo & 0x3FFFF) >> 4) << 32) | ((uint64_t)swz << 62);
}
#define WG_FENCE() asm volatile("wgmma.fence.sync.aligned;" ::: "memory")
#define WG_COMMIT() asm volatile("wgmma.commit_group.sync.aligned;" ::: "memory")
template <int N> __device__ __forceinline__ void wg_wait() { asm volatile("wgmma.wait_group.sync.aligned %0;" :: "n"(N) : "memory"); }
template <int N> __device__ __forceinline__ void fence_regs(float (&d)[N]) {
#pragma unroll
    for (int i = 0; i < N; i++) asm volatile("" : "+f"(d[i]) :: "memory");
}
__device__ __forceinline__ float ex2f(float x) { float y; asm("ex2.approx.ftz.f32 %0, %1;" : "=f"(y) : "f"(x)); return y; }
__device__ __forceinline__ float tanh_fast(float x) { float y; asm("tanh.approx.f32 %0, %1;" : "=f"(y) : "f"(x)); return y; }
__device__ __forceinline__ uint32_t pack_bf16(float lo, float hi) { uint32_t r; asm("cvt.rn.bf16x2.f32 %0, %1, %2;" : "=r"(r) : "f"(hi), "f"(lo)); return r; }
__device__ __forceinline__ float bf_lo(uint32_t u) { return __uint_as_float(u << 16); }
__device__ __forceinline__ float bf_hi(uint32_t u) { return __uint_as_float(u & 0xFFFF0000u); }
__device__ __forceinline__ uint32_t hfma2(uint32_t a, uint32_t b, uint32_t c) { uint32_t r; asm("fma.rn.f16x2 %0, %1, %2, %3;" : "=r"(r) : "r"(a), "r"(b), "r"(c)); return r; }
__device__ __forceinline__ uint32_t hmul2(uint32_t a, uint32_t b) { uint32_t r; asm("mul.rn.f16x2 %0, %1, %2;" : "=r"(r) : "r"(a), "r"(b)); return r; }
__device__ __forceinline__ unsigned int ld_acquire(const unsigned int* p) { unsigned int v; asm volatile("ld.acquire.gpu.u32 %0, [%1];" : "=r"(v) : "l"(p) : "memory"); return v; }
__device__ __forceinline__ void red_release(unsigned int* p) { asm volatile("red.release.gpu.global.add.u32 [%0], 1;" :: "l"(p) : "memory"); }
__device__ __forceinline__ void stsm4(uint32_t addr, uint32_t a, uint32_t b, uint32_t c, uint32_t d) {
    asm volatile("stmatrix.sync.aligned.m8n8.x4.shared.b16 [%0], {%1,%2,%3,%4};" :: "r"(addr), "r"(a), "r"(b), "r"(c), "r"(d) : "memory");
}
__device__ __forceinline__ void bulk_s2g(void* dst, uint32_t src, int bytes) {
    asm volatile("cp.async.bulk.global.shared::cta.bulk_group [%0], [%1], %2;" :: "l"(dst), "r"(src), "r"(bytes) : "memory");
}
__device__ __forceinline__ void bulk_commit() { asm volatile("cp.async.bulk.commit_group;" ::: "memory"); }
__device__ __forceinline__ void bulk_wait_all() { asm volatile("cp.async.bulk.wait_group 0;" ::: "memory"); }
__device__ __forceinline__ void bulk_wait_read() { asm volatile("cp.async.bulk.wait_group.read 0;" ::: "memory"); }
__device__ __forceinline__ void bar_sync(int id, int n) { asm volatile("bar.sync %0, %1;" :: "r"(id), "r"(n) : "memory"); }
__device__ __forceinline__ void bar_arrive(int id, int n) { asm volatile("bar.arrive %0, %1;" :: "r"(id), "r"(n) : "memory"); }
__device__ __forceinline__ float warp_sum(float v) {
#pragma unroll
    for (int o = 16; o; o >>= 1) v += __shfl_xor_sync(0xffffffffu, v, o);
    return v;
}
__device__ __forceinline__ float warp_max(float v) {
#pragma unroll
    for (int o = 16; o; o >>= 1) v = fmaxf(v, __shfl_xor_sync(0xffffffffu, v, o));
    return v;
}

__device__ __forceinline__ void wgmma_ss_n64(float (&d)[32], uint64_t adesc, uint64_t bdesc, int scale_d) {
    asm volatile("{\n.reg .pred p;\nsetp.ne.b32 p, %34, 0;\n"
      "wgmma.mma_async.sync.aligned.m64n64k16.f32.bf16.bf16 {%0,%1,%2,%3,%4,%5,%6,%7,%8,%9,%10,%11,%12,%13,%14,%15,%16,%17,%18,%19,%20,%21,%22,%23,%24,%25,%26,%27,%28,%29,%30,%31}, %32, %33, p, 1, 1, 0, 1;\n}"
      : "+f"(d[0]), "+f"(d[1]), "+f"(d[2]), "+f"(d[3]), "+f"(d[4]), "+f"(d[5]), "+f"(d[6]), "+f"(d[7]), "+f"(d[8]), "+f"(d[9]), "+f"(d[10]), "+f"(d[11]), "+f"(d[12]), "+f"(d[13]), "+f"(d[14]), "+f"(d[15]), "+f"(d[16]), "+f"(d[17]), "+f"(d[18]), "+f"(d[19]), "+f"(d[20]), "+f"(d[21]), "+f"(d[22]), "+f"(d[23]), "+f"(d[24]), "+f"(d[25]), "+f"(d[26]), "+f"(d[27]), "+f"(d[28]), "+f"(d[29]), "+f"(d[30]), "+f"(d[31])
      : "l"(adesc), "l"(bdesc), "r"(scale_d));
}
__device__ __forceinline__ void wgmma_ss_n96(float (&d)[48], uint64_t adesc, uint64_t bdesc, int scale_d) {
    asm volatile("{\n.reg .pred p;\nsetp.ne.b32 p, %50, 0;\n"
      "wgmma.mma_async.sync.aligned.m64n96k16.f32.bf16.bf16 {%0,%1,%2,%3,%4,%5,%6,%7,%8,%9,%10,%11,%12,%13,%14,%15,%16,%17,%18,%19,%20,%21,%22,%23,%24,%25,%26,%27,%28,%29,%30,%31,%32,%33,%34,%35,%36,%37,%38,%39,%40,%41,%42,%43,%44,%45,%46,%47}, %48, %49, p, 1, 1, 0, 1;\n}"
      : "+f"(d[0]), "+f"(d[1]), "+f"(d[2]), "+f"(d[3]), "+f"(d[4]), "+f"(d[5]), "+f"(d[6]), "+f"(d[7]), "+f"(d[8]), "+f"(d[9]), "+f"(d[10]), "+f"(d[11]), "+f"(d[12]), "+f"(d[13]), "+f"(d[14]), "+f"(d[15]), "+f"(d[16]), "+f"(d[17]), "+f"(d[18]), "+f"(d[19]), "+f"(d[20]), "+f"(d[21]), "+f"(d[22]), "+f"(d[23]), "+f"(d[24]), "+f"(d[25]), "+f"(d[26]), "+f"(d[27]), "+f"(d[28]), "+f"(d[29]), "+f"(d[30]), "+f"(d[31]), "+f"(d[32]), "+f"(d[33]), "+f"(d[34]), "+f"(d[35]), "+f"(d[36]), "+f"(d[37]), "+f"(d[38]), "+f"(d[39]), "+f"(d[40]), "+f"(d[41]), "+f"(d[42]), "+f"(d[43]), "+f"(d[44]), "+f"(d[45]), "+f"(d[46]), "+f"(d[47])
      : "l"(adesc), "l"(bdesc), "r"(scale_d));
}
__device__ __forceinline__ void wgmma_ss_n128(float (&d)[64], uint64_t adesc, uint64_t bdesc, int scale_d) {
    asm volatile("{\n.reg .pred p;\nsetp.ne.b32 p, %66, 0;\n"
      "wgmma.mma_async.sync.aligned.m64n128k16.f32.bf16.bf16 {%0,%1,%2,%3,%4,%5,%6,%7,%8,%9,%10,%11,%12,%13,%14,%15,%16,%17,%18,%19,%20,%21,%22,%23,%24,%25,%26,%27,%28,%29,%30,%31,%32,%33,%34,%35,%36,%37,%38,%39,%40,%41,%42,%43,%44,%45,%46,%47,%48,%49,%50,%51,%52,%53,%54,%55,%56,%57,%58,%59,%60,%61,%62,%63}, %64, %65, p, 1, 1, 0, 1;\n}"
      : "+f"(d[0]), "+f"(d[1]), "+f"(d[2]), "+f"(d[3]), "+f"(d[4]), "+f"(d[5]), "+f"(d[6]), "+f"(d[7]), "+f"(d[8]), "+f"(d[9]), "+f"(d[10]), "+f"(d[11]), "+f"(d[12]), "+f"(d[13]), "+f"(d[14]), "+f"(d[15]), "+f"(d[16]), "+f"(d[17]), "+f"(d[18]), "+f"(d[19]), "+f"(d[20]), "+f"(d[21]), "+f"(d[22]), "+f"(d[23]), "+f"(d[24]), "+f"(d[25]), "+f"(d[26]), "+f"(d[27]), "+f"(d[28]), "+f"(d[29]), "+f"(d[30]), "+f"(d[31]), "+f"(d[32]), "+f"(d[33]), "+f"(d[34]), "+f"(d[35]), "+f"(d[36]), "+f"(d[37]), "+f"(d[38]), "+f"(d[39]), "+f"(d[40]), "+f"(d[41]), "+f"(d[42]), "+f"(d[43]), "+f"(d[44]), "+f"(d[45]), "+f"(d[46]), "+f"(d[47]), "+f"(d[48]), "+f"(d[49]), "+f"(d[50]), "+f"(d[51]), "+f"(d[52]), "+f"(d[53]), "+f"(d[54]), "+f"(d[55]), "+f"(d[56]), "+f"(d[57]), "+f"(d[58]), "+f"(d[59]), "+f"(d[60]), "+f"(d[61]), "+f"(d[62]), "+f"(d[63])
      : "l"(adesc), "l"(bdesc), "r"(scale_d));
}
__device__ __forceinline__ void wgmma_ss_n192(float (&d)[96], uint64_t adesc, uint64_t bdesc, int scale_d) {
    asm volatile("{\n.reg .pred p;\nsetp.ne.b32 p, %98, 0;\n"
      "wgmma.mma_async.sync.aligned.m64n192k16.f32.bf16.bf16 {%0,%1,%2,%3,%4,%5,%6,%7,%8,%9,%10,%11,%12,%13,%14,%15,%16,%17,%18,%19,%20,%21,%22,%23,%24,%25,%26,%27,%28,%29,%30,%31,%32,%33,%34,%35,%36,%37,%38,%39,%40,%41,%42,%43,%44,%45,%46,%47,%48,%49,%50,%51,%52,%53,%54,%55,%56,%57,%58,%59,%60,%61,%62,%63,%64,%65,%66,%67,%68,%69,%70,%71,%72,%73,%74,%75,%76,%77,%78,%79,%80,%81,%82,%83,%84,%85,%86,%87,%88,%89,%90,%91,%92,%93,%94,%95}, %96, %97, p, 1, 1, 0, 1;\n}"
      : "+f"(d[0]), "+f"(d[1]), "+f"(d[2]), "+f"(d[3]), "+f"(d[4]), "+f"(d[5]), "+f"(d[6]), "+f"(d[7]), "+f"(d[8]), "+f"(d[9]), "+f"(d[10]), "+f"(d[11]), "+f"(d[12]), "+f"(d[13]), "+f"(d[14]), "+f"(d[15]), "+f"(d[16]), "+f"(d[17]), "+f"(d[18]), "+f"(d[19]), "+f"(d[20]), "+f"(d[21]), "+f"(d[22]), "+f"(d[23]), "+f"(d[24]), "+f"(d[25]), "+f"(d[26]), "+f"(d[27]), "+f"(d[28]), "+f"(d[29]), "+f"(d[30]), "+f"(d[31]), "+f"(d[32]), "+f"(d[33]), "+f"(d[34]), "+f"(d[35]), "+f"(d[36]), "+f"(d[37]), "+f"(d[38]), "+f"(d[39]), "+f"(d[40]), "+f"(d[41]), "+f"(d[42]), "+f"(d[43]), "+f"(d[44]), "+f"(d[45]), "+f"(d[46]), "+f"(d[47]), "+f"(d[48]), "+f"(d[49]), "+f"(d[50]), "+f"(d[51]), "+f"(d[52]), "+f"(d[53]), "+f"(d[54]), "+f"(d[55]), "+f"(d[56]), "+f"(d[57]), "+f"(d[58]), "+f"(d[59]), "+f"(d[60]), "+f"(d[61]), "+f"(d[62]), "+f"(d[63]), "+f"(d[64]), "+f"(d[65]), "+f"(d[66]), "+f"(d[67]), "+f"(d[68]), "+f"(d[69]), "+f"(d[70]), "+f"(d[71]), "+f"(d[72]), "+f"(d[73]), "+f"(d[74]), "+f"(d[75]), "+f"(d[76]), "+f"(d[77]), "+f"(d[78]), "+f"(d[79]), "+f"(d[80]), "+f"(d[81]), "+f"(d[82]), "+f"(d[83]), "+f"(d[84]), "+f"(d[85]), "+f"(d[86]), "+f"(d[87]), "+f"(d[88]), "+f"(d[89]), "+f"(d[90]), "+f"(d[91]), "+f"(d[92]), "+f"(d[93]), "+f"(d[94]), "+f"(d[95])
      : "l"(adesc), "l"(bdesc), "r"(scale_d));
}
__device__ __forceinline__ void qk_wgmma_n64(float (&d)[32], const uint32_t (&a)[4], uint64_t desc) {
    asm volatile("wgmma.mma_async.sync.aligned.m64n64k16.f32.bf16.bf16 {%0,%1,%2,%3,%4,%5,%6,%7,%8,%9,%10,%11,%12,%13,%14,%15,%16,%17,%18,%19,%20,%21,%22,%23,%24,%25,%26,%27,%28,%29,%30,%31}, {%32,%33,%34,%35}, %36, 0, 1, 1, 0;"
      : "=f"(d[0]), "=f"(d[1]), "=f"(d[2]), "=f"(d[3]), "=f"(d[4]), "=f"(d[5]), "=f"(d[6]), "=f"(d[7]), "=f"(d[8]), "=f"(d[9]), "=f"(d[10]), "=f"(d[11]), "=f"(d[12]), "=f"(d[13]), "=f"(d[14]), "=f"(d[15]), "=f"(d[16]), "=f"(d[17]), "=f"(d[18]), "=f"(d[19]), "=f"(d[20]), "=f"(d[21]), "=f"(d[22]), "=f"(d[23]), "=f"(d[24]), "=f"(d[25]), "=f"(d[26]), "=f"(d[27]), "=f"(d[28]), "=f"(d[29]), "=f"(d[30]), "=f"(d[31])
      : "r"(a[0]), "r"(a[1]), "r"(a[2]), "r"(a[3]), "l"(desc));
}

__device__ __forceinline__ void pv_wgmma(float (&d)[12], uint32_t a0, uint32_t a1, uint32_t a2, uint32_t a3, uint64_t desc) {
    asm volatile("wgmma.mma_async.sync.aligned.m64n24k16.f32.bf16.bf16 {%0,%1,%2,%3,%4,%5,%6,%7,%8,%9,%10,%11}, {%12,%13,%14,%15}, %16, 1, 1, 1, 1;"
      : "+f"(d[0]), "+f"(d[1]), "+f"(d[2]), "+f"(d[3]), "+f"(d[4]), "+f"(d[5]), "+f"(d[6]), "+f"(d[7]), "+f"(d[8]), "+f"(d[9]), "+f"(d[10]), "+f"(d[11])
      : "r"(a0), "r"(a1), "r"(a2), "r"(a3), "l"(desc));
}

__device__ __forceinline__ void tile_of(int bid, int& mb, int& nt) {
    int grp = bid >> 4, in = bid & 15;
    mb = (grp >> 1) * 4 + (in >> 2);
    nt = (grp & 1) * 4 + (in & 3);
}

constexpr int K1_STAGES = 5, K1_STAGE = 16384 + 24576;
constexpr int K1_BAR = K1_STAGES * K1_STAGE, K1_RS = K1_BAR + 128, K1_CS = K1_RS + 1024, K1_SMEM = K1_CS + 768;

__device__ __forceinline__ float2 row_stats_regs(uint4 a, uint4 b) {
    float v[16];
    v[0] = bf_lo(a.x); v[1] = bf_hi(a.x); v[2] = bf_lo(a.y); v[3] = bf_hi(a.y);
    v[4] = bf_lo(a.z); v[5] = bf_hi(a.z); v[6] = bf_lo(a.w); v[7] = bf_hi(a.w);
    v[8] = bf_lo(b.x); v[9] = bf_hi(b.x); v[10] = bf_lo(b.y); v[11] = bf_hi(b.y);
    v[12] = bf_lo(b.z); v[13] = bf_hi(b.z); v[14] = bf_lo(b.w); v[15] = bf_hi(b.w);
    float s = 0.f;
#pragma unroll
    for (int i = 0; i < 16; i++) s += v[i];
    float mean = warp_sum(s) * (1.0f / DM);
    float q = 0.f;
#pragma unroll
    for (int i = 0; i < 16; i++) { float d = v[i] - mean; q = fmaf(d, d, q); }
    float var = warp_sum(q) * (1.0f / DM);
    float rstd = rsqrtf(var + 1e-5f);
    return make_float2(rstd, -mean * rstd);
}
__device__ __forceinline__ float2 row_stats_x(const __nv_bfloat16* x, int row, int lane) {
    const uint4* p = (const uint4*)(x + (size_t)row * DM);
    return row_stats_regs(__ldg(p + lane), __ldg(p + 32 + lane));
}
__device__ __forceinline__ void colsum8(const __nv_bfloat16* w, int ld, int col, int k0, int nk, float (&s)[8]) {
#pragma unroll
    for (int i = 0; i < 8; i++) s[i] = 0.f;
    for (int k = k0; k < k0 + nk; k += 8) {
        uint4 u[8];
#pragma unroll
        for (int i = 0; i < 8; i++) u[i] = __ldg((const uint4*)(w + (size_t)(k + i) * ld + col));
#pragma unroll
        for (int i = 0; i < 8; i++) {
            s[0] += bf_lo(u[i].x); s[1] += bf_hi(u[i].x); s[2] += bf_lo(u[i].y); s[3] += bf_hi(u[i].y);
            s[4] += bf_lo(u[i].z); s[5] += bf_hi(u[i].z); s[6] += bf_lo(u[i].w); s[7] += bf_hi(u[i].w);
        }
    }
}
__device__ __forceinline__ bool wait_count(const unsigned int* p, unsigned int target, int lane) {
    int ok = 1;
    if (lane == 0) {
        int it = 0;
        while (ld_acquire(p) < target) { if (++it > (1 << 18)) { ok = 0; break; } }
    }
    ok = __shfl_sync(0xffffffffu, ok, 0);
    return ok != 0;
}

__global__ void __launch_bounds__(384, 1)
qkv_kernel(const __grid_constant__ CUtensorMap tm_x, const __grid_constant__ CUtensorMap tm_w,
           const __nv_bfloat16* __restrict__ x, const __nv_bfloat16* __restrict__ wqkv) {
    extern __shared__ __align__(1024) unsigned char smem[];
    const uint32_t sb = smem_u32(smem);
    const int tid = threadIdx.x, warp = __shfl_sync(0xffffffffu, tid >> 5, 0), lane = tid & 31;
    TL(0);
    int mb, nt;
    tile_of(blockIdx.x, mb, nt);
    const uint32_t full = sb + K1_BAR, empty = full + 40, auxb = full + 80;
    if (tid == 0) {
        prefetch_tmap(&tm_x); prefetch_tmap(&tm_w);
        for (int i = 0; i < K1_STAGES; i++) { mbar_init(full + 8 * i, 1); mbar_init(empty + 8 * i, 8); }
        mbar_init(auxb, 3);
        fence_barrier_init();
    }
    __syncthreads();
    pdl_launch();
    if (warp == 0) {
        if (blockIdx.x == 0) { g_cnt2[lane] = 0; g_cnt2[32 + lane] = 0; }
        if (lane == 0) {
            for (int kb = 0; kb < 8; kb++) {
                int s = kb % K1_STAGES;
                if (kb >= K1_STAGES) mbar_wait(empty + 8 * s, 0);
                mbar_expect(full + 8 * s, K1_STAGE);
                tma2d(sb + s * K1_STAGE, &tm_x, kb * 64, mb * 128, full + 8 * s);
                tma3d(sb + s * K1_STAGE + 16384, &tm_w, 0, kb * 64, nt * 3, full + 8 * s);
            }
        }
    } else if (warp < 4) {
        float2* s_rs = (float2*)(smem + K1_RS);
        float* s_cs = (float*)(smem + K1_CS);
        if (warp < 3) {
            const int r0 = mb * 128 + nt * 16 + (warp - 1) * 8;
            uint4 u[16];
#pragma unroll
            for (int i = 0; i < 8; i++) {
                const uint4* p = (const uint4*)(x + (size_t)(r0 + i) * DM);
                u[2 * i] = __ldg(p + lane); u[2 * i + 1] = __ldg(p + 32 + lane);
            }
            float2 mine = make_float2(0.f, 0.f);
#pragma unroll
            for (int i = 0; i < 8; i++) {
                float2 st = row_stats_regs(u[2 * i], u[2 * i + 1]);
                if (lane == i) mine = st;
            }
            if (lane < 8) g_rowstat1[r0 + lane] = mine;
            __syncwarp();
            if (lane == 0) red_release(&g_cnt[mb]);
        } else {
            uint4 u[24];
#pragma unroll
            for (int c = 0; c < 3; c++)
#pragma unroll
                for (int i = 0; i < 8; i++)
                    u[c * 8 + i] = __ldg((const uint4*)(wqkv + (size_t)(mb * 32 + (lane >> 3) * 8 + i) * 1536 + nt * 192 + (c * 8 + (lane & 7)) * 8));
#pragma unroll
            for (int c = 0; c < 3; c++) {
                float cs[8];
#pragma unroll
                for (int i = 0; i < 8; i++) cs[i] = 0.f;
#pragma unroll
                for (int i = 0; i < 8; i++) {
                    const uint4 w = u[c * 8 + i];
                    cs[0] += bf_lo(w.x); cs[1] += bf_hi(w.x); cs[2] += bf_lo(w.y); cs[3] += bf_hi(w.y);
                    cs[4] += bf_lo(w.z); cs[5] += bf_hi(w.z); cs[6] += bf_lo(w.w); cs[7] += bf_hi(w.w);
                }
#pragma unroll
                for (int i = 0; i < 8; i++) {
                    cs[i] += __shfl_xor_sync(0xffffffffu, cs[i], 8);
                    cs[i] += __shfl_xor_sync(0xffffffffu, cs[i], 16);
                }
                if (lane < 8) {
                    float4* d = (float4*)(g_cs1_part + mb * 1536 + nt * 192 + (c * 8 + lane) * 8);
                    d[0] = make_float4(cs[0], cs[1], cs[2], cs[3]);
                    d[1] = make_float4(cs[4], cs[5], cs[6], cs[7]);
                }
            }
            __syncwarp();
            if (lane == 0) red_release(&g_cnt[16 + nt]);
        }
        TX(8 + warp);
        if (warp == 1) {
            if (wait_count(&g_cnt[mb], 16, lane)) {
#pragma unroll
                for (int i = 0; i < 4; i++) s_rs[lane + 32 * i] = __ldcg(&g_rowstat1[mb * 128 + lane + 32 * i]);
            } else {
                for (int i = 0; i < 128; i++) {
                    float2 st = row_stats_x(x, mb * 128 + i, lane);
                    if (lane == 0) s_rs[i] = st;
                }
            }
        } else {
            int c0 = (warp - 2) * 96;
            if (wait_count(&g_cnt[16 + nt], 16, lane)) {
#pragma unroll
                for (int i = 0; i < 3; i++) {
                    float s = 0.f;
#pragma unroll
                    for (int p = 0; p < 16; p++) s += __ldcg(&g_cs1_part[p * 1536 + nt * 192 + c0 + lane + 32 * i]);
                    s_cs[c0 + lane + 32 * i] = s;
                }
            } else if (lane < 12) {
                float s[8];
                colsum8(wqkv, 1536, nt * 192 + c0 + lane * 8, 0, 512, s);
#pragma unroll
                for (int i = 0; i < 8; i++) s_cs[c0 + lane * 8 + i] = s[i];
            }
        }
        __syncwarp();
        TX(12 + warp);
        if (lane == 0) mbar_arrive(auxb);
        bar_sync(2, 256 + 96);
        const int a = tid - 32;
        if (a < 24) {
            const int col0 = nt * 192 + a * 8;
            const int which = col0 >> 9, head = (col0 & 511) >> 4;
            bulk_s2g(g_qkv + ((size_t)((which * NH + head) * 2 + (a & 1)) * 256 + mb * 16) * 64, sb + a * 2048, 2048);
            bulk_commit();
        }
        {
            const int hh = a >> 3, w = a & 7;
            const float4* p = (const float4*)(smem + 49152) + (hh * 256 + w * 32) / 2;
            float m = 0.f;
#pragma unroll
            for (int i = 0; i < 8; i++) {
                const int ii = (i + a) & 7;
                float4 u = p[2 * ii], v = p[2 * ii + 1];
                float n0 = u.x + u.z + v.x + v.z, n1 = u.y + u.w + v.y + v.w;
                if (!(n0 <= 3.0e38f) || !(n1 <= 3.0e38f)) m = __int_as_float(0x7f800000);
                m = fmaxf(m, fmaxf(n0, n1));
            }
            const int col0 = nt * 192 + hh * 16;
            g_nrm[((col0 >> 9) * NH + ((col0 & 511) >> 4)) * 128 + mb * 8 + w] = m;
        }
        if (a < 24) bulk_wait_all();
        TL(27);
    } else {
        const int wgi = (warp >> 2) - 1, ww = warp & 3;
        float acc[96];
#pragma unroll 1
        for (int kb = 0; kb < 8; kb++) {
            int s = kb % K1_STAGES;
            mbar_wait(full + 8 * s, (kb / K1_STAGES) & 1);
            if (warp == 4) TX(kb);
            uint64_t ad = make_desc(sb + s * K1_STAGE + wgi * 8192, 16, 1024, 1);
            uint64_t bd = make_desc(sb + s * K1_STAGE + 16384, 8192, 1024, 1);
            WG_FENCE();
#pragma unroll
            for (int k = 0; k < 4; k++) wgmma_ss_n192(acc, ad + k * 2, bd + k * 128, (kb | k) != 0);
            WG_COMMIT();
            if (kb > 0) {
                wg_wait<1>();
                if (lane == 0) mbar_arrive(empty + 8 * ((kb - 1) % K1_STAGES));
            }
        }
        wg_wait<0>();
        fence_regs(acc);
        TL(1);
        if (warp == 4) TX(16);
        mbar_wait(auxb, 0);
        if (warp == 4) TX(17);
        bar_sync(1, 256);
        const float2* s_rs = (const float2*)(smem + K1_RS);
        const float* s_cs = (const float*)(smem + K1_CS);
        const int g = lane >> 2, t = lane & 3;
        const int rl = wgi * 64 + ww * 16 + g;
        const float2 st0 = s_rs[rl], st1 = s_rs[rl + 8];
        const float QS = 0.25f * 1.4426950408889634f;
        const uint32_t stg = sb + ((lane >> 4) * 16 + wgi * 8 + ww * 2 + ((lane >> 3) & 1)) * 128 + (lane & 7) * 16;
        float2* s_np = (float2*)(smem + 49152) + (warp - 4) * 32 + lane;
#pragma unroll
        for (int hh = 0; hh < 12; hh++) {
            const int which = (nt * 192 + hh * 16) >> 9;
            const float sc = (which == 0) ? QS : 1.0f;
            const float a0 = st0.x * sc, b0 = st0.y * sc, a1 = st1.x * sc, b1 = st1.y * sc;
            const float2 c0 = *(const float2*)(s_cs + 16 * hh + 2 * t), c1 = *(const float2*)(s_cs + 16 * hh + 8 + 2 * t);
            const float* a = acc + 8 * hh;
            float v0 = fmaf(a0, a[0], b0 * c0.x), v1 = fmaf(a0, a[1], b0 * c0.y), v2 = fmaf(a1, a[2], b1 * c0.x), v3 = fmaf(a1, a[3], b1 * c0.y);
            float v4 = fmaf(a0, a[4], b0 * c1.x), v5 = fmaf(a0, a[5], b0 * c1.y), v6 = fmaf(a1, a[6], b1 * c1.x), v7 = fmaf(a1, a[7], b1 * c1.y);
            stsm4(stg + hh * 4096, pack_bf16(v0, v1), pack_bf16(v2, v3), pack_bf16(v4, v5), pack_bf16(v6, v7));
            s_np[hh * 256] = make_float2(fmaf(v0, v0, fmaf(v1, v1, fmaf(v4, v4, v5 * v5))), fmaf(v2, v2, fmaf(v3, v3, fmaf(v6, v6, v7 * v7))));
        }
        fence_proxy_async();
        bar_arrive(2, 256 + 96);
        TL(2);
        if (warp == 4) TX(18);
    }
}

constexpr int AT_K = 0, AT_V = 65536, AT_ONES = 131072, AT_BAR = 163840, AT_SMEM = AT_BAR + 128;
#define POLY_MASK 0xAD6A

__device__ __forceinline__ uint32_t exp2_pair_poly(float x0, float x1) {
    uint32_t t0 = __float_as_uint(x0 + 32895.0f);
    uint32_t t1 = __float_as_uint(x1 + 32895.0f);
    uint32_t gd = __byte_perm(t0, t1, 0x6420);
    uint32_t wm = __byte_perm(t0, t1, 0x5612);
    uint32_t v = hfma2(gd, 0x71477147u, 0x354f354fu);
    uint32_t z = hmul2(v, gd);
    return (wm >> 1) + z;
}
__device__ __forceinline__ uint32_t exp2_pair_mufu(float x0, float x1) { return pack_bf16(ex2f(x0), ex2f(x1)); }
template <uint32_t MASK>
__device__ __forceinline__ void exp_blocks(const float (&s)[32], uint32_t (&p)[16]) {
#pragma unroll
    for (int b = 0; b < 8; b++) {
        if ((MASK >> b) & 1) {
            p[2 * b] = exp2_pair_poly(s[4 * b], s[4 * b + 1]);
            p[2 * b + 1] = exp2_pair_poly(s[4 * b + 2], s[4 * b + 3]);
        } else {
            p[2 * b] = exp2_pair_mufu(s[4 * b], s[4 * b + 1]);
            p[2 * b + 1] = exp2_pair_mufu(s[4 * b + 2], s[4 * b + 3]);
        }
    }
}
#define PV4(P) _Pragma("unroll") for (int i = 0; i < 4; i++) { pv_wgmma(o, P[4 * i], P[4 * i + 1], P[4 * i + 2], P[4 * i + 3], vd); vd += 16; }

__device__ __forceinline__ void attn_store(float (&o)[12], int row0, int head, int lane) {
    float l0 = __shfl_sync(0xffffffffu, o[8], lane & 28);
    float l1 = __shfl_sync(0xffffffffu, o[10], lane & 28);
    float r0 = 1.0f / l0, r1 = 1.0f / l1;
    uint32_t* op = (uint32_t*)g_ao;
    int mb = row0 >> 7, rg = (row0 & 127) >> 3;
    int kb = head >> 2, kc = (head & 3) * 2;
    size_t base = (((size_t)(mb * 8 + kb) * 8 + kc) * 16 + rg) * 32 + lane;
    op[base] = pack_bf16(o[0] * r0, o[1] * r0);
    op[base + 32] = pack_bf16(o[2] * r1, o[3] * r1);
    op[base + 16 * 32] = pack_bf16(o[4] * r0, o[5] * r0);
    op[base + 16 * 32 + 32] = pack_bf16(o[6] * r1, o[7] * r1);
}

__device__ __forceinline__ void attn_load_q(uint32_t (&q)[4], const __nv_bfloat16* gq, int row0, int lane) {
    const uint32_t* qp = (const uint32_t*)gq;
    int j0 = row0 >> 3;
    q[0] = __ldcg(qp + (0 * 256 + j0) * 32 + lane);
    q[1] = __ldcg(qp + (0 * 256 + j0 + 1) * 32 + lane);
    q[2] = __ldcg(qp + (1 * 256 + j0) * 32 + lane);
    q[3] = __ldcg(qp + (1 * 256 + j0 + 1) * 32 + lane);
}

__device__ __forceinline__ void attn_tile_safe(const uint32_t (&q)[4], uint64_t kd, uint64_t vd, int row0, int head, int lane) {
    float o[12];
#pragma unroll
    for (int i = 0; i < 12; i++) o[i] = 0.f;
    float m0 = -INFINITY, m1 = -INFINITY;
    fence_regs(o);
#pragma unroll 1
    for (int j = 0; j < 32; j++) {
        float s[32];
        uint32_t p[16];
        WG_FENCE();
        qk_wgmma_n64(s, q, kd); kd += 64;
        WG_COMMIT();
        wg_wait<0>();
        fence_regs(s);
        fence_regs(o);
        float x0 = m0, x1 = m1;
#pragma unroll
        for (int b = 0; b < 8; b++) {
            x0 = fmaxf(x0, fmaxf(s[4 * b], s[4 * b + 1]));
            x1 = fmaxf(x1, fmaxf(s[4 * b + 2], s[4 * b + 3]));
        }
        x0 = fmaxf(x0, __shfl_xor_sync(0xffffffffu, x0, 1)); x0 = fmaxf(x0, __shfl_xor_sync(0xffffffffu, x0, 2));
        x1 = fmaxf(x1, __shfl_xor_sync(0xffffffffu, x1, 1)); x1 = fmaxf(x1, __shfl_xor_sync(0xffffffffu, x1, 2));
        float al0 = ex2f(m0 - x0), al1 = ex2f(m1 - x1);
        m0 = x0; m1 = x1;
#pragma unroll
        for (int i = 0; i < 3; i++) { o[4 * i] *= al0; o[4 * i + 1] *= al0; o[4 * i + 2] *= al1; o[4 * i + 3] *= al1; }
#pragma unroll
        for (int b = 0; b < 8; b++) {
            p[2 * b] = exp2_pair_mufu(s[4 * b] - m0, s[4 * b + 1] - m0);
            p[2 * b + 1] = exp2_pair_mufu(s[4 * b + 2] - m1, s[4 * b + 3] - m1);
        }
        fence_regs(o);
        WG_FENCE();
        PV4(p);
        WG_COMMIT();
        wg_wait<0>();
        fence_regs(o);
    }
    attn_store(o, row0, head, lane);
}

__global__ void __launch_bounds__(512, 1)
attn_kernel(const __nv_bfloat16* __restrict__ wg_, const __nv_bfloat16* __restrict__ wu_,
            const __nv_bfloat16* __restrict__ wo_, const __nv_bfloat16* __restrict__ wd_) {
    extern __shared__ __align__(1024) unsigned char smem[];
    const uint32_t sb = smem_u32(smem);
    const int tid = threadIdx.x, wg = tid >> 7, warp = (tid >> 5) & 3, lane = tid & 31;
    pdl_launch();
    if (blockIdx.x >= 128) {
        const int e = blockIdx.x - 128;
        const __nv_bfloat16* w = (e < 2) ? wg_ : wu_;
        float* red = (float*)smem;
        const int cgrp = tid & 127, kq = tid >> 7;
        if (cgrp < 112) {
            float s[8];
            colsum8(w, FF, (e & 1) * 896 + cgrp * 8, kq * 128, 128, s);
#pragma unroll
            for (int i = 0; i < 8; i++) red[kq * 896 + cgrp * 8 + i] = s[i];
        }
        __syncthreads();
        for (int c = tid; c < 896; c += 512)
            g_cs2[(e >> 1) * FF + (e & 1) * 896 + c] = red[c] + red[896 + c] + red[1792 + c] + red[2688 + c];
        if (tid < 32) {
            const char* p0 = (const char*)wo_ + e * (DM * DM * 2 / 4);
            for (int i = lane; i < 32; i += 32)
                asm volatile("cp.async.bulk.prefetch.L2.global [%0], %1;" :: "l"(p0 + i * 4096), "r"(4096) : "memory");
            const char* p1 = (const char*)wd_ + e * (FF * DM * 2 / 4);
            for (int i = lane; i < 112; i += 32)
                asm volatile("cp.async.bulk.prefetch.L2.global [%0], %1;" :: "l"(p1 + i * 4096), "r"(4096) : "memory");
        }
        return;
    }
    const int head = blockIdx.x >> 2, qq = blockIdx.x & 3;
    const __nv_bfloat16* gq = g_qkv + (size_t)head * (S_LEN * 16);
    const __nv_bfloat16* gk = g_qkv + (size_t)(NH + head) * (S_LEN * 16);
    const __nv_bfloat16* gv = g_qkv + (size_t)(2 * NH + head) * (S_LEN * 16);
    if (tid == 0) {
        for (int i = 0; i < 8; i++) mbar_init(sb + AT_BAR + 8 * i, 1);
        fence_barrier_init();
    }
    {
        uint4 one = make_uint4(0x00003F80u, 0, 0, 0);
#pragma unroll
        for (int i = 0; i < 4; i++) *(uint4*)(smem + AT_ONES + (i * 512 + tid) * 16) = one;
        fence_proxy_async();
    }
    __syncthreads();
    TL(3);
    pdl_wait();
    TL(4);
    if (warp == 0 && lane < 2) {
        const int i = wg * 2 + lane;
        uint32_t bar = sb + AT_BAR + 8 * i;
        mbar_expect(bar, 16384);
        bulk_g2s(sb + AT_K + i * 4096, gk + i * 2048, 4096, bar);
        bulk_g2s(sb + AT_K + 32768 + i * 4096, gk + 16384 + i * 2048, 4096, bar);
        bulk_g2s(sb + AT_V + i * 4096, gv + i * 2048, 4096, bar);
        bulk_g2s(sb + AT_V + 32768 + i * 4096, gv + 16384 + i * 2048, 4096, bar);
    }
    uint32_t q[4], q2[4];
    attn_load_q(q, gq, qq * 512 + wg * 64 + warp * 16, lane);
    attn_load_q(q2, gq, qq * 512 + (4 + wg) * 64 + warp * 16, lane);
    bool fast;
    {
        const float* nq = g_nrm + (0 * NH + head) * 128 + qq * 32;
        const float* nk = g_nrm + (1 * NH + head) * 128;
        const float* nv = g_nrm + (2 * NH + head) * 128;
        float4 k4 = __ldcg((const float4*)nk + lane), v4 = __ldcg((const float4*)nv + lane);
        float qm = warp_max(__ldcg(nq + lane));
        float km = warp_max(fmaxf(fmaxf(k4.x, k4.y), fmaxf(k4.z, k4.w)));
        float vm = warp_max(fmaxf(fmaxf(v4.x, v4.y), fmaxf(v4.z, v4.w)));
        fast = __all_sync(0xffffffffu, (qm * km <= 3500.0f) && (vm <= 1.0e24f));
    }
    TL(24);
    const uint64_t kdesc0 = make_desc(sb + AT_K, 32768, 128, 0);
    const uint64_t vdesc0 = make_desc(sb + AT_V, 128, 32768, 0);
    if (!fast) {
        for (int i = 0; i < 8; i++) mbar_wait(sb + AT_BAR + 8 * i, 0);
#pragma unroll 1
        for (int tile = 0; tile < 2; tile++) {
            const int row0 = qq * 512 + (tile * 4 + wg) * 64 + warp * 16;
            attn_tile_safe(q, kdesc0, vdesc0, row0, head, lane);
#pragma unroll
            for (int i = 0; i < 4; i++) q[i] = q2[i];
        }
        return;
    }
#pragma unroll 1
    for (int tile = 0; tile < 2; tile++) {
        const int row0 = qq * 512 + (tile * 4 + wg) * 64 + warp * 16;
        float o[12];
#pragma unroll
        for (int i = 0; i < 12; i++) o[i] = 0.f;
        fence_regs(o);
        float sa[32];
        uint32_t pa[16];
        uint64_t kd = kdesc0, vd = vdesc0;
        if (tile == 0) { mbar_wait(sb + AT_BAR, 0); TL(25); }
        WG_FENCE();
        qk_wgmma_n64(sa, q, kd); kd += 64;
        WG_COMMIT();
#pragma unroll 1
        for (int jj = 0; jj < 8; jj++) {
            if (tile == 0 && jj < 7) mbar_wait(sb + AT_BAR + 8 * (jj + 1), 0);
            if (wg == 0 && warp == 0) TX(128 + tile * 8 + jj);
#pragma unroll
            for (int j = 0; j < 4; j++) {
                wg_wait<0>();
                fence_regs(sa);
                if (j & 1) exp_blocks<(POLY_MASK >> 8)>(sa, pa); else exp_blocks<(POLY_MASK & 255)>(sa, pa);
                WG_FENCE();
                qk_wgmma_n64(sa, q, kd); kd += 64;
                PV4(pa);
                WG_COMMIT();
            }
        }
        wg_wait<0>();
        fence_regs(o);
        fence_regs(sa);
        if (tile == 0) TL(26);
        attn_store(o, row0, head, lane);
#pragma unroll
        for (int i = 0; i < 4; i++) q[i] = q2[i];
    }
    TL(5);
}

constexpr int F_R2 = 131072, F_X = 196608, F_BAR = 229376;
constexpr int F_RS = F_BAR + 256, F_CS = F_RS + 1024, F_SMEM = F_CS + 1792;
enum { B_FA = 0, B_HF = 2, B_BF = 6, B_BE = 9, B_CF = 12, B_CE = 18, B_ADONE = 24, B_BDONE = 25, B_XA = 26, B_XC = 27, B_PRDY = 28, B_AUX = 29 };

__device__ __forceinline__ uint32_t mapa(uint32_t a, uint32_t rank) { uint32_t r; asm("mapa.shared::cluster.u32 %0, %1, %2;" : "=r"(r) : "r"(a), "r"(rank)); return r; }
__device__ __forceinline__ void st_async4(uint32_t dst, float a, float b, float c, float d, uint32_t bar) {
    asm volatile("st.async.weak.shared::cluster.mbarrier::complete_tx::bytes.v4.f32 [%0], {%1,%2,%3,%4}, [%5];"
                 :: "r"(dst), "f"(a), "f"(b), "f"(c), "f"(d), "r"(bar) : "memory");
}
__device__ __forceinline__ void mbar_arrive_remote(uint32_t a) { asm volatile("mbarrier.arrive.release.cluster.shared::cluster.b64 _, [%0];" :: "r"(a) : "memory"); }
__device__ __forceinline__ void mbar_wait_cluster(uint32_t a, int parity) {
    uint32_t done;
    int it = 0;
    do {
        asm volatile("{\n.reg .pred p;\nmbarrier.try_wait.parity.acquire.cluster.shared::cta.b64 p, [%1], %2;\nselp.u32 %0, 1, 0, p;\n}"
                     : "=r"(done) : "r"(a), "r"(parity) : "memory");
        if (++it > (1 << 24)) __trap();
    } while (!done);
}
__device__ __forceinline__ void poll_count(const unsigned int* p, unsigned int target) {
    int it = 0;
    while (ld_acquire(p) < target) { if (++it > (1 << 22)) __trap(); }
    asm volatile("fence.proxy.async.global;" ::: "memory");
}
__device__ __forceinline__ void publish_arrive(int id) { asm volatile("bar.arrive %0, 288;" :: "r"(id) : "memory"); }
__device__ __forceinline__ void publish_sync(int id, unsigned int* p, int lane) {
    asm volatile("bar.sync %0, 288;" :: "r"(id) : "memory");
    if (lane == 0) red_release(p);
}
template <int R>
__device__ __forceinline__ void xchg(float (&acc)[64], float (&o)[32], uint32_t sb, unsigned char* smem, int bar, int ctid) {
    const uint32_t dst = mapa(sb + F_X + ctid * 16, 1 - R), rb = mapa(sb + F_BAR + 8 * bar, 1 - R);
#pragma unroll
    for (int q = 0; q < 8; q++) {
        const int j = (1 - R) * 32 + 4 * q;
        st_async4(dst + q * 4096, acc[j], acc[j + 1], acc[j + 2], acc[j + 3], rb);
    }
    mbar_wait_cluster(sb + F_BAR + 8 * bar, 0);
#pragma unroll
    for (int q = 0; q < 8; q++) {
        float4 v = *(const float4*)(smem + F_X + q * 4096 + ctid * 16);
        const int j = R * 32 + 4 * q;
        o[4 * q] = acc[j] + v.x; o[4 * q + 1] = acc[j + 1] + v.y; o[4 * q + 2] = acc[j + 2] + v.z; o[4 * q + 3] = acc[j + 3] + v.w;
    }
}

template <int NB>
__device__ __forceinline__ void ffn_epilogue(const float* ag, const float* au, const float* s_cs, int cs_off, int jb0,
                                             float2 st0, float2 st1, int mb, int rgl, int lane) {
    const int t = lane & 3;
    uint32_t* gp = (uint32_t*)g_g;
    const float C1 = 0.7978845608028654f, C2 = 0.044715f * 0.7978845608028654f;
    const float k10 = st0.x * C1, k20 = st0.x * st0.x * st0.x * C2, k11 = st1.x * C1, k21 = st1.x * st1.x * st1.x * C2;
#pragma unroll
    for (int j = 0; j < NB; j++) {
        const float2 cg = *(const float2*)(s_cs + cs_off + 8 * j + 2 * t);
        const float2 cu = *(const float2*)(s_cs + 224 + cs_off + 8 * j + 2 * t);
        float r[4];
#pragma unroll
        for (int e = 0; e < 4; e++) {
            const float nm = (e < 2) ? st0.y : st1.y, k1 = (e < 2) ? k10 : k11, k2 = (e < 2) ? k20 : k21;
            const float tg = fmaf(nm, (e & 1) ? cg.y : cg.x, ag[4 * j + e]);
            const float tu = fmaf(nm, (e & 1) ? cu.y : cu.x, au[4 * j + e]);
            const float th = tanh_fast(tg * fmaf(tg * tg, k2, k1));
            const float p = tg * tu;
            r[e] = fmaf(p, th, p);
        }
        const int jb = jb0 + j;
        size_t o = (((size_t)mb * 28 * 8 + jb) * 16 + rgl) * 32 + lane;
        gp[o] = pack_bf16(r[0], r[1]);
        gp[o + 32] = pack_bf16(r[2], r[3]);
    }
}

__global__ void __cluster_dims__(2, 1, 1) __launch_bounds__(384, 1)
tail_kernel(const __grid_constant__ CUtensorMap tm_o, const __grid_constant__ CUtensorMap tm_g,
            const __grid_constant__ CUtensorMap tm_u, const __grid_constant__ CUtensorMap tm_d,
            const __nv_bfloat16* __restrict__ x, __nv_bfloat16* __restrict__ out) {
    extern __shared__ __align__(1024) unsigned char smem[];
    const uint32_t sb = smem_u32(smem);
    const uint32_t bars = sb + F_BAR;
    const int tid = threadIdx.x, warp = tid >> 5, lane = tid & 31;
    TL(6);
    const int cl = blockIdx.x >> 1, r = blockIdx.x & 1;
    const int mb = ((cl & 7) >> 1) * 4 + (cl >> 4), ntA = (cl & 1) * 2 + ((cl >> 3) & 1);
    const int nt = ntA * 2 + r;
    if (tid == 0) {
        prefetch_tmap(&tm_o); prefetch_tmap(&tm_g); prefetch_tmap(&tm_u); prefetch_tmap(&tm_d);
        for (int i = 0; i < 30; i++) {
            int cnt = 1;
            if ((i >= B_BE && i < B_BE + 3) || (i >= B_CE && i < B_CE + 6) || i == B_ADONE || i == B_BDONE || i == B_PRDY) cnt = 8;
            if (i == B_AUX) cnt = 3;
            mbar_init(bars + 8 * i, cnt);
        }
        mbar_expect(bars + 8 * B_XA, 32768);
        mbar_expect(bars + 8 * B_XC, 32768);
        fence_barrier_init();
    }
    __syncthreads();
    asm volatile("barrier.cluster.arrive.release.aligned;" ::: "memory");
    if (warp < 4) {
        asm volatile("setmaxnreg.dec.sync.aligned.u32 56;");
        if (warp == 0) {
            if (lane == 0) {
                auto load_b = [&](int it) {
                    const int s = it % 3, pass = it >> 3, kb = it & 7;
                    const int ng = pass ? 3 : 4, c0 = nt * 224 + pass * 128;
                    const uint32_t bar = bars + 8 * (B_BF + s), dst = sb + F_R2 + s * 32768;
                    mbar_expect(bar, ng * 8192);
                    for (int i = 0; i < ng; i++) {
                        tma2d(dst + i * 4096, &tm_g, c0 + i * 32, kb * 64, bar);
                        tma2d(dst + 16384 + i * 4096, &tm_u, c0 + i * 32, kb * 64, bar);
                    }
                };
                for (int i = 0; i < 4; i++) {
                    const uint32_t bar = bars + 8 * (B_FA + (i >> 1));
                    if (!(i & 1)) mbar_expect(bar, 65536);
                    tma2d(sb + i * 32768 + 16384, &tm_o, ntA * 128, (4 * r + i) * 64, bar);
                    tma2d(sb + i * 32768 + 24576, &tm_o, ntA * 128 + 64, (4 * r + i) * 64, bar);
                }
                pdl_wait();
                TL(16);
                for (int i = 0; i < 4; i++)
                    bulk_g2s(sb + i * 32768, g_ao + (size_t)(mb * 8 + 4 * r + i) * 8192, 16384, bars + 8 * (B_FA + (i >> 1)));
                load_b(0); load_b(1);
                if (blockIdx.x == 0)
                    for (int i = 0; i < 32; i++) g_cnt[i] = 0;
                mbar_wait(bars + 8 * (B_BE + 2), 0);
                load_b(2);
                poll_count(&g_cnt2[mb], 8);
                TL(17);
                for (int kb = 0; kb < 8; kb++) {
                    const uint32_t bar = bars + 8 * (B_HF + (kb >> 1));
                    if (!(kb & 1)) mbar_expect(bar, 32768);
                    bulk_g2s(sb + kb * 16384, g_h + (size_t)(mb * 8 + kb) * 8192, 16384, bar);
                }
                for (int it = 3; it < 16; it++) {
                    const int s = it % 3, n = it / 3;
                    mbar_wait(bars + 8 * (B_BE + s), (s == 2 ? n : n - 1) & 1);
                    load_b(it);
                }
                mbar_wait(bars + 8 * B_BDONE, 0);
                for (int i = 0; i < 6; i++) {
                    const uint32_t bar = bars + 8 * (B_CF + i);
                    mbar_expect(bar, 32768);
                    tma2d(sb + i * 32768 + 16384, &tm_d, ntA * 128, (2 * i + r) * 64, bar);
                    tma2d(sb + i * 32768 + 24576, &tm_d, ntA * 128 + 64, (2 * i + r) * 64, bar);
                }
                poll_count(&g_cnt2[16 + mb], 8);
                TL(18);
                for (int kb = 0; kb < 14; kb++) {
                    const int s = kb % 6;
                    const uint32_t bar = bars + 8 * (B_CF + s);
                    if (kb >= 6) {
                        mbar_wait(bars + 8 * (B_CE + s), ((kb / 6) - 1) & 1);
                        mbar_expect(bar, 32768);
                        tma2d(sb + s * 32768 + 16384, &tm_d, ntA * 128, (2 * kb + r) * 64, bar);
                        tma2d(sb + s * 32768 + 24576, &tm_d, ntA * 128 + 64, (2 * kb + r) * 64, bar);
                    }
                    bulk_g2s(sb + s * 32768, g_g + (size_t)(mb * 28 + 2 * kb + r) * 8192, 16384, bar);
                }
            }
        } else {
            pdl_wait();
            float2* s_rs = (float2*)(smem + F_RS);
            float* s_cs = (float*)(smem + F_CS);
            for (int c = tid - 32; c < 448; c += 96)
                s_cs[c] = __ldcg(&g_cs2[(c >= 224 ? FF - 224 : 0) + nt * 224 + c]);
            if (warp == 1) { publish_sync(1, &g_cnt2[mb], lane); TL(9); }
            if (lane == 0) poll_count(&g_cnt2[mb], 8);
            __syncwarp();
            for (int rr = tid - 32; rr < 128; rr += 96) {
                const float4* hp = (const float4*)(g_hstat + (size_t)(mb * 128 + rr) * 8);
                float4 a = __ldcg(hp), b = __ldcg(hp + 1), c = __ldcg(hp + 2), d = __ldcg(hp + 3);
                float mean = 0.125f * (a.x + a.z + b.x + b.z + c.x + c.z + d.x + d.z);
                float m2 = a.y + a.w + b.y + b.w + c.y + c.w + d.y + d.w;
                float e;
                e = a.x - mean; m2 = fmaf(64.f * e, e, m2); e = a.z - mean; m2 = fmaf(64.f * e, e, m2);
                e = b.x - mean; m2 = fmaf(64.f * e, e, m2); e = b.z - mean; m2 = fmaf(64.f * e, e, m2);
                e = c.x - mean; m2 = fmaf(64.f * e, e, m2); e = c.z - mean; m2 = fmaf(64.f * e, e, m2);
                e = d.x - mean; m2 = fmaf(64.f * e, e, m2); e = d.z - mean; m2 = fmaf(64.f * e, e, m2);
                s_rs[rr] = make_float2(rsqrtf(m2 * (1.0f / DM) + 1e-5f), -mean);
            }
            __syncwarp();
            if (lane == 0) mbar_arrive(bars + 8 * B_AUX);
            if (warp == 1) { publish_sync(2, &g_cnt2[16 + mb], lane); TL(13); }
        }
        __syncwarp();
        asm volatile("barrier.cluster.wait.acquire.aligned;" ::: "memory");
    } else {
        asm volatile("setmaxnreg.inc.sync.aligned.u32 216;");
        const int wgi = (warp >> 2) - 1, ww = warp & 3, ctid = tid - 128;
        const int g = lane >> 2, t = lane & 3;
        const int rl = wgi * 64 + ww * 16 + g, row = mb * 128 + rl;
        const int rgl = wgi * 8 + ww * 2;
        const float2* s_rs = (const float2*)(smem + F_RS);
        const float* s_cs = (const float*)(smem + F_CS);
        uint32_t* hp = (uint32_t*)g_h + ((size_t)(mb * 8 + nt) * 8 * 16 + rgl) * 32 + lane;
        TL(23);
        {
            uint32_t xr[16];
            const uint32_t* xp = (const uint32_t*)(x + (size_t)row * DM + nt * 64) + t;
#pragma unroll
            for (int j = 0; j < 8; j++) { xr[2 * j] = __ldg(xp + 4 * j); xr[2 * j + 1] = __ldg(xp + 8 * (DM / 2) + 4 * j); }
            float acc[64];
#pragma unroll 1
            for (int i = 0; i < 4; i++) {
                if (!(i & 1)) { mbar_wait(bars + 8 * (B_FA + (i >> 1)), 0); TL(19 + (i >> 1)); }
                uint64_t ad = make_desc(sb + i * 32768 + wgi * 1024, 2048, 128, 0);
                uint64_t bd = make_desc(sb + i * 32768 + 16384, 8192, 1024, 1);
                WG_FENCE();
#pragma unroll
                for (int k = 0; k < 4; k++) wgmma_ss_n128(acc, ad + k * 256, bd + k * 128, (i | k) != 0);
                WG_COMMIT();
            }
            wg_wait<0>();
            fence_regs(acc);
            TL(7);
            asm volatile("barrier.cluster.wait.acquire.aligned;" ::: "memory");
            float o[32];
            if (r == 0) xchg<0>(acc, o, sb, smem, B_XA, ctid); else xchg<1>(acc, o, sb, smem, B_XA, ctid);
            TL(21);
            fence_proxy_async();
            __syncwarp();
            if (lane == 0) mbar_arrive(bars + 8 * (B_BE + 2));
            float v0[16], v1[16];
            float s0 = 0.f, s1 = 0.f;
#pragma unroll
            for (int j = 0; j < 8; j++) {
                uint32_t u0 = pack_bf16(bf_lo(xr[2 * j]) + o[4 * j], bf_hi(xr[2 * j]) + o[4 * j + 1]);
                uint32_t u1 = pack_bf16(bf_lo(xr[2 * j + 1]) + o[4 * j + 2], bf_hi(xr[2 * j + 1]) + o[4 * j + 3]);
                hp[j * 16 * 32] = u0;
                hp[j * 16 * 32 + 32] = u1;
                v0[2 * j] = bf_lo(u0); v0[2 * j + 1] = bf_hi(u0);
                v1[2 * j] = bf_lo(u1); v1[2 * j + 1] = bf_hi(u1);
                s0 += v0[2 * j] + v0[2 * j + 1];
                s1 += v1[2 * j] + v1[2 * j + 1];
            }
            float m0 = s0 * (1.0f / 16), m1 = s1 * (1.0f / 16), q0 = 0.f, q1 = 0.f;
#pragma unroll
            for (int i = 0; i < 16; i++) {
                float d0 = v0[i] - m0, d1 = v1[i] - m1;
                q0 = fmaf(d0, d0, q0); q1 = fmaf(d1, d1, q1);
            }
#pragma unroll
            for (int st = 0; st < 2; st++) {
                float hn = st ? 16.f : 8.f;
                float om0 = __shfl_xor_sync(0xffffffffu, m0, 1 << st), oq0 = __shfl_xor_sync(0xffffffffu, q0, 1 << st);
                float om1 = __shfl_xor_sync(0xffffffffu, m1, 1 << st), oq1 = __shfl_xor_sync(0xffffffffu, q1, 1 << st);
                float d0 = om0 - m0, d1 = om1 - m1;
                q0 = q0 + oq0 + d0 * d0 * hn; q1 = q1 + oq1 + d1 * d1 * hn;
                m0 = 0.5f * (m0 + om0); m1 = 0.5f * (m1 + om1);
            }
            if (t == 0) {
                g_hstat[row * 8 + nt] = make_float2(m0, q0);
                g_hstat[(row + 8) * 8 + nt] = make_float2(m1, q1);
            }
            publish_arrive(1);
            TL(8);
        }
        {
            float ag[64], au[64];
#pragma unroll 1
            for (int kb = 0; kb < 8; kb++) {
                const int s = kb % 3;
                if (!(kb & 1)) mbar_wait(bars + 8 * (B_HF + (kb >> 1)), 0);
                mbar_wait(bars + 8 * (B_BF + s), (kb / 3) & 1);
                if (warp == 4) TX(32 + kb);
                uint64_t ad = make_desc(sb + kb * 16384 + wgi * 1024, 2048, 128, 0);
                uint64_t bd = make_desc(sb + F_R2 + s * 32768, 4096, 512, 2);
                WG_FENCE();
#pragma unroll
                for (int k = 0; k < 4; k++) {
                    wgmma_ss_n128(ag, ad + k * 256, bd + k * 64, (kb | k) != 0);
                    wgmma_ss_n128(au, ad + k * 256, bd + 1024 + k * 64, (kb | k) != 0);
                }
                WG_COMMIT();
                if (kb > 0) {
                    wg_wait<1>();
                    if (lane == 0) mbar_arrive(bars + 8 * (B_BE + (kb - 1) % 3));
                }
            }
            wg_wait<0>();
            if (lane == 0) mbar_arrive(bars + 8 * (B_BE + 7 % 3));
            fence_regs(ag); fence_regs(au);
            TL(10);
            mbar_wait(bars + 8 * B_AUX, 0);
            ffn_epilogue<16>(ag, au, s_cs, 0, nt * 28, s_rs[rl], s_rs[rl + 8], mb, rgl, lane);
        }
        {
            float ag[48], au[48];
#pragma unroll 1
            for (int kb = 0; kb < 8; kb++) {
                const int it = 8 + kb, s = it % 3;
                mbar_wait(bars + 8 * (B_BF + s), (it / 3) & 1);
                if (warp == 4) TX(32 + it);
                uint64_t ad = make_desc(sb + kb * 16384 + wgi * 1024, 2048, 128, 0);
                uint64_t bd = make_desc(sb + F_R2 + s * 32768, 4096, 512, 2);
                WG_FENCE();
#pragma unroll
                for (int k = 0; k < 4; k++) {
                    wgmma_ss_n96(ag, ad + k * 256, bd + k * 64, (kb | k) != 0);
                    wgmma_ss_n96(au, ad + k * 256, bd + 1024 + k * 64, (kb | k) != 0);
                }
                WG_COMMIT();
                if (kb > 0) {
                    wg_wait<1>();
                    if (lane == 0) mbar_arrive(bars + 8 * (B_BE + (it - 1) % 3));
                }
            }
            wg_wait<0>();
            if (lane == 0) {
                mbar_arrive(bars + 8 * B_BDONE);
                mbar_arrive_remote(mapa(bars + 8 * B_PRDY, 1 - r));
            }
            fence_regs(ag); fence_regs(au);
            TL(11);
            ffn_epilogue<12>(ag, au, s_cs, 128, nt * 28 + 16, s_rs[rl], s_rs[rl + 8], mb, rgl, lane);
            publish_arrive(2);
            TL(12);
        }
        {
            uint32_t hr[16];
#pragma unroll
            for (int j = 0; j < 8; j++) { hr[2 * j] = __ldcg(hp + j * 16 * 32); hr[2 * j + 1] = __ldcg(hp + j * 16 * 32 + 32); }
            float acc[64];
#pragma unroll 1
            for (int kb = 0; kb < 14; kb++) {
                const int s = kb % 6;
                mbar_wait(bars + 8 * (B_CF + s), (kb / 6) & 1);
                if (warp == 4) TX(96 + kb);
                uint64_t ad = make_desc(sb + s * 32768 + wgi * 1024, 2048, 128, 0);
                uint64_t bd = make_desc(sb + s * 32768 + 16384, 8192, 1024, 1);
                WG_FENCE();
#pragma unroll
                for (int k = 0; k < 4; k++) wgmma_ss_n128(acc, ad + k * 256, bd + k * 128, (kb | k) != 0);
                WG_COMMIT();
                if (kb > 0) {
                    wg_wait<1>();
                    if (lane == 0) mbar_arrive(bars + 8 * (B_CE + (kb - 1) % 6));
                }
            }
            wg_wait<0>();
            fence_regs(acc);
            TL(14);
            mbar_wait_cluster(bars + 8 * B_PRDY, 0);
            float o[32];
            if (r == 0) xchg<0>(acc, o, sb, smem, B_XC, ctid); else xchg<1>(acc, o, sb, smem, B_XC, ctid);
            TL(22);
            const float a0 = s_rs[rl].x, a1 = s_rs[rl + 8].x;
            const float k0 = 0.5f * a0 * a0, k1 = 0.5f * a1 * a1;
            uint32_t* op = (uint32_t*)(out + (size_t)row * DM + nt * 64) + t;
#pragma unroll
            for (int j = 0; j < 8; j++) {
                op[4 * j] = pack_bf16(fmaf(k0, o[4 * j], bf_lo(hr[2 * j])), fmaf(k0, o[4 * j + 1], bf_hi(hr[2 * j])));
                op[8 * (DM / 2) + 4 * j] = pack_bf16(fmaf(k1, o[4 * j + 2], bf_lo(hr[2 * j + 1])), fmaf(k1, o[4 * j + 3], bf_hi(hr[2 * j + 1])));
            }
            TL(15);
        }
    }
}

typedef CUresult (*EncodeFn)(CUtensorMap*, CUtensorMapDataType, cuuint32_t, void*, const cuuint64_t*, const cuuint64_t*,
                             const cuuint32_t*, const cuuint32_t*, CUtensorMapInterleave, CUtensorMapSwizzle,
                             CUtensorMapL2promotion, CUtensorMapFloatOOBfill);

void encode(EncodeFn fn, CUtensorMap* m, const void* ptr, int rank, const cuuint64_t* dims, const cuuint64_t* strides,
            const cuuint32_t* box, CUtensorMapSwizzle swz) {
    cuuint32_t es[3] = {1, 1, 1};
    fn(m, CU_TENSOR_MAP_DATA_TYPE_BFLOAT16, rank, (void*)ptr, dims, strides, box, es, CU_TENSOR_MAP_INTERLEAVE_NONE, swz,
       CU_TENSOR_MAP_L2_PROMOTION_L2_256B, CU_TENSOR_MAP_FLOAT_OOB_FILL_NONE);
}

template <typename... KArgs, typename... Args>
void launch(void (*kern)(KArgs...), int grid, int block, int smem, bool pdl, Args... args) {
    cudaLaunchConfig_t cfg = {};
    cfg.gridDim = dim3(grid); cfg.blockDim = dim3(block); cfg.dynamicSmemBytes = smem;
    cfg.stream = cudaStreamPerThread;
    cudaLaunchAttribute at[1];
    at[0].id = cudaLaunchAttributeProgrammaticStreamSerialization;
    at[0].val.programmaticStreamSerializationAllowed = 1;
    cfg.attrs = at; cfg.numAttrs = pdl ? 1 : 0;
    cudaLaunchKernelEx(&cfg, kern, KArgs(args)...);
}

}

extern "C" void kernel_launch(void* const* d_in, const int* in_sizes, int n_in, void* d_out, int out_size) {
    const __nv_bfloat16* x = (const __nv_bfloat16*)d_in[0];
    const __nv_bfloat16* wqkv = (const __nv_bfloat16*)d_in[1];
    const __nv_bfloat16* wo = (const __nv_bfloat16*)d_in[2];
    const __nv_bfloat16* wgate = (const __nv_bfloat16*)d_in[4];
    const __nv_bfloat16* wup = (const __nv_bfloat16*)d_in[5];
    const __nv_bfloat16* wdown = (const __nv_bfloat16*)d_in[6];
    __nv_bfloat16* out = (__nv_bfloat16*)d_out;

    static CUtensorMap tm_x, tm_wqkv, tm_wo, tm_wg, tm_wu, tm_wd;
    static const void* cached[6] = {nullptr, nullptr, nullptr, nullptr, nullptr, nullptr};
    if (cached[0] != x || cached[1] != wqkv || cached[2] != wo || cached[3] != wgate || cached[4] != wup || cached[5] != wdown) {
        void* fp = nullptr;
        cudaDriverEntryPointQueryResult qr;
        cudaGetDriverEntryPoint("cuTensorMapEncodeTiled", &fp, cudaEnableDefault, &qr);
        EncodeFn fn = (EncodeFn)fp;
        { cuuint64_t d[2] = {512, 2048}, s[1] = {1024}; cuuint32_t b[2] = {64, 128};
          encode(fn, &tm_x, x, 2, d, s, b, CU_TENSOR_MAP_SWIZZLE_128B); }
        { cuuint64_t d[3] = {64, 512, 24}, s[2] = {3072, 128}; cuuint32_t b[3] = {64, 64, 3};
          encode(fn, &tm_wqkv, wqkv, 3, d, s, b, CU_TENSOR_MAP_SWIZZLE_128B); }
        { cuuint64_t d[2] = {512, 512}, s[1] = {1024}; cuuint32_t b[2] = {64, 64};
          encode(fn, &tm_wo, wo, 2, d, s, b, CU_TENSOR_MAP_SWIZZLE_128B); }
        { cuuint64_t d[2] = {1792, 512}, s[1] = {3584}; cuuint32_t b[2] = {32, 64};
          encode(fn, &tm_wg, wgate, 2, d, s, b, CU_TENSOR_MAP_SWIZZLE_64B);
          encode(fn, &tm_wu, wup, 2, d, s, b, CU_TENSOR_MAP_SWIZZLE_64B); }
        { cuuint64_t d[2] = {512, 1792}, s[1] = {1024}; cuuint32_t b[2] = {64, 64};
          encode(fn, &tm_wd, wdown, 2, d, s, b, CU_TENSOR_MAP_SWIZZLE_128B); }
        cudaFuncSetAttribute(qkv_kernel, cudaFuncAttributeMaxDynamicSharedMemorySize, K1_SMEM);
        cudaFuncSetAttribute(attn_kernel, cudaFuncAttributeMaxDynamicSharedMemorySize, AT_SMEM);
        cudaFuncSetAttribute(tail_kernel, cudaFuncAttributeMaxDynamicSharedMemorySize, F_SMEM);
        cached[0] = x; cached[1] = wqkv; cached[2] = wo; cached[3] = wgate; cached[4] = wup; cached[5] = wdown;
    }
    launch(qkv_kernel, 128, 384, K1_SMEM, false, tm_x, tm_wqkv, x, wqkv);
    launch(attn_kernel, 132, 512, AT_SMEM, true, wgate, wup, wo, wdown);
    launch(tail_kernel, 128, 384, F_SMEM, true, tm_wo, tm_wg, tm_wu, tm_wd, x, out);
}
```

```cpp
#include <cuda_runtime.h>
#include <cuda_bf16.h>
#include <cuda.h>
#include <stdint.h>

#define TAILMAP 1
namespace {

constexpr int S_LEN = 2048, DM = 512, NH = 32, FF = 1792;

__device__ __align__(1024) __nv_bfloat16 g_qkv[3 * NH * S_LEN * 16];
__device__ __align__(1024) __nv_bfloat16 g_ao[S_LEN * DM];
__device__ __align__(1024) __nv_bfloat16 g_h[S_LEN * DM];
__device__ __align__(1024) __nv_bfloat16 g_g[S_LEN * FF];
__device__ __align__(16) float2 g_rowstat1[S_LEN];
__device__ float g_cs1_part[16 * 1536];
__device__ unsigned int g_cnt[32];
__device__ unsigned int g_cnt2[64];
__device__ float g_nrm[3 * NH * 128];
__device__ float2 g_hstat[S_LEN * 8];
__device__ float g_cs2[2 * FF];

#define TL(slot)
#define TX(slot)
__device__ __forceinline__ uint32_t smem_u32(const void* p) { return (uint32_t)__cvta_generic_to_shared(p); }
__device__ __forceinline__ void mbar_init(uint32_t a, int c) { asm volatile("mbarrier.init.shared.b64 [%0], %1;" :: "r"(a), "r"(c)); }
__device__ __forceinline__ void mbar_expect(uint32_t a, int bytes) { asm volatile("mbarrier.arrive.expect_tx.shared.b64 _, [%0], %1;" :: "r"(a), "r"(bytes) : "memory"); }
__device__ __forceinline__ void mbar_arrive(uint32_t a) { asm volatile("mbarrier.arrive.shared.b64 _, [%0];" :: "r"(a) : "memory"); }
__device__ __forceinline__ void mbar_wait(uint32_t a, int parity) {
    uint32_t done;
    int it = 0;
    do {
        asm volatile("{\n.reg .pred p;\nmbarrier.try_wait.parity.shared.b64 p, [%1], %2;\nselp.u32 %0, 1, 0, p;\n}"
                     : "=r"(done) : "r"(a), "r"(parity) : "memory");
        if (++it > (1 << 24)) __trap();
    } while (!done);
}
__device__ __forceinline__ void bulk_g2s(uint32_t dst, const void* src, int bytes, uint32_t bar) {
    asm volatile("cp.async.bulk.shared::cluster.global.mbarrier::complete_tx::bytes [%0], [%1], %2, [%3];"
                 :: "r"(dst), "l"(src), "r"(bytes), "r"(bar) : "memory");
}
__device__ __forceinline__ void tma2d(uint32_t dst, const CUtensorMap* m, int c0, int c1, uint32_t bar) {
    asm volatile("cp.async.bulk.tensor.2d.shared::cluster.global.mbarrier::complete_tx::bytes [%0], [%1, {%3, %4}], [%2];"
                 :: "r"(dst), "l"(m), "r"(bar), "r"(c0), "r"(c1) : "memory");
}
__device__ __forceinline__ void tma3d(uint32_t dst, const CUtensorMap* m, int c0, int c1, int c2, uint32_t bar) {
    asm volatile("cp.async.bulk.tensor.3d.shared::cluster.global.mbarrier::complete_tx::bytes [%0], [%1, {%3, %4, %5}], [%2];"
                 :: "r"(dst), "l"(m), "r"(bar), "r"(c0), "r"(c1), "r"(c2) : "memory");
}
__device__ __forceinline__ void prefetch_tmap(const CUtensorMap* m) { asm volatile("prefetch.tensormap [%0];" :: "l"(m) : "memory"); }
__device__ __forceinline__ void pdl_wait() { asm volatile("griddepcontrol.wait;" ::: "memory"); }
__device__ __forceinline__ void pdl_launch() { asm volatile("griddepcontrol.launch_dependents;" ::: "memory"); }
__device__ __forceinline__ void fence_barrier_init() { asm volatile("fence.mbarrier_init.release.cluster;" ::: "memory"); }
__device__ __forceinline__ void fence_proxy_async() { asm volatile("fence.proxy.async.shared::cta;" ::: "memory"); }
__device__ __forceinline__ uint64_t make_desc(uint32_t saddr, uint32_t lbo, uint32_t sbo, uint32_t swz) {
    return (uint64_t)((saddr & 0x3FFFF) >> 4) | ((uint64_t)((lbo & 0x3FFFF) >> 4) << 16) |
           ((uint64_t)((sbo & 0x3FFFF) >> 4) << 32) | ((uint64_t)swz << 62);
}
#define WG_FENCE() asm volatile("wgmma.fence.sync.aligned;" ::: "memory")
#define WG_COMMIT() asm volatile("wgmma.commit_group.sync.aligned;" ::: "memory")
template <int N> __device__ __forceinline__ void wg_wait() { asm volatile("wgmma.wait_group.sync.aligned %0;" :: "n"(N) : "memory"); }
template <int N> __device__ __forceinline__ void fence_regs(float (&d)[N]) {
#pragma unroll
    for (int i = 0; i < N; i++) asm volatile("" : "+f"(d[i]) :: "memory");
}
__device__ __forceinline__ float ex2f(float x) { float y; asm("ex2.approx.ftz.f32 %0, %1;" : "=f"(y) : "f"(x)); return y; }
__device__ __forceinline__ float tanh_fast(float x) { float y; asm("tanh.approx.f32 %0, %1;" : "=f"(y) : "f"(x)); return y; }
__device__ __forceinline__ uint32_t pack_bf16(float lo, float hi) { uint32_t r; asm("cvt.rn.bf16x2.f32 %0, %1, %2;" : "=r"(r) : "f"(hi), "f"(lo)); return r; }
__device__ __forceinline__ float bf_lo(uint32_t u) { return __uint_as_float(u << 16); }
__device__ __forceinline__ float bf_hi(uint32_t u) { return __uint_as_float(u & 0xFFFF0000u); }
__device__ __forceinline__ uint32_t hfma2(uint32_t a, uint32_t b, uint32_t c) { uint32_t r; asm("fma.rn.f16x2 %0, %1, %2, %3;" : "=r"(r) : "r"(a), "r"(b), "r"(c)); return r; }
__device__ __forceinline__ uint32_t hmul2(uint32_t a, uint32_t b) { uint32_t r; asm("mul.rn.f16x2 %0, %1, %2;" : "=r"(r) : "r"(a), "r"(b)); return r; }
__device__ __forceinline__ unsigned int ld_acquire(const unsigned int* p) { unsigned int v; asm volatile("ld.acquire.gpu.u32 %0, [%1];" : "=r"(v) : "l"(p) : "memory"); return v; }
__device__ __forceinline__ void red_release(unsigned int* p) { asm volatile("red.release.gpu.global.add.u32 [%0], 1;" :: "l"(p) : "memory"); }
__device__ __forceinline__ void stsm4(uint32_t addr, uint32_t a, uint32_t b, uint32_t c, uint32_t d) {
    asm volatile("stmatrix.sync.aligned.m8n8.x4.shared.b16 [%0], {%1,%2,%3,%4};" :: "r"(addr), "r"(a), "r"(b), "r"(c), "r"(d) : "memory");
}
__device__ __forceinline__ void bulk_s2g(void* dst, uint32_t src, int bytes) {
    asm volatile("cp.async.bulk.global.shared::cta.bulk_group [%0], [%1], %2;" :: "l"(dst), "r"(src), "r"(bytes) : "memory");
}
__device__ __forceinline__ void bulk_commit() { asm volatile("cp.async.bulk.commit_group;" ::: "memory"); }
__device__ __forceinline__ void bulk_wait_all() { asm volatile("cp.async.bulk.wait_group 0;" ::: "memory"); }
__device__ __forceinline__ void bulk_wait_read() { asm volatile("cp.async.bulk.wait_group.read 0;" ::: "memory"); }
__device__ __forceinline__ void bar_sync(int id, int n) { asm volatile("bar.sync %0, %1;" :: "r"(id), "r"(n) : "memory"); }
__device__ __forceinline__ void bar_arrive(int id, int n) { asm volatile("bar.arrive %0, %1;" :: "r"(id), "r"(n) : "memory"); }
__device__ __forceinline__ float warp_sum(float v) {
#pragma unroll
    for (int o = 16; o; o >>= 1) v += __shfl_xor_sync(0xffffffffu, v, o);
    return v;
}
__device__ __forceinline__ float warp_max(float v) {
#pragma unroll
    for (int o = 16; o; o >>= 1) v = fmaxf(v, __shfl_xor_sync(0xffffffffu, v, o));
    return v;
}

__device__ __forceinline__ void wgmma_ss_n64(float (&d)[32], uint64_t adesc, uint64_t bdesc, int scale_d) {
    asm volatile("{\n.reg .pred p;\nsetp.ne.b32 p, %34, 0;\n"
      "wgmma.mma_async.sync.aligned.m64n64k16.f32.bf16.bf16 {%0,%1,%2,%3,%4,%5,%6,%7,%8,%9,%10,%11,%12,%13,%14,%15,%16,%17,%18,%19,%20,%21,%22,%23,%24,%25,%26,%27,%28,%29,%30,%31}, %32, %33, p, 1, 1, 0, 1;\n}"
      : "+f"(d[0]), "+f"(d[1]), "+f"(d[2]), "+f"(d[3]), "+f"(d[4]), "+f"(d[5]), "+f"(d[6]), "+f"(d[7]), "+f"(d[8]), "+f"(d[9]), "+f"(d[10]), "+f"(d[11]), "+f"(d[12]), "+f"(d[13]), "+f"(d[14]), "+f"(d[15]), "+f"(d[16]), "+f"(d[17]), "+f"(d[18]), "+f"(d[19]), "+f"(d[20]), "+f"(d[21]), "+f"(d[22]), "+f"(d[23]), "+f"(d[24]), "+f"(d[25]), "+f"(d[26]), "+f"(d[27]), "+f"(d[28]), "+f"(d[29]), "+f"(d[30]), "+f"(d[31])
      : "l"(adesc), "l"(bdesc), "r"(scale_d));
}
__device__ __forceinline__ void wgmma_ss_n96(float (&d)[48], uint64_t adesc, uint64_t bdesc, int scale_d) {
    asm volatile("{\n.reg .pred p;\nsetp.ne.b32 p, %50, 0;\n"
      "wgmma.mma_async.sync.aligned.m64n96k16.f32.bf16.bf16 {%0,%1,%2,%3,%4,%5,%6,%7,%8,%9,%10,%11,%12,%13,%14,%15,%16,%17,%18,%19,%20,%21,%22,%23,%24,%25,%26,%27,%28,%29,%30,%31,%32,%33,%34,%35,%36,%37,%38,%39,%40,%41,%42,%43,%44,%45,%46,%47}, %48, %49, p, 1, 1, 0, 1;\n}"
      : "+f"(d[0]), "+f"(d[1]), "+f"(d[2]), "+f"(d[3]), "+f"(d[4]), "+f"(d[5]), "+f"(d[6]), "+f"(d[7]), "+f"(d[8]), "+f"(d[9]), "+f"(d[10]), "+f"(d[11]), "+f"(d[12]), "+f"(d[13]), "+f"(d[14]), "+f"(d[15]), "+f"(d[16]), "+f"(d[17]), "+f"(d[18]), "+f"(d[19]), "+f"(d[20]), "+f"(d[21]), "+f"(d[22]), "+f"(d[23]), "+f"(d[24]), "+f"(d[25]), "+f"(d[26]), "+f"(d[27]), "+f"(d[28]), "+f"(d[29]), "+f"(d[30]), "+f"(d[31]), "+f"(d[32]), "+f"(d[33]), "+f"(d[34]), "+f"(d[35]), "+f"(d[36]), "+f"(d[37]), "+f"(d[38]), "+f"(d[39]), "+f"(d[40]), "+f"(d[41]), "+f"(d[42]), "+f"(d[43]), "+f"(d[44]), "+f"(d[45]), "+f"(d[46]), "+f"(d[47])
      : "l"(adesc), "l"(bdesc), "r"(scale_d));
}
__device__ __forceinline__ void wgmma_ss_n128(float (&d)[64], uint64_t adesc, uint64_t bdesc, int scale_d) {
    asm volatile("{\n.reg .pred p;\nsetp.ne.b32 p, %66, 0;\n"
      "wgmma.mma_async.sync.aligned.m64n128k16.f32.bf16.bf16 {%0,%1,%2,%3,%4,%5,%6,%7,%8,%9,%10,%11,%12,%13,%14,%15,%16,%17,%18,%19,%20,%21,%22,%23,%24,%25,%26,%27,%28,%29,%30,%31,%32,%33,%34,%35,%36,%37,%38,%39,%40,%41,%42,%43,%44,%45,%46,%47,%48,%49,%50,%51,%52,%53,%54,%55,%56,%57,%58,%59,%60,%61,%62,%63}, %64, %65, p, 1, 1, 0, 1;\n}"
      : "+f"(d[0]), "+f"(d[1]), "+f"(d[2]), "+f"(d[3]), "+f"(d[4]), "+f"(d[5]), "+f"(d[6]), "+f"(d[7]), "+f"(d[8]), "+f"(d[9]), "+f"(d[10]), "+f"(d[11]), "+f"(d[12]), "+f"(d[13]), "+f"(d[14]), "+f"(d[15]), "+f"(d[16]), "+f"(d[17]), "+f"(d[18]), "+f"(d[19]), "+f"(d[20]), "+f"(d[21]), "+f"(d[22]), "+f"(d[23]), "+f"(d[24]), "+f"(d[25]), "+f"(d[26]), "+f"(d[27]), "+f"(d[28]), "+f"(d[29]), "+f"(d[30]), "+f"(d[31]), "+f"(d[32]), "+f"(d[33]), "+f"(d[34]), "+f"(d[35]), "+f"(d[36]), "+f"(d[37]), "+f"(d[38]), "+f"(d[39]), "+f"(d[40]), "+f"(d[41]), "+f"(d[42]), "+f"(d[43]), "+f"(d[44]), "+f"(d[45]), "+f"(d[46]), "+f"(d[47]), "+f"(d[48]), "+f"(d[49]), "+f"(d[50]), "+f"(d[51]), "+f"(d[52]), "+f"(d[53]), "+f"(d[54]), "+f"(d[55]), "+f"(d[56]), "+f"(d[57]), "+f"(d[58]), "+f"(d[59]), "+f"(d[60]), "+f"(d[61]), "+f"(d[62]), "+f"(d[63])
      : "l"(adesc), "l"(bdesc), "r"(scale_d));
}
__device__ __forceinline__ void wgmma_ss_n192(float (&d)[96], uint64_t adesc, uint64_t bdesc, int scale_d) {
    asm volatile("{\n.reg .pred p;\nsetp.ne.b32 p, %98, 0;\n"
      "wgmma.mma_async.sync.aligned.m64n192k16.f32.bf16.bf16 {%0,%1,%2,%3,%4,%5,%6,%7,%8,%9,%10,%11,%12,%13,%14,%15,%16,%17,%18,%19,%20,%21,%22,%23,%24,%25,%26,%27,%28,%29,%30,%31,%32,%33,%34,%35,%36,%37,%38,%39,%40,%41,%42,%43,%44,%45,%46,%47,%48,%49,%50,%51,%52,%53,%54,%55,%56,%57,%58,%59,%60,%61,%62,%63,%64,%65,%66,%67,%68,%69,%70,%71,%72,%73,%74,%75,%76,%77,%78,%79,%80,%81,%82,%83,%84,%85,%86,%87,%88,%89,%90,%91,%92,%93,%94,%95}, %96, %97, p, 1, 1, 0, 1;\n}"
      : "+f"(d[0]), "+f"(d[1]), "+f"(d[2]), "+f"(d[3]), "+f"(d[4]), "+f"(d[5]), "+f"(d[6]), "+f"(d[7]), "+f"(d[8]), "+f"(d[9]), "+f"(d[10]), "+f"(d[11]), "+f"(d[12]), "+f"(d[13]), "+f"(d[14]), "+f"(d[15]), "+f"(d[16]), "+f"(d[17]), "+f"(d[18]), "+f"(d[19]), "+f"(d[20]), "+f"(d[21]), "+f"(d[22]), "+f"(d[23]), "+f"(d[24]), "+f"(d[25]), "+f"(d[26]), "+f"(d[27]), "+f"(d[28]), "+f"(d[29]), "+f"(d[30]), "+f"(d[31]), "+f"(d[32]), "+f"(d[33]), "+f"(d[34]), "+f"(d[35]), "+f"(d[36]), "+f"(d[37]), "+f"(d[38]), "+f"(d[39]), "+f"(d[40]), "+f"(d[41]), "+f"(d[42]), "+f"(d[43]), "+f"(d[44]), "+f"(d[45]), "+f"(d[46]), "+f"(d[47]), "+f"(d[48]), "+f"(d[49]), "+f"(d[50]), "+f"(d[51]), "+f"(d[52]), "+f"(d[53]), "+f"(d[54]), "+f"(d[55]), "+f"(d[56]), "+f"(d[57]), "+f"(d[58]), "+f"(d[59]), "+f"(d[60]), "+f"(d[61]), "+f"(d[62]), "+f"(d[63]), "+f"(d[64]), "+f"(d[65]), "+f"(d[66]), "+f"(d[67]), "+f"(d[68]), "+f"(d[69]), "+f"(d[70]), "+f"(d[71]), "+f"(d[72]), "+f"(d[73]), "+f"(d[74]), "+f"(d[75]), "+f"(d[76]), "+f"(d[77]), "+f"(d[78]), "+f"(d[79]), "+f"(d[80]), "+f"(d[81]), "+f"(d[82]), "+f"(d[83]), "+f"(d[84]), "+f"(d[85]), "+f"(d[86]), "+f"(d[87]), "+f"(d[88]), "+f"(d[89]), "+f"(d[90]), "+f"(d[91]), "+f"(d[92]), "+f"(d[93]), "+f"(d[94]), "+f"(d[95])
      : "l"(adesc), "l"(bdesc), "r"(scale_d));
}
__device__ __forceinline__ void qk_wgmma_n64(float (&d)[32], const uint32_t (&a)[4], uint64_t desc) {
    asm volatile("wgmma.mma_async.sync.aligned.m64n64k16.f32.bf16.bf16 {%0,%1,%2,%3,%4,%5,%6,%7,%8,%9,%10,%11,%12,%13,%14,%15,%16,%17,%18,%19,%20,%21,%22,%23,%24,%25,%26,%27,%28,%29,%30,%31}, {%32,%33,%34,%35}, %36, 0, 1, 1, 0;"
      : "=f"(d[0]), "=f"(d[1]), "=f"(d[2]), "=f"(d[3]), "=f"(d[4]), "=f"(d[5]), "=f"(d[6]), "=f"(d[7]), "=f"(d[8]), "=f"(d[9]), "=f"(d[10]), "=f"(d[11]), "=f"(d[12]), "=f"(d[13]), "=f"(d[14]), "=f"(d[15]), "=f"(d[16]), "=f"(d[17]), "=f"(d[18]), "=f"(d[19]), "=f"(d[20]), "=f"(d[21]), "=f"(d[22]), "=f"(d[23]), "=f"(d[24]), "=f"(d[25]), "=f"(d[26]), "=f"(d[27]), "=f"(d[28]), "=f"(d[29]), "=f"(d[30]), "=f"(d[31])
      : "r"(a[0]), "r"(a[1]), "r"(a[2]), "r"(a[3]), "l"(desc));
}

__device__ __forceinline__ void pv_wgmma(float (&d)[12], uint32_t a0, uint32_t a1, uint32_t a2, uint32_t a3, uint64_t desc) {
    asm volatile("wgmma.mma_async.sync.aligned.m64n24k16.f32.bf16.bf16 {%0,%1,%2,%3,%4,%5,%6,%7,%8,%9,%10,%11}, {%12,%13,%14,%15}, %16, 1, 1, 1, 1;"
      : "+f"(d[0]), "+f"(d[1]), "+f"(d[2]), "+f"(d[3]), "+f"(d[4]), "+f"(d[5]), "+f"(d[6]), "+f"(d[7]), "+f"(d[8]), "+f"(d[9]), "+f"(d[10]), "+f"(d[11])
      : "r"(a0), "r"(a1), "r"(a2), "r"(a3), "l"(desc));
}

__device__ __forceinline__ void tile_of(int bid, int& mb, int& nt) {
    int grp = bid >> 4, in = bid & 15;
    mb = (grp >> 1) * 4 + (in >> 2);
    nt = (grp & 1) * 4 + (in & 3);
}

constexpr int K1_STAGES = 5, K1_STAGE = 16384 + 24576;
constexpr int K1_BAR = K1_STAGES * K1_STAGE, K1_RS = K1_BAR + 128, K1_CS = K1_RS + 1024, K1_SMEM = K1_CS + 768;

__device__ __forceinline__ float2 row_stats_regs(uint4 a, uint4 b) {
    float v[16];
    v[0] = bf_lo(a.x); v[1] = bf_hi(a.x); v[2] = bf_lo(a.y); v[3] = bf_hi(a.y);
    v[4] = bf_lo(a.z); v[5] = bf_hi(a.z); v[6] = bf_lo(a.w); v[7] = bf_hi(a.w);
    v[8] = bf_lo(b.x); v[9] = bf_hi(b.x); v[10] = bf_lo(b.y); v[11] = bf_hi(b.y);
    v[12] = bf_lo(b.z); v[13] = bf_hi(b.z); v[14] = bf_lo(b.w); v[15] = bf_hi(b.w);
    float s = 0.f;
#pragma unroll
    for (int i = 0; i < 16; i++) s += v[i];
    float mean = warp_sum(s) * (1.0f / DM);
    float q = 0.f;
#pragma unroll
    for (int i = 0; i < 16; i++) { float d = v[i] - mean; q = fmaf(d, d, q); }
    float var = warp_sum(q) * (1.0f / DM);
    float rstd = rsqrtf(var + 1e-5f);
    return make_float2(rstd, -mean * rstd);
}
__device__ __forceinline__ float2 row_stats_x(const __nv_bfloat16* x, int row, int lane) {
    const uint4* p = (const uint4*)(x + (size_t)row * DM);
    return row_stats_regs(__ldg(p + lane), __ldg(p + 32 + lane));
}
__device__ __forceinline__ void colsum8(const __nv_bfloat16* w, int ld, int col, int k0, int nk, float (&s)[8]) {
#pragma unroll
    for (int i = 0; i < 8; i++) s[i] = 0.f;
    for (int k = k0; k < k0 + nk; k += 8) {
        uint4 u[8];
#pragma unroll
        for (int i = 0; i < 8; i++) u[i] = __ldg((const uint4*)(w + (size_t)(k + i) * ld + col));
#pragma unroll
        for (int i = 0; i < 8; i++) {
            s[0] += bf_lo(u[i].x); s[1] += bf_hi(u[i].x); s[2] += bf_lo(u[i].y); s[3] += bf_hi(u[i].y);
            s[4] += bf_lo(u[i].z); s[5] += bf_hi(u[i].z); s[6] += bf_lo(u[i].w); s[7] += bf_hi(u[i].w);
        }
    }
}
__device__ __forceinline__ bool wait_count(const unsigned int* p, unsigned int target, int lane) {
    int ok = 1;
    if (lane == 0) {
        int it = 0;
        while (ld_acquire(p) < target) { if (++it > (1 << 18)) { ok = 0; break; } }
    }
    ok = __shfl_sync(0xffffffffu, ok, 0);
    return ok != 0;
}

__global__ void __launch_bounds__(384, 1)
qkv_kernel(const __grid_constant__ CUtensorMap tm_x, const __grid_constant__ CUtensorMap tm_w,
           const __nv_bfloat16* __restrict__ x, const __nv_bfloat16* __restrict__ wqkv) {
    extern __shared__ __align__(1024) unsigned char smem[];
    const uint32_t sb = smem_u32(smem);
    const int tid = threadIdx.x, warp = __shfl_sync(0xffffffffu, tid >> 5, 0), lane = tid & 31;
    TL(0);
    int mb, nt;
    tile_of(blockIdx.x, mb, nt);
    const uint32_t full = sb + K1_BAR, empty = full + 40, auxb = full + 80;
    if (tid == 0) {
        prefetch_tmap(&tm_x); prefetch_tmap(&tm_w);
        for (int i = 0; i < K1_STAGES; i++) { mbar_init(full + 8 * i, 1); mbar_init(empty + 8 * i, 8); }
        mbar_init(auxb, 3);
        fence_barrier_init();
    }
    __syncthreads();
    pdl_launch();
    if (warp == 0) {
        if (blockIdx.x == 0) { g_cnt2[lane] = 0; g_cnt2[32 + lane] = 0; }
        if (lane == 0) {
            for (int kb = 0; kb < 8; kb++) {
                int s = kb % K1_STAGES;
                if (kb >= K1_STAGES) mbar_wait(empty + 8 * s, 0);
                mbar_expect(full + 8 * s, K1_STAGE);
                tma2d(sb + s * K1_STAGE, &tm_x, kb * 64, mb * 128, full + 8 * s);
                tma3d(sb + s * K1_STAGE + 16384, &tm_w, 0, kb * 64, nt * 3, full + 8 * s);
            }
        }
    } else if (warp < 4) {
        float2* s_rs = (float2*)(smem + K1_RS);
        float* s_cs = (float*)(smem + K1_CS);
        if (warp < 3) {
            const int r0 = mb * 128 + nt * 16 + (warp - 1) * 8;
            uint4 u[16];
#pragma unroll
            for (int i = 0; i < 8; i++) {
                const uint4* p = (const uint4*)(x + (size_t)(r0 + i) * DM);
                u[2 * i] = __ldg(p + lane); u[2 * i + 1] = __ldg(p + 32 + lane);
            }
            float2 mine = make_float2(0.f, 0.f);
#pragma unroll
            for (int i = 0; i < 8; i++) {
                float2 st = row_stats_regs(u[2 * i], u[2 * i + 1]);
                if (lane == i) mine = st;
            }
            if (lane < 8) g_rowstat1[r0 + lane] = mine;
            __syncwarp();
            if (lane == 0) red_release(&g_cnt[mb]);
        } else {
            uint4 u[24];
#pragma unroll
            for (int c = 0; c < 3; c++)
#pragma unroll
                for (int i = 0; i < 8; i++)
                    u[c * 8 + i] = __ldg((const uint4*)(wqkv + (size_t)(mb * 32 + (lane >> 3) * 8 + i) * 1536 + nt * 192 + (c * 8 + (lane & 7)) * 8));
#pragma unroll
            for (int c = 0; c < 3; c++) {
                float cs[8];
#pragma unroll
                for (int i = 0; i < 8; i++) cs[i] = 0.f;
#pragma unroll
                for (int i = 0; i < 8; i++) {
                    const uint4 w = u[c * 8 + i];
                    cs[0] += bf_lo(w.x); cs[1] += bf_hi(w.x); cs[2] += bf_lo(w.y); cs[3] += bf_hi(w.y);
                    cs[4] += bf_lo(w.z); cs[5] += bf_hi(w.z); cs[6] += bf_lo(w.w); cs[7] += bf_hi(w.w);
                }
#pragma unroll
                for (int i = 0; i < 8; i++) {
                    cs[i] += __shfl_xor_sync(0xffffffffu, cs[i], 8);
                    cs[i] += __shfl_xor_sync(0xffffffffu, cs[i], 16);
                }
                if (lane < 8) {
                    float4* d = (float4*)(g_cs1_part + mb * 1536 + nt * 192 + (c * 8 + lane) * 8);
                    d[0] = make_float4(cs[0], cs[1], cs[2], cs[3]);
                    d[1] = make_float4(cs[4], cs[5], cs[6], cs[7]);
                }
            }
            __syncwarp();
            if (lane == 0) red_release(&g_cnt[16 + nt]);
        }
        TX(8 + warp);
        if (warp == 1) {
            if (wait_count(&g_cnt[mb], 16, lane)) {
#pragma unroll
                for (int i = 0; i < 4; i++) s_rs[lane + 32 * i] = __ldcg(&g_rowstat1[mb * 128 + lane + 32 * i]);
            } else {
                for (int i = 0; i < 128; i++) {
                    float2 st = row_stats_x(x, mb * 128 + i, lane);
                    if (lane == 0) s_rs[i] = st;
                }
            }
        } else {
            int c0 = (warp - 2) * 96;
            if (wait_count(&g_cnt[16 + nt], 16, lane)) {
#pragma unroll
                for (int i = 0; i < 3; i++) {
                    float s = 0.f;
#pragma unroll
                    for (int p = 0; p < 16; p++) s += __ldcg(&g_cs1_part[p * 1536 + nt * 192 + c0 + lane + 32 * i]);
                    s_cs[c0 + lane + 32 * i] = s;
                }
            } else if (lane < 12) {
                float s[8];
                colsum8(wqkv, 1536, nt * 192 + c0 + lane * 8, 0, 512, s);
#pragma unroll
                for (int i = 0; i < 8; i++) s_cs[c0 + lane * 8 + i] = s[i];
            }
        }
        __syncwarp();
        TX(12 + warp);
        if (lane == 0) mbar_arrive(auxb);
        bar_sync(2, 256 + 96);
        const int a = tid - 32;
        if (a < 24) {
            const int col0 = nt * 192 + a * 8;
            const int which = col0 >> 9, head = (col0 & 511) >> 4;
            bulk_s2g(g_qkv + ((size_t)((which * NH + head) * 2 + (a & 1)) * 256 + mb * 16) * 64, sb + a * 2048, 2048);
            bulk_commit();
        }
        {
            const int hh = a >> 3, w = a & 7;
            const float4* p = (const float4*)(smem + 49152) + (hh * 256 + w * 32) / 2;
            float m = 0.f;
#pragma unroll
            for (int i = 0; i < 8; i++) {
                const int ii = (i + a) & 7;
                float4 u = p[2 * ii], v = p[2 * ii + 1];
                float n0 = u.x + u.z + v.x + v.z, n1 = u.y + u.w + v.y + v.w;
                if (!(n0 <= 3.0e38f) || !(n1 <= 3.0e38f)) m = __int_as_float(0x7f800000);
                m = fmaxf(m, fmaxf(n0, n1));
            }
            const int col0 = nt * 192 + hh * 16;
            g_nrm[((col0 >> 9) * NH + ((col0 & 511) >> 4)) * 128 + mb * 8 + w] = m;
        }
        if (a < 24) bulk_wait_all();
        TL(27);
    } else {
        const int wgi = (warp >> 2) - 1, ww = warp & 3;
        float acc[96];
#pragma unroll 1
        for (int kb = 0; kb < 8; kb++) {
            int s = kb % K1_STAGES;
            mbar_wait(full + 8 * s, (kb / K1_STAGES) & 1);
            if (warp == 4) TX(kb);
            uint64_t ad = make_desc(sb + s * K1_STAGE + wgi * 8192, 16, 1024, 1);
            uint64_t bd = make_desc(sb + s * K1_STAGE + 16384, 8192, 1024, 1);
            WG_FENCE();
#pragma unroll
            for (int k = 0; k < 4; k++) wgmma_ss_n192(acc, ad + k * 2, bd + k * 128, (kb | k) != 0);
            WG_COMMIT();
            if (kb > 0) {
                wg_wait<1>();
                if (lane == 0) mbar_arrive(empty + 8 * ((kb - 1) % K1_STAGES));
            }
        }
        wg_wait<0>();
        fence_regs(acc);
        TL(1);
        if (warp == 4) TX(16);
        mbar_wait(auxb, 0);
        if (warp == 4) TX(17);
        bar_sync(1, 256);
        const float2* s_rs = (const float2*)(smem + K1_RS);
        const float* s_cs = (const float*)(smem + K1_CS);
        const int g = lane >> 2, t = lane & 3;
        const int rl = wgi * 64 + ww * 16 + g;
        const float2 st0 = s_rs[rl], st1 = s_rs[rl + 8];
        const float QS = 0.25f * 1.4426950408889634f;
        const uint32_t stg = sb + ((lane >> 4) * 16 + wgi * 8 + ww * 2 + ((lane >> 3) & 1)) * 128 + (lane & 7) * 16;
        float2* s_np = (float2*)(smem + 49152) + (warp - 4) * 32 + lane;
#pragma unroll
        for (int hh = 0; hh < 12; hh++) {
            const int which = (nt * 192 + hh * 16) >> 9;
            const float sc = (which == 0) ? QS : 1.0f;
            const float a0 = st0.x * sc, b0 = st0.y * sc, a1 = st1.x * sc, b1 = st1.y * sc;
            const float2 c0 = *(const float2*)(s_cs + 16 * hh + 2 * t), c1 = *(const float2*)(s_cs + 16 * hh + 8 + 2 * t);
            const float* a = acc + 8 * hh;
            float v0 = fmaf(a0, a[0], b0 * c0.x), v1 = fmaf(a0, a[1], b0 * c0.y), v2 = fmaf(a1, a[2], b1 * c0.x), v3 = fmaf(a1, a[3], b1 * c0.y);
            float v4 = fmaf(a0, a[4], b0 * c1.x), v5 = fmaf(a0, a[5], b0 * c1.y), v6 = fmaf(a1, a[6], b1 * c1.x), v7 = fmaf(a1, a[7], b1 * c1.y);
            stsm4(stg + hh * 4096, pack_bf16(v0, v1), pack_bf16(v2, v3), pack_bf16(v4, v5), pack_bf16(v6, v7));
            s_np[hh * 256] = make_float2(fmaf(v0, v0, fmaf(v1, v1, fmaf(v4, v4, v5 * v5))), fmaf(v2, v2, fmaf(v3, v3, fmaf(v6, v6, v7 * v7))));
        }
        fence_proxy_async();
        bar_arrive(2, 256 + 96);
        TL(2);
        if (warp == 4) TX(18);
    }
}

constexpr int AT_K = 0, AT_V = 65536, AT_ONES = 131072, AT_BAR = 163840, AT_SMEM = AT_BAR + 128;
#define POLY_MASK 0xAD6A

__device__ __forceinline__ uint32_t exp2_pair_poly(float x0, float x1) {
    uint32_t t0 = __float_as_uint(x0 + 32895.0f);
    uint32_t t1 = __float_as_uint(x1 + 32895.0f);
    uint32_t gd = __byte_perm(t0, t1, 0x6420);
    uint32_t wm = __byte_perm(t0, t1, 0x5612);
    uint32_t v = hfma2(gd, 0x71477147u, 0x354f354fu);
    uint32_t z = hmul2(v, gd);
    return (wm >> 1) + z;
}
__device__ __forceinline__ uint32_t exp2_pair_mufu(float x0, float x1) { return pack_bf16(ex2f(x0), ex2f(x1)); }
template <uint32_t MASK>
__device__ __forceinline__ void exp_blocks(const float (&s)[32], uint32_t (&p)[16]) {
#pragma unroll
    for (int b = 0; b < 8; b++) {
        if ((MASK >> b) & 1) {
            p[2 * b] = exp2_pair_poly(s[4 * b], s[4 * b + 1]);
            p[2 * b + 1] = exp2_pair_poly(s[4 * b + 2], s[4 * b + 3]);
        } else {
            p[2 * b] = exp2_pair_mufu(s[4 * b], s[4 * b + 1]);
            p[2 * b + 1] = exp2_pair_mufu(s[4 * b + 2], s[4 * b + 3]);
        }
    }
}
#define PV4(P) _Pragma("unroll") for (int i = 0; i < 4; i++) { pv_wgmma(o, P[4 * i], P[4 * i + 1], P[4 * i + 2], P[4 * i + 3], vd); vd += 16; }

__device__ __forceinline__ void attn_store(float (&o)[12], int row0, int head, int lane) {
    float l0 = __shfl_sync(0xffffffffu, o[8], lane & 28);
    float l1 = __shfl_sync(0xffffffffu, o[10], lane & 28);
    float r0 = 1.0f / l0, r1 = 1.0f / l1;
    uint32_t* op = (uint32_t*)g_ao;
    int mb = row0 >> 7, rg = (row0 & 127) >> 3;
    int kb = head >> 2, kc = (head & 3) * 2;
    size_t base = (((size_t)(mb * 8 + kb) * 8 + kc) * 16 + rg) * 32 + lane;
    op[base] = pack_bf16(o[0] * r0, o[1] * r0);
    op[base + 32] = pack_bf16(o[2] * r1, o[3] * r1);
    op[base + 16 * 32] = pack_bf16(o[4] * r0, o[5] * r0);
    op[base + 16 * 32 + 32] = pack_bf16(o[6] * r1, o[7] * r1);
}

__device__ __forceinline__ void attn_load_q(uint32_t (&q)[4], const __nv_bfloat16* gq, int row0, int lane) {
    const uint32_t* qp = (const uint32_t*)gq;
    int j0 = row0 >> 3;
    q[0] = __ldcg(qp + (0 * 256 + j0) * 32 + lane);
    q[1] = __ldcg(qp + (0 * 256 + j0 + 1) * 32 + lane);
    q[2] = __ldcg(qp + (1 * 256 + j0) * 32 + lane);
    q[3] = __ldcg(qp + (1 * 256 + j0 + 1) * 32 + lane);
}

__device__ __forceinline__ void attn_tile_safe(const uint32_t (&q)[4], uint64_t kd, uint64_t vd, int row0, int head, int lane) {
    float o[12];
#pragma unroll
    for (int i = 0; i < 12; i++) o[i] = 0.f;
    float m0 = -INFINITY, m1 = -INFINITY;
    fence_regs(o);
#pragma unroll 1
    for (int j = 0; j < 32; j++) {
        float s[32];
        uint32_t p[16];
        WG_FENCE();
        qk_wgmma_n64(s, q, kd); kd += 64;
        WG_COMMIT();
        wg_wait<0>();
        fence_regs(s);
        fence_regs(o);
        float x0 = m0, x1 = m1;
#pragma unroll
        for (int b = 0; b < 8; b++) {
            x0 = fmaxf(x0, fmaxf(s[4 * b], s[4 * b + 1]));
            x1 = fmaxf(x1, fmaxf(s[4 * b + 2], s[4 * b + 3]));
        }
        x0 = fmaxf(x0, __shfl_xor_sync(0xffffffffu, x0, 1)); x0 = fmaxf(x0, __shfl_xor_sync(0xffffffffu, x0, 2));
        x1 = fmaxf(x1, __shfl_xor_sync(0xffffffffu, x1, 1)); x1 = fmaxf(x1, __shfl_xor_sync(0xffffffffu, x1, 2));
        float al0 = ex2f(m0 - x0), al1 = ex2f(m1 - x1);
        m0 = x0; m1 = x1;
#pragma unroll
        for (int i = 0; i < 3; i++) { o[4 * i] *= al0; o[4 * i + 1] *= al0; o[4 * i + 2] *= al1; o[4 * i + 3] *= al1; }
#pragma unroll
        for (int b = 0; b < 8; b++) {
            p[2 * b] = exp2_pair_mufu(s[4 * b] - m0, s[4 * b + 1] - m0);
            p[2 * b + 1] = exp2_pair_mufu(s[4 * b + 2] - m1, s[4 * b + 3] - m1);
        }
        fence_regs(o);
        WG_FENCE();
        PV4(p);
        WG_COMMIT();
        wg_wait<0>();
        fence_regs(o);
    }
    attn_store(o, row0, head, lane);
}

__global__ void __launch_bounds__(512, 1)
attn_kernel(const __nv_bfloat16* __restrict__ wg_, const __nv_bfloat16* __restrict__ wu_,
            const __nv_bfloat16* __restrict__ wo_, const __nv_bfloat16* __restrict__ wd_) {
    extern __shared__ __align__(1024) unsigned char smem[];
    const uint32_t sb = smem_u32(smem);
    const int tid = threadIdx.x, wg = tid >> 7, warp = (tid >> 5) & 3, lane = tid & 31;
    pdl_launch();
    if (blockIdx.x >= 128) {
        const int e = blockIdx.x - 128;
        const __nv_bfloat16* w = (e < 2) ? wg_ : wu_;
        float* red = (float*)smem;
        const int cgrp = tid & 127, kq = tid >> 7;
        if (cgrp < 112) {
            float s[8];
            colsum8(w, FF, (e & 1) * 896 + cgrp * 8, kq * 128, 128, s);
#pragma unroll
            for (int i = 0; i < 8; i++) red[kq * 896 + cgrp * 8 + i] = s[i];
        }
        __syncthreads();
        for (int c = tid; c < 896; c += 512)
            g_cs2[(e >> 1) * FF + (e & 1) * 896 + c] = red[c] + red[896 + c] + red[1792 + c] + red[2688 + c];
        if (tid < 32) {
            const char* p0 = (const char*)wo_ + e * (DM * DM * 2 / 4);
            for (int i = lane; i < 32; i += 32)
                asm volatile("cp.async.bulk.prefetch.L2.global [%0], %1;" :: "l"(p0 + i * 4096), "r"(4096) : "memory");
            const char* p1 = (const char*)wd_ + e * (FF * DM * 2 / 4);
            for (int i = lane; i < 112; i += 32)
                asm volatile("cp.async.bulk.prefetch.L2.global [%0], %1;" :: "l"(p1 + i * 4096), "r"(4096) : "memory");
        }
        return;
    }
    const int head = blockIdx.x >> 2, qq = blockIdx.x & 3;
    const __nv_bfloat16* gq = g_qkv + (size_t)head * (S_LEN * 16);
    const __nv_bfloat16* gk = g_qkv + (size_t)(NH + head) * (S_LEN * 16);
    const __nv_bfloat16* gv = g_qkv + (size_t)(2 * NH + head) * (S_LEN * 16);
    if (tid == 0) {
        for (int i = 0; i < 8; i++) mbar_init(sb + AT_BAR + 8 * i, 1);
        fence_barrier_init();
    }
    {
        uint4 one = make_uint4(0x00003F80u, 0, 0, 0);
#pragma unroll
        for (int i = 0; i < 4; i++) *(uint4*)(smem + AT_ONES + (i * 512 + tid) * 16) = one;
        fence_proxy_async();
    }
    __syncthreads();
    TL(3);
    pdl_wait();
    TL(4);
    auto load_kv = [&](int i) {
        uint32_t bar = sb + AT_BAR + 8 * i;
        mbar_expect(bar, 16384);
        bulk_g2s(sb + AT_K + i * 4096, gk + i * 2048, 4096, bar);
        bulk_g2s(sb + AT_K + 32768 + i * 4096, gk + 16384 + i * 2048, 4096, bar);
        bulk_g2s(sb + AT_V + i * 4096, gv + i * 2048, 4096, bar);
        bulk_g2s(sb + AT_V + 32768 + i * 4096, gv + 16384 + i * 2048, 4096, bar);
    };
    if (tid == 0) { load_kv(0); load_kv(1); }
    uint32_t q[4], q2[4];
    attn_load_q(q, gq, qq * 512 + wg * 64 + warp * 16, lane);
    attn_load_q(q2, gq, qq * 512 + (4 + wg) * 64 + warp * 16, lane);
    bool fast;
    {
        const float* nq = g_nrm + (0 * NH + head) * 128 + qq * 32;
        const float* nk = g_nrm + (1 * NH + head) * 128;
        const float* nv = g_nrm + (2 * NH + head) * 128;
        float4 k4 = __ldcg((const float4*)nk + lane), v4 = __ldcg((const float4*)nv + lane);
        float qm = warp_max(__ldcg(nq + lane));
        float km = warp_max(fmaxf(fmaxf(k4.x, k4.y), fmaxf(k4.z, k4.w)));
        float vm = warp_max(fmaxf(fmaxf(v4.x, v4.y), fmaxf(v4.z, v4.w)));
        fast = __all_sync(0xffffffffu, (qm * km <= 3500.0f) && (vm <= 1.0e24f));
    }
    TL(24);
    const uint64_t kdesc0 = make_desc(sb + AT_K, 32768, 128, 0);
    const uint64_t vdesc0 = make_desc(sb + AT_V, 128, 32768, 0);
    if (!fast) {
        if (tid == 0) for (int i = 2; i < 8; i++) load_kv(i);
        for (int i = 0; i < 8; i++) mbar_wait(sb + AT_BAR + 8 * i, 0);
#pragma unroll 1
        for (int tile = 0; tile < 2; tile++) {
            const int row0 = qq * 512 + (tile * 4 + wg) * 64 + warp * 16;
            attn_tile_safe(q, kdesc0, vdesc0, row0, head, lane);
#pragma unroll
            for (int i = 0; i < 4; i++) q[i] = q2[i];
        }
        return;
    }
#pragma unroll 1
    for (int tile = 0; tile < 2; tile++) {
        const int row0 = qq * 512 + (tile * 4 + wg) * 64 + warp * 16;
        float o[12];
#pragma unroll
        for (int i = 0; i < 12; i++) o[i] = 0.f;
        fence_regs(o);
        float sa[32];
        uint32_t pa[16];
        uint64_t kd = kdesc0, vd = vdesc0;
        if (tile == 0) { mbar_wait(sb + AT_BAR, 0); TL(25); }
        WG_FENCE();
        qk_wgmma_n64(sa, q, kd); kd += 64;
        WG_COMMIT();
#pragma unroll 1
        for (int jj = 0; jj < 8; jj++) {
            if (tile == 0 && jj < 7) {
                if (tid == 0 && jj < 6) load_kv(jj + 2);
                mbar_wait(sb + AT_BAR + 8 * (jj + 1), 0);
            }
            if (wg == 0 && warp == 0) TX(128 + tile * 8 + jj);
#pragma unroll
            for (int j = 0; j < 4; j++) {
                wg_wait<0>();
                fence_regs(sa);
                if (j & 1) exp_blocks<(POLY_MASK >> 8)>(sa, pa); else exp_blocks<(POLY_MASK & 255)>(sa, pa);
                WG_FENCE();
                qk_wgmma_n64(sa, q, kd); kd += 64;
                PV4(pa);
                WG_COMMIT();
            }
        }
        wg_wait<0>();
        fence_regs(o);
        fence_regs(sa);
        if (tile == 0) TL(26);
        attn_store(o, row0, head, lane);
#pragma unroll
        for (int i = 0; i < 4; i++) q[i] = q2[i];
    }
    TL(5);
}

constexpr int F_R2 = 131072, F_X = 196608, F_BAR = 229376;
constexpr int F_RS = F_BAR + 256, F_CS = F_RS + 1024, F_SMEM = F_CS + 1792;
enum { B_FA = 0, B_HF = 4, B_BF = 8, B_BE = 11, B_CF = 14, B_CE = 20, B_ADONE = 26, B_BDONE = 27, B_XC = 28, B_PRDY = 29, B_AUX = 30, B_NUM = 31 };

__device__ __forceinline__ uint32_t mapa(uint32_t a, uint32_t rank) { uint32_t r; asm("mapa.shared::cluster.u32 %0, %1, %2;" : "=r"(r) : "r"(a), "r"(rank)); return r; }
__device__ __forceinline__ void st_async4(uint32_t dst, float a, float b, float c, float d, uint32_t bar) {
    asm volatile("st.async.weak.shared::cluster.mbarrier::complete_tx::bytes.v4.f32 [%0], {%1,%2,%3,%4}, [%5];"
                 :: "r"(dst), "f"(a), "f"(b), "f"(c), "f"(d), "r"(bar) : "memory");
}
__device__ __forceinline__ void mbar_arrive_remote(uint32_t a) { asm volatile("mbarrier.arrive.release.cluster.shared::cluster.b64 _, [%0];" :: "r"(a) : "memory"); }
__device__ __forceinline__ void mbar_wait_cluster(uint32_t a, int parity) {
    uint32_t done;
    int it = 0;
    do {
        asm volatile("{\n.reg .pred p;\nmbarrier.try_wait.parity.acquire.cluster.shared::cta.b64 p, [%1], %2;\nselp.u32 %0, 1, 0, p;\n}"
                     : "=r"(done) : "r"(a), "r"(parity) : "memory");
        if (++it > (1 << 24)) __trap();
    } while (!done);
}
__device__ __forceinline__ void poll_count(const unsigned int* p, unsigned int target) {
    int it = 0;
    while (ld_acquire(p) < target) { if (++it > (1 << 22)) __trap(); }
    asm volatile("fence.proxy.async.global;" ::: "memory");
}
__device__ __forceinline__ void tma2d_store(const CUtensorMap* m, uint32_t src, int c0, int c1) {
    asm volatile("cp.async.bulk.tensor.2d.global.shared::cta.bulk_group [%0, {%2, %3}], [%1];" :: "l"(m), "r"(src), "r"(c0), "r"(c1) : "memory");
}
template <int R>
__device__ __forceinline__ void xchg(float (&acc)[64], float (&o)[32], uint32_t sb, unsigned char* smem, int bar, int ctid) {
    const uint32_t dst = mapa(sb + F_X + ctid * 16, 1 - R), rb = mapa(sb + F_BAR + 8 * bar, 1 - R);
#pragma unroll
    for (int q = 0; q < 8; q++) {
        const int j = (1 - R) * 32 + 4 * q;
        st_async4(dst + q * 4096, acc[j], acc[j + 1], acc[j + 2], acc[j + 3], rb);
    }
    mbar_wait_cluster(sb + F_BAR + 8 * bar, 0);
#pragma unroll
    for (int q = 0; q < 8; q++) {
        float4 v = *(const float4*)(smem + F_X + q * 4096 + ctid * 16);
        const int j = R * 32 + 4 * q;
        o[4 * q] = acc[j] + v.x; o[4 * q + 1] = acc[j + 1] + v.y; o[4 * q + 2] = acc[j + 2] + v.z; o[4 * q + 3] = acc[j + 3] + v.w;
    }
}

template <int NB, bool STAGE>
__device__ __forceinline__ void ffn_epilogue(const float* ag, const float* au, const float* s_cs, int cs_off, uint32_t* gp, uint32_t stg,
                                             float2 st0, float2 st1, int lane) {
    const int t = lane & 3;
    const float C1 = 0.7978845608028654f, C2 = 0.044715f * 0.7978845608028654f;
    const float k10 = st0.x * C1, k20 = st0.x * st0.x * st0.x * C2, k11 = st1.x * C1, k21 = st1.x * st1.x * st1.x * C2;
#pragma unroll
    for (int j2 = 0; j2 < NB / 2; j2++) {
        uint32_t pk[4];
#pragma unroll
        for (int jj = 0; jj < 2; jj++) {
            const int j = 2 * j2 + jj;
            const float2 cg = *(const float2*)(s_cs + cs_off + 8 * j + 2 * t);
            const float2 cu = *(const float2*)(s_cs + 224 + cs_off + 8 * j + 2 * t);
            float r[4];
#pragma unroll
            for (int e = 0; e < 4; e++) {
                const float nm = (e < 2) ? st0.y : st1.y, k1 = (e < 2) ? k10 : k11, k2 = (e < 2) ? k20 : k21;
                const float tg = fmaf(nm, (e & 1) ? cg.y : cg.x, ag[4 * j + e]);
                const float tu = fmaf(nm, (e & 1) ? cu.y : cu.x, au[4 * j + e]);
                const float th = tanh_fast(tg * fmaf(tg * tg, k2, k1));
                const float p = tg * tu;
                r[e] = fmaf(p, th, p);
            }
            pk[2 * jj] = pack_bf16(r[0], r[1]);
            pk[2 * jj + 1] = pack_bf16(r[2], r[3]);
        }
        if (STAGE) {
            stsm4(stg + j2 * 4096, pk[0], pk[1], pk[2], pk[3]);
        } else {
            gp[j2 * 1024] = pk[0]; gp[j2 * 1024 + 32] = pk[1]; gp[j2 * 1024 + 512] = pk[2]; gp[j2 * 1024 + 544] = pk[3];
        }
    }
}

__global__ void __cluster_dims__(2, 1, 1) __launch_bounds__(384, 1)
tail_kernel(const __grid_constant__ CUtensorMap tm_o, const __grid_constant__ CUtensorMap tm_g,
            const __grid_constant__ CUtensorMap tm_u, const __grid_constant__ CUtensorMap tm_d,
            const __grid_constant__ CUtensorMap tm_out, const __nv_bfloat16* __restrict__ x) {
    extern __shared__ __align__(1024) unsigned char smem[];
    const uint32_t sb = smem_u32(smem);
    const uint32_t bars = sb + F_BAR;
    const int tid = threadIdx.x, warp = __shfl_sync(0xffffffffu, tid >> 5, 0), lane = tid & 31;
    TL(6);
    const int cl = blockIdx.x >> 1, r = blockIdx.x & 1;
    const int mb = ((cl & 7) >> 1) * 4 + (cl >> 4), ntA = (cl & 1) * 2 + ((cl >> 3) & 1);
    const int nt = ntA * 2 + r;
    if (tid == 0) {
        for (int i = 0; i < B_NUM; i++) {
            int cnt = 1;
            if ((i >= B_BE && i < B_BE + 3) || (i >= B_CE && i < B_CE + 6) || i == B_BDONE) cnt = 8;
            if (i == B_AUX) cnt = 2;
            mbar_init(bars + 8 * i, cnt);
        }
        mbar_expect(bars + 8 * B_XC, 32768);
        fence_barrier_init();
    }
    __syncthreads();
    asm volatile("barrier.cluster.arrive.release.aligned;" ::: "memory");
    if (warp < 4) {
        asm volatile("setmaxnreg.dec.sync.aligned.u32 56;");
        if (warp == 0) {
            if (lane == 0) {
                auto load_b = [&](int it) {
                    const int s = it % 3, pass = it >> 3, kb = it & 7;
                    const int ng = pass ? 3 : 4, c0 = nt * 224 + pass * 128;
                    const uint32_t bar = bars + 8 * (B_BF + s), dst = sb + F_R2 + s * 32768;
                    mbar_expect(bar, ng * 8192);
                    for (int i = 0; i < ng; i++) {
                        tma2d(dst + i * 4096, &tm_g, c0 + i * 32, kb * 64, bar);
                        tma2d(dst + 16384 + i * 4096, &tm_u, c0 + i * 32, kb * 64, bar);
                    }
                };
                for (int i = 0; i < 8; i++) {
                    const uint32_t bar = bars + 8 * (B_FA + (i >> 1));
                    if (!(i & 1)) mbar_expect(bar, 49152);
                    tma2d(sb + F_R2 + 32768 + i * 8192, &tm_o, nt * 64, i * 64, bar);
                }
                pdl_wait();
                TL(16);
                for (int i = 0; i < 8; i++)
                    bulk_g2s(sb + i * 16384, g_ao + (size_t)(mb * 8 + i) * 8192, 16384, bars + 8 * (B_FA + (i >> 1)));
                load_b(0);
                if (blockIdx.x == 0)
                    for (int i = 0; i < 32; i++) g_cnt[i] = 0;
                mbar_wait(bars + 8 * B_ADONE, 0);
                load_b(1); load_b(2);
                poll_count(&g_cnt2[mb], 8);
                TL(17);
                for (int kb = 0; kb < 8; kb++) {
                    const uint32_t bar = bars + 8 * (B_HF + (kb >> 1));
                    if (!(kb & 1)) mbar_expect(bar, (kb >> 1) == ntA ? 16384 : 32768);
                    if (kb != nt) bulk_g2s(sb + kb * 16384, g_h + (size_t)(mb * 8 + kb) * 8192, 16384, bar);
                }
                for (int it = 3; it < 16; it++) {
                    mbar_wait(bars + 8 * (B_BE + it % 3), (it / 3 - 1) & 1);
                    load_b(it);
                }
                mbar_wait(bars + 8 * B_BDONE, 0);
                for (int i = 0; i < 6; i++) {
                    const uint32_t bar = bars + 8 * (B_CF + i);
                    mbar_expect(bar, 32768);
                    tma2d(sb + i * 32768 + 16384, &tm_d, ntA * 128, (2 * i + r) * 64, bar);
                    tma2d(sb + i * 32768 + 24576, &tm_d, ntA * 128 + 64, (2 * i + r) * 64, bar);
                }
                poll_count(&g_cnt2[16 + mb], 8);
                TL(18);
                for (int kb = 0; kb < 14; kb++) {
                    const int s = kb % 6;
                    const uint32_t bar = bars + 8 * (B_CF + s);
                    if (kb >= 6) {
                        mbar_wait(bars + 8 * (B_CE + s), ((kb / 6) - 1) & 1);
                        mbar_expect(bar, 32768);
                        tma2d(sb + s * 32768 + 16384, &tm_d, ntA * 128, (2 * kb + r) * 64, bar);
                        tma2d(sb + s * 32768 + 24576, &tm_d, ntA * 128 + 64, (2 * kb + r) * 64, bar);
                    }
                    bulk_g2s(sb + s * 32768, g_g + (size_t)(mb * 28 + 2 * kb + r) * 8192, 16384, bar);
                }
            }
            __syncwarp();
            asm volatile("barrier.cluster.wait.acquire.aligned;" ::: "memory");
        } else if (warp == 1) {
            asm volatile("barrier.cluster.wait.acquire.aligned;" ::: "memory");
            bar_sync(1, 288);
            if (lane == 0) {
                bulk_s2g(g_h + (size_t)(mb * 8 + nt) * 8192, sb + nt * 16384, 16384);
                bulk_commit();
                bulk_wait_all();
                asm volatile("fence.proxy.async.global;" ::: "memory");
                red_release(&g_cnt2[mb]);
                TL(9);
            }
            __syncwarp();
            bar_sync(2, 288);
            if (lane == 0) {
                bulk_s2g(g_g + ((size_t)mb * 224 + nt * 28 + 16) * 1024, sb + F_X, 24576);
                bulk_commit();
                bulk_wait_all();
                asm volatile("fence.proxy.async.global;" ::: "memory");
                red_release(&g_cnt2[16 + mb]);
                mbar_arrive_remote(mapa(bars + 8 * B_PRDY, 1 - r));
                TL(13);
            }
            __syncwarp();
            bar_sync(3, 288);
            if (lane == 0) {
                tma2d_store(&tm_out, sb, nt * 64, mb * 128);
                bulk_commit();
                bulk_wait_all();
                TL(15);
            }
        } else {
            asm volatile("barrier.cluster.wait.acquire.aligned;" ::: "memory");
            pdl_wait();
            float2* s_rs = (float2*)(smem + F_RS);
            float* s_cs = (float*)(smem + F_CS);
            for (int c = tid - 64; c < 448; c += 64)
                s_cs[c] = __ldcg(&g_cs2[(c >= 224 ? FF - 224 : 0) + nt * 224 + c]);
            if (lane == 0) poll_count(&g_cnt2[mb], 8);
            __syncwarp();
            for (int rr = tid - 64; rr < 128; rr += 64) {
                const float4* hp = (const float4*)(g_hstat + (size_t)(mb * 128 + rr) * 8);
                float4 a = __ldcg(hp), b = __ldcg(hp + 1), c = __ldcg(hp + 2), d = __ldcg(hp + 3);
                float mean = 0.125f * (a.x + a.z + b.x + b.z + c.x + c.z + d.x + d.z);
                float m2 = a.y + a.w + b.y + b.w + c.y + c.w + d.y + d.w;
                float e;
                e = a.x - mean; m2 = fmaf(64.f * e, e, m2); e = a.z - mean; m2 = fmaf(64.f * e, e, m2);
                e = b.x - mean; m2 = fmaf(64.f * e, e, m2); e = b.z - mean; m2 = fmaf(64.f * e, e, m2);
                e = c.x - mean; m2 = fmaf(64.f * e, e, m2); e = c.z - mean; m2 = fmaf(64.f * e, e, m2);
                e = d.x - mean; m2 = fmaf(64.f * e, e, m2); e = d.z - mean; m2 = fmaf(64.f * e, e, m2);
                s_rs[rr] = make_float2(rsqrtf(m2 * (1.0f / DM) + 1e-5f), -mean);
            }
            __syncwarp();
            if (lane == 0) mbar_arrive(bars + 8 * B_AUX);
        }
    } else {
        asm volatile("setmaxnreg.inc.sync.aligned.u32 216;");
        const int wgi = (warp >> 2) - 1, ww = warp & 3, ctid = tid - 128;
        const int g = lane >> 2, t = lane & 3;
        const int rl = wgi * 64 + ww * 16 + g, row = mb * 128 + rl;
        const int rgl = wgi * 8 + ww * 2;
        const float2* s_rs = (const float2*)(smem + F_RS);
        const float* s_cs = (const float*)(smem + F_CS);
        const uint32_t stl = ((lane >> 4) * 16 + rgl + ((lane >> 3) & 1)) * 128 + (lane & 7) * 16;
        TL(23);
        {
            uint32_t xr[16];
            const uint32_t* xp = (const uint32_t*)(x + (size_t)row * DM + nt * 64) + t;
#pragma unroll
            for (int j = 0; j < 8; j++) { xr[2 * j] = __ldg(xp + 4 * j); xr[2 * j + 1] = __ldg(xp + 8 * (DM / 2) + 4 * j); }
            float acc[32];
#pragma unroll 1
            for (int i = 0; i < 8; i++) {
                if (!(i & 1)) { mbar_wait(bars + 8 * (B_FA + (i >> 1)), 0); if (i == 0) TL(19); }
                uint64_t ad = make_desc(sb + i * 16384 + wgi * 1024, 2048, 128, 0);
                uint64_t bd = make_desc(sb + F_R2 + 32768 + i * 8192, 8192, 1024, 1);
                WG_FENCE();
#pragma unroll
                for (int k = 0; k < 4; k++) wgmma_ss_n64(acc, ad + k * 256, bd + k * 128, (i | k) != 0);
                WG_COMMIT();
            }
            wg_wait<0>();
            fence_regs(acc);
            TL(7);
            bar_sync(4, 256);
            if (tid == 128) mbar_arrive(bars + 8 * B_ADONE);
            float v0[16], v1[16];
            float s0 = 0.f, s1 = 0.f;
#pragma unroll
            for (int j2 = 0; j2 < 4; j2++) {
                uint32_t u[4];
#pragma unroll
                for (int jj = 0; jj < 2; jj++) {
                    const int j = 2 * j2 + jj;
                    u[2 * jj] = pack_bf16(bf_lo(xr[2 * j]) + acc[4 * j], bf_hi(xr[2 * j]) + acc[4 * j + 1]);
                    u[2 * jj + 1] = pack_bf16(bf_lo(xr[2 * j + 1]) + acc[4 * j + 2], bf_hi(xr[2 * j + 1]) + acc[4 * j + 3]);
                    v0[2 * j] = bf_lo(u[2 * jj]); v0[2 * j + 1] = bf_hi(u[2 * jj]);
                    v1[2 * j] = bf_lo(u[2 * jj + 1]); v1[2 * j + 1] = bf_hi(u[2 * jj + 1]);
                    s0 += v0[2 * j] + v0[2 * j + 1];
                    s1 += v1[2 * j] + v1[2 * j + 1];
                }
                stsm4(sb + nt * 16384 + stl + j2 * 4096, u[0], u[1], u[2], u[3]);
            }
            fence_proxy_async();
            float m0 = s0 * (1.0f / 16), m1 = s1 * (1.0f / 16), q0 = 0.f, q1 = 0.f;
#pragma unroll
            for (int i = 0; i < 16; i++) {
                float d0 = v0[i] - m0, d1 = v1[i] - m1;
                q0 = fmaf(d0, d0, q0); q1 = fmaf(d1, d1, q1);
            }
#pragma unroll
            for (int st = 0; st < 2; st++) {
                float hn = st ? 16.f : 8.f;
                float om0 = __shfl_xor_sync(0xffffffffu, m0, 1 << st), oq0 = __shfl_xor_sync(0xffffffffu, q0, 1 << st);
                float om1 = __shfl_xor_sync(0xffffffffu, m1, 1 << st), oq1 = __shfl_xor_sync(0xffffffffu, q1, 1 << st);
                float d0 = om0 - m0, d1 = om1 - m1;
                q0 = q0 + oq0 + d0 * d0 * hn; q1 = q1 + oq1 + d1 * d1 * hn;
                m0 = 0.5f * (m0 + om0); m1 = 0.5f * (m1 + om1);
            }
            if (t == 0) {
                g_hstat[row * 8 + nt] = make_float2(m0, q0);
                g_hstat[(row + 8) * 8 + nt] = make_float2(m1, q1);
            }
            bar_arrive(1, 288);
            bar_sync(4, 256);
            TL(8);
        }
        uint32_t* gp = (uint32_t*)g_g + (((size_t)mb * 224 + nt * 28) * 16 + rgl) * 32 + lane;
        {
            float ag[64], au[64];
#pragma unroll 1
            for (int kb = 0; kb < 8; kb++) {
                const int s = kb % 3;
                if (!(kb & 1)) mbar_wait(bars + 8 * (B_HF + (kb >> 1)), 0);
                mbar_wait(bars + 8 * (B_BF + s), (kb / 3) & 1);
                if (warp == 4) TX(32 + kb);
                uint64_t ad = make_desc(sb + kb * 16384 + wgi * 1024, 2048, 128, 0);
                uint64_t bd = make_desc(sb + F_R2 + s * 32768, 4096, 512, 2);
                WG_FENCE();
#pragma unroll
                for (int k = 0; k < 4; k++) {
                    wgmma_ss_n128(ag, ad + k * 256, bd + k * 64, (kb | k) != 0);
                    wgmma_ss_n128(au, ad + k * 256, bd + 1024 + k * 64, (kb | k) != 0);
                }
                WG_COMMIT();
                if (kb > 0) {
                    wg_wait<1>();
                    if (lane == 0) mbar_arrive(bars + 8 * (B_BE + (kb - 1) % 3));
                }
            }
            wg_wait<0>();
            if (lane == 0) mbar_arrive(bars + 8 * (B_BE + 7 % 3));
            fence_regs(ag); fence_regs(au);
            TL(10);
            mbar_wait(bars + 8 * B_AUX, 0);
            ffn_epilogue<16, false>(ag, au, s_cs, 0, gp, 0, s_rs[rl], s_rs[rl + 8], lane);
        }
        uint32_t hr[16];
        {
            const uint32_t* hs = (const uint32_t*)(smem + nt * 16384) + rgl * 32 + lane;
#pragma unroll
            for (int j = 0; j < 8; j++) { hr[2 * j] = hs[j * 512]; hr[2 * j + 1] = hs[j * 512 + 32]; }
        }
        {
            float ag[48], au[48];
#pragma unroll 1
            for (int kb = 0; kb < 8; kb++) {
                const int it = 8 + kb, s = it % 3;
                mbar_wait(bars + 8 * (B_BF + s), (it / 3) & 1);
                if (warp == 4) TX(32 + it);
                uint64_t ad = make_desc(sb + kb * 16384 + wgi * 1024, 2048, 128, 0);
                uint64_t bd = make_desc(sb + F_R2 + s * 32768, 4096, 512, 2);
                WG_FENCE();
#pragma unroll
                for (int k = 0; k < 4; k++) {
                    wgmma_ss_n96(ag, ad + k * 256, bd + k * 64, (kb | k) != 0);
                    wgmma_ss_n96(au, ad + k * 256, bd + 1024 + k * 64, (kb | k) != 0);
                }
                WG_COMMIT();
                if (kb > 0) {
                    wg_wait<1>();
                    if (lane == 0) mbar_arrive(bars + 8 * (B_BE + (it - 1) % 3));
                }
            }
            wg_wait<0>();
            if (lane == 0) mbar_arrive(bars + 8 * B_BDONE);
            fence_regs(ag); fence_regs(au);
            TL(11);
            mbar_wait(bars + 8 * B_BDONE, 0);
            ffn_epilogue<12, true>(ag, au, s_cs, 128, gp, sb + F_X + stl, s_rs[rl], s_rs[rl + 8], lane);
            fence_proxy_async();
            bar_arrive(2, 288);
            TL(12);
        }
        {
            float acc[64];
#pragma unroll 1
            for (int kb = 0; kb < 14; kb++) {
                const int s = kb % 6;
                mbar_wait(bars + 8 * (B_CF + s), (kb / 6) & 1);
                if (warp == 4) TX(96 + kb);
                uint64_t ad = make_desc(sb + s * 32768 + wgi * 1024, 2048, 128, 0);
                uint64_t bd = make_desc(sb + s * 32768 + 16384, 8192, 1024, 1);
                WG_FENCE();
#pragma unroll
                for (int k = 0; k < 4; k++) wgmma_ss_n128(acc, ad + k * 256, bd + k * 128, (kb | k) != 0);
                WG_COMMIT();
                if (kb > 0) {
                    wg_wait<1>();
                    if (lane == 0) mbar_arrive(bars + 8 * (B_CE + (kb - 1) % 6));
                }
            }
            wg_wait<0>();
            fence_regs(acc);
            TL(14);
            asm volatile("barrier.cluster.wait.acquire.aligned;" ::: "memory");
            mbar_wait_cluster(bars + 8 * B_PRDY, 0);
            float o[32];
            if (r == 0) xchg<0>(acc, o, sb, smem, B_XC, ctid); else xchg<1>(acc, o, sb, smem, B_XC, ctid);
            TL(22);
            bar_sync(4, 256);
            const float a0 = s_rs[rl].x, a1 = s_rs[rl + 8].x;
            const float k0 = 0.5f * a0 * a0, k1 = 0.5f * a1 * a1;
            const int srow = wgi * 64 + ww * 16 + ((lane >> 3) & 1) * 8 + (lane & 7);
#pragma unroll
            for (int j2 = 0; j2 < 4; j2++) {
                uint32_t u[4];
#pragma unroll
                for (int jj = 0; jj < 2; jj++) {
                    const int j = 2 * j2 + jj;
                    u[2 * jj] = pack_bf16(fmaf(k0, o[4 * j], bf_lo(hr[2 * j])), fmaf(k0, o[4 * j + 1], bf_hi(hr[2 * j])));
                    u[2 * jj + 1] = pack_bf16(fmaf(k1, o[4 * j + 2], bf_lo(hr[2 * j + 1])), fmaf(k1, o[4 * j + 3], bf_hi(hr[2 * j + 1])));
                }
                const int chunk = 2 * j2 + (lane >> 4);
                stsm4(sb + srow * 128 + ((chunk ^ (lane & 7)) * 16), u[0], u[1], u[2], u[3]);
            }
            fence_proxy_async();
            bar_arrive(3, 288);
        }
    }
}

typedef CUresult (*EncodeFn)(CUtensorMap*, CUtensorMapDataType, cuuint32_t, void*, const cuuint64_t*, const cuuint64_t*,
                             const cuuint32_t*, const cuuint32_t*, CUtensorMapInterleave, CUtensorMapSwizzle,
                             CUtensorMapL2promotion, CUtensorMapFloatOOBfill);

void encode(EncodeFn fn, CUtensorMap* m, const void* ptr, int rank, const cuuint64_t* dims, const cuuint64_t* strides,
            const cuuint32_t* box, CUtensorMapSwizzle swz) {
    cuuint32_t es[3] = {1, 1, 1};
    fn(m, CU_TENSOR_MAP_DATA_TYPE_BFLOAT16, rank, (void*)ptr, dims, strides, box, es, CU_TENSOR_MAP_INTERLEAVE_NONE, swz,
       CU_TENSOR_MAP_L2_PROMOTION_L2_256B, CU_TENSOR_MAP_FLOAT_OOB_FILL_NONE);
}

template <typename... KArgs, typename... Args>
void launch(void (*kern)(KArgs...), int grid, int block, int smem, bool pdl, Args... args) {
    cudaLaunchConfig_t cfg = {};
    cfg.gridDim = dim3(grid); cfg.blockDim = dim3(block); cfg.dynamicSmemBytes = smem;
    cfg.stream = cudaStreamPerThread;
    cudaLaunchAttribute at[1];
    at[0].id = cudaLaunchAttributeProgrammaticStreamSerialization;
    at[0].val.programmaticStreamSerializationAllowed = 1;
    cfg.attrs = at; cfg.numAttrs = pdl ? 1 : 0;
    cudaLaunchKernelEx(&cfg, kern, KArgs(args)...);
}

}

extern "C" void kernel_launch(void* const* d_in, const int* in_sizes, int n_in, void* d_out, int out_size) {
    const __nv_bfloat16* x = (const __nv_bfloat16*)d_in[0];
    const __nv_bfloat16* wqkv = (const __nv_bfloat16*)d_in[1];
    const __nv_bfloat16* wo = (const __nv_bfloat16*)d_in[2];
    const __nv_bfloat16* wgate = (const __nv_bfloat16*)d_in[4];
    const __nv_bfloat16* wup = (const __nv_bfloat16*)d_in[5];
    const __nv_bfloat16* wdown = (const __nv_bfloat16*)d_in[6];
    __nv_bfloat16* out = (__nv_bfloat16*)d_out;

    static CUtensorMap tm_x, tm_wqkv, tm_wo, tm_wg, tm_wu, tm_wd, tm_out;
    static const void* cached[7] = {nullptr, nullptr, nullptr, nullptr, nullptr, nullptr, nullptr};
    if (cached[0] != x || cached[1] != wqkv || cached[2] != wo || cached[3] != wgate || cached[4] != wup || cached[5] != wdown || cached[6] != out) {
        void* fp = nullptr;
        cudaDriverEntryPointQueryResult qr;
        cudaGetDriverEntryPoint("cuTensorMapEncodeTiled", &fp, cudaEnableDefault, &qr);
        EncodeFn fn = (EncodeFn)fp;
        { cuuint64_t d[2] = {512, 2048}, s[1] = {1024}; cuuint32_t b[2] = {64, 128};
          encode(fn, &tm_x, x, 2, d, s, b, CU_TENSOR_MAP_SWIZZLE_128B);
          encode(fn, &tm_out, out, 2, d, s, b, CU_TENSOR_MAP_SWIZZLE_128B); }
        { cuuint64_t d[3] = {64, 512, 24}, s[2] = {3072, 128}; cuuint32_t b[3] = {64, 64, 3};
          encode(fn, &tm_wqkv, wqkv, 3, d, s, b, CU_TENSOR_MAP_SWIZZLE_128B); }
        { cuuint64_t d[2] = {512, 512}, s[1] = {1024}; cuuint32_t b[2] = {64, 64};
          encode(fn, &tm_wo, wo, 2, d, s, b, CU_TENSOR_MAP_SWIZZLE_128B); }
        { cuuint64_t d[2] = {1792, 512}, s[1] = {3584}; cuuint32_t b[2] = {32, 64};
          encode(fn, &tm_wg, wgate, 2, d, s, b, CU_TENSOR_MAP_SWIZZLE_64B);
          encode(fn, &tm_wu, wup, 2, d, s, b, CU_TENSOR_MAP_SWIZZLE_64B); }
        { cuuint64_t d[2] = {512, 1792}, s[1] = {1024}; cuuint32_t b[2] = {64, 64};
          encode(fn, &tm_wd, wdown, 2, d, s, b, CU_TENSOR_MAP_SWIZZLE_128B); }
        cudaFuncSetAttribute(qkv_kernel, cudaFuncAttributeMaxDynamicSharedMemorySize, K1_SMEM);
        cudaFuncSetAttribute(attn_kernel, cudaFuncAttributeMaxDynamicSharedMemorySize, AT_SMEM);
        cudaFuncSetAttribute(tail_kernel, cudaFuncAttributeMaxDynamicSharedMemorySize, F_SMEM);
        cached[0] = x; cached[1] = wqkv; cached[2] = wo; cached[3] = wgate; cached[4] = wup; cached[5] = wdown; cached[6] = out;
    }
    launch(qkv_kernel, 128, 384, K1_SMEM, false, tm_x, tm_wqkv, x, wqkv);
    launch(attn_kernel, 132, 512, AT_SMEM, true, wgate, wup, wo, wdown);
    launch(tail_kernel, 128, 384, F_SMEM, true, tm_wo, tm_wg, tm_wu, tm_wd, tm_out, x);
}
```

```cpp
#include <cuda_runtime.h>
#include <cuda_bf16.h>
#include <cuda.h>
#include <stdint.h>

#define TAILMAP 1
namespace {

constexpr int S_LEN = 2048, DM = 512, NH = 32, FF = 1792;

__device__ __align__(1024) __nv_bfloat16 g_qkv[3 * NH * S_LEN * 16];
__device__ __align__(1024) __nv_bfloat16 g_ao[S_LEN * DM];
__device__ __align__(1024) __nv_bfloat16 g_h[S_LEN * DM];
__device__ __align__(1024) __nv_bfloat16 g_g[S_LEN * FF];
__device__ __align__(16) float2 g_rowstat1[S_LEN];
__device__ float g_cs1_part[16 * 1536];
__device__ unsigned int g_cnt[32];
__device__ unsigned int g_cnt2[64];
__device__ float g_nrm[3 * NH * 128];
__device__ float2 g_hstat[S_LEN * 8];
__device__ float g_cs2[2 * FF];

#define TL(slot)
#define TX(slot)
__device__ __forceinline__ uint32_t smem_u32(const void* p) { return (uint32_t)__cvta_generic_to_shared(p); }
__device__ __forceinline__ void mbar_init(uint32_t a, int c) { asm volatile("mbarrier.init.shared.b64 [%0], %1;" :: "r"(a), "r"(c)); }
__device__ __forceinline__ void mbar_expect(uint32_t a, int bytes) { asm volatile("mbarrier.arrive.expect_tx.shared.b64 _, [%0], %1;" :: "r"(a), "r"(bytes) : "memory"); }
__device__ __forceinline__ void mbar_arrive(uint32_t a) { asm volatile("mbarrier.arrive.shared.b64 _, [%0];" :: "r"(a) : "memory"); }
__device__ __forceinline__ void mbar_wait(uint32_t a, int parity) {
    uint32_t done;
    int it = 0;
    do {
        asm volatile("{\n.reg .pred p;\nmbarrier.try_wait.parity.shared.b64 p, [%1], %2;\nselp.u32 %0, 1, 0, p;\n}"
                     : "=r"(done) : "r"(a), "r"(parity) : "memory");
        if (++it > (1 << 24)) __trap();
    } while (!done);
}
__device__ __forceinline__ void bulk_g2s(uint32_t dst, const void* src, int bytes, uint32_t bar) {
    asm volatile("cp.async.bulk.shared::cluster.global.mbarrier::complete_tx::bytes [%0], [%1], %2, [%3];"
                 :: "r"(dst), "l"(src), "r"(bytes), "r"(bar) : "memory");
}
__device__ __forceinline__ void tma2d(uint32_t dst, const CUtensorMap* m, int c0, int c1, uint32_t bar) {
    asm volatile("cp.async.bulk.tensor.2d.shared::cluster.global.mbarrier::complete_tx::bytes [%0], [%1, {%3, %4}], [%2];"
                 :: "r"(dst), "l"(m), "r"(bar), "r"(c0), "r"(c1) : "memory");
}
__device__ __forceinline__ void tma3d(uint32_t dst, const CUtensorMap* m, int c0, int c1, int c2, uint32_t bar) {
    asm volatile("cp.async.bulk.tensor.3d.shared::cluster.global.mbarrier::complete_tx::bytes [%0], [%1, {%3, %4, %5}], [%2];"
                 :: "r"(dst), "l"(m), "r"(bar), "r"(c0), "r"(c1), "r"(c2) : "memory");
}
__device__ __forceinline__ void prefetch_tmap(const CUtensorMap* m) { asm volatile("prefetch.tensormap [%0];" :: "l"(m) : "memory"); }
__device__ __forceinline__ void pdl_wait() { asm volatile("griddepcontrol.wait;" ::: "memory"); }
__device__ __forceinline__ void pdl_launch() { asm volatile("griddepcontrol.launch_dependents;" ::: "memory"); }
__device__ __forceinline__ void fence_barrier_init() { asm volatile("fence.mbarrier_init.release.cluster;" ::: "memory"); }
__device__ __forceinline__ void fence_proxy_async() { asm volatile("fence.proxy.async.shared::cta;" ::: "memory"); }
__device__ __forceinline__ uint64_t make_desc(uint32_t saddr, uint32_t lbo, uint32_t sbo, uint32_t swz) {
    return (uint64_t)((saddr & 0x3FFFF) >> 4) | ((uint64_t)((lbo & 0x3FFFF) >> 4) << 16) |
           ((uint64_t)((sbo & 0x3FFFF) >> 4) << 32) | ((uint64_t)swz << 62);
}
#define WG_FENCE() asm volatile("wgmma.fence.sync.aligned;" ::: "memory")
#define WG_COMMIT() asm volatile("wgmma.commit_group.sync.aligned;" ::: "memory")
template <int N> __device__ __forceinline__ void wg_wait() { asm volatile("wgmma.wait_group.sync.aligned %0;" :: "n"(N) : "memory"); }
template <int N> __device__ __forceinline__ void fence_regs(float (&d)[N]) {
#pragma unroll
    for (int i = 0; i < N; i++) asm volatile("" : "+f"(d[i]) :: "memory");
}
__device__ __forceinline__ float ex2f(float x) { float y; asm("ex2.approx.ftz.f32 %0, %1;" : "=f"(y) : "f"(x)); return y; }
__device__ __forceinline__ float tanh_fast(float x) { float y; asm("tanh.approx.f32 %0, %1;" : "=f"(y) : "f"(x)); return y; }
__device__ __forceinline__ uint32_t pack_bf16(float lo, float hi) { uint32_t r; asm("cvt.rn.bf16x2.f32 %0, %1, %2;" : "=r"(r) : "f"(hi), "f"(lo)); return r; }
__device__ __forceinline__ float bf_lo(uint32_t u) { return __uint_as_float(u << 16); }
__device__ __forceinline__ float bf_hi(uint32_t u) { return __uint_as_float(u & 0xFFFF0000u); }
__device__ __forceinline__ uint32_t hfma2(uint32_t a, uint32_t b, uint32_t c) { uint32_t r; asm("fma.rn.f16x2 %0, %1, %2, %3;" : "=r"(r) : "r"(a), "r"(b), "r"(c)); return r; }
__device__ __forceinline__ uint32_t hmul2(uint32_t a, uint32_t b) { uint32_t r; asm("mul.rn.f16x2 %0, %1, %2;" : "=r"(r) : "r"(a), "r"(b)); return r; }
__device__ __forceinline__ unsigned int ld_acquire(const unsigned int* p) { unsigned int v; asm volatile("ld.acquire.gpu.u32 %0, [%1];" : "=r"(v) : "l"(p) : "memory"); return v; }
__device__ __forceinline__ void red_release(unsigned int* p) { asm volatile("red.release.gpu.global.add.u32 [%0], 1;" :: "l"(p) : "memory"); }
__device__ __forceinline__ void stsm4(uint32_t addr, uint32_t a, uint32_t b, uint32_t c, uint32_t d) {
    asm volatile("stmatrix.sync.aligned.m8n8.x4.shared.b16 [%0], {%1,%2,%3,%4};" :: "r"(addr), "r"(a), "r"(b), "r"(c), "r"(d) : "memory");
}
__device__ __forceinline__ void bulk_s2g(void* dst, uint32_t src, int bytes) {
    asm volatile("cp.async.bulk.global.shared::cta.bulk_group [%0], [%1], %2;" :: "l"(dst), "r"(src), "r"(bytes) : "memory");
}
__device__ __forceinline__ void bulk_commit() { asm volatile("cp.async.bulk.commit_group;" ::: "memory"); }
__device__ __forceinline__ void bulk_wait_all() { asm volatile("cp.async.bulk.wait_group 0;" ::: "memory"); }
__device__ __forceinline__ void bulk_wait_read() { asm volatile("cp.async.bulk.wait_group.read 0;" ::: "memory"); }
__device__ __forceinline__ void bar_sync(int id, int n) { asm volatile("bar.sync %0, %1;" :: "r"(id), "r"(n) : "memory"); }
__device__ __forceinline__ void bar_arrive(int id, int n) { asm volatile("bar.arrive %0, %1;" :: "r"(id), "r"(n) : "memory"); }
__device__ __forceinline__ float warp_sum(float v) {
#pragma unroll
    for (int o = 16; o; o >>= 1) v += __shfl_xor_sync(0xffffffffu, v, o);
    return v;
}
__device__ __forceinline__ float warp_max(float v) {
#pragma unroll
    for (int o = 16; o; o >>= 1) v = fmaxf(v, __shfl_xor_sync(0xffffffffu, v, o));
    return v;
}

__device__ __forceinline__ void wgmma_ss_n64(float (&d)[32], uint64_t adesc, uint64_t bdesc, int scale_d) {
    asm volatile("{\n.reg .pred p;\nsetp.ne.b32 p, %34, 0;\n"
      "wgmma.mma_async.sync.aligned.m64n64k16.f32.bf16.bf16 {%0,%1,%2,%3,%4,%5,%6,%7,%8,%9,%10,%11,%12,%13,%14,%15,%16,%17,%18,%19,%20,%21,%22,%23,%24,%25,%26,%27,%28,%29,%30,%31}, %32, %33, p, 1, 1, 0, 1;\n}"
      : "+f"(d[0]), "+f"(d[1]), "+f"(d[2]), "+f"(d[3]), "+f"(d[4]), "+f"(d[5]), "+f"(d[6]), "+f"(d[7]), "+f"(d[8]), "+f"(d[9]), "+f"(d[10]), "+f"(d[11]), "+f"(d[12]), "+f"(d[13]), "+f"(d[14]), "+f"(d[15]), "+f"(d[16]), "+f"(d[17]), "+f"(d[18]), "+f"(d[19]), "+f"(d[20]), "+f"(d[21]), "+f"(d[22]), "+f"(d[23]), "+f"(d[24]), "+f"(d[25]), "+f"(d[26]), "+f"(d[27]), "+f"(d[28]), "+f"(d[29]), "+f"(d[30]), "+f"(d[31])
      : "l"(adesc), "l"(bdesc), "r"(scale_d));
}
__device__ __forceinline__ void wgmma_ss_n96(float (&d)[48], uint64_t adesc, uint64_t bdesc, int scale_d) {
    asm volatile("{\n.reg .pred p;\nsetp.ne.b32 p, %50, 0;\n"
      "wgmma.mma_async.sync.aligned.m64n96k16.f32.bf16.bf16 {%0,%1,%2,%3,%4,%5,%6,%7,%8,%9,%10,%11,%12,%13,%14,%15,%16,%17,%18,%19,%20,%21,%22,%23,%24,%25,%26,%27,%28,%29,%30,%31,%32,%33,%34,%35,%36,%37,%38,%39,%40,%41,%42,%43,%44,%45,%46,%47}, %48, %49, p, 1, 1, 0, 1;\n}"
      : "+f"(d[0]), "+f"(d[1]), "+f"(d[2]), "+f"(d[3]), "+f"(d[4]), "+f"(d[5]), "+f"(d[6]), "+f"(d[7]), "+f"(d[8]), "+f"(d[9]), "+f"(d[10]), "+f"(d[11]), "+f"(d[12]), "+f"(d[13]), "+f"(d[14]), "+f"(d[15]), "+f"(d[16]), "+f"(d[17]), "+f"(d[18]), "+f"(d[19]), "+f"(d[20]), "+f"(d[21]), "+f"(d[22]), "+f"(d[23]), "+f"(d[24]), "+f"(d[25]), "+f"(d[26]), "+f"(d[27]), "+f"(d[28]), "+f"(d[29]), "+f"(d[30]), "+f"(d[31]), "+f"(d[32]), "+f"(d[33]), "+f"(d[34]), "+f"(d[35]), "+f"(d[36]), "+f"(d[37]), "+f"(d[38]), "+f"(d[39]), "+f"(d[40]), "+f"(d[41]), "+f"(d[42]), "+f"(d[43]), "+f"(d[44]), "+f"(d[45]), "+f"(d[46]), "+f"(d[47])
      : "l"(adesc), "l"(bdesc), "r"(scale_d));
}
__device__ __forceinline__ void wgmma_ss_n128(float (&d)[64], uint64_t adesc, uint64_t bdesc, int scale_d) {
    asm volatile("{\n.reg .pred p;\nsetp.ne.b32 p, %66, 0;\n"
      "wgmma.mma_async.sync.aligned.m64n128k16.f32.bf16.bf16 {%0,%1,%2,%3,%4,%5,%6,%7,%8,%9,%10,%11,%12,%13,%14,%15,%16,%17,%18,%19,%20,%21,%22,%23,%24,%25,%26,%27,%28,%29,%30,%31,%32,%33,%34,%35,%36,%37,%38,%39,%40,%41,%42,%43,%44,%45,%46,%47,%48,%49,%50,%51,%52,%53,%54,%55,%56,%57,%58,%59,%60,%61,%62,%63}, %64, %65, p, 1, 1, 0, 1;\n}"
      : "+f"(d[0]), "+f"(d[1]), "+f"(d[2]), "+f"(d[3]), "+f"(d[4]), "+f"(d[5]), "+f"(d[6]), "+f"(d[7]), "+f"(d[8]), "+f"(d[9]), "+f"(d[10]), "+f"(d[11]), "+f"(d[12]), "+f"(d[13]), "+f"(d[14]), "+f"(d[15]), "+f"(d[16]), "+f"(d[17]), "+f"(d[18]), "+f"(d[19]), "+f"(d[20]), "+f"(d[21]), "+f"(d[22]), "+f"(d[23]), "+f"(d[24]), "+f"(d[25]), "+f"(d[26]), "+f"(d[27]), "+f"(d[28]), "+f"(d[29]), "+f"(d[30]), "+f"(d[31]), "+f"(d[32]), "+f"(d[33]), "+f"(d[34]), "+f"(d[35]), "+f"(d[36]), "+f"(d[37]), "+f"(d[38]), "+f"(d[39]), "+f"(d[40]), "+f"(d[41]), "+f"(d[42]), "+f"(d[43]), "+f"(d[44]), "+f"(d[45]), "+f"(d[46]), "+f"(d[47]), "+f"(d[48]), "+f"(d[49]), "+f"(d[50]), "+f"(d[51]), "+f"(d[52]), "+f"(d[53]), "+f"(d[54]), "+f"(d[55]), "+f"(d[56]), "+f"(d[57]), "+f"(d[58]), "+f"(d[59]), "+f"(d[60]), "+f"(d[61]), "+f"(d[62]), "+f"(d[63])
      : "l"(adesc), "l"(bdesc), "r"(scale_d));
}
__device__ __forceinline__ void wgmma_ss_n192(float (&d)[96], uint64_t adesc, uint64_t bdesc, int scale_d) {
    asm volatile("{\n.reg .pred p;\nsetp.ne.b32 p, %98, 0;\n"
      "wgmma.mma_async.sync.aligned.m64n192k16.f32.bf16.bf16 {%0,%1,%2,%3,%4,%5,%6,%7,%8,%9,%10,%11,%12,%13,%14,%15,%16,%17,%18,%19,%20,%21,%22,%23,%24,%25,%26,%27,%28,%29,%30,%31,%32,%33,%34,%35,%36,%37,%38,%39,%40,%41,%42,%43,%44,%45,%46,%47,%48,%49,%50,%51,%52,%53,%54,%55,%56,%57,%58,%59,%60,%61,%62,%63,%64,%65,%66,%67,%68,%69,%70,%71,%72,%73,%74,%75,%76,%77,%78,%79,%80,%81,%82,%83,%84,%85,%86,%87,%88,%89,%90,%91,%92,%93,%94,%95}, %96, %97, p, 1, 1, 0, 1;\n}"
      : "+f"(d[0]), "+f"(d[1]), "+f"(d[2]), "+f"(d[3]), "+f"(d[4]), "+f"(d[5]), "+f"(d[6]), "+f"(d[7]), "+f"(d[8]), "+f"(d[9]), "+f"(d[10]), "+f"(d[11]), "+f"(d[12]), "+f"(d[13]), "+f"(d[14]), "+f"(d[15]), "+f"(d[16]), "+f"(d[17]), "+f"(d[18]), "+f"(d[19]), "+f"(d[20]), "+f"(d[21]), "+f"(d[22]), "+f"(d[23]), "+f"(d[24]), "+f"(d[25]), "+f"(d[26]), "+f"(d[27]), "+f"(d[28]), "+f"(d[29]), "+f"(d[30]), "+f"(d[31]), "+f"(d[32]), "+f"(d[33]), "+f"(d[34]), "+f"(d[35]), "+f"(d[36]), "+f"(d[37]), "+f"(d[38]), "+f"(d[39]), "+f"(d[40]), "+f"(d[41]), "+f"(d[42]), "+f"(d[43]), "+f"(d[44]), "+f"(d[45]), "+f"(d[46]), "+f"(d[47]), "+f"(d[48]), "+f"(d[49]), "+f"(d[50]), "+f"(d[51]), "+f"(d[52]), "+f"(d[53]), "+f"(d[54]), "+f"(d[55]), "+f"(d[56]), "+f"(d[57]), "+f"(d[58]), "+f"(d[59]), "+f"(d[60]), "+f"(d[61]), "+f"(d[62]), "+f"(d[63]), "+f"(d[64]), "+f"(d[65]), "+f"(d[66]), "+f"(d[67]), "+f"(d[68]), "+f"(d[69]), "+f"(d[70]), "+f"(d[71]), "+f"(d[72]), "+f"(d[73]), "+f"(d[74]), "+f"(d[75]), "+f"(d[76]), "+f"(d[77]), "+f"(d[78]), "+f"(d[79]), "+f"(d[80]), "+f"(d[81]), "+f"(d[82]), "+f"(d[83]), "+f"(d[84]), "+f"(d[85]), "+f"(d[86]), "+f"(d[87]), "+f"(d[88]), "+f"(d[89]), "+f"(d[90]), "+f"(d[91]), "+f"(d[92]), "+f"(d[93]), "+f"(d[94]), "+f"(d[95])
      : "l"(adesc), "l"(bdesc), "r"(scale_d));
}
__device__ __forceinline__ void qk_wgmma_n64(float (&d)[32], const uint32_t (&a)[4], uint64_t desc) {
    asm volatile("wgmma.mma_async.sync.aligned.m64n64k16.f32.bf16.bf16 {%0,%1,%2,%3,%4,%5,%6,%7,%8,%9,%10,%11,%12,%13,%14,%15,%16,%17,%18,%19,%20,%21,%22,%23,%24,%25,%26,%27,%28,%29,%30,%31}, {%32,%33,%34,%35}, %36, 0, 1, 1, 0;"
      : "=f"(d[0]), "=f"(d[1]), "=f"(d[2]), "=f"(d[3]), "=f"(d[4]), "=f"(d[5]), "=f"(d[6]), "=f"(d[7]), "=f"(d[8]), "=f"(d[9]), "=f"(d[10]), "=f"(d[11]), "=f"(d[12]), "=f"(d[13]), "=f"(d[14]), "=f"(d[15]), "=f"(d[16]), "=f"(d[17]), "=f"(d[18]), "=f"(d[19]), "=f"(d[20]), "=f"(d[21]), "=f"(d[22]), "=f"(d[23]), "=f"(d[24]), "=f"(d[25]), "=f"(d[26]), "=f"(d[27]), "=f"(d[28]), "=f"(d[29]), "=f"(d[30]), "=f"(d[31])
      : "r"(a[0]), "r"(a[1]), "r"(a[2]), "r"(a[3]), "l"(desc));
}

__device__ __forceinline__ void pv_wgmma(float (&d)[12], uint32_t a0, uint32_t a1, uint32_t a2, uint32_t a3, uint64_t desc) {
    asm volatile("wgmma.mma_async.sync.aligned.m64n24k16.f32.bf16.bf16 {%0,%1,%2,%3,%4,%5,%6,%7,%8,%9,%10,%11}, {%12,%13,%14,%15}, %16, 1, 1, 1, 1;"
      : "+f"(d[0]), "+f"(d[1]), "+f"(d[2]), "+f"(d[3]), "+f"(d[4]), "+f"(d[5]), "+f"(d[6]), "+f"(d[7]), "+f"(d[8]), "+f"(d[9]), "+f"(d[10]), "+f"(d[11])
      : "r"(a0), "r"(a1), "r"(a2), "r"(a3), "l"(desc));
}

__device__ __forceinline__ void tile_of(int bid, int& mb, int& nt) {
    int grp = bid >> 4, in = bid & 15;
    mb = (grp >> 1) * 4 + (in >> 2);
    nt = (grp & 1) * 4 + (in & 3);
}

constexpr int K1_STAGES = 5, K1_STAGE = 16384 + 24576;
constexpr int K1_BAR = K1_STAGES * K1_STAGE, K1_RS = K1_BAR + 128, K1_CS = K1_RS + 1024, K1_SMEM = K1_CS + 768;

__device__ __forceinline__ float2 row_stats_regs(uint4 a, uint4 b) {
    float v[16];
    v[0] = bf_lo(a.x); v[1] = bf_hi(a.x); v[2] = bf_lo(a.y); v[3] = bf_hi(a.y);
    v[4] = bf_lo(a.z); v[5] = bf_hi(a.z); v[6] = bf_lo(a.w); v[7] = bf_hi(a.w);
    v[8] = bf_lo(b.x); v[9] = bf_hi(b.x); v[10] = bf_lo(b.y); v[11] = bf_hi(b.y);
    v[12] = bf_lo(b.z); v[13] = bf_hi(b.z); v[14] = bf_lo(b.w); v[15] = bf_hi(b.w);
    float s = 0.f;
#pragma unroll
    for (int i = 0; i < 16; i++) s += v[i];
    float mean = warp_sum(s) * (1.0f / DM);
    float q = 0.f;
#pragma unroll
    for (int i = 0; i < 16; i++) { float d = v[i] - mean; q = fmaf(d, d, q); }
    float var = warp_sum(q) * (1.0f / DM);
    float rstd = rsqrtf(var + 1e-5f);
    return make_float2(rstd, -mean * rstd);
}
__device__ __forceinline__ float2 row_stats_x(const __nv_bfloat16* x, int row, int lane) {
    const uint4* p = (const uint4*)(x + (size_t)row * DM);
    return row_stats_regs(__ldg(p + lane), __ldg(p + 32 + lane));
}
__device__ __forceinline__ void colsum8(const __nv_bfloat16* w, int ld, int col, int k0, int nk, float (&s)[8]) {
#pragma unroll
    for (int i = 0; i < 8; i++) s[i] = 0.f;
    for (int k = k0; k < k0 + nk; k += 8) {
        uint4 u[8];
#pragma unroll
        for (int i = 0; i < 8; i++) u[i] = __ldg((const uint4*)(w + (size_t)(k + i) * ld + col));
#pragma unroll
        for (int i = 0; i < 8; i++) {
            s[0] += bf_lo(u[i].x); s[1] += bf_hi(u[i].x); s[2] += bf_lo(u[i].y); s[3] += bf_hi(u[i].y);
            s[4] += bf_lo(u[i].z); s[5] += bf_hi(u[i].z); s[6] += bf_lo(u[i].w); s[7] += bf_hi(u[i].w);
        }
    }
}
__device__ __forceinline__ bool wait_count(const unsigned int* p, unsigned int target, int lane) {
    int ok = 1;
    if (lane == 0) {
        int it = 0;
        while (ld_acquire(p) < target) { if (++it > (1 << 18)) { ok = 0; break; } }
    }
    ok = __shfl_sync(0xffffffffu, ok, 0);
    return ok != 0;
}

__global__ void __launch_bounds__(384, 1)
qkv_kernel(const __grid_constant__ CUtensorMap tm_x, const __grid_constant__ CUtensorMap tm_w,
           const __nv_bfloat16* __restrict__ x, const __nv_bfloat16* __restrict__ wqkv) {
    extern __shared__ __align__(1024) unsigned char smem[];
    const uint32_t sb = smem_u32(smem);
    const int tid = threadIdx.x, warp = __shfl_sync(0xffffffffu, tid >> 5, 0), lane = tid & 31;
    TL(0);
    int mb, nt;
    tile_of(blockIdx.x, mb, nt);
    const uint32_t full = sb + K1_BAR, empty = full + 40, auxb = full + 80;
    if (tid == 0) {
        prefetch_tmap(&tm_x); prefetch_tmap(&tm_w);
        for (int i = 0; i < K1_STAGES; i++) { mbar_init(full + 8 * i, 1); mbar_init(empty + 8 * i, 8); }
        mbar_init(auxb, 3);
        fence_barrier_init();
    }
    __syncthreads();
    pdl_launch();
    if (warp == 0) {
        if (blockIdx.x == 0) { g_cnt2[lane] = 0; g_cnt2[32 + lane] = 0; }
        if (lane == 0) {
            for (int kb = 0; kb < 8; kb++) {
                int s = kb % K1_STAGES;
                if (kb >= K1_STAGES) mbar_wait(empty + 8 * s, 0);
                mbar_expect(full + 8 * s, K1_STAGE);
                tma2d(sb + s * K1_STAGE, &tm_x, kb * 64, mb * 128, full + 8 * s);
                tma3d(sb + s * K1_STAGE + 16384, &tm_w, 0, kb * 64, nt * 3, full + 8 * s);
            }
        }
    } else if (warp < 4) {
        float2* s_rs = (float2*)(smem + K1_RS);
        float* s_cs = (float*)(smem + K1_CS);
        if (warp < 3) {
            const int r0 = mb * 128 + nt * 16 + (warp - 1) * 8;
            uint4 u[16];
#pragma unroll
            for (int i = 0; i < 8; i++) {
                const uint4* p = (const uint4*)(x + (size_t)(r0 + i) * DM);
                u[2 * i] = __ldg(p + lane); u[2 * i + 1] = __ldg(p + 32 + lane);
            }
            float2 mine = make_float2(0.f, 0.f);
#pragma unroll
            for (int i = 0; i < 8; i++) {
                float2 st = row_stats_regs(u[2 * i], u[2 * i + 1]);
                if (lane == i) mine = st;
            }
            if (lane < 8) g_rowstat1[r0 + lane] = mine;
            __syncwarp();
            if (lane == 0) red_release(&g_cnt[mb]);
        } else {
            uint4 u[24];
#pragma unroll
            for (int c = 0; c < 3; c++)
#pragma unroll
                for (int i = 0; i < 8; i++)
                    u[c * 8 + i] = __ldg((const uint4*)(wqkv + (size_t)(mb * 32 + (lane >> 3) * 8 + i) * 1536 + nt * 192 + (c * 8 + (lane & 7)) * 8));
#pragma unroll
            for (int c = 0; c < 3; c++) {
                float cs[8];
#pragma unroll
                for (int i = 0; i < 8; i++) cs[i] = 0.f;
#pragma unroll
                for (int i = 0; i < 8; i++) {
                    const uint4 w = u[c * 8 + i];
                    cs[0] += bf_lo(w.x); cs[1] += bf_hi(w.x); cs[2] += bf_lo(w.y); cs[3] += bf_hi(w.y);
                    cs[4] += bf_lo(w.z); cs[5] += bf_hi(w.z); cs[6] += bf_lo(w.w); cs[7] += bf_hi(w.w);
                }
#pragma unroll
                for (int i = 0; i < 8; i++) {
                    cs[i] += __shfl_xor_sync(0xffffffffu, cs[i], 8);
                    cs[i] += __shfl_xor_sync(0xffffffffu, cs[i], 16);
                }
                if (lane < 8) {
                    float4* d = (float4*)(g_cs1_part + mb * 1536 + nt * 192 + (c * 8 + lane) * 8);
                    d[0] = make_float4(cs[0], cs[1], cs[2], cs[3]);
                    d[1] = make_float4(cs[4], cs[5], cs[6], cs[7]);
                }
            }
            __syncwarp();
            if (lane == 0) red_release(&g_cnt[16 + nt]);
        }
        TX(8 + warp);
        if (warp == 1) {
            if (wait_count(&g_cnt[mb], 16, lane)) {
#pragma unroll
                for (int i = 0; i < 4; i++) s_rs[lane + 32 * i] = __ldcg(&g_rowstat1[mb * 128 + lane + 32 * i]);
            } else {
                for (int i = 0; i < 128; i++) {
                    float2 st = row_stats_x(x, mb * 128 + i, lane);
                    if (lane == 0) s_rs[i] = st;
                }
            }
        } else {
            int c0 = (warp - 2) * 96;
            if (wait_count(&g_cnt[16 + nt], 16, lane)) {
#pragma unroll
                for (int i = 0; i < 3; i++) {
                    float s = 0.f;
#pragma unroll
                    for (int p = 0; p < 16; p++) s += __ldcg(&g_cs1_part[p * 1536 + nt * 192 + c0 + lane + 32 * i]);
                    s_cs[c0 + lane + 32 * i] = s;
                }
            } else if (lane < 12) {
                float s[8];
                colsum8(wqkv, 1536, nt * 192 + c0 + lane * 8, 0, 512, s);
#pragma unroll
                for (int i = 0; i < 8; i++) s_cs[c0 + lane * 8 + i] = s[i];
            }
        }
        __syncwarp();
        TX(12 + warp);
        if (lane == 0) mbar_arrive(auxb);
        bar_sync(2, 256 + 96);
        const int a = tid - 32;
        if (a < 24) {
            const int col0 = nt * 192 + a * 8;
            const int which = col0 >> 9, head = (col0 & 511) >> 4;
            bulk_s2g(g_qkv + ((size_t)((which * NH + head) * 2 + (a & 1)) * 256 + mb * 16) * 64, sb + a * 2048, 2048);
            bulk_commit();
        }
        {
            const int hh = a >> 3, w = a & 7;
            const float4* p = (const float4*)(smem + 49152) + (hh * 256 + w * 32) / 2;
            float m = 0.f;
#pragma unroll
            for (int i = 0; i < 8; i++) {
                const int ii = (i + a) & 7;
                float4 u = p[2 * ii], v = p[2 * ii + 1];
                float n0 = u.x + u.z + v.x + v.z, n1 = u.y + u.w + v.y + v.w;
                if (!(n0 <= 3.0e38f) || !(n1 <= 3.0e38f)) m = __int_as_float(0x7f800000);
                m = fmaxf(m, fmaxf(n0, n1));
            }
            const int col0 = nt * 192 + hh * 16;
            g_nrm[((col0 >> 9) * NH + ((col0 & 511) >> 4)) * 128 + mb * 8 + w] = m;
        }
        if (a < 24) bulk_wait_all();
        TL(27);
    } else {
        const int wgi = (warp >> 2) - 1, ww = warp & 3;
        float acc[96];
#pragma unroll 1
        for (int kb = 0; kb < 8; kb++) {
            int s = kb % K1_STAGES;
            mbar_wait(full + 8 * s, (kb / K1_STAGES) & 1);
            if (warp == 4) TX(kb);
            uint64_t ad = make_desc(sb + s * K1_STAGE + wgi * 8192, 16, 1024, 1);
            uint64_t bd = make_desc(sb + s * K1_STAGE + 16384, 8192, 1024, 1);
            WG_FENCE();
#pragma unroll
            for (int k = 0; k < 4; k++) wgmma_ss_n192(acc, ad + k * 2, bd + k * 128, (kb | k) != 0);
            WG_COMMIT();
            if (kb > 0) {
                wg_wait<1>();
                if (lane == 0) mbar_arrive(empty + 8 * ((kb - 1) % K1_STAGES));
            }
        }
        wg_wait<0>();
        fence_regs(acc);
        TL(1);
        if (warp == 4) TX(16);
        mbar_wait(auxb, 0);
        if (warp == 4) TX(17);
        bar_sync(1, 256);
        const float2* s_rs = (const float2*)(smem + K1_RS);
        const float* s_cs = (const float*)(smem + K1_CS);
        const int g = lane >> 2, t = lane & 3;
        const int rl = wgi * 64 + ww * 16 + g;
        const float2 st0 = s_rs[rl], st1 = s_rs[rl + 8];
        const float QS = 0.25f * 1.4426950408889634f;
        const uint32_t stg = sb + ((lane >> 4) * 16 + wgi * 8 + ww * 2 + ((lane >> 3) & 1)) * 128 + (lane & 7) * 16;
        float2* s_np = (float2*)(smem + 49152) + (warp - 4) * 32 + lane;
#pragma unroll
        for (int hh = 0; hh < 12; hh++) {
            const int which = (nt * 192 + hh * 16) >> 9;
            const float sc = (which == 0) ? QS : 1.0f;
            const float a0 = st0.x * sc, b0 = st0.y * sc, a1 = st1.x * sc, b1 = st1.y * sc;
            const float2 c0 = *(const float2*)(s_cs + 16 * hh + 2 * t), c1 = *(const float2*)(s_cs + 16 * hh + 8 + 2 * t);
            const float* a = acc + 8 * hh;
            float v0 = fmaf(a0, a[0], b0 * c0.x), v1 = fmaf(a0, a[1], b0 * c0.y), v2 = fmaf(a1, a[2], b1 * c0.x), v3 = fmaf(a1, a[3], b1 * c0.y);
            float v4 = fmaf(a0, a[4], b0 * c1.x), v5 = fmaf(a0, a[5], b0 * c1.y), v6 = fmaf(a1, a[6], b1 * c1.x), v7 = fmaf(a1, a[7], b1 * c1.y);
            stsm4(stg + hh * 4096, pack_bf16(v0, v1), pack_bf16(v2, v3), pack_bf16(v4, v5), pack_bf16(v6, v7));
            s_np[hh * 256] = make_float2(fmaf(v0, v0, fmaf(v1, v1, fmaf(v4, v4, v5 * v5))), fmaf(v2, v2, fmaf(v3, v3, fmaf(v6, v6, v7 * v7))));
        }
        fence_proxy_async();
        bar_arrive(2, 256 + 96);
        TL(2);
        if (warp == 4) TX(18);
    }
}

constexpr int AT_K = 0, AT_V = 65536, AT_ONES = 131072, AT_BAR = 163840, AT_SMEM = AT_BAR + 128;
#define POLY_MASK 0xAD6A

__device__ __forceinline__ uint32_t exp2_pair_poly(float x0, float x1) {
    uint32_t t0 = __float_as_uint(x0 + 32895.0f);
    uint32_t t1 = __float_as_uint(x1 + 32895.0f);
    uint32_t gd = __byte_perm(t0, t1, 0x6420);
    uint32_t wm = __byte_perm(t0, t1, 0x5612);
    uint32_t v = hfma2(gd, 0x71477147u, 0x354f354fu);
    uint32_t z = hmul2(v, gd);
    return (wm >> 1) + z;
}
__device__ __forceinline__ uint32_t exp2_pair_mufu(float x0, float x1) { return pack_bf16(ex2f(x0), ex2f(x1)); }
template <uint32_t MASK>
__device__ __forceinline__ void exp_blocks(const float (&s)[32], uint32_t (&p)[16]) {
#pragma unroll
    for (int b = 0; b < 8; b++) {
        if ((MASK >> b) & 1) {
            p[2 * b] = exp2_pair_poly(s[4 * b], s[4 * b + 1]);
            p[2 * b + 1] = exp2_pair_poly(s[4 * b + 2], s[4 * b + 3]);
        } else {
            p[2 * b] = exp2_pair_mufu(s[4 * b], s[4 * b + 1]);
            p[2 * b + 1] = exp2_pair_mufu(s[4 * b + 2], s[4 * b + 3]);
        }
    }
}
#define PV4(P) _Pragma("unroll") for (int i = 0; i < 4; i++) { pv_wgmma(o, P[4 * i], P[4 * i + 1], P[4 * i + 2], P[4 * i + 3], vd); vd += 16; }

__device__ __forceinline__ void attn_store(float (&o)[12], int row0, int head, int lane) {
    float l0 = __shfl_sync(0xffffffffu, o[8], lane & 28);
    float l1 = __shfl_sync(0xffffffffu, o[10], lane & 28);
    float r0 = 1.0f / l0, r1 = 1.0f / l1;
    uint32_t* op = (uint32_t*)g_ao;
    int mb = row0 >> 7, rg = (row0 & 127) >> 3;
    int kb = head >> 2, kc = (head & 3) * 2;
    size_t base = (((size_t)(mb * 8 + kb) * 8 + kc) * 16 + rg) * 32 + lane;
    op[base] = pack_bf16(o[0] * r0, o[1] * r0);
    op[base + 32] = pack_bf16(o[2] * r1, o[3] * r1);
    op[base + 16 * 32] = pack_bf16(o[4] * r0, o[5] * r0);
    op[base + 16 * 32 + 32] = pack_bf16(o[6] * r1, o[7] * r1);
}

__device__ __forceinline__ void attn_load_q(uint32_t (&q)[4], const __nv_bfloat16* gq, int row0, int lane) {
    const uint32_t* qp = (const uint32_t*)gq;
    int j0 = row0 >> 3;
    q[0] = __ldcg(qp + (0 * 256 + j0) * 32 + lane);
    q[1] = __ldcg(qp + (0 * 256 + j0 + 1) * 32 + lane);
    q[2] = __ldcg(qp + (1 * 256 + j0) * 32 + lane);
    q[3] = __ldcg(qp + (1 * 256 + j0 + 1) * 32 + lane);
}

__device__ __forceinline__ void attn_tile_safe(const uint32_t (&q)[4], uint64_t kd, uint64_t vd, int row0, int head, int lane) {
    float o[12];
#pragma unroll
    for (int i = 0; i < 12; i++) o[i] = 0.f;
    float m0 = -INFINITY, m1 = -INFINITY;
    fence_regs(o);
#pragma unroll 1
    for (int j = 0; j < 32; j++) {
        float s[32];
        uint32_t p[16];
        WG_FENCE();
        qk_wgmma_n64(s, q, kd); kd += 64;
        WG_COMMIT();
        wg_wait<0>();
        fence_regs(s);
        fence_regs(o);
        float x0 = m0, x1 = m1;
#pragma unroll
        for (int b = 0; b < 8; b++) {
            x0 = fmaxf(x0, fmaxf(s[4 * b], s[4 * b + 1]));
            x1 = fmaxf(x1, fmaxf(s[4 * b + 2], s[4 * b + 3]));
        }
        x0 = fmaxf(x0, __shfl_xor_sync(0xffffffffu, x0, 1)); x0 = fmaxf(x0, __shfl_xor_sync(0xffffffffu, x0, 2));
        x1 = fmaxf(x1, __shfl_xor_sync(0xffffffffu, x1, 1)); x1 = fmaxf(x1, __shfl_xor_sync(0xffffffffu, x1, 2));
        float al0 = ex2f(m0 - x0), al1 = ex2f(m1 - x1);
        m0 = x0; m1 = x1;
#pragma unroll
        for (int i = 0; i < 3; i++) { o[4 * i] *= al0; o[4 * i + 1] *= al0; o[4 * i + 2] *= al1; o[4 * i + 3] *= al1; }
#pragma unroll
        for (int b = 0; b < 8; b++) {
            p[2 * b] = exp2_pair_mufu(s[4 * b] - m0, s[4 * b + 1] - m0);
            p[2 * b + 1] = exp2_pair_mufu(s[4 * b + 2] - m1, s[4 * b + 3] - m1);
        }
        fence_regs(o);
        WG_FENCE();
        PV4(p);
        WG_COMMIT();
        wg_wait<0>();
        fence_regs(o);
    }
    attn_store(o, row0, head, lane);
}

__global__ void __launch_bounds__(512, 1)
attn_kernel(const __nv_bfloat16* __restrict__ wg_, const __nv_bfloat16* __restrict__ wu_,
            const __nv_bfloat16* __restrict__ wo_, const __nv_bfloat16* __restrict__ wd_) {
    extern __shared__ __align__(1024) unsigned char smem[];
    const uint32_t sb = smem_u32(smem);
    const int tid = threadIdx.x, wg = tid >> 7, warp = (tid >> 5) & 3, lane = tid & 31;
    pdl_launch();
    if (blockIdx.x >= 128) {
        const int e = blockIdx.x - 128;
        const __nv_bfloat16* w = (e < 2) ? wg_ : wu_;
        float* red = (float*)smem;
        const int cgrp = tid & 127, kq = tid >> 7;
        if (cgrp < 112) {
            float s[8];
            colsum8(w, FF, (e & 1) * 896 + cgrp * 8, kq * 128, 128, s);
#pragma unroll
            for (int i = 0; i < 8; i++) red[kq * 896 + cgrp * 8 + i] = s[i];
        }
        __syncthreads();
        for (int c = tid; c < 896; c += 512)
            g_cs2[(e >> 1) * FF + (e & 1) * 896 + c] = red[c] + red[896 + c] + red[1792 + c] + red[2688 + c];
        if (tid < 32) {
            const char* p0 = (const char*)wo_ + e * (DM * DM * 2 / 4);
            for (int i = lane; i < 32; i += 32)
                asm volatile("cp.async.bulk.prefetch.L2.global [%0], %1;" :: "l"(p0 + i * 4096), "r"(4096) : "memory");
            const char* p1 = (const char*)wd_ + e * (FF * DM * 2 / 4);
            for (int i = lane; i < 112; i += 32)
                asm volatile("cp.async.bulk.prefetch.L2.global [%0], %1;" :: "l"(p1 + i * 4096), "r"(4096) : "memory");
        }
        return;
    }
    const int head = blockIdx.x >> 2, qq = blockIdx.x & 3;
    const __nv_bfloat16* gq = g_qkv + (size_t)head * (S_LEN * 16);
    const __nv_bfloat16* gk = g_qkv + (size_t)(NH + head) * (S_LEN * 16);
    const __nv_bfloat16* gv = g_qkv + (size_t)(2 * NH + head) * (S_LEN * 16);
    if (tid == 0) {
        for (int i = 0; i < 8; i++) mbar_init(sb + AT_BAR + 8 * i, 1);
        fence_barrier_init();
    }
    {
        uint4 one = make_uint4(0x00003F80u, 0, 0, 0);
#pragma unroll
        for (int i = 0; i < 4; i++) *(uint4*)(smem + AT_ONES + (i * 512 + tid) * 16) = one;
        fence_proxy_async();
    }
    __syncthreads();
    TL(3);
    pdl_wait();
    TL(4);
    auto load_kv = [&](int i) {
        uint32_t bar = sb + AT_BAR + 8 * i;
        mbar_expect(bar, 16384);
        bulk_g2s(sb + AT_K + i * 4096, gk + i * 2048, 4096, bar);
        bulk_g2s(sb + AT_K + 32768 + i * 4096, gk + 16384 + i * 2048, 4096, bar);
        bulk_g2s(sb + AT_V + i * 4096, gv + i * 2048, 4096, bar);
        bulk_g2s(sb + AT_V + 32768 + i * 4096, gv + 16384 + i * 2048, 4096, bar);
    };
    if (tid == 0) { load_kv(0); load_kv(1); }
    uint32_t q[4], q2[4];
    attn_load_q(q, gq, qq * 512 + wg * 64 + warp * 16, lane);
    attn_load_q(q2, gq, qq * 512 + (4 + wg) * 64 + warp * 16, lane);
    bool fast;
    {
        const float* nq = g_nrm + (0 * NH + head) * 128 + qq * 32;
        const float* nk = g_nrm + (1 * NH + head) * 128;
        const float* nv = g_nrm + (2 * NH + head) * 128;
        float4 k4 = __ldcg((const float4*)nk + lane), v4 = __ldcg((const float4*)nv + lane);
        float qm = warp_max(__ldcg(nq + lane));
        float km = warp_max(fmaxf(fmaxf(k4.x, k4.y), fmaxf(k4.z, k4.w)));
        float vm = warp_max(fmaxf(fmaxf(v4.x, v4.y), fmaxf(v4.z, v4.w)));
        fast = __all_sync(0xffffffffu, (qm * km <= 3500.0f) && (vm <= 1.0e24f));
    }
    TL(24);
    const uint64_t kdesc0 = make_desc(sb + AT_K, 32768, 128, 0);
    const uint64_t vdesc0 = make_desc(sb + AT_V, 128, 32768, 0);
    if (!fast) {
        if (tid == 0) for (int i = 2; i < 8; i++) load_kv(i);
        for (int i = 0; i < 8; i++) mbar_wait(sb + AT_BAR + 8 * i, 0);
#pragma unroll 1
        for (int tile = 0; tile < 2; tile++) {
            const int row0 = qq * 512 + (tile * 4 + wg) * 64 + warp * 16;
            attn_tile_safe(q, kdesc0, vdesc0, row0, head, lane);
#pragma unroll
            for (int i = 0; i < 4; i++) q[i] = q2[i];
        }
        return;
    }
#pragma unroll 1
    for (int tile = 0; tile < 2; tile++) {
        const int row0 = qq * 512 + (tile * 4 + wg) * 64 + warp * 16;
        float o[12];
#pragma unroll
        for (int i = 0; i < 12; i++) o[i] = 0.f;
        fence_regs(o);
        float sa[32];
        uint32_t pa[16];
        uint64_t kd = kdesc0, vd = vdesc0;
        if (tile == 0) { mbar_wait(sb + AT_BAR, 0); TL(25); }
        WG_FENCE();
        qk_wgmma_n64(sa, q, kd); kd += 64;
        WG_COMMIT();
#pragma unroll 1
        for (int jj = 0; jj < 8; jj++) {
            if (tile == 0 && jj < 7) {
                if (tid == 0 && jj < 6) load_kv(jj + 2);
                mbar_wait(sb + AT_BAR + 8 * (jj + 1), 0);
            }
            if (wg == 0 && warp == 0) TX(128 + tile * 8 + jj);
#pragma unroll
            for (int j = 0; j < 4; j++) {
                wg_wait<0>();
                fence_regs(sa);
                if (j & 1) exp_blocks<(POLY_MASK >> 8)>(sa, pa); else exp_blocks<(POLY_MASK & 255)>(sa, pa);
                WG_FENCE();
                qk_wgmma_n64(sa, q, kd); kd += 64;
                PV4(pa);
                WG_COMMIT();
            }
        }
        wg_wait<0>();
        fence_regs(o);
        fence_regs(sa);
        if (tile == 0) TL(26);
        attn_store(o, row0, head, lane);
#pragma unroll
        for (int i = 0; i < 4; i++) q[i] = q2[i];
    }
    TL(5);
}

constexpr int F_R2 = 131072, F_X = 196608, F_BAR = 229376;
constexpr int F_RS = F_BAR + 256, F_CS = F_RS + 1024, F_SMEM = F_CS + 1792;
enum { B_FA = 0, B_HF = 4, B_BF = 8, B_BE = 11, B_CF = 14, B_CE = 20, B_ADONE = 26, B_BDONE = 27, B_XC = 28, B_PRDY = 29, B_AUX = 30, B_NUM = 31 };

__device__ __forceinline__ uint32_t mapa(uint32_t a, uint32_t rank) { uint32_t r; asm("mapa.shared::cluster.u32 %0, %1, %2;" : "=r"(r) : "r"(a), "r"(rank)); return r; }
__device__ __forceinline__ void st_async4(uint32_t dst, float a, float b, float c, float d, uint32_t bar) {
    asm volatile("st.async.weak.shared::cluster.mbarrier::complete_tx::bytes.v4.f32 [%0], {%1,%2,%3,%4}, [%5];"
                 :: "r"(dst), "f"(a), "f"(b), "f"(c), "f"(d), "r"(bar) : "memory");
}
__device__ __forceinline__ void mbar_arrive_remote(uint32_t a) { asm volatile("mbarrier.arrive.release.cluster.shared::cluster.b64 _, [%0];" :: "r"(a) : "memory"); }
__device__ __forceinline__ void mbar_wait_cluster(uint32_t a, int parity) {
    uint32_t done;
    int it = 0;
    do {
        asm volatile("{\n.reg .pred p;\nmbarrier.try_wait.parity.acquire.cluster.shared::cta.b64 p, [%1], %2;\nselp.u32 %0, 1, 0, p;\n}"
                     : "=r"(done) : "r"(a), "r"(parity) : "memory");
        if (++it > (1 << 24)) __trap();
    } while (!done);
}
__device__ __forceinline__ void poll_count(const unsigned int* p, unsigned int target) {
    int it = 0;
    while (ld_acquire(p) < target) { if (++it > (1 << 22)) __trap(); }
    asm volatile("fence.proxy.async.global;" ::: "memory");
}
__device__ __forceinline__ void tma2d_store(const CUtensorMap* m, uint32_t src, int c0, int c1) {
    asm volatile("cp.async.bulk.tensor.2d.global.shared::cta.bulk_group [%0, {%2, %3}], [%1];" :: "l"(m), "r"(src), "r"(c0), "r"(c1) : "memory");
}
template <int R>
__device__ __forceinline__ void xchg(float (&acc)[64], float (&o)[32], uint32_t sb, unsigned char* smem, int bar, int ctid) {
    const uint32_t dst = mapa(sb + F_X + ctid * 16, 1 - R), rb = mapa(sb + F_BAR + 8 * bar, 1 - R);
#pragma unroll
    for (int q = 0; q < 8; q++) {
        const int j = (1 - R) * 32 + 4 * q;
        st_async4(dst + q * 4096, acc[j], acc[j + 1], acc[j + 2], acc[j + 3], rb);
    }
    mbar_wait_cluster(sb + F_BAR + 8 * bar, 0);
#pragma unroll
    for (int q = 0; q < 8; q++) {
        float4 v = *(const float4*)(smem + F_X + q * 4096 + ctid * 16);
        const int j = R * 32 + 4 * q;
        o[4 * q] = acc[j] + v.x; o[4 * q + 1] = acc[j + 1] + v.y; o[4 * q + 2] = acc[j + 2] + v.z; o[4 * q + 3] = acc[j + 3] + v.w;
    }
}

template <int NB, bool STAGE>
__device__ __forceinline__ void ffn_epilogue(const float* ag, const float* au, const float* s_cs, int cs_off, uint32_t* gp, uint32_t stg,
                                             float2 st0, float2 st1, int lane) {
    const int t = lane & 3;
    const float C1 = 0.7978845608028654f, C2 = 0.044715f * 0.7978845608028654f;
    const float k10 = st0.x * C1, k20 = st0.x * st0.x * st0.x * C2, k11 = st1.x * C1, k21 = st1.x * st1.x * st1.x * C2;
#pragma unroll
    for (int j2 = 0; j2 < NB / 2; j2++) {
        uint32_t pk[4];
#pragma unroll
        for (int jj = 0; jj < 2; jj++) {
            const int j = 2 * j2 + jj;
            const float2 cg = *(const float2*)(s_cs + cs_off + 8 * j + 2 * t);
            const float2 cu = *(const float2*)(s_cs + 224 + cs_off + 8 * j + 2 * t);
            float r[4];
#pragma unroll
            for (int e = 0; e < 4; e++) {
                const float nm = (e < 2) ? st0.y : st1.y, k1 = (e < 2) ? k10 : k11, k2 = (e < 2) ? k20 : k21;
                const float tg = fmaf(nm, (e & 1) ? cg.y : cg.x, ag[4 * j + e]);
                const float tu = fmaf(nm, (e & 1) ? cu.y : cu.x, au[4 * j + e]);
                const float th = tanh_fast(tg * fmaf(tg * tg, k2, k1));
                const float p = tg * tu;
                r[e] = fmaf(p, th, p);
            }
            pk[2 * jj] = pack_bf16(r[0], r[1]);
            pk[2 * jj + 1] = pack_bf16(r[2], r[3]);
        }
        if (STAGE) {
            stsm4(stg + j2 * 4096, pk[0], pk[1], pk[2], pk[3]);
        } else {
            gp[j2 * 1024] = pk[0]; gp[j2 * 1024 + 32] = pk[1]; gp[j2 * 1024 + 512] = pk[2]; gp[j2 * 1024 + 544] = pk[3];
        }
    }
}

__global__ void __cluster_dims__(2, 1, 1) __launch_bounds__(384, 1)
tail_kernel(const __grid_constant__ CUtensorMap tm_o, const __grid_constant__ CUtensorMap tm_g,
            const __grid_constant__ CUtensorMap tm_u, const __grid_constant__ CUtensorMap tm_d,
            const __grid_constant__ CUtensorMap tm_out, const __nv_bfloat16* __restrict__ x) {
    extern __shared__ __align__(1024) unsigned char smem[];
    const uint32_t sb = smem_u32(smem);
    const uint32_t bars = sb + F_BAR;
    const int tid = threadIdx.x, warp = __shfl_sync(0xffffffffu, tid >> 5, 0), lane = tid & 31;
    TL(6);
    const int cl = blockIdx.x >> 1, r = blockIdx.x & 1;
    const int mb = ((cl & 7) >> 1) * 4 + (cl >> 4), ntA = (cl & 1) * 2 + ((cl >> 3) & 1);
    const int nt = ntA * 2 + r;
    if (tid < B_NUM) {
        const int i = tid;
        int cnt = 1;
        if ((i >= B_BE && i < B_BE + 3) || (i >= B_CE && i < B_CE + 6) || i == B_BDONE || i == B_PRDY) cnt = 8;
        if (i == B_AUX) cnt = 2;
        mbar_init(bars + 8 * i, cnt);
        if (i == B_XC) mbar_expect(bars + 8 * B_XC, 32768);
        fence_barrier_init();
    } else if (tid >= 32 && tid < 37) {
        prefetch_tmap(tid == 32 ? &tm_o : tid == 33 ? &tm_g : tid == 34 ? &tm_u : tid == 35 ? &tm_d : &tm_out);
    }
    __syncthreads();
    asm volatile("barrier.cluster.arrive.release.aligned;" ::: "memory");
    if (warp < 4) {
        asm volatile("setmaxnreg.dec.sync.aligned.u32 56;");
        if (warp == 0) {
            if (lane == 0) {
                auto load_b = [&](int it) {
                    const int s = it % 3, pass = it >> 3, kb = it & 7;
                    const int ng = pass ? 3 : 4, c0 = nt * 224 + pass * 128;
                    const uint32_t bar = bars + 8 * (B_BF + s), dst = sb + F_R2 + s * 32768;
                    mbar_expect(bar, ng * 8192);
                    for (int i = 0; i < ng; i++) {
                        tma2d(dst + i * 4096, &tm_g, c0 + i * 32, kb * 64, bar);
                        tma2d(dst + 16384 + i * 4096, &tm_u, c0 + i * 32, kb * 64, bar);
                    }
                };
                for (int i = 0; i < 8; i++) {
                    const uint32_t bar = bars + 8 * (B_FA + (i >> 1));
                    if (!(i & 1)) mbar_expect(bar, 49152);
                    tma2d(sb + F_R2 + 32768 + i * 8192, &tm_o, nt * 64, i * 64, bar);
                }
                pdl_wait();
                TL(16);
                for (int i = 0; i < 8; i++)
                    bulk_g2s(sb + i * 16384, g_ao + (size_t)(mb * 8 + i) * 8192, 16384, bars + 8 * (B_FA + (i >> 1)));
                load_b(0);
                if (blockIdx.x == 0)
                    for (int i = 0; i < 32; i++) g_cnt[i] = 0;
                mbar_wait(bars + 8 * B_ADONE, 0);
                load_b(1); load_b(2);
                poll_count(&g_cnt2[mb], 8);
                TL(17);
                for (int kb = 0; kb < 8; kb++) {
                    const uint32_t bar = bars + 8 * (B_HF + (kb >> 1));
                    if (!(kb & 1)) mbar_expect(bar, (kb >> 1) == ntA ? 16384 : 32768);
                    if (kb != nt) bulk_g2s(sb + kb * 16384, g_h + (size_t)(mb * 8 + kb) * 8192, 16384, bar);
                }
                for (int it = 3; it < 16; it++) {
                    mbar_wait(bars + 8 * (B_BE + it % 3), (it / 3 - 1) & 1);
                    load_b(it);
                }
                mbar_wait(bars + 8 * B_BDONE, 0);
                for (int i = 0; i < 6; i++) {
                    const uint32_t bar = bars + 8 * (B_CF + i);
                    mbar_expect(bar, 32768);
                    tma2d(sb + i * 32768 + 16384, &tm_d, ntA * 128, (2 * i + r) * 64, bar);
                    tma2d(sb + i * 32768 + 24576, &tm_d, ntA * 128 + 64, (2 * i + r) * 64, bar);
                }
                poll_count(&g_cnt2[16 + mb], 8);
                TL(18);
                for (int kb = 0; kb < 14; kb++) {
                    const int s = kb % 6;
                    const uint32_t bar = bars + 8 * (B_CF + s);
                    if (kb >= 6) {
                        mbar_wait(bars + 8 * (B_CE + s), ((kb / 6) - 1) & 1);
                        mbar_expect(bar, 32768);
                        tma2d(sb + s * 32768 + 16384, &tm_d, ntA * 128, (2 * kb + r) * 64, bar);
                        tma2d(sb + s * 32768 + 24576, &tm_d, ntA * 128 + 64, (2 * kb + r) * 64, bar);
                    }
                    bulk_g2s(sb + s * 32768, g_g + (size_t)(mb * 28 + 2 * kb + r) * 8192, 16384, bar);
                }
            }
            __syncwarp();
            asm volatile("barrier.cluster.wait.acquire.aligned;" ::: "memory");
        } else if (warp == 1) {
            asm volatile("barrier.cluster.wait.acquire.aligned;" ::: "memory");
            bar_sync(1, 288);
            if (lane == 0) {
                red_release(&g_cnt2[mb]);
                TL(9);
            }
            __syncwarp();
            bar_sync(2, 288);
            if (lane == 0) {
                red_release(&g_cnt2[16 + mb]);
                TL(13);
            }
            __syncwarp();
            bar_sync(3, 288);
            if (lane == 0) {
                tma2d_store(&tm_out, sb, nt * 64, mb * 128);
                bulk_commit();
                bulk_wait_all();
                TL(15);
            }
        } else {
            asm volatile("barrier.cluster.wait.acquire.aligned;" ::: "memory");
            pdl_wait();
            float2* s_rs = (float2*)(smem + F_RS);
            float* s_cs = (float*)(smem + F_CS);
            for (int c = tid - 64; c < 448; c += 64)
                s_cs[c] = __ldcg(&g_cs2[(c >= 224 ? FF - 224 : 0) + nt * 224 + c]);
            if (lane == 0) poll_count(&g_cnt2[mb], 8);
            __syncwarp();
            for (int rr = tid - 64; rr < 128; rr += 64) {
                const float4* hp = (const float4*)(g_hstat + (size_t)(mb * 128 + rr) * 8);
                float4 a = __ldcg(hp), b = __ldcg(hp + 1), c = __ldcg(hp + 2), d = __ldcg(hp + 3);
                float mean = 0.125f * (a.x + a.z + b.x + b.z + c.x + c.z + d.x + d.z);
                float m2 = a.y + a.w + b.y + b.w + c.y + c.w + d.y + d.w;
                float e;
                e = a.x - mean; m2 = fmaf(64.f * e, e, m2); e = a.z - mean; m2 = fmaf(64.f * e, e, m2);
                e = b.x - mean; m2 = fmaf(64.f * e, e, m2); e = b.z - mean; m2 = fmaf(64.f * e, e, m2);
                e = c.x - mean; m2 = fmaf(64.f * e, e, m2); e = c.z - mean; m2 = fmaf(64.f * e, e, m2);
                e = d.x - mean; m2 = fmaf(64.f * e, e, m2); e = d.z - mean; m2 = fmaf(64.f * e, e, m2);
                s_rs[rr] = make_float2(rsqrtf(m2 * (1.0f / DM) + 1e-5f), -mean);
            }
            __syncwarp();
            if (lane == 0) mbar_arrive(bars + 8 * B_AUX);
        }
    } else {
        asm volatile("setmaxnreg.inc.sync.aligned.u32 216;");
        const int wgi = (warp >> 2) - 1, ww = warp & 3, ctid = tid - 128;
        const int g = lane >> 2, t = lane & 3;
        const int rl = wgi * 64 + ww * 16 + g, row = mb * 128 + rl;
        const int rgl = wgi * 8 + ww * 2;
        const float2* s_rs = (const float2*)(smem + F_RS);
        const float* s_cs = (const float*)(smem + F_CS);
        const uint32_t stl = ((lane >> 4) * 16 + rgl + ((lane >> 3) & 1)) * 128 + (lane & 7) * 16;
        TL(23);
        {
            uint32_t xr[16];
            const uint32_t* xp = (const uint32_t*)(x + (size_t)row * DM + nt * 64) + t;
#pragma unroll
            for (int j = 0; j < 8; j++) { xr[2 * j] = __ldg(xp + 4 * j); xr[2 * j + 1] = __ldg(xp + 8 * (DM / 2) + 4 * j); }
            float acc[32];
#pragma unroll 1
            for (int i = 0; i < 8; i++) {
                if (!(i & 1)) { mbar_wait(bars + 8 * (B_FA + (i >> 1)), 0); if (i == 0) TL(19); }
                uint64_t ad = make_desc(sb + i * 16384 + wgi * 1024, 2048, 128, 0);
                uint64_t bd = make_desc(sb + F_R2 + 32768 + i * 8192, 8192, 1024, 1);
                WG_FENCE();
#pragma unroll
                for (int k = 0; k < 4; k++) wgmma_ss_n64(acc, ad + k * 256, bd + k * 128, (i | k) != 0);
                WG_COMMIT();
            }
            wg_wait<0>();
            fence_regs(acc);
            TL(7);
            bar_sync(4, 256);
            if (tid == 128) mbar_arrive(bars + 8 * B_ADONE);
            uint32_t* hp = (uint32_t*)g_h + ((size_t)(mb * 8 + nt) * 8 * 16 + rgl) * 32 + lane;
            float v0[16], v1[16];
            float s0 = 0.f, s1 = 0.f;
#pragma unroll
            for (int j2 = 0; j2 < 4; j2++) {
                uint32_t u[4];
#pragma unroll
                for (int jj = 0; jj < 2; jj++) {
                    const int j = 2 * j2 + jj;
                    u[2 * jj] = pack_bf16(bf_lo(xr[2 * j]) + acc[4 * j], bf_hi(xr[2 * j]) + acc[4 * j + 1]);
                    u[2 * jj + 1] = pack_bf16(bf_lo(xr[2 * j + 1]) + acc[4 * j + 2], bf_hi(xr[2 * j + 1]) + acc[4 * j + 3]);
                    v0[2 * j] = bf_lo(u[2 * jj]); v0[2 * j + 1] = bf_hi(u[2 * jj]);
                    v1[2 * j] = bf_lo(u[2 * jj + 1]); v1[2 * j + 1] = bf_hi(u[2 * jj + 1]);
                    s0 += v0[2 * j] + v0[2 * j + 1];
                    s1 += v1[2 * j] + v1[2 * j + 1];
                }
                stsm4(sb + nt * 16384 + stl + j2 * 4096, u[0], u[1], u[2], u[3]);
                hp[j2 * 1024] = u[0]; hp[j2 * 1024 + 32] = u[1]; hp[j2 * 1024 + 512] = u[2]; hp[j2 * 1024 + 544] = u[3];
            }
            fence_proxy_async();
            float m0 = s0 * (1.0f / 16), m1 = s1 * (1.0f / 16), q0 = 0.f, q1 = 0.f;
#pragma unroll
            for (int i = 0; i < 16; i++) {
                float d0 = v0[i] - m0, d1 = v1[i] - m1;
                q0 = fmaf(d0, d0, q0); q1 = fmaf(d1, d1, q1);
            }
#pragma unroll
            for (int st = 0; st < 2; st++) {
                float hn = st ? 16.f : 8.f;
                float om0 = __shfl_xor_sync(0xffffffffu, m0, 1 << st), oq0 = __shfl_xor_sync(0xffffffffu, q0, 1 << st);
                float om1 = __shfl_xor_sync(0xffffffffu, m1, 1 << st), oq1 = __shfl_xor_sync(0xffffffffu, q1, 1 << st);
                float d0 = om0 - m0, d1 = om1 - m1;
                q0 = q0 + oq0 + d0 * d0 * hn; q1 = q1 + oq1 + d1 * d1 * hn;
                m0 = 0.5f * (m0 + om0); m1 = 0.5f * (m1 + om1);
            }
            if (t == 0) {
                g_hstat[row * 8 + nt] = make_float2(m0, q0);
                g_hstat[(row + 8) * 8 + nt] = make_float2(m1, q1);
            }
            bar_arrive(1, 288);
            bar_sync(4, 256);
            TL(8);
        }
        uint32_t* gp = (uint32_t*)g_g + (((size_t)mb * 224 + nt * 28) * 16 + rgl) * 32 + lane;
        {
            float ag[64], au[64];
#pragma unroll 1
            for (int kb = 0; kb < 8; kb++) {
                const int s = kb % 3;
                if (!(kb & 1)) mbar_wait(bars + 8 * (B_HF + (kb >> 1)), 0);
                mbar_wait(bars + 8 * (B_BF + s), (kb / 3) & 1);
                if (warp == 4) TX(32 + kb);
                uint64_t ad = make_desc(sb + kb * 16384 + wgi * 1024, 2048, 128, 0);
                uint64_t bd = make_desc(sb + F_R2 + s * 32768, 4096, 512, 2);
                WG_FENCE();
#pragma unroll
                for (int k = 0; k < 4; k++) {
                    wgmma_ss_n128(ag, ad + k * 256, bd + k * 64, (kb | k) != 0);
                    wgmma_ss_n128(au, ad + k * 256, bd + 1024 + k * 64, (kb | k) != 0);
                }
                WG_COMMIT();
                if (kb > 0) {
                    wg_wait<1>();
                    if (lane == 0) mbar_arrive(bars + 8 * (B_BE + (kb - 1) % 3));
                }
            }
            wg_wait<0>();
            if (lane == 0) mbar_arrive(bars + 8 * (B_BE + 7 % 3));
            fence_regs(ag); fence_regs(au);
            TL(10);
            mbar_wait(bars + 8 * B_AUX, 0);
            ffn_epilogue<16, false>(ag, au, s_cs, 0, gp, 0, s_rs[rl], s_rs[rl + 8], lane);
        }
        uint32_t hr[16];
        {
            const uint32_t* hs = (const uint32_t*)(smem + nt * 16384) + rgl * 32 + lane;
#pragma unroll
            for (int j = 0; j < 8; j++) { hr[2 * j] = hs[j * 512]; hr[2 * j + 1] = hs[j * 512 + 32]; }
        }
        {
            float ag[48], au[48];
#pragma unroll 1
            for (int kb = 0; kb < 8; kb++) {
                const int it = 8 + kb, s = it % 3;
                mbar_wait(bars + 8 * (B_BF + s), (it / 3) & 1);
                if (warp == 4) TX(32 + it);
                uint64_t ad = make_desc(sb + kb * 16384 + wgi * 1024, 2048, 128, 0);
                uint64_t bd = make_desc(sb + F_R2 + s * 32768, 4096, 512, 2);
                WG_FENCE();
#pragma unroll
                for (int k = 0; k < 4; k++) {
                    wgmma_ss_n96(ag, ad + k * 256, bd + k * 64, (kb | k) != 0);
                    wgmma_ss_n96(au, ad + k * 256, bd + 1024 + k * 64, (kb | k) != 0);
                }
                WG_COMMIT();
                if (kb > 0) {
                    wg_wait<1>();
                    if (lane == 0) mbar_arrive(bars + 8 * (B_BE + (it - 1) % 3));
                }
            }
            wg_wait<0>();
            asm volatile("barrier.cluster.wait.acquire.aligned;" ::: "memory");
            if (lane == 0) {
                mbar_arrive(bars + 8 * B_BDONE);
                mbar_arrive_remote(mapa(bars + 8 * B_PRDY, 1 - r));
            }
            fence_regs(ag); fence_regs(au);
            TL(11);
            ffn_epilogue<12, false>(ag, au, s_cs, 128, gp + 16 * 512, 0, s_rs[rl], s_rs[rl + 8], lane);
            bar_arrive(2, 288);
            TL(12);
        }
        {
            float acc[64];
#pragma unroll 1
            for (int kb = 0; kb < 14; kb++) {
                const int s = kb % 6;
                mbar_wait(bars + 8 * (B_CF + s), (kb / 6) & 1);
                if (warp == 4) TX(96 + kb);
                uint64_t ad = make_desc(sb + s * 32768 + wgi * 1024, 2048, 128, 0);
                uint64_t bd = make_desc(sb + s * 32768 + 16384, 8192, 1024, 1);
                WG_FENCE();
#pragma unroll
                for (int k = 0; k < 4; k++) wgmma_ss_n128(acc, ad + k * 256, bd + k * 128, (kb | k) != 0);
                WG_COMMIT();
                if (kb > 0) {
                    wg_wait<1>();
                    if (lane == 0) mbar_arrive(bars + 8 * (B_CE + (kb - 1) % 6));
                }
            }
            wg_wait<0>();
            fence_regs(acc);
            TL(14);
            mbar_wait_cluster(bars + 8 * B_PRDY, 0);
            float o[32];
            if (r == 0) xchg<0>(acc, o, sb, smem, B_XC, ctid); else xchg<1>(acc, o, sb, smem, B_XC, ctid);
            TL(22);
            bar_sync(4, 256);
            const float a0 = s_rs[rl].x, a1 = s_rs[rl + 8].x;
            const float k0 = 0.5f * a0 * a0, k1 = 0.5f * a1 * a1;
            const int srow = wgi * 64 + ww * 16 + ((lane >> 3) & 1) * 8 + (lane & 7);
#pragma unroll
            for (int j2 = 0; j2 < 4; j2++) {
                uint32_t u[4];
#pragma unroll
                for (int jj = 0; jj < 2; jj++) {
                    const int j = 2 * j2 + jj;
                    u[2 * jj] = pack_bf16(fmaf(k0, o[4 * j], bf_lo(hr[2 * j])), fmaf(k0, o[4 * j + 1], bf_hi(hr[2 * j])));
                    u[2 * jj + 1] = pack_bf16(fmaf(k1, o[4 * j + 2], bf_lo(hr[2 * j + 1])), fmaf(k1, o[4 * j + 3], bf_hi(hr[2 * j + 1])));
                }
                const int chunk = 2 * j2 + (lane >> 4);
                stsm4(sb + srow * 128 + ((chunk ^ (lane & 7)) * 16), u[0], u[1], u[2], u[3]);
            }
            fence_proxy_async();
            bar_arrive(3, 288);
        }
    }
}

typedef CUresult (*EncodeFn)(CUtensorMap*, CUtensorMapDataType, cuuint32_t, void*, const cuuint64_t*, const cuuint64_t*,
                             const cuuint32_t*, const cuuint32_t*, CUtensorMapInterleave, CUtensorMapSwizzle,
                             CUtensorMapL2promotion, CUtensorMapFloatOOBfill);

void encode(EncodeFn fn, CUtensorMap* m, const void* ptr, int rank, const cuuint64_t* dims, const cuuint64_t* strides,
            const cuuint32_t* box, CUtensorMapSwizzle swz) {
    cuuint32_t es[3] = {1, 1, 1};
    fn(m, CU_TENSOR_MAP_DATA_TYPE_BFLOAT16, rank, (void*)ptr, dims, strides, box, es, CU_TENSOR_MAP_INTERLEAVE_NONE, swz,
       CU_TENSOR_MAP_L2_PROMOTION_L2_256B, CU_TENSOR_MAP_FLOAT_OOB_FILL_NONE);
}

template <typename... KArgs, typename... Args>
void launch(void (*kern)(KArgs...), int grid, int block, int smem, bool pdl, Args... args) {
    cudaLaunchConfig_t cfg = {};
    cfg.gridDim = dim3(grid); cfg.blockDim = dim3(block); cfg.dynamicSmemBytes = smem;
    cfg.stream = cudaStreamPerThread;
    cudaLaunchAttribute at[1];
    at[0].id = cudaLaunchAttributeProgrammaticStreamSerialization;
    at[0].val.programmaticStreamSerializationAllowed = 1;
    cfg.attrs = at; cfg.numAttrs = pdl ? 1 : 0;
    cudaLaunchKernelEx(&cfg, kern, KArgs(args)...);
}

}

extern "C" void kernel_launch(void* const* d_in, const int* in_sizes, int n_in, void* d_out, int out_size) {
    const __nv_bfloat16* x = (const __nv_bfloat16*)d_in[0];
    const __nv_bfloat16* wqkv = (const __nv_bfloat16*)d_in[1];
    const __nv_bfloat16* wo = (const __nv_bfloat16*)d_in[2];
    const __nv_bfloat16* wgate = (const __nv_bfloat16*)d_in[4];
    const __nv_bfloat16* wup = (const __nv_bfloat16*)d_in[5];
    const __nv_bfloat16* wdown = (const __nv_bfloat16*)d_in[6];
    __nv_bfloat16* out = (__nv_bfloat16*)d_out;

    static CUtensorMap tm_x, tm_wqkv, tm_wo, tm_wg, tm_wu, tm_wd, tm_out;
    static const void* cached[7] = {nullptr, nullptr, nullptr, nullptr, nullptr, nullptr, nullptr};
    if (cached[0] != x || cached[1] != wqkv || cached[2] != wo || cached[3] != wgate || cached[4] != wup || cached[5] != wdown || cached[6] != out) {
        void* fp = nullptr;
        cudaDriverEntryPointQueryResult qr;
        cudaGetDriverEntryPoint("cuTensorMapEncodeTiled", &fp, cudaEnableDefault, &qr);
        EncodeFn fn = (EncodeFn)fp;
        { cuuint64_t d[2] = {512, 2048}, s[1] = {1024}; cuuint32_t b[2] = {64, 128};
          encode(fn, &tm_x, x, 2, d, s, b, CU_TENSOR_MAP_SWIZZLE_128B);
          encode(fn, &tm_out, out, 2, d, s, b, CU_TENSOR_MAP_SWIZZLE_128B); }
        { cuuint64_t d[3] = {64, 512, 24}, s[2] = {3072, 128}; cuuint32_t b[3] = {64, 64, 3};
          encode(fn, &tm_wqkv, wqkv, 3, d, s, b, CU_TENSOR_MAP_SWIZZLE_128B); }
        { cuuint64_t d[2] = {512, 512}, s[1] = {1024}; cuuint32_t b[2] = {64, 64};
          encode(fn, &tm_wo, wo, 2, d, s, b, CU_TENSOR_MAP_SWIZZLE_128B); }
        { cuuint64_t d[2] = {1792, 512}, s[1] = {3584}; cuuint32_t b[2] = {32, 64};
          encode(fn, &tm_wg, wgate, 2, d, s, b, CU_TENSOR_MAP_SWIZZLE_64B);
          encode(fn, &tm_wu, wup, 2, d, s, b, CU_TENSOR_MAP_SWIZZLE_64B); }
        { cuuint64_t d[2] = {512, 1792}, s[1] = {1024}; cuuint32_t b[2] = {64, 64};
          encode(fn, &tm_wd, wdown, 2, d, s, b, CU_TENSOR_MAP_SWIZZLE_128B); }
        cudaFuncSetAttribute(qkv_kernel, cudaFuncAttributeMaxDynamicSharedMemorySize, K1_SMEM);
        cudaFuncSetAttribute(attn_kernel, cudaFuncAttributeMaxDynamicSharedMemorySize, AT_SMEM);
        cudaFuncSetAttribute(tail_kernel, cudaFuncAttributeMaxDynamicSharedMemorySize, F_SMEM);
        cached[0] = x; cached[1] = wqkv; cached[2] = wo; cached[3] = wgate; cached[4] = wup; cached[5] = wdown; cached[6] = out;
    }
    launch(qkv_kernel, 128, 384, K1_SMEM, false, tm_x, tm_wqkv, x, wqkv);
    launch(attn_kernel, 132, 512, AT_SMEM, true, wgate, wup, wo, wdown);
    launch(tail_kernel, 128, 384, F_SMEM, true, tm_wo, tm_wg, tm_wu, tm_wd, tm_out, x);
}
```

```cpp
#include <cuda_runtime.h>
#include <cuda_bf16.h>
#include <cuda.h>
#include <stdint.h>

#define K1_DIRECT
namespace {

constexpr int S_LEN = 2048, DM = 512, NH = 32, FF = 1792;

__device__ __align__(1024) __nv_bfloat16 g_qkv[3 * NH * S_LEN * 16];
__device__ __align__(1024) __nv_bfloat16 g_ao[S_LEN * DM];
__device__ __align__(1024) __nv_bfloat16 g_h[S_LEN * DM];
__device__ __align__(1024) __nv_bfloat16 g_g[S_LEN * FF];
__device__ __align__(16) float2 g_rowstat1[S_LEN];
__device__ float g_cs1_part[16 * 1536];
__device__ unsigned int g_cnt[32];
__device__ unsigned int g_cnt2[64];
__device__ float g_nrm[3 * NH * 128];
__device__ float2 g_hstat[S_LEN * 8];
__device__ float g_cs2[2 * FF];

#define TL(slot)
#define TX(slot)
__device__ __forceinline__ uint32_t smem_u32(const void* p) { return (uint32_t)__cvta_generic_to_shared(p); }
__device__ __forceinline__ void mbar_init(uint32_t a, int c) { asm volatile("mbarrier.init.shared.b64 [%0], %1;" :: "r"(a), "r"(c)); }
__device__ __forceinline__ void mbar_expect(uint32_t a, int bytes) { asm volatile("mbarrier.arrive.expect_tx.shared.b64 _, [%0], %1;" :: "r"(a), "r"(bytes) : "memory"); }
__device__ __forceinline__ void mbar_arrive(uint32_t a) { asm volatile("mbarrier.arrive.shared.b64 _, [%0];" :: "r"(a) : "memory"); }
__device__ __forceinline__ void mbar_wait(uint32_t a, int parity) {
    uint32_t done;
    int it = 0;
    do {
        asm volatile("{\n.reg .pred p;\nmbarrier.try_wait.parity.shared.b64 p, [%1], %2;\nselp.u32 %0, 1, 0, p;\n}"
                     : "=r"(done) : "r"(a), "r"(parity) : "memory");
        if (++it > (1 << 24)) __trap();
    } while (!done);
}
__device__ __forceinline__ void bulk_g2s(uint32_t dst, const void* src, int bytes, uint32_t bar) {
    asm volatile("cp.async.bulk.shared::cluster.global.mbarrier::complete_tx::bytes [%0], [%1], %2, [%3];"
                 :: "r"(dst), "l"(src), "r"(bytes), "r"(bar) : "memory");
}
__device__ __forceinline__ void tma2d(uint32_t dst, const CUtensorMap* m, int c0, int c1, uint32_t bar) {
    asm volatile("cp.async.bulk.tensor.2d.shared::cluster.global.mbarrier::complete_tx::bytes [%0], [%1, {%3, %4}], [%2];"
                 :: "r"(dst), "l"(m), "r"(bar), "r"(c0), "r"(c1) : "memory");
}
__device__ __forceinline__ void tma3d(uint32_t dst, const CUtensorMap* m, int c0, int c1, int c2, uint32_t bar) {
    asm volatile("cp.async.bulk.tensor.3d.shared::cluster.global.mbarrier::complete_tx::bytes [%0], [%1, {%3, %4, %5}], [%2];"
                 :: "r"(dst), "l"(m), "r"(bar), "r"(c0), "r"(c1), "r"(c2) : "memory");
}
__device__ __forceinline__ void prefetch_tmap(const CUtensorMap* m) { asm volatile("prefetch.tensormap [%0];" :: "l"(m) : "memory"); }
__device__ __forceinline__ void pdl_wait() { asm volatile("griddepcontrol.wait;" ::: "memory"); }
__device__ __forceinline__ void pdl_launch() { asm volatile("griddepcontrol.launch_dependents;" ::: "memory"); }
__device__ __forceinline__ void fence_barrier_init() { asm volatile("fence.mbarrier_init.release.cluster;" ::: "memory"); }
__device__ __forceinline__ void fence_proxy_async() { asm volatile("fence.proxy.async.shared::cta;" ::: "memory"); }
__device__ __forceinline__ uint64_t make_desc(uint32_t saddr, uint32_t lbo, uint32_t sbo, uint32_t swz) {
    return (uint64_t)((saddr & 0x3FFFF) >> 4) | ((uint64_t)((lbo & 0x3FFFF) >> 4) << 16) |
           ((uint64_t)((sbo & 0x3FFFF) >> 4) << 32) | ((uint64_t)swz << 62);
}
#define WG_FENCE() asm volatile("wgmma.fence.sync.aligned;" ::: "memory")
#define WG_COMMIT() asm volatile("wgmma.commit_group.sync.aligned;" ::: "memory")
template <int N> __device__ __forceinline__ void wg_wait() { asm volatile("wgmma.wait_group.sync.aligned %0;" :: "n"(N) : "memory"); }
template <int N> __device__ __forceinline__ void fence_regs(float (&d)[N]) {
#pragma unroll
    for (int i = 0; i < N; i++) asm volatile("" : "+f"(d[i]) :: "memory");
}
__device__ __forceinline__ float ex2f(float x) { float y; asm("ex2.approx.ftz.f32 %0, %1;" : "=f"(y) : "f"(x)); return y; }
__device__ __forceinline__ float tanh_fast(float x) { float y; asm("tanh.approx.f32 %0, %1;" : "=f"(y) : "f"(x)); return y; }
__device__ __forceinline__ uint32_t pack_bf16(float lo, float hi) { uint32_t r; asm("cvt.rn.bf16x2.f32 %0, %1, %2;" : "=r"(r) : "f"(hi), "f"(lo)); return r; }
__device__ __forceinline__ float bf_lo(uint32_t u) { return __uint_as_float(u << 16); }
__device__ __forceinline__ float bf_hi(uint32_t u) { return __uint_as_float(u & 0xFFFF0000u); }
__device__ __forceinline__ uint32_t hfma2(uint32_t a, uint32_t b, uint32_t c) { uint32_t r; asm("fma.rn.f16x2 %0, %1, %2, %3;" : "=r"(r) : "r"(a), "r"(b), "r"(c)); return r; }
__device__ __forceinline__ uint32_t hmul2(uint32_t a, uint32_t b) { uint32_t r; asm("mul.rn.f16x2 %0, %1, %2;" : "=r"(r) : "r"(a), "r"(b)); return r; }
__device__ __forceinline__ unsigned int ld_acquire(const unsigned int* p) { unsigned int v; asm volatile("ld.acquire.gpu.u32 %0, [%1];" : "=r"(v) : "l"(p) : "memory"); return v; }
__device__ __forceinline__ void red_release(unsigned int* p) { asm volatile("red.release.gpu.global.add.u32 [%0], 1;" :: "l"(p) : "memory"); }
__device__ __forceinline__ void stsm4(uint32_t addr, uint32_t a, uint32_t b, uint32_t c, uint32_t d) {
    asm volatile("stmatrix.sync.aligned.m8n8.x4.shared.b16 [%0], {%1,%2,%3,%4};" :: "r"(addr), "r"(a), "r"(b), "r"(c), "r"(d) : "memory");
}
__device__ __forceinline__ void bulk_s2g(void* dst, uint32_t src, int bytes) {
    asm volatile("cp.async.bulk.global.shared::cta.bulk_group [%0], [%1], %2;" :: "l"(dst), "r"(src), "r"(bytes) : "memory");
}
__device__ __forceinline__ void bulk_commit() { asm volatile("cp.async.bulk.commit_group;" ::: "memory"); }
__device__ __forceinline__ void bulk_wait_all() { asm volatile("cp.async.bulk.wait_group 0;" ::: "memory"); }
__device__ __forceinline__ void bulk_wait_read() { asm volatile("cp.async.bulk.wait_group.read 0;" ::: "memory"); }
__device__ __forceinline__ void bar_sync(int id, int n) { asm volatile("bar.sync %0, %1;" :: "r"(id), "r"(n) : "memory"); }
__device__ __forceinline__ void bar_arrive(int id, int n) { asm volatile("bar.arrive %0, %1;" :: "r"(id), "r"(n) : "memory"); }
__device__ __forceinline__ float warp_sum(float v) {
#pragma unroll
    for (int o = 16; o; o >>= 1) v += __shfl_xor_sync(0xffffffffu, v, o);
    return v;
}
__device__ __forceinline__ float warp_max(float v) {
#pragma unroll
    for (int o = 16; o; o >>= 1) v = fmaxf(v, __shfl_xor_sync(0xffffffffu, v, o));
    return v;
}

__device__ __forceinline__ void wgmma_ss_n64(float (&d)[32], uint64_t adesc, uint64_t bdesc, int scale_d) {
    asm volatile("{\n.reg .pred p;\nsetp.ne.b32 p, %34, 0;\n"
      "wgmma.mma_async.sync.aligned.m64n64k16.f32.bf16.bf16 {%0,%1,%2,%3,%4,%5,%6,%7,%8,%9,%10,%11,%12,%13,%14,%15,%16,%17,%18,%19,%20,%21,%22,%23,%24,%25,%26,%27,%28,%29,%30,%31}, %32, %33, p, 1, 1, 0, 1;\n}"
      : "+f"(d[0]), "+f"(d[1]), "+f"(d[2]), "+f"(d[3]), "+f"(d[4]), "+f"(d[5]), "+f"(d[6]), "+f"(d[7]), "+f"(d[8]), "+f"(d[9]), "+f"(d[10]), "+f"(d[11]), "+f"(d[12]), "+f"(d[13]), "+f"(d[14]), "+f"(d[15]), "+f"(d[16]), "+f"(d[17]), "+f"(d[18]), "+f"(d[19]), "+f"(d[20]), "+f"(d[21]), "+f"(d[22]), "+f"(d[23]), "+f"(d[24]), "+f"(d[25]), "+f"(d[26]), "+f"(d[27]), "+f"(d[28]), "+f"(d[29]), "+f"(d[30]), "+f"(d[31])
      : "l"(adesc), "l"(bdesc), "r"(scale_d));
}
__device__ __forceinline__ void wgmma_ss_n96(float (&d)[48], uint64_t adesc, uint64_t bdesc, int scale_d) {
    asm volatile("{\n.reg .pred p;\nsetp.ne.b32 p, %50, 0;\n"
      "wgmma.mma_async.sync.aligned.m64n96k16.f32.bf16.bf16 {%0,%1,%2,%3,%4,%5,%6,%7,%8,%9,%10,%11,%12,%13,%14,%15,%16,%17,%18,%19,%20,%21,%22,%23,%24,%25,%26,%27,%28,%29,%30,%31,%32,%33,%34,%35,%36,%37,%38,%39,%40,%41,%42,%43,%44,%45,%46,%47}, %48, %49, p, 1, 1, 0, 1;\n}"
      : "+f"(d[0]), "+f"(d[1]), "+f"(d[2]), "+f"(d[3]), "+f"(d[4]), "+f"(d[5]), "+f"(d[6]), "+f"(d[7]), "+f"(d[8]), "+f"(d[9]), "+f"(d[10]), "+f"(d[11]), "+f"(d[12]), "+f"(d[13]), "+f"(d[14]), "+f"(d[15]), "+f"(d[16]), "+f"(d[17]), "+f"(d[18]), "+f"(d[19]), "+f"(d[20]), "+f"(d[21]), "+f"(d[22]), "+f"(d[23]), "+f"(d[24]), "+f"(d[25]), "+f"(d[26]), "+f"(d[27]), "+f"(d[28]), "+f"(d[29]), "+f"(d[30]), "+f"(d[31]), "+f"(d[32]), "+f"(d[33]), "+f"(d[34]), "+f"(d[35]), "+f"(d[36]), "+f"(d[37]), "+f"(d[38]), "+f"(d[39]), "+f"(d[40]), "+f"(d[41]), "+f"(d[42]), "+f"(d[43]), "+f"(d[44]), "+f"(d[45]), "+f"(d[46]), "+f"(d[47])
      : "l"(adesc), "l"(bdesc), "r"(scale_d));
}
__device__ __forceinline__ void wgmma_ss_n128(float (&d)[64], uint64_t adesc, uint64_t bdesc, int scale_d) {
    asm volatile("{\n.reg .pred p;\nsetp.ne.b32 p, %66, 0;\n"
      "wgmma.mma_async.sync.aligned.m64n128k16.f32.bf16.bf16 {%0,%1,%2,%3,%4,%5,%6,%7,%8,%9,%10,%11,%12,%13,%14,%15,%16,%17,%18,%19,%20,%21,%22,%23,%24,%25,%26,%27,%28,%29,%30,%31,%32,%33,%34,%35,%36,%37,%38,%39,%40,%41,%42,%43,%44,%45,%46,%47,%48,%49,%50,%51,%52,%53,%54,%55,%56,%57,%58,%59,%60,%61,%62,%63}, %64, %65, p, 1, 1, 0, 1;\n}"
      : "+f"(d[0]), "+f"(d[1]), "+f"(d[2]), "+f"(d[3]), "+f"(d[4]), "+f"(d[5]), "+f"(d[6]), "+f"(d[7]), "+f"(d[8]), "+f"(d[9]), "+f"(d[10]), "+f"(d[11]), "+f"(d[12]), "+f"(d[13]), "+f"(d[14]), "+f"(d[15]), "+f"(d[16]), "+f"(d[17]), "+f"(d[18]), "+f"(d[19]), "+f"(d[20]), "+f"(d[21]), "+f"(d[22]), "+f"(d[23]), "+f"(d[24]), "+f"(d[25]), "+f"(d[26]), "+f"(d[27]), "+f"(d[28]), "+f"(d[29]), "+f"(d[30]), "+f"(d[31]), "+f"(d[32]), "+f"(d[33]), "+f"(d[34]), "+f"(d[35]), "+f"(d[36]), "+f"(d[37]), "+f"(d[38]), "+f"(d[39]), "+f"(d[40]), "+f"(d[41]), "+f"(d[42]), "+f"(d[43]), "+f"(d[44]), "+f"(d[45]), "+f"(d[46]), "+f"(d[47]), "+f"(d[48]), "+f"(d[49]), "+f"(d[50]), "+f"(d[51]), "+f"(d[52]), "+f"(d[53]), "+f"(d[54]), "+f"(d[55]), "+f"(d[56]), "+f"(d[57]), "+f"(d[58]), "+f"(d[59]), "+f"(d[60]), "+f"(d[61]), "+f"(d[62]), "+f"(d[63])
      : "l"(adesc), "l"(bdesc), "r"(scale_d));
}
__device__ __forceinline__ void wgmma_ss_n192(float (&d)[96], uint64_t adesc, uint64_t bdesc, int scale_d) {
    asm volatile("{\n.reg .pred p;\nsetp.ne.b32 p, %98, 0;\n"
      "wgmma.mma_async.sync.aligned.m64n192k16.f32.bf16.bf16 {%0,%1,%2,%3,%4,%5,%6,%7,%8,%9,%10,%11,%12,%13,%14,%15,%16,%17,%18,%19,%20,%21,%22,%23,%24,%25,%26,%27,%28,%29,%30,%31,%32,%33,%34,%35,%36,%37,%38,%39,%40,%41,%42,%43,%44,%45,%46,%47,%48,%49,%50,%51,%52,%53,%54,%55,%56,%57,%58,%59,%60,%61,%62,%63,%64,%65,%66,%67,%68,%69,%70,%71,%72,%73,%74,%75,%76,%77,%78,%79,%80,%81,%82,%83,%84,%85,%86,%87,%88,%89,%90,%91,%92,%93,%94,%95}, %96, %97, p, 1, 1, 0, 1;\n}"
      : "+f"(d[0]), "+f"(d[1]), "+f"(d[2]), "+f"(d[3]), "+f"(d[4]), "+f"(d[5]), "+f"(d[6]), "+f"(d[7]), "+f"(d[8]), "+f"(d[9]), "+f"(d[10]), "+f"(d[11]), "+f"(d[12]), "+f"(d[13]), "+f"(d[14]), "+f"(d[15]), "+f"(d[16]), "+f"(d[17]), "+f"(d[18]), "+f"(d[19]), "+f"(d[20]), "+f"(d[21]), "+f"(d[22]), "+f"(d[23]), "+f"(d[24]), "+f"(d[25]), "+f"(d[26]), "+f"(d[27]), "+f"(d[28]), "+f"(d[29]), "+f"(d[30]), "+f"(d[31]), "+f"(d[32]), "+f"(d[33]), "+f"(d[34]), "+f"(d[35]), "+f"(d[36]), "+f"(d[37]), "+f"(d[38]), "+f"(d[39]), "+f"(d[40]), "+f"(d[41]), "+f"(d[42]), "+f"(d[43]), "+f"(d[44]), "+f"(d[45]), "+f"(d[46]), "+f"(d[47]), "+f"(d[48]), "+f"(d[49]), "+f"(d[50]), "+f"(d[51]), "+f"(d[52]), "+f"(d[53]), "+f"(d[54]), "+f"(d[55]), "+f"(d[56]), "+f"(d[57]), "+f"(d[58]), "+f"(d[59]), "+f"(d[60]), "+f"(d[61]), "+f"(d[62]), "+f"(d[63]), "+f"(d[64]), "+f"(d[65]), "+f"(d[66]), "+f"(d[67]), "+f"(d[68]), "+f"(d[69]), "+f"(d[70]), "+f"(d[71]), "+f"(d[72]), "+f"(d[73]), "+f"(d[74]), "+f"(d[75]), "+f"(d[76]), "+f"(d[77]), "+f"(d[78]), "+f"(d[79]), "+f"(d[80]), "+f"(d[81]), "+f"(d[82]), "+f"(d[83]), "+f"(d[84]), "+f"(d[85]), "+f"(d[86]), "+f"(d[87]), "+f"(d[88]), "+f"(d[89]), "+f"(d[90]), "+f"(d[91]), "+f"(d[92]), "+f"(d[93]), "+f"(d[94]), "+f"(d[95])
      : "l"(adesc), "l"(bdesc), "r"(scale_d));
}
__device__ __forceinline__ void qk_wgmma_n64(float (&d)[32], const uint32_t (&a)[4], uint64_t desc) {
    asm volatile("wgmma.mma_async.sync.aligned.m64n64k16.f32.bf16.bf16 {%0,%1,%2,%3,%4,%5,%6,%7,%8,%9,%10,%11,%12,%13,%14,%15,%16,%17,%18,%19,%20,%21,%22,%23,%24,%25,%26,%27,%28,%29,%30,%31}, {%32,%33,%34,%35}, %36, 0, 1, 1, 0;"
      : "=f"(d[0]), "=f"(d[1]), "=f"(d[2]), "=f"(d[3]), "=f"(d[4]), "=f"(d[5]), "=f"(d[6]), "=f"(d[7]), "=f"(d[8]), "=f"(d[9]), "=f"(d[10]), "=f"(d[11]), "=f"(d[12]), "=f"(d[13]), "=f"(d[14]), "=f"(d[15]), "=f"(d[16]), "=f"(d[17]), "=f"(d[18]), "=f"(d[19]), "=f"(d[20]), "=f"(d[21]), "=f"(d[22]), "=f"(d[23]), "=f"(d[24]), "=f"(d[25]), "=f"(d[26]), "=f"(d[27]), "=f"(d[28]), "=f"(d[29]), "=f"(d[30]), "=f"(d[31])
      : "r"(a[0]), "r"(a[1]), "r"(a[2]), "r"(a[3]), "l"(desc));
}

__device__ __forceinline__ void pv_wgmma(float (&d)[12], uint32_t a0, uint32_t a1, uint32_t a2, uint32_t a3, uint64_t desc) {
    asm volatile("wgmma.mma_async.sync.aligned.m64n24k16.f32.bf16.bf16 {%0,%1,%2,%3,%4,%5,%6,%7,%8,%9,%10,%11}, {%12,%13,%14,%15}, %16, 1, 1, 1, 1;"
      : "+f"(d[0]), "+f"(d[1]), "+f"(d[2]), "+f"(d[3]), "+f"(d[4]), "+f"(d[5]), "+f"(d[6]), "+f"(d[7]), "+f"(d[8]), "+f"(d[9]), "+f"(d[10]), "+f"(d[11])
      : "r"(a0), "r"(a1), "r"(a2), "r"(a3), "l"(desc));
}

__device__ __forceinline__ void tile_of(int bid, int& mb, int& nt) {
    int grp = bid >> 4, in = bid & 15;
    mb = (grp >> 1) * 4 + (in >> 2);
    nt = (grp & 1) * 4 + (in & 3);
}

constexpr int K1_STAGES = 5, K1_STAGE = 16384 + 24576;
constexpr int K1_BAR = K1_STAGES * K1_STAGE, K1_RS = K1_BAR + 128, K1_CS = K1_RS + 1024, K1_SMEM = K1_CS + 768;

__device__ __forceinline__ float2 row_stats_regs(uint4 a, uint4 b) {
    float v[16];
    v[0] = bf_lo(a.x); v[1] = bf_hi(a.x); v[2] = bf_lo(a.y); v[3] = bf_hi(a.y);
    v[4] = bf_lo(a.z); v[5] = bf_hi(a.z); v[6] = bf_lo(a.w); v[7] = bf_hi(a.w);
    v[8] = bf_lo(b.x); v[9] = bf_hi(b.x); v[10] = bf_lo(b.y); v[11] = bf_hi(b.y);
    v[12] = bf_lo(b.z); v[13] = bf_hi(b.z); v[14] = bf_lo(b.w); v[15] = bf_hi(b.w);
    float s = 0.f;
#pragma unroll
    for (int i = 0; i < 16; i++) s += v[i];
    float mean = warp_sum(s) * (1.0f / DM);
    float q = 0.f;
#pragma unroll
    for (int i = 0; i < 16; i++) { float d = v[i] - mean; q = fmaf(d, d, q); }
    float var = warp_sum(q) * (1.0f / DM);
    float rstd = rsqrtf(var + 1e-5f);
    return make_float2(rstd, -mean * rstd);
}
__device__ __forceinline__ float2 row_stats_x(const __nv_bfloat16* x, int row, int lane) {
    const uint4* p = (const uint4*)(x + (size_t)row * DM);
    return row_stats_regs(__ldg(p + lane), __ldg(p + 32 + lane));
}
__device__ __forceinline__ void colsum8(const __nv_bfloat16* w, int ld, int col, int k0, int nk, float (&s)[8]) {
#pragma unroll
    for (int i = 0; i < 8; i++) s[i] = 0.f;
    for (int k = k0; k < k0 + nk; k += 8) {
        uint4 u[8];
#pragma unroll
        for (int i = 0; i < 8; i++) u[i] = __ldg((const uint4*)(w + (size_t)(k + i) * ld + col));
#pragma unroll
        for (int i = 0; i < 8; i++) {
            s[0] += bf_lo(u[i].x); s[1] += bf_hi(u[i].x); s[2] += bf_lo(u[i].y); s[3] += bf_hi(u[i].y);
            s[4] += bf_lo(u[i].z); s[5] += bf_hi(u[i].z); s[6] += bf_lo(u[i].w); s[7] += bf_hi(u[i].w);
        }
    }
}
__device__ __forceinline__ bool wait_count(const unsigned int* p, unsigned int target, int lane) {
    int ok = 1;
    if (lane == 0) {
        int it = 0;
        while (ld_acquire(p) < target) { if (++it > (1 << 18)) { ok = 0; break; } }
    }
    ok = __shfl_sync(0xffffffffu, ok, 0);
    return ok != 0;
}

__global__ void __launch_bounds__(384, 1)
qkv_kernel(const __grid_constant__ CUtensorMap tm_x, const __grid_constant__ CUtensorMap tm_w,
           const __nv_bfloat16* __restrict__ x, const __nv_bfloat16* __restrict__ wqkv) {
    extern __shared__ __align__(1024) unsigned char smem[];
    const uint32_t sb = smem_u32(smem);
    const int tid = threadIdx.x, warp = __shfl_sync(0xffffffffu, tid >> 5, 0), lane = tid & 31;
    TL(0);
    int mb, nt;
    tile_of(blockIdx.x, mb, nt);
    const uint32_t full = sb + K1_BAR, empty = full + 40, auxb = full + 80;
    if (tid == 0) {
        prefetch_tmap(&tm_x); prefetch_tmap(&tm_w);
        for (int i = 0; i < K1_STAGES; i++) { mbar_init(full + 8 * i, 1); mbar_init(empty + 8 * i, 8); }
        mbar_init(auxb, 3);
        fence_barrier_init();
    }
    __syncthreads();
    pdl_launch();
    if (warp == 0) {
        if (blockIdx.x == 0) { g_cnt2[lane] = 0; g_cnt2[32 + lane] = 0; }
        if (lane == 0) {
            for (int kb = 0; kb < 8; kb++) {
                int s = kb % K1_STAGES;
                if (kb >= K1_STAGES) mbar_wait(empty + 8 * s, 0);
                mbar_expect(full + 8 * s, K1_STAGE);
                tma2d(sb + s * K1_STAGE, &tm_x, kb * 64, mb * 128, full + 8 * s);
                tma3d(sb + s * K1_STAGE + 16384, &tm_w, 0, kb * 64, nt * 3, full + 8 * s);
            }
        }
    } else if (warp < 4) {
        float2* s_rs = (float2*)(smem + K1_RS);
        float* s_cs = (float*)(smem + K1_CS);
        if (warp < 3) {
            const int r0 = mb * 128 + nt * 16 + (warp - 1) * 8;
            uint4 u[16];
#pragma unroll
            for (int i = 0; i < 8; i++) {
                const uint4* p = (const uint4*)(x + (size_t)(r0 + i) * DM);
                u[2 * i] = __ldg(p + lane); u[2 * i + 1] = __ldg(p + 32 + lane);
            }
            float2 mine = make_float2(0.f, 0.f);
#pragma unroll
            for (int i = 0; i < 8; i++) {
                float2 st = row_stats_regs(u[2 * i], u[2 * i + 1]);
                if (lane == i) mine = st;
            }
            if (lane < 8) g_rowstat1[r0 + lane] = mine;
            __syncwarp();
            if (lane == 0) red_release(&g_cnt[mb]);
        } else {
            uint4 u[24];
#pragma unroll
            for (int c = 0; c < 3; c++)
#pragma unroll
                for (int i = 0; i < 8; i++)
                    u[c * 8 + i] = __ldg((const uint4*)(wqkv + (size_t)(mb * 32 + (lane >> 3) * 8 + i) * 1536 + nt * 192 + (c * 8 + (lane & 7)) * 8));
#pragma unroll
            for (int c = 0; c < 3; c++) {
                float cs[8];
#pragma unroll
                for (int i = 0; i < 8; i++) cs[i] = 0.f;
#pragma unroll
                for (int i = 0; i < 8; i++) {
                    const uint4 w = u[c * 8 + i];
                    cs[0] += bf_lo(w.x); cs[1] += bf_hi(w.x); cs[2] += bf_lo(w.y); cs[3] += bf_hi(w.y);
                    cs[4] += bf_lo(w.z); cs[5] += bf_hi(w.z); cs[6] += bf_lo(w.w); cs[7] += bf_hi(w.w);
                }
#pragma unroll
                for (int i = 0; i < 8; i++) {
                    cs[i] += __shfl_xor_sync(0xffffffffu, cs[i], 8);
                    cs[i] += __shfl_xor_sync(0xffffffffu, cs[i], 16);
                }
                if (lane < 8) {
                    float4* d = (float4*)(g_cs1_part + mb * 1536 + nt * 192 + (c * 8 + lane) * 8);
                    d[0] = make_float4(cs[0], cs[1], cs[2], cs[3]);
                    d[1] = make_float4(cs[4], cs[5], cs[6], cs[7]);
                }
            }
            __syncwarp();
            if (lane == 0) red_release(&g_cnt[16 + nt]);
        }
        TX(8 + warp);
        if (warp == 1) {
            if (wait_count(&g_cnt[mb], 16, lane)) {
#pragma unroll
                for (int i = 0; i < 4; i++) s_rs[lane + 32 * i] = __ldcg(&g_rowstat1[mb * 128 + lane + 32 * i]);
            } else {
                for (int i = 0; i < 128; i++) {
                    float2 st = row_stats_x(x, mb * 128 + i, lane);
                    if (lane == 0) s_rs[i] = st;
                }
            }
        } else {
            int c0 = (warp - 2) * 96;
            if (wait_count(&g_cnt[16 + nt], 16, lane)) {
#pragma unroll
                for (int i = 0; i < 3; i++) {
                    float s = 0.f;
#pragma unroll
                    for (int p = 0; p < 16; p++) s += __ldcg(&g_cs1_part[p * 1536 + nt * 192 + c0 + lane + 32 * i]);
                    s_cs[c0 + lane + 32 * i] = s;
                }
            } else if (lane < 12) {
                float s[8];
                colsum8(wqkv, 1536, nt * 192 + c0 + lane * 8, 0, 512, s);
#pragma unroll
                for (int i = 0; i < 8; i++) s_cs[c0 + lane * 8 + i] = s[i];
            }
        }
        __syncwarp();
        TX(12 + warp);
        if (lane == 0) mbar_arrive(auxb);
        bar_sync(2, 256 + 96);
        const int a = tid - 32;
        {
            const int hh = a >> 3, w = a & 7;
            const float4* p = (const float4*)(smem + 49152) + (hh * 256 + w * 32) / 2;
            float m = 0.f;
#pragma unroll
            for (int i = 0; i < 8; i++) {
                const int ii = (i + a) & 7;
                float4 u = p[2 * ii], v = p[2 * ii + 1];
                float n0 = u.x + u.z + v.x + v.z, n1 = u.y + u.w + v.y + v.w;
                if (!(n0 <= 3.0e38f) || !(n1 <= 3.0e38f)) m = __int_as_float(0x7f800000);
                m = fmaxf(m, fmaxf(n0, n1));
            }
            const int col0 = nt * 192 + hh * 16;
            g_nrm[((col0 >> 9) * NH + ((col0 & 511) >> 4)) * 128 + mb * 8 + w] = m;
        }
        if (a < 24) bulk_wait_all();
        TL(27);
    } else {
        const int wgi = (warp >> 2) - 1, ww = warp & 3;
        float acc[96];
#pragma unroll 1
        for (int kb = 0; kb < 8; kb++) {
            int s = kb % K1_STAGES;
            mbar_wait(full + 8 * s, (kb / K1_STAGES) & 1);
            if (warp == 4) TX(kb);
            uint64_t ad = make_desc(sb + s * K1_STAGE + wgi * 8192, 16, 1024, 1);
            uint64_t bd = make_desc(sb + s * K1_STAGE + 16384, 8192, 1024, 1);
            WG_FENCE();
#pragma unroll
            for (int k = 0; k < 4; k++) wgmma_ss_n192(acc, ad + k * 2, bd + k * 128, (kb | k) != 0);
            WG_COMMIT();
            if (kb > 0) {
                wg_wait<1>();
                if (lane == 0) mbar_arrive(empty + 8 * ((kb - 1) % K1_STAGES));
            }
        }
        wg_wait<0>();
        fence_regs(acc);
        TL(1);
        if (warp == 4) TX(16);
        mbar_wait(auxb, 0);
        if (warp == 4) TX(17);
        bar_sync(1, 256);
        const float2* s_rs = (const float2*)(smem + K1_RS);
        const float* s_cs = (const float*)(smem + K1_CS);
        const int g = lane >> 2, t = lane & 3;
        const int rl = wgi * 64 + ww * 16 + g;
        const float2 st0 = s_rs[rl], st1 = s_rs[rl + 8];
        const float QS = 0.25f * 1.4426950408889634f;
        const uint32_t stg = sb + ((lane >> 4) * 16 + wgi * 8 + ww * 2 + ((lane >> 3) & 1)) * 128 + (lane & 7) * 16;
        float2* s_np = (float2*)(smem + 49152) + (warp - 4) * 32 + lane;
#pragma unroll
        for (int hh = 0; hh < 12; hh++) {
            const int which = (nt * 192 + hh * 16) >> 9;
            const float sc = (which == 0) ? QS : 1.0f;
            const float a0 = st0.x * sc, b0 = st0.y * sc, a1 = st1.x * sc, b1 = st1.y * sc;
            const float2 c0 = *(const float2*)(s_cs + 16 * hh + 2 * t), c1 = *(const float2*)(s_cs + 16 * hh + 8 + 2 * t);
            const float* a = acc + 8 * hh;
            float v0 = fmaf(a0, a[0], b0 * c0.x), v1 = fmaf(a0, a[1], b0 * c0.y), v2 = fmaf(a1, a[2], b1 * c0.x), v3 = fmaf(a1, a[3], b1 * c0.y);
            float v4 = fmaf(a0, a[4], b0 * c1.x), v5 = fmaf(a0, a[5], b0 * c1.y), v6 = fmaf(a1, a[6], b1 * c1.x), v7 = fmaf(a1, a[7], b1 * c1.y);
            {
                const int head = ((nt * 192 + hh * 16) & 511) >> 4;
                uint32_t* o = (uint32_t*)g_qkv + ((size_t)((which * NH + head) * 2) * 256 + mb * 16 + wgi * 8 + ww * 2) * 32 + lane;
                o[0] = pack_bf16(v0, v1); o[32] = pack_bf16(v2, v3); o[8192] = pack_bf16(v4, v5); o[8192 + 32] = pack_bf16(v6, v7);
            }
            s_np[hh * 256] = make_float2(fmaf(v0, v0, fmaf(v1, v1, fmaf(v4, v4, v5 * v5))), fmaf(v2, v2, fmaf(v3, v3, fmaf(v6, v6, v7 * v7))));
        }
        fence_proxy_async();
        bar_arrive(2, 256 + 96);
        TL(2);
        if (warp == 4) TX(18);
    }
}

constexpr int AT_K = 0, AT_V = 65536, AT_ONES = 131072, AT_BAR = 163840, AT_SMEM = AT_BAR + 128;
#define POLY_MASK 0xAD6A

__device__ __forceinline__ uint32_t exp2_pair_poly(float x0, float x1) {
    uint32_t t0 = __float_as_uint(x0 + 32895.0f);
    uint32_t t1 = __float_as_uint(x1 + 32895.0f);
    uint32_t gd = __byte_perm(t0, t1, 0x6420);
    uint32_t wm = __byte_perm(t0, t1, 0x5612);
    uint32_t v = hfma2(gd, 0x71477147u, 0x354f354fu);
    uint32_t z = hmul2(v, gd);
    return (wm >> 1) + z;
}
__device__ __forceinline__ uint32_t exp2_pair_mufu(float x0, float x1) { return pack_bf16(ex2f(x0), ex2f(x1)); }
template <uint32_t MASK>
__device__ __forceinline__ void exp_blocks(const float (&s)[32], uint32_t (&p)[16]) {
#pragma unroll
    for (int b = 0; b < 8; b++) {
        if ((MASK >> b) & 1) {
            p[2 * b] = exp2_pair_poly(s[4 * b], s[4 * b + 1]);
            p[2 * b + 1] = exp2_pair_poly(s[4 * b + 2], s[4 * b + 3]);
        } else {
            p[2 * b] = exp2_pair_mufu(s[4 * b], s[4 * b + 1]);
            p[2 * b + 1] = exp2_pair_mufu(s[4 * b + 2], s[4 * b + 3]);
        }
    }
}
#define PV4(P) _Pragma("unroll") for (int i = 0; i < 4; i++) { pv_wgmma(o, P[4 * i], P[4 * i + 1], P[4 * i + 2], P[4 * i + 3], vd); vd += 16; }

__device__ __forceinline__ void attn_store(float (&o)[12], int row0, int head, int lane) {
    float l0 = __shfl_sync(0xffffffffu, o[8], lane & 28);
    float l1 = __shfl_sync(0xffffffffu, o[10], lane & 28);
    float r0 = 1.0f / l0, r1 = 1.0f / l1;
    uint32_t* op = (uint32_t*)g_ao;
    int mb = row0 >> 7, rg = (row0 & 127) >> 3;
    int kb = head >> 2, kc = (head & 3) * 2;
    size_t base = (((size_t)(mb * 8 + kb) * 8 + kc) * 16 + rg) * 32 + lane;
    op[base] = pack_bf16(o[0] * r0, o[1] * r0);
    op[base + 32] = pack_bf16(o[2] * r1, o[3] * r1);
    op[base + 16 * 32] = pack_bf16(o[4] * r0, o[5] * r0);
    op[base + 16 * 32 + 32] = pack_bf16(o[6] * r1, o[7] * r1);
}

__device__ __forceinline__ void attn_load_q(uint32_t (&q)[4], const __nv_bfloat16* gq, int row0, int lane) {
    const uint32_t* qp = (const uint32_t*)gq;
    int j0 = row0 >> 3;
    q[0] = __ldcg(qp + (0 * 256 + j0) * 32 + lane);
    q[1] = __ldcg(qp + (0 * 256 + j0 + 1) * 32 + lane);
    q[2] = __ldcg(qp + (1 * 256 + j0) * 32 + lane);
    q[3] = __ldcg(qp + (1 * 256 + j0 + 1) * 32 + lane);
}

__device__ __forceinline__ void attn_tile_safe(const uint32_t (&q)[4], uint64_t kd, uint64_t vd, int row0, int head, int lane) {
    float o[12];
#pragma unroll
    for (int i = 0; i < 12; i++) o[i] = 0.f;
    float m0 = -INFINITY, m1 = -INFINITY;
    fence_regs(o);
#pragma unroll 1
    for (int j = 0; j < 32; j++) {
        float s[32];
        uint32_t p[16];
        WG_FENCE();
        qk_wgmma_n64(s, q, kd); kd += 64;
        WG_COMMIT();
        wg_wait<0>();
        fence_regs(s);
        fence_regs(o);
        float x0 = m0, x1 = m1;
#pragma unroll
        for (int b = 0; b < 8; b++) {
            x0 = fmaxf(x0, fmaxf(s[4 * b], s[4 * b + 1]));
            x1 = fmaxf(x1, fmaxf(s[4 * b + 2], s[4 * b + 3]));
        }
        x0 = fmaxf(x0, __shfl_xor_sync(0xffffffffu, x0, 1)); x0 = fmaxf(x0, __shfl_xor_sync(0xffffffffu, x0, 2));
        x1 = fmaxf(x1, __shfl_xor_sync(0xffffffffu, x1, 1)); x1 = fmaxf(x1, __shfl_xor_sync(0xffffffffu, x1, 2));
        float al0 = ex2f(m0 - x0), al1 = ex2f(m1 - x1);
        m0 = x0; m1 = x1;
#pragma unroll
        for (int i = 0; i < 3; i++) { o[4 * i] *= al0; o[4 * i + 1] *= al0; o[4 * i + 2] *= al1; o[4 * i + 3] *= al1; }
#pragma unroll
        for (int b = 0; b < 8; b++) {
            p[2 * b] = exp2_pair_mufu(s[4 * b] - m0, s[4 * b + 1] - m0);
            p[2 * b + 1] = exp2_pair_mufu(s[4 * b + 2] - m1, s[4 * b + 3] - m1);
        }
        fence_regs(o);
        WG_FENCE();
        PV4(p);
        WG_COMMIT();
        wg_wait<0>();
        fence_regs(o);
    }
    attn_store(o, row0, head, lane);
}

__global__ void __launch_bounds__(512, 1)
attn_kernel(const __nv_bfloat16* __restrict__ wg_, const __nv_bfloat16* __restrict__ wu_,
            const __nv_bfloat16* __restrict__ wo_, const __nv_bfloat16* __restrict__ wd_) {
    extern __shared__ __align__(1024) unsigned char smem[];
    const uint32_t sb = smem_u32(smem);
    const int tid = threadIdx.x, wg = tid >> 7, warp = (tid >> 5) & 3, lane = tid & 31;
    pdl_launch();
    if (blockIdx.x >= 128) {
        const int e = blockIdx.x - 128;
        const __nv_bfloat16* w = (e < 2) ? wg_ : wu_;
        float* red = (float*)smem;
        const int cgrp = tid & 127, kq = tid >> 7;
        if (cgrp < 112) {
            float s[8];
            colsum8(w, FF, (e & 1) * 896 + cgrp * 8, kq * 128, 128, s);
#pragma unroll
            for (int i = 0; i < 8; i++) red[kq * 896 + cgrp * 8 + i] = s[i];
        }
        __syncthreads();
        for (int c = tid; c < 896; c += 512)
            g_cs2[(e >> 1) * FF + (e & 1) * 896 + c] = red[c] + red[896 + c] + red[1792 + c] + red[2688 + c];
        if (tid < 32) {
            const char* p0 = (const char*)wo_ + e * (DM * DM * 2 / 4);
            for (int i = lane; i < 32; i += 32)
                asm volatile("cp.async.bulk.prefetch.L2.global [%0], %1;" :: "l"(p0 + i * 4096), "r"(4096) : "memory");
            const char* p1 = (const char*)wd_ + e * (FF * DM * 2 / 4);
            for (int i = lane; i < 112; i += 32)
                asm volatile("cp.async.bulk.prefetch.L2.global [%0], %1;" :: "l"(p1 + i * 4096), "r"(4096) : "memory");
        }
        return;
    }
    const int head = blockIdx.x >> 2, qq = blockIdx.x & 3;
    const __nv_bfloat16* gq = g_qkv + (size_t)head * (S_LEN * 16);
    const __nv_bfloat16* gk = g_qkv + (size_t)(NH + head) * (S_LEN * 16);
    const __nv_bfloat16* gv = g_qkv + (size_t)(2 * NH + head) * (S_LEN * 16);
    if (tid == 0) {
        for (int i = 0; i < 8; i++) mbar_init(sb + AT_BAR + 8 * i, 1);
        fence_barrier_init();
    }
    {
        uint4 one = make_uint4(0x00003F80u, 0, 0, 0);
#pragma unroll
        for (int i = 0; i < 4; i++) *(uint4*)(smem + AT_ONES + (i * 512 + tid) * 16) = one;
        fence_proxy_async();
    }
    __syncthreads();
    TL(3);
    pdl_wait();
    TL(4);
    auto load_kv = [&](int i) {
        uint32_t bar = sb + AT_BAR + 8 * i;
        mbar_expect(bar, 16384);
        bulk_g2s(sb + AT_K + i * 4096, gk + i * 2048, 4096, bar);
        bulk_g2s(sb + AT_K + 32768 + i * 4096, gk + 16384 + i * 2048, 4096, bar);
        bulk_g2s(sb + AT_V + i * 4096, gv + i * 2048, 4096, bar);
        bulk_g2s(sb + AT_V + 32768 + i * 4096, gv + 16384 + i * 2048, 4096, bar);
    };
    if (tid == 0) { load_kv(0); load_kv(1); }
    uint32_t q[4], q2[4];
    attn_load_q(q, gq, qq * 512 + wg * 64 + warp * 16, lane);
    attn_load_q(q2, gq, qq * 512 + (4 + wg) * 64 + warp * 16, lane);
    bool fast;
    {
        const float* nq = g_nrm + (0 * NH + head) * 128 + qq * 32;
        const float* nk = g_nrm + (1 * NH + head) * 128;
        const float* nv = g_nrm + (2 * NH + head) * 128;
        float4 k4 = __ldcg((const float4*)nk + lane), v4 = __ldcg((const float4*)nv + lane);
        float qm = warp_max(__ldcg(nq + lane));
        float km = warp_max(fmaxf(fmaxf(k4.x, k4.y), fmaxf(k4.z, k4.w)));
        float vm = warp_max(fmaxf(fmaxf(v4.x, v4.y), fmaxf(v4.z, v4.w)));
        fast = __all_sync(0xffffffffu, (qm * km <= 3500.0f) && (vm <= 1.0e24f));
    }
    TL(24);
    const uint64_t kdesc0 = make_desc(sb + AT_K, 32768, 128, 0);
    const uint64_t vdesc0 = make_desc(sb + AT_V, 128, 32768, 0);
    if (!fast) {
        if (tid == 0) for (int i = 2; i < 8; i++) load_kv(i);
        for (int i = 0; i < 8; i++) mbar_wait(sb + AT_BAR + 8 * i, 0);
#pragma unroll 1
        for (int tile = 0; tile < 2; tile++) {
            const int row0 = qq * 512 + (tile * 4 + wg) * 64 + warp * 16;
            attn_tile_safe(q, kdesc0, vdesc0, row0, head, lane);
#pragma unroll
            for (int i = 0; i < 4; i++) q[i] = q2[i];
        }
        return;
    }
#pragma unroll 1
    for (int tile = 0; tile < 2; tile++) {
        const int row0 = qq * 512 + (tile * 4 + wg) * 64 + warp * 16;
        float o[12];
#pragma unroll
        for (int i = 0; i < 12; i++) o[i] = 0.f;
        fence_regs(o);
        float sa[32];
        uint32_t pa[16];
        uint64_t kd = kdesc0, vd = vdesc0;
        if (tile == 0) { mbar_wait(sb + AT_BAR, 0); TL(25); }
        WG_FENCE();
        qk_wgmma_n64(sa, q, kd); kd += 64;
        WG_COMMIT();
#pragma unroll 1
        for (int jj = 0; jj < 8; jj++) {
            if (tile == 0 && jj < 7) {
                if (tid == 0 && jj < 6) load_kv(jj + 2);
                mbar_wait(sb + AT_BAR + 8 * (jj + 1), 0);
            }
            if (wg == 0 && warp == 0) TX(128 + tile * 8 + jj);
#pragma unroll
            for (int j = 0; j < 4; j++) {
                wg_wait<0>();
                fence_regs(sa);
                if (j & 1) exp_blocks<(POLY_MASK >> 8)>(sa, pa); else exp_blocks<(POLY_MASK & 255)>(sa, pa);
                WG_FENCE();
                qk_wgmma_n64(sa, q, kd); kd += 64;
                PV4(pa);
                WG_COMMIT();
            }
        }
        wg_wait<0>();
        fence_regs(o);
        fence_regs(sa);
        if (tile == 0) TL(26);
        attn_store(o, row0, head, lane);
#pragma unroll
        for (int i = 0; i < 4; i++) q[i] = q2[i];
    }
    TL(5);
}

constexpr int F_R2 = 131072, F_X = 196608, F_BAR = 229376;
constexpr int F_RS = F_BAR + 256, F_CS = F_RS + 1024, F_SMEM = F_CS + 1792;
enum { B_FA = 0, B_HF = 4, B_BF = 8, B_BE = 11, B_CF = 14, B_CE = 20, B_ADONE = 26, B_BDONE = 27, B_XC = 28, B_PRDY = 29, B_AUX = 30, B_NUM = 31 };

__device__ __forceinline__ uint32_t mapa(uint32_t a, uint32_t rank) { uint32_t r; asm("mapa.shared::cluster.u32 %0, %1, %2;" : "=r"(r) : "r"(a), "r"(rank)); return r; }
__device__ __forceinline__ void st_async4(uint32_t dst, float a, float b, float c, float d, uint32_t bar) {
    asm volatile("st.async.weak.shared::cluster.mbarrier::complete_tx::bytes.v4.f32 [%0], {%1,%2,%3,%4}, [%5];"
                 :: "r"(dst), "f"(a), "f"(b), "f"(c), "f"(d), "r"(bar) : "memory");
}
__device__ __forceinline__ void mbar_arrive_remote(uint32_t a) { asm volatile("mbarrier.arrive.relaxed.cluster.shared::cluster.b64 _, [%0];" :: "r"(a) : "memory"); }
__device__ __forceinline__ void mbar_wait_cluster(uint32_t a, int parity) {
    uint32_t done;
    int it = 0;
    do {
        asm volatile("{\n.reg .pred p;\nmbarrier.try_wait.parity.acquire.cluster.shared::cta.b64 p, [%1], %2;\nselp.u32 %0, 1, 0, p;\n}"
                     : "=r"(done) : "r"(a), "r"(parity) : "memory");
        if (++it > (1 << 24)) __trap();
    } while (!done);
}
__device__ __forceinline__ void poll_count(const unsigned int* p, unsigned int target) {
    int it = 0;
    while (ld_acquire(p) < target) { if (++it > (1 << 22)) __trap(); }
    asm volatile("fence.proxy.async.global;" ::: "memory");
}
__device__ __forceinline__ void tma2d_store(const CUtensorMap* m, uint32_t src, int c0, int c1) {
    asm volatile("cp.async.bulk.tensor.2d.global.shared::cta.bulk_group [%0, {%2, %3}], [%1];" :: "l"(m), "r"(src), "r"(c0), "r"(c1) : "memory");
}
template <int R>
__device__ __forceinline__ void xchg(float (&acc)[64], float (&o)[32], uint32_t sb, unsigned char* smem, int bar, int ctid) {
    const uint32_t dst = mapa(sb + F_X + ctid * 16, 1 - R), rb = mapa(sb + F_BAR + 8 * bar, 1 - R);
#pragma unroll
    for (int q = 0; q < 8; q++) {
        const int j = (1 - R) * 32 + 4 * q;
        st_async4(dst + q * 4096, acc[j], acc[j + 1], acc[j + 2], acc[j + 3], rb);
    }
    mbar_wait_cluster(sb + F_BAR + 8 * bar, 0);
#pragma unroll
    for (int q = 0; q < 8; q++) {
        float4 v = *(const float4*)(smem + F_X + q * 4096 + ctid * 16);
        const int j = R * 32 + 4 * q;
        o[4 * q] = acc[j] + v.x; o[4 * q + 1] = acc[j + 1] + v.y; o[4 * q + 2] = acc[j + 2] + v.z; o[4 * q + 3] = acc[j + 3] + v.w;
    }
}

template <int NB, bool STAGE>
__device__ __forceinline__ void ffn_epilogue(const float* ag, const float* au, const float* s_cs, int cs_off, uint32_t* gp, uint32_t stg,
                                             float2 st0, float2 st1, int lane) {
    const int t = lane & 3;
    const float C1 = 0.7978845608028654f, C2 = 0.044715f * 0.7978845608028654f;
    const float k10 = st0.x * C1, k20 = st0.x * st0.x * st0.x * C2, k11 = st1.x * C1, k21 = st1.x * st1.x * st1.x * C2;
#pragma unroll
    for (int j2 = 0; j2 < NB / 2; j2++) {
        uint32_t pk[4];
#pragma unroll
        for (int jj = 0; jj < 2; jj++) {
            const int j = 2 * j2 + jj;
            const float2 cg = *(const float2*)(s_cs + cs_off + 8 * j + 2 * t);
            const float2 cu = *(const float2*)(s_cs + 224 + cs_off + 8 * j + 2 * t);
            float r[4];
#pragma unroll
            for (int e = 0; e < 4; e++) {
                const float nm = (e < 2) ? st0.y : st1.y, k1 = (e < 2) ? k10 : k11, k2 = (e < 2) ? k20 : k21;
                const float tg = fmaf(nm, (e & 1) ? cg.y : cg.x, ag[4 * j + e]);
                const float tu = fmaf(nm, (e & 1) ? cu.y : cu.x, au[4 * j + e]);
                const float th = tanh_fast(tg * fmaf(tg * tg, k2, k1));
                const float p = tg * tu;
                r[e] = fmaf(p, th, p);
            }
            pk[2 * jj] = pack_bf16(r[0], r[1]);
            pk[2 * jj + 1] = pack_bf16(r[2], r[3]);
        }
        if (STAGE) {
            stsm4(stg + j2 * 4096, pk[0], pk[1], pk[2], pk[3]);
        } else {
            gp[j2 * 1024] = pk[0]; gp[j2 * 1024 + 32] = pk[1]; gp[j2 * 1024 + 512] = pk[2]; gp[j2 * 1024 + 544] = pk[3];
        }
    }
}

__global__ void __cluster_dims__(2, 1, 1) __launch_bounds__(384, 1)
tail_kernel(const __grid_constant__ CUtensorMap tm_o, const __grid_constant__ CUtensorMap tm_g,
            const __grid_constant__ CUtensorMap tm_u, const __grid_constant__ CUtensorMap tm_d,
            const __grid_constant__ CUtensorMap tm_out, const __nv_bfloat16* __restrict__ x) {
    extern __shared__ __align__(1024) unsigned char smem[];
    const uint32_t sb = smem_u32(smem);
    const uint32_t bars = sb + F_BAR;
    const int tid = threadIdx.x, warp = __shfl_sync(0xffffffffu, tid >> 5, 0), lane = tid & 31;
    TL(6);
    const int cl = blockIdx.x >> 1, r = blockIdx.x & 1;
    const int mb = ((cl & 7) >> 1) * 4 + (cl >> 4), ntA = (cl & 1) * 2 + ((cl >> 3) & 1);
    const int nt = ntA * 2 + r;
    if (tid < B_NUM) {
        const int i = tid;
        int cnt = 1;
        if ((i >= B_BE && i < B_BE + 3) || (i >= B_CE && i < B_CE + 6) || i == B_BDONE || i == B_PRDY) cnt = 8;
        if (i == B_AUX) cnt = 2;
        mbar_init(bars + 8 * i, cnt);
        if (i == B_XC) mbar_expect(bars + 8 * B_XC, 32768);
    }
    if (warp == 0) { __syncwarp(); if (lane == 0) fence_barrier_init(); }
    __syncthreads();
    asm volatile("barrier.cluster.arrive.relaxed.aligned;" ::: "memory");
    if (warp < 4) {
        asm volatile("setmaxnreg.dec.sync.aligned.u32 56;");
        if (warp == 0) {
            if (lane == 0) {
                auto load_b = [&](int it) {
                    const int s = it % 3, pass = it >> 3, kb = it & 7;
                    const int ng = pass ? 3 : 4, c0 = nt * 224 + pass * 128;
                    const uint32_t bar = bars + 8 * (B_BF + s), dst = sb + F_R2 + s * 32768;
                    mbar_expect(bar, ng * 8192);
                    for (int i = 0; i < ng; i++) {
                        tma2d(dst + i * 4096, &tm_g, c0 + i * 32, kb * 64, bar);
                        tma2d(dst + 16384 + i * 4096, &tm_u, c0 + i * 32, kb * 64, bar);
                    }
                };
                for (int i = 0; i < 8; i++) {
                    const uint32_t bar = bars + 8 * (B_FA + (i >> 1));
                    if (!(i & 1)) mbar_expect(bar, 49152);
                    tma2d(sb + F_R2 + 32768 + i * 8192, &tm_o, nt * 64, i * 64, bar);
                }
                pdl_wait();
                TL(16);
                for (int i = 0; i < 8; i++)
                    bulk_g2s(sb + i * 16384, g_ao + (size_t)(mb * 8 + i) * 8192, 16384, bars + 8 * (B_FA + (i >> 1)));
                load_b(0);
                if (blockIdx.x == 0)
                    for (int i = 0; i < 32; i++) g_cnt[i] = 0;
                mbar_wait(bars + 8 * B_ADONE, 0);
                load_b(1); load_b(2);
                poll_count(&g_cnt2[mb], 8);
                TL(17);
                for (int kb = 0; kb < 8; kb++) {
                    const uint32_t bar = bars + 8 * (B_HF + (kb >> 1));
                    if (!(kb & 1)) mbar_expect(bar, (kb >> 1) == ntA ? 16384 : 32768);
                    if (kb != nt) bulk_g2s(sb + kb * 16384, g_h + (size_t)(mb * 8 + kb) * 8192, 16384, bar);
                }
                for (int it = 3; it < 16; it++) {
                    mbar_wait(bars + 8 * (B_BE + it % 3), (it / 3 - 1) & 1);
                    load_b(it);
                }
                mbar_wait(bars + 8 * B_BDONE, 0);
                for (int i = 0; i < 6; i++) {
                    const uint32_t bar = bars + 8 * (B_CF + i);
                    mbar_expect(bar, 32768);
                    tma2d(sb + i * 32768 + 16384, &tm_d, ntA * 128, (2 * i + r) * 64, bar);
                    tma2d(sb + i * 32768 + 24576, &tm_d, ntA * 128 + 64, (2 * i + r) * 64, bar);
                }
                poll_count(&g_cnt2[16 + mb], 8);
                TL(18);
                for (int kb = 0; kb < 14; kb++) {
                    const int s = kb % 6;
                    const uint32_t bar = bars + 8 * (B_CF + s);
                    if (kb >= 6) {
                        mbar_wait(bars + 8 * (B_CE + s), ((kb / 6) - 1) & 1);
                        mbar_expect(bar, 32768);
                        tma2d(sb + s * 32768 + 16384, &tm_d, ntA * 128, (2 * kb + r) * 64, bar);
                        tma2d(sb + s * 32768 + 24576, &tm_d, ntA * 128 + 64, (2 * kb + r) * 64, bar);
                    }
                    bulk_g2s(sb + s * 32768, g_g + (size_t)(mb * 28 + 2 * kb + r) * 8192, 16384, bar);
                }
            }
            __syncwarp();
            asm volatile("barrier.cluster.wait.acquire.aligned;" ::: "memory");
        } else if (warp == 1) {
            asm volatile("barrier.cluster.wait.acquire.aligned;" ::: "memory");
            bar_sync(1, 288);
            if (lane == 0) {
                red_release(&g_cnt2[mb]);
                TL(9);
            }
            __syncwarp();
            bar_sync(2, 288);
            if (lane == 0) {
                red_release(&g_cnt2[16 + mb]);
                TL(13);
            }
            __syncwarp();
            bar_sync(3, 288);
            if (lane == 0) {
                tma2d_store(&tm_out, sb, nt * 64, mb * 128);
                bulk_commit();
                bulk_wait_all();
                TL(15);
            }
        } else {
            asm volatile("barrier.cluster.wait.acquire.aligned;" ::: "memory");
            pdl_wait();
            float2* s_rs = (float2*)(smem + F_RS);
            float* s_cs = (float*)(smem + F_CS);
            for (int c = tid - 64; c < 448; c += 64)
                s_cs[c] = __ldcg(&g_cs2[(c >= 224 ? FF - 224 : 0) + nt * 224 + c]);
            if (lane == 0) poll_count(&g_cnt2[mb], 8);
            __syncwarp();
            for (int rr = tid - 64; rr < 128; rr += 64) {
                const float4* hp = (const float4*)(g_hstat + (size_t)(mb * 128 + rr) * 8);
                float4 a = __ldcg(hp), b = __ldcg(hp + 1), c = __ldcg(hp + 2), d = __ldcg(hp + 3);
                float mean = 0.125f * (a.x + a.z + b.x + b.z + c.x + c.z + d.x + d.z);
                float m2 = a.y + a.w + b.y + b.w + c.y + c.w + d.y + d.w;
                float e;
                e = a.x - mean; m2 = fmaf(64.f * e, e, m2); e = a.z - mean; m2 = fmaf(64.f * e, e, m2);
                e = b.x - mean; m2 = fmaf(64.f * e, e, m2); e = b.z - mean; m2 = fmaf(64.f * e, e, m2);
                e = c.x - mean; m2 = fmaf(64.f * e, e, m2); e = c.z - mean; m2 = fmaf(64.f * e, e, m2);
                e = d.x - mean; m2 = fmaf(64.f * e, e, m2); e = d.z - mean; m2 = fmaf(64.f * e, e, m2);
                s_rs[rr] = make_float2(rsqrtf(m2 * (1.0f / DM) + 1e-5f), -mean);
            }
            __syncwarp();
            if (lane == 0) mbar_arrive(bars + 8 * B_AUX);
        }
    } else {
        asm volatile("setmaxnreg.inc.sync.aligned.u32 216;");
        const int wgi = (warp >> 2) - 1, ww = warp & 3, ctid = tid - 128;
        const int g = lane >> 2, t = lane & 3;
        const int rl = wgi * 64 + ww * 16 + g, row = mb * 128 + rl;
        const int rgl = wgi * 8 + ww * 2;
        const float2* s_rs = (const float2*)(smem + F_RS);
        const float* s_cs = (const float*)(smem + F_CS);
        const uint32_t stl = ((lane >> 4) * 16 + rgl + ((lane >> 3) & 1)) * 128 + (lane & 7) * 16;
        TL(23);
        {
            uint32_t xr[16];
            const uint32_t* xp = (const uint32_t*)(x + (size_t)row * DM + nt * 64) + t;
#pragma unroll
            for (int j = 0; j < 8; j++) { xr[2 * j] = __ldg(xp + 4 * j); xr[2 * j + 1] = __ldg(xp + 8 * (DM / 2) + 4 * j); }
            float acc[32];
#pragma unroll 1
            for (int i = 0; i < 8; i++) {
                if (!(i & 1)) { mbar_wait(bars + 8 * (B_FA + (i >> 1)), 0); if (i == 0) TL(19); }
                uint64_t ad = make_desc(sb + i * 16384 + wgi * 1024, 2048, 128, 0);
                uint64_t bd = make_desc(sb + F_R2 + 32768 + i * 8192, 8192, 1024, 1);
                WG_FENCE();
#pragma unroll
                for (int k = 0; k < 4; k++) wgmma_ss_n64(acc, ad + k * 256, bd + k * 128, (i | k) != 0);
                WG_COMMIT();
            }
            wg_wait<0>();
            fence_regs(acc);
            TL(7);
            bar_sync(4, 256);
            if (tid == 128) mbar_arrive(bars + 8 * B_ADONE);
            uint32_t* hp = (uint32_t*)g_h + ((size_t)(mb * 8 + nt) * 8 * 16 + rgl) * 32 + lane;
            float v0[16], v1[16];
            float s0 = 0.f, s1 = 0.f;
#pragma unroll
            for (int j2 = 0; j2 < 4; j2++) {
                uint32_t u[4];
#pragma unroll
                for (int jj = 0; jj < 2; jj++) {
                    const int j = 2 * j2 + jj;
                    u[2 * jj] = pack_bf16(bf_lo(xr[2 * j]) + acc[4 * j], bf_hi(xr[2 * j]) + acc[4 * j + 1]);
                    u[2 * jj + 1] = pack_bf16(bf_lo(xr[2 * j + 1]) + acc[4 * j + 2], bf_hi(xr[2 * j + 1]) + acc[4 * j + 3]);
                    v0[2 * j] = bf_lo(u[2 * jj]); v0[2 * j + 1] = bf_hi(u[2 * jj]);
                    v1[2 * j] = bf_lo(u[2 * jj + 1]); v1[2 * j + 1] = bf_hi(u[2 * jj + 1]);
                    s0 += v0[2 * j] + v0[2 * j + 1];
                    s1 += v1[2 * j] + v1[2 * j + 1];
                }
                stsm4(sb + nt * 16384 + stl + j2 * 4096, u[0], u[1], u[2], u[3]);
                hp[j2 * 1024] = u[0]; hp[j2 * 1024 + 32] = u[1]; hp[j2 * 1024 + 512] = u[2]; hp[j2 * 1024 + 544] = u[3];
            }
            fence_proxy_async();
            float m0 = s0 * (1.0f / 16), m1 = s1 * (1.0f / 16), q0 = 0.f, q1 = 0.f;
#pragma unroll
            for (int i = 0; i < 16; i++) {
                float d0 = v0[i] - m0, d1 = v1[i] - m1;
                q0 = fmaf(d0, d0, q0); q1 = fmaf(d1, d1, q1);
            }
#pragma unroll
            for (int st = 0; st < 2; st++) {
                float hn = st ? 16.f : 8.f;
                float om0 = __shfl_xor_sync(0xffffffffu, m0, 1 << st), oq0 = __shfl_xor_sync(0xffffffffu, q0, 1 << st);
                float om1 = __shfl_xor_sync(0xffffffffu, m1, 1 << st), oq1 = __shfl_xor_sync(0xffffffffu, q1, 1 << st);
                float d0 = om0 - m0, d1 = om1 - m1;
                q0 = q0 + oq0 + d0 * d0 * hn; q1 = q1 + oq1 + d1 * d1 * hn;
                m0 = 0.5f * (m0 + om0); m1 = 0.5f * (m1 + om1);
            }
            if (t == 0) {
                g_hstat[row * 8 + nt] = make_float2(m0, q0);
                g_hstat[(row + 8) * 8 + nt] = make_float2(m1, q1);
            }
            bar_arrive(1, 288);
            bar_sync(4, 256);
            TL(8);
        }
        uint32_t* gp = (uint32_t*)g_g + (((size_t)mb * 224 + nt * 28) * 16 + rgl) * 32 + lane;
        {
            float ag[64], au[64];
#pragma unroll 1
            for (int kb = 0; kb < 8; kb++) {
                const int s = kb % 3;
                if (!(kb & 1)) mbar_wait(bars + 8 * (B_HF + (kb >> 1)), 0);
                mbar_wait(bars + 8 * (B_BF + s), (kb / 3) & 1);
                if (warp == 4) TX(32 + kb);
                uint64_t ad = make_desc(sb + kb * 16384 + wgi * 1024, 2048, 128, 0);
                uint64_t bd = make_desc(sb + F_R2 + s * 32768, 4096, 512, 2);
                WG_FENCE();
#pragma unroll
                for (int k = 0; k < 4; k++) {
                    wgmma_ss_n128(ag, ad + k * 256, bd + k * 64, (kb | k) != 0);
                    wgmma_ss_n128(au, ad + k * 256, bd + 1024 + k * 64, (kb | k) != 0);
                }
                WG_COMMIT();
                if (kb > 0) {
                    wg_wait<1>();
                    if (lane == 0) mbar_arrive(bars + 8 * (B_BE + (kb - 1) % 3));
                }
            }
            wg_wait<0>();
            if (lane == 0) mbar_arrive(bars + 8 * (B_BE + 7 % 3));
            fence_regs(ag); fence_regs(au);
            TL(10);
            mbar_wait(bars + 8 * B_AUX, 0);
            ffn_epilogue<16, false>(ag, au, s_cs, 0, gp, 0, s_rs[rl], s_rs[rl + 8], lane);
        }
        uint32_t hr[16];
        {
            const uint32_t* hs = (const uint32_t*)(smem + nt * 16384) + rgl * 32 + lane;
#pragma unroll
            for (int j = 0; j < 8; j++) { hr[2 * j] = hs[j * 512]; hr[2 * j + 1] = hs[j * 512 + 32]; }
        }
        {
            float ag[48], au[48];
#pragma unroll 1
            for (int kb = 0; kb < 8; kb++) {
                const int it = 8 + kb, s = it % 3;
                mbar_wait(bars + 8 * (B_BF + s), (it / 3) & 1);
                if (warp == 4) TX(32 + it);
                uint64_t ad = make_desc(sb + kb * 16384 + wgi * 1024, 2048, 128, 0);
                uint64_t bd = make_desc(sb + F_R2 + s * 32768, 4096, 512, 2);
                WG_FENCE();
#pragma unroll
                for (int k = 0; k < 4; k++) {
                    wgmma_ss_n96(ag, ad + k * 256, bd + k * 64, (kb | k) != 0);
                    wgmma_ss_n96(au, ad + k * 256, bd + 1024 + k * 64, (kb | k) != 0);
                }
                WG_COMMIT();
                if (kb > 0) {
                    wg_wait<1>();
                    if (lane == 0) mbar_arrive(bars + 8 * (B_BE + (it - 1) % 3));
                }
            }
            wg_wait<0>();
            asm volatile("barrier.cluster.wait.acquire.aligned;" ::: "memory");
            if (lane == 0) {
                mbar_arrive(bars + 8 * B_BDONE);
                mbar_arrive_remote(mapa(bars + 8 * B_PRDY, 1 - r));
            }
            fence_regs(ag); fence_regs(au);
            TL(11);
            ffn_epilogue<12, false>(ag, au, s_cs, 128, gp + 16 * 512, 0, s_rs[rl], s_rs[rl + 8], lane);
            bar_arrive(2, 288);
            TL(12);
        }
        {
            float acc[64];
#pragma unroll 1
            for (int kb = 0; kb < 14; kb++) {
                const int s = kb % 6;
                mbar_wait(bars + 8 * (B_CF + s), (kb / 6) & 1);
                if (warp == 4) TX(96 + kb);
                uint64_t ad = make_desc(sb + s * 32768 + wgi * 1024, 2048, 128, 0);
                uint64_t bd = make_desc(sb + s * 32768 + 16384, 8192, 1024, 1);
                WG_FENCE();
#pragma unroll
                for (int k = 0; k < 4; k++) wgmma_ss_n128(acc, ad + k * 256, bd + k * 128, (kb | k) != 0);
                WG_COMMIT();
                if (kb > 0) {
                    wg_wait<1>();
                    if (lane == 0) mbar_arrive(bars + 8 * (B_CE + (kb - 1) % 6));
                }
            }
            wg_wait<0>();
            fence_regs(acc);
            TL(14);
            mbar_wait_cluster(bars + 8 * B_PRDY, 0);
            float o[32];
            if (r == 0) xchg<0>(acc, o, sb, smem, B_XC, ctid); else xchg<1>(acc, o, sb, smem, B_XC, ctid);
            TL(22);
            bar_sync(4, 256);
            const float a0 = s_rs[rl].x, a1 = s_rs[rl + 8].x;
            const float k0 = 0.5f * a0 * a0, k1 = 0.5f * a1 * a1;
            const int srow = wgi * 64 + ww * 16 + ((lane >> 3) & 1) * 8 + (lane & 7);
#pragma unroll
            for (int j2 = 0; j2 < 4; j2++) {
                uint32_t u[4];
#pragma unroll
                for (int jj = 0; jj < 2; jj++) {
                    const int j = 2 * j2 + jj;
                    u[2 * jj] = pack_bf16(fmaf(k0, o[4 * j], bf_lo(hr[2 * j])), fmaf(k0, o[4 * j + 1], bf_hi(hr[2 * j])));
                    u[2 * jj + 1] = pack_bf16(fmaf(k1, o[4 * j + 2], bf_lo(hr[2 * j + 1])), fmaf(k1, o[4 * j + 3], bf_hi(hr[2 * j + 1])));
                }
                const int chunk = 2 * j2 + (lane >> 4);
                stsm4(sb + srow * 128 + ((chunk ^ (lane & 7)) * 16), u[0], u[1], u[2], u[3]);
            }
            fence_proxy_async();
            bar_arrive(3, 288);
        }
    }
}

typedef CUresult (*EncodeFn)(CUtensorMap*, CUtensorMapDataType, cuuint32_t, void*, const cuuint64_t*, const cuuint64_t*,
                             const cuuint32_t*, const cuuint32_t*, CUtensorMapInterleave, CUtensorMapSwizzle,
                             CUtensorMapL2promotion, CUtensorMapFloatOOBfill);

void encode(EncodeFn fn, CUtensorMap* m, const void* ptr, int rank, const cuuint64_t* dims, const cuuint64_t* strides,
            const cuuint32_t* box, CUtensorMapSwizzle swz) {
    cuuint32_t es[3] = {1, 1, 1};
    fn(m, CU_TENSOR_MAP_DATA_TYPE_BFLOAT16, rank, (void*)ptr, dims, strides, box, es, CU_TENSOR_MAP_INTERLEAVE_NONE, swz,
       CU_TENSOR_MAP_L2_PROMOTION_L2_256B, CU_TENSOR_MAP_FLOAT_OOB_FILL_NONE);
}

template <typename... KArgs, typename... Args>
void launch(void (*kern)(KArgs...), int grid, int block, int smem, bool pdl, Args... args) {
    cudaLaunchConfig_t cfg = {};
    cfg.gridDim = dim3(grid); cfg.blockDim = dim3(block); cfg.dynamicSmemBytes = smem;
    cfg.stream = cudaStreamPerThread;
    cudaLaunchAttribute at[1];
    at[0].id = cudaLaunchAttributeProgrammaticStreamSerialization;
    at[0].val.programmaticStreamSerializationAllowed = 1;
    cfg.attrs = at; cfg.numAttrs = pdl ? 1 : 0;
    cudaLaunchKernelEx(&cfg, kern, KArgs(args)...);
}

}

extern "C" void kernel_launch(void* const* d_in, const int* in_sizes, int n_in, void* d_out, int out_size) {
    const __nv_bfloat16* x = (const __nv_bfloat16*)d_in[0];
    const __nv_bfloat16* wqkv = (const __nv_bfloat16*)d_in[1];
    const __nv_bfloat16* wo = (const __nv_bfloat16*)d_in[2];
    const __nv_bfloat16* wgate = (const __nv_bfloat16*)d_in[4];
    const __nv_bfloat16* wup = (const __nv_bfloat16*)d_in[5];
    const __nv_bfloat16* wdown = (const __nv_bfloat16*)d_in[6];
    __nv_bfloat16* out = (__nv_bfloat16*)d_out;

    static CUtensorMap tm_x, tm_wqkv, tm_wo, tm_wg, tm_wu, tm_wd, tm_out;
    static const void* cached[7] = {nullptr, nullptr, nullptr, nullptr, nullptr, nullptr, nullptr};
    if (cached[0] != x || cached[1] != wqkv || cached[2] != wo || cached[3] != wgate || cached[4] != wup || cached[5] != wdown || cached[6] != out) {
        void* fp = nullptr;
        cudaDriverEntryPointQueryResult qr;
        cudaGetDriverEntryPoint("cuTensorMapEncodeTiled", &fp, cudaEnableDefault, &qr);
        EncodeFn fn = (EncodeFn)fp;
        { cuuint64_t d[2] = {512, 2048}, s[1] = {1024}; cuuint32_t b[2] = {64, 128};
          encode(fn, &tm_x, x, 2, d, s, b, CU_TENSOR_MAP_SWIZZLE_128B);
          encode(fn, &tm_out, out, 2, d, s, b, CU_TENSOR_MAP_SWIZZLE_128B); }
        { cuuint64_t d[3] = {64, 512, 24}, s[2] = {3072, 128}; cuuint32_t b[3] = {64, 64, 3};
          encode(fn, &tm_wqkv, wqkv, 3, d, s, b, CU_TENSOR_MAP_SWIZZLE_128B); }
        { cuuint64_t d[2] = {512, 512}, s[1] = {1024}; cuuint32_t b[2] = {64, 64};
          encode(fn, &tm_wo, wo, 2, d, s, b, CU_TENSOR_MAP_SWIZZLE_128B); }
        { cuuint64_t d[2] = {1792, 512}, s[1] = {3584}; cuuint32_t b[2] = {32, 64};
          encode(fn, &tm_wg, wgate, 2, d, s, b, CU_TENSOR_MAP_SWIZZLE_64B);
          encode(fn, &tm_wu, wup, 2, d, s, b, CU_TENSOR_MAP_SWIZZLE_64B); }
        { cuuint64_t d[2] = {512, 1792}, s[1] = {1024}; cuuint32_t b[2] = {64, 64};
          encode(fn, &tm_wd, wdown, 2, d, s, b, CU_TENSOR_MAP_SWIZZLE_128B); }
        cudaFuncSetAttribute(qkv_kernel, cudaFuncAttributeMaxDynamicSharedMemorySize, K1_SMEM);
        cudaFuncSetAttribute(attn_kernel, cudaFuncAttributeMaxDynamicSharedMemorySize, AT_SMEM);
        cudaFuncSetAttribute(tail_kernel, cudaFuncAttributeMaxDynamicSharedMemorySize, F_SMEM);
        cached[0] = x; cached[1] = wqkv; cached[2] = wo; cached[3] = wgate; cached[4] = wup; cached[5] = wdown; cached[6] = out;
    }
    launch(qkv_kernel, 128, 384, K1_SMEM, false, tm_x, tm_wqkv, x, wqkv);
    launch(attn_kernel, 132, 512, AT_SMEM, true, wgate, wup, wo, wdown);
    launch(tail_kernel, 128, 384, F_SMEM, true, tm_wo, tm_wg, tm_wu, tm_wd, tm_out, x);
}
```

```cpp
#include <cuda_runtime.h>
#include <cuda_bf16.h>
#include <cuda.h>
#include <stdint.h>

#define K1_DIRECT
namespace {

constexpr int S_LEN = 2048, DM = 512, NH = 32, FF = 1792;

__device__ __align__(1024) __nv_bfloat16 g_qkv[3 * NH * S_LEN * 16];
__device__ __align__(1024) __nv_bfloat16 g_ao[S_LEN * DM];
__device__ __align__(1024) __nv_bfloat16 g_h[S_LEN * DM];
__device__ __align__(1024) __nv_bfloat16 g_g[S_LEN * FF];
__device__ __align__(16) float2 g_rowstat1[S_LEN];
__device__ float g_cs1_part[16 * 1536];
__device__ unsigned int g_cnt[32];
__device__ unsigned int g_cnt2[64];
__device__ float g_nrm[3 * NH * 128];
__device__ float2 g_hstat[S_LEN * 8];
__device__ float g_cs2[2 * FF];

#define TLDECL
#define TL(slot)
#define TLDUMP
#define TX(slot)
__device__ __forceinline__ uint32_t smem_u32(const void* p) { return (uint32_t)__cvta_generic_to_shared(p); }
__device__ __forceinline__ void mbar_init(uint32_t a, int c) { asm volatile("mbarrier.init.shared.b64 [%0], %1;" :: "r"(a), "r"(c)); }
__device__ __forceinline__ void mbar_expect(uint32_t a, int bytes) { asm volatile("mbarrier.arrive.expect_tx.shared.b64 _, [%0], %1;" :: "r"(a), "r"(bytes) : "memory"); }
__device__ __forceinline__ void mbar_arrive(uint32_t a) { asm volatile("mbarrier.arrive.shared.b64 _, [%0];" :: "r"(a) : "memory"); }
__device__ __forceinline__ void mbar_wait(uint32_t a, int parity) {
    uint32_t done;
    int it = 0;
    do {
        asm volatile("{\n.reg .pred p;\nmbarrier.try_wait.parity.shared.b64 p, [%1], %2;\nselp.u32 %0, 1, 0, p;\n}"
                     : "=r"(done) : "r"(a), "r"(parity) : "memory");
        if (++it > (1 << 24)) __trap();
    } while (!done);
}
__device__ __forceinline__ void bulk_g2s(uint32_t dst, const void* src, int bytes, uint32_t bar) {
    asm volatile("cp.async.bulk.shared::cluster.global.mbarrier::complete_tx::bytes [%0], [%1], %2, [%3];"
                 :: "r"(dst), "l"(src), "r"(bytes), "r"(bar) : "memory");
}
__device__ __forceinline__ void tma2d(uint32_t dst, const CUtensorMap* m, int c0, int c1, uint32_t bar) {
    asm volatile("cp.async.bulk.tensor.2d.shared::cluster.global.mbarrier::complete_tx::bytes [%0], [%1, {%3, %4}], [%2];"
                 :: "r"(dst), "l"(m), "r"(bar), "r"(c0), "r"(c1) : "memory");
}
__device__ __forceinline__ void tma3d(uint32_t dst, const CUtensorMap* m, int c0, int c1, int c2, uint32_t bar) {
    asm volatile("cp.async.bulk.tensor.3d.shared::cluster.global.mbarrier::complete_tx::bytes [%0], [%1, {%3, %4, %5}], [%2];"
                 :: "r"(dst), "l"(m), "r"(bar), "r"(c0), "r"(c1), "r"(c2) : "memory");
}
__device__ __forceinline__ void prefetch_tmap(const CUtensorMap* m) { asm volatile("prefetch.tensormap [%0];" :: "l"(m) : "memory"); }
__device__ __forceinline__ void pdl_wait() { asm volatile("griddepcontrol.wait;" ::: "memory"); }
__device__ __forceinline__ void pdl_launch() { asm volatile("griddepcontrol.launch_dependents;" ::: "memory"); }
__device__ __forceinline__ void fence_barrier_init() { asm volatile("fence.mbarrier_init.release.cluster;" ::: "memory"); }
__device__ __forceinline__ void fence_proxy_async() { asm volatile("fence.proxy.async.shared::cta;" ::: "memory"); }
__device__ __forceinline__ uint64_t make_desc(uint32_t saddr, uint32_t lbo, uint32_t sbo, uint32_t swz) {
    return (uint64_t)((saddr & 0x3FFFF) >> 4) | ((uint64_t)((lbo & 0x3FFFF) >> 4) << 16) |
           ((uint64_t)((sbo & 0x3FFFF) >> 4) << 32) | ((uint64_t)swz << 62);
}
#define WG_FENCE() asm volatile("wgmma.fence.sync.aligned;" ::: "memory")
#define WG_COMMIT() asm volatile("wgmma.commit_group.sync.aligned;" ::: "memory")
template <int N> __device__ __forceinline__ void wg_wait() { asm volatile("wgmma.wait_group.sync.aligned %0;" :: "n"(N) : "memory"); }
template <int N> __device__ __forceinline__ void fence_regs(float (&d)[N]) {
#pragma unroll
    for (int i = 0; i < N; i++) asm volatile("" : "+f"(d[i]) :: "memory");
}
__device__ __forceinline__ float ex2f(float x) { float y; asm("ex2.approx.ftz.f32 %0, %1;" : "=f"(y) : "f"(x)); return y; }
__device__ __forceinline__ float tanh_fast(float x) { float y; asm("tanh.approx.f32 %0, %1;" : "=f"(y) : "f"(x)); return y; }
__device__ __forceinline__ uint32_t pack_bf16(float lo, float hi) { uint32_t r; asm("cvt.rn.bf16x2.f32 %0, %1, %2;" : "=r"(r) : "f"(hi), "f"(lo)); return r; }
__device__ __forceinline__ float bf_lo(uint32_t u) { return __uint_as_float(u << 16); }
__device__ __forceinline__ float bf_hi(uint32_t u) { return __uint_as_float(u & 0xFFFF0000u); }
__device__ __forceinline__ uint32_t hfma2(uint32_t a, uint32_t b, uint32_t c) { uint32_t r; asm("fma.rn.f16x2 %0, %1, %2, %3;" : "=r"(r) : "r"(a), "r"(b), "r"(c)); return r; }
__device__ __forceinline__ uint32_t hmul2(uint32_t a, uint32_t b) { uint32_t r; asm("mul.rn.f16x2 %0, %1, %2;" : "=r"(r) : "r"(a), "r"(b)); return r; }
__device__ __forceinline__ unsigned int ld_acquire(const unsigned int* p) { unsigned int v; asm volatile("ld.acquire.gpu.u32 %0, [%1];" : "=r"(v) : "l"(p) : "memory"); return v; }
__device__ __forceinline__ void red_release(unsigned int* p) { asm volatile("red.release.gpu.global.add.u32 [%0], 1;" :: "l"(p) : "memory"); }
__device__ __forceinline__ void stsm4(uint32_t addr, uint32_t a, uint32_t b, uint32_t c, uint32_t d) {
    asm volatile("stmatrix.sync.aligned.m8n8.x4.shared.b16 [%0], {%1,%2,%3,%4};" :: "r"(addr), "r"(a), "r"(b), "r"(c), "r"(d) : "memory");
}
__device__ __forceinline__ void bulk_s2g(void* dst, uint32_t src, int bytes) {
    asm volatile("cp.async.bulk.global.shared::cta.bulk_group [%0], [%1], %2;" :: "l"(dst), "r"(src), "r"(bytes) : "memory");
}
__device__ __forceinline__ void bulk_commit() { asm volatile("cp.async.bulk.commit_group;" ::: "memory"); }
__device__ __forceinline__ void bulk_wait_all() { asm volatile("cp.async.bulk.wait_group 0;" ::: "memory"); }
__device__ __forceinline__ void bulk_wait_read() { asm volatile("cp.async.bulk.wait_group.read 0;" ::: "memory"); }
__device__ __forceinline__ void bar_sync(int id, int n) { asm volatile("bar.sync %0, %1;" :: "r"(id), "r"(n) : "memory"); }
__device__ __forceinline__ void bar_arrive(int id, int n) { asm volatile("bar.arrive %0, %1;" :: "r"(id), "r"(n) : "memory"); }
__device__ __forceinline__ float warp_sum(float v) {
#pragma unroll
    for (int o = 16; o; o >>= 1) v += __shfl_xor_sync(0xffffffffu, v, o);
    return v;
}
__device__ __forceinline__ float warp_max(float v) {
#pragma unroll
    for (int o = 16; o; o >>= 1) v = fmaxf(v, __shfl_xor_sync(0xffffffffu, v, o));
    return v;
}

__device__ __forceinline__ void wgmma_ss_n64(float (&d)[32], uint64_t adesc, uint64_t bdesc, int scale_d) {
    asm volatile("{\n.reg .pred p;\nsetp.ne.b32 p, %34, 0;\n"
      "wgmma.mma_async.sync.aligned.m64n64k16.f32.bf16.bf16 {%0,%1,%2,%3,%4,%5,%6,%7,%8,%9,%10,%11,%12,%13,%14,%15,%16,%17,%18,%19,%20,%21,%22,%23,%24,%25,%26,%27,%28,%29,%30,%31}, %32, %33, p, 1, 1, 0, 1;\n}"
      : "+f"(d[0]), "+f"(d[1]), "+f"(d[2]), "+f"(d[3]), "+f"(d[4]), "+f"(d[5]), "+f"(d[6]), "+f"(d[7]), "+f"(d[8]), "+f"(d[9]), "+f"(d[10]), "+f"(d[11]), "+f"(d[12]), "+f"(d[13]), "+f"(d[14]), "+f"(d[15]), "+f"(d[16]), "+f"(d[17]), "+f"(d[18]), "+f"(d[19]), "+f"(d[20]), "+f"(d[21]), "+f"(d[22]), "+f"(d[23]), "+f"(d[24]), "+f"(d[25]), "+f"(d[26]), "+f"(d[27]), "+f"(d[28]), "+f"(d[29]), "+f"(d[30]), "+f"(d[31])
      : "l"(adesc), "l"(bdesc), "r"(scale_d));
}
__device__ __forceinline__ void wgmma_ss_n96(float (&d)[48], uint64_t adesc, uint64_t bdesc, int scale_d) {
    asm volatile("{\n.reg .pred p;\nsetp.ne.b32 p, %50, 0;\n"
      "wgmma.mma_async.sync.aligned.m64n96k16.f32.bf16.bf16 {%0,%1,%2,%3,%4,%5,%6,%7,%8,%9,%10,%11,%12,%13,%14,%15,%16,%17,%18,%19,%20,%21,%22,%23,%24,%25,%26,%27,%28,%29,%30,%31,%32,%33,%34,%35,%36,%37,%38,%39,%40,%41,%42,%43,%44,%45,%46,%47}, %48, %49, p, 1, 1, 0, 1;\n}"
      : "+f"(d[0]), "+f"(d[1]), "+f"(d[2]), "+f"(d[3]), "+f"(d[4]), "+f"(d[5]), "+f"(d[6]), "+f"(d[7]), "+f"(d[8]), "+f"(d[9]), "+f"(d[10]), "+f"(d[11]), "+f"(d[12]), "+f"(d[13]), "+f"(d[14]), "+f"(d[15]), "+f"(d[16]), "+f"(d[17]), "+f"(d[18]), "+f"(d[19]), "+f"(d[20]), "+f"(d[21]), "+f"(d[22]), "+f"(d[23]), "+f"(d[24]), "+f"(d[25]), "+f"(d[26]), "+f"(d[27]), "+f"(d[28]), "+f"(d[29]), "+f"(d[30]), "+f"(d[31]), "+f"(d[32]), "+f"(d[33]), "+f"(d[34]), "+f"(d[35]), "+f"(d[36]), "+f"(d[37]), "+f"(d[38]), "+f"(d[39]), "+f"(d[40]), "+f"(d[41]), "+f"(d[42]), "+f"(d[43]), "+f"(d[44]), "+f"(d[45]), "+f"(d[46]), "+f"(d[47])
      : "l"(adesc), "l"(bdesc), "r"(scale_d));
}
__device__ __forceinline__ void wgmma_ss_n128(float (&d)[64], uint64_t adesc, uint64_t bdesc, int scale_d) {
    asm volatile("{\n.reg .pred p;\nsetp.ne.b32 p, %66, 0;\n"
      "wgmma.mma_async.sync.aligned.m64n128k16.f32.bf16.bf16 {%0,%1,%2,%3,%4,%5,%6,%7,%8,%9,%10,%11,%12,%13,%14,%15,%16,%17,%18,%19,%20,%21,%22,%23,%24,%25,%26,%27,%28,%29,%30,%31,%32,%33,%34,%35,%36,%37,%38,%39,%40,%41,%42,%43,%44,%45,%46,%47,%48,%49,%50,%51,%52,%53,%54,%55,%56,%57,%58,%59,%60,%61,%62,%63}, %64, %65, p, 1, 1, 0, 1;\n}"
      : "+f"(d[0]), "+f"(d[1]), "+f"(d[2]), "+f"(d[3]), "+f"(d[4]), "+f"(d[5]), "+f"(d[6]), "+f"(d[7]), "+f"(d[8]), "+f"(d[9]), "+f"(d[10]), "+f"(d[11]), "+f"(d[12]), "+f"(d[13]), "+f"(d[14]), "+f"(d[15]), "+f"(d[16]), "+f"(d[17]), "+f"(d[18]), "+f"(d[19]), "+f"(d[20]), "+f"(d[21]), "+f"(d[22]), "+f"(d[23]), "+f"(d[24]), "+f"(d[25]), "+f"(d[26]), "+f"(d[27]), "+f"(d[28]), "+f"(d[29]), "+f"(d[30]), "+f"(d[31]), "+f"(d[32]), "+f"(d[33]), "+f"(d[34]), "+f"(d[35]), "+f"(d[36]), "+f"(d[37]), "+f"(d[38]), "+f"(d[39]), "+f"(d[40]), "+f"(d[41]), "+f"(d[42]), "+f"(d[43]), "+f"(d[44]), "+f"(d[45]), "+f"(d[46]), "+f"(d[47]), "+f"(d[48]), "+f"(d[49]), "+f"(d[50]), "+f"(d[51]), "+f"(d[52]), "+f"(d[53]), "+f"(d[54]), "+f"(d[55]), "+f"(d[56]), "+f"(d[57]), "+f"(d[58]), "+f"(d[59]), "+f"(d[60]), "+f"(d[61]), "+f"(d[62]), "+f"(d[63])
      : "l"(adesc), "l"(bdesc), "r"(scale_d));
}
__device__ __forceinline__ void wgmma_ss_n192(float (&d)[96], uint64_t adesc, uint64_t bdesc, int scale_d) {
    asm volatile("{\n.reg .pred p;\nsetp.ne.b32 p, %98, 0;\n"
      "wgmma.mma_async.sync.aligned.m64n192k16.f32.bf16.bf16 {%0,%1,%2,%3,%4,%5,%6,%7,%8,%9,%10,%11,%12,%13,%14,%15,%16,%17,%18,%19,%20,%21,%22,%23,%24,%25,%26,%27,%28,%29,%30,%31,%32,%33,%34,%35,%36,%37,%38,%39,%40,%41,%42,%43,%44,%45,%46,%47,%48,%49,%50,%51,%52,%53,%54,%55,%56,%57,%58,%59,%60,%61,%62,%63,%64,%65,%66,%67,%68,%69,%70,%71,%72,%73,%74,%75,%76,%77,%78,%79,%80,%81,%82,%83,%84,%85,%86,%87,%88,%89,%90,%91,%92,%93,%94,%95}, %96, %97, p, 1, 1, 0, 1;\n}"
      : "+f"(d[0]), "+f"(d[1]), "+f"(d[2]), "+f"(d[3]), "+f"(d[4]), "+f"(d[5]), "+f"(d[6]), "+f"(d[7]), "+f"(d[8]), "+f"(d[9]), "+f"(d[10]), "+f"(d[11]), "+f"(d[12]), "+f"(d[13]), "+f"(d[14]), "+f"(d[15]), "+f"(d[16]), "+f"(d[17]), "+f"(d[18]), "+f"(d[19]), "+f"(d[20]), "+f"(d[21]), "+f"(d[22]), "+f"(d[23]), "+f"(d[24]), "+f"(d[25]), "+f"(d[26]), "+f"(d[27]), "+f"(d[28]), "+f"(d[29]), "+f"(d[30]), "+f"(d[31]), "+f"(d[32]), "+f"(d[33]), "+f"(d[34]), "+f"(d[35]), "+f"(d[36]), "+f"(d[37]), "+f"(d[38]), "+f"(d[39]), "+f"(d[40]), "+f"(d[41]), "+f"(d[42]), "+f"(d[43]), "+f"(d[44]), "+f"(d[45]), "+f"(d[46]), "+f"(d[47]), "+f"(d[48]), "+f"(d[49]), "+f"(d[50]), "+f"(d[51]), "+f"(d[52]), "+f"(d[53]), "+f"(d[54]), "+f"(d[55]), "+f"(d[56]), "+f"(d[57]), "+f"(d[58]), "+f"(d[59]), "+f"(d[60]), "+f"(d[61]), "+f"(d[62]), "+f"(d[63]), "+f"(d[64]), "+f"(d[65]), "+f"(d[66]), "+f"(d[67]), "+f"(d[68]), "+f"(d[69]), "+f"(d[70]), "+f"(d[71]), "+f"(d[72]), "+f"(d[73]), "+f"(d[74]), "+f"(d[75]), "+f"(d[76]), "+f"(d[77]), "+f"(d[78]), "+f"(d[79]), "+f"(d[80]), "+f"(d[81]), "+f"(d[82]), "+f"(d[83]), "+f"(d[84]), "+f"(d[85]), "+f"(d[86]), "+f"(d[87]), "+f"(d[88]), "+f"(d[89]), "+f"(d[90]), "+f"(d[91]), "+f"(d[92]), "+f"(d[93]), "+f"(d[94]), "+f"(d[95])
      : "l"(adesc), "l"(bdesc), "r"(scale_d));
}
__device__ __forceinline__ void qk_wgmma_n64(float (&d)[32], const uint32_t (&a)[4], uint64_t desc) {
    asm volatile("wgmma.mma_async.sync.aligned.m64n64k16.f32.bf16.bf16 {%0,%1,%2,%3,%4,%5,%6,%7,%8,%9,%10,%11,%12,%13,%14,%15,%16,%17,%18,%19,%20,%21,%22,%23,%24,%25,%26,%27,%28,%29,%30,%31}, {%32,%33,%34,%35}, %36, 0, 1, 1, 0;"
      : "=f"(d[0]), "=f"(d[1]), "=f"(d[2]), "=f"(d[3]), "=f"(d[4]), "=f"(d[5]), "=f"(d[6]), "=f"(d[7]), "=f"(d[8]), "=f"(d[9]), "=f"(d[10]), "=f"(d[11]), "=f"(d[12]), "=f"(d[13]), "=f"(d[14]), "=f"(d[15]), "=f"(d[16]), "=f"(d[17]), "=f"(d[18]), "=f"(d[19]), "=f"(d[20]), "=f"(d[21]), "=f"(d[22]), "=f"(d[23]), "=f"(d[24]), "=f"(d[25]), "=f"(d[26]), "=f"(d[27]), "=f"(d[28]), "=f"(d[29]), "=f"(d[30]), "=f"(d[31])
      : "r"(a[0]), "r"(a[1]), "r"(a[2]), "r"(a[3]), "l"(desc));
}

__device__ __forceinline__ void pv_wgmma(float (&d)[12], uint32_t a0, uint32_t a1, uint32_t a2, uint32_t a3, uint64_t desc) {
    asm volatile("wgmma.mma_async.sync.aligned.m64n24k16.f32.bf16.bf16 {%0,%1,%2,%3,%4,%5,%6,%7,%8,%9,%10,%11}, {%12,%13,%14,%15}, %16, 1, 1, 1, 1;"
      : "+f"(d[0]), "+f"(d[1]), "+f"(d[2]), "+f"(d[3]), "+f"(d[4]), "+f"(d[5]), "+f"(d[6]), "+f"(d[7]), "+f"(d[8]), "+f"(d[9]), "+f"(d[10]), "+f"(d[11])
      : "r"(a0), "r"(a1), "r"(a2), "r"(a3), "l"(desc));
}

__device__ __forceinline__ void tile_of(int bid, int& mb, int& nt) {
    int grp = bid >> 4, in = bid & 15;
    mb = (grp >> 1) * 4 + (in >> 2);
    nt = (grp & 1) * 4 + (in & 3);
}

constexpr int K1_STAGES = 5, K1_STAGE = 16384 + 24576;
constexpr int K1_BAR = K1_STAGES * K1_STAGE, K1_RS = K1_BAR + 128, K1_CS = K1_RS + 1024, K1_SMEM = K1_CS + 768;

__device__ __forceinline__ float2 row_stats_regs(uint4 a, uint4 b) {
    float v[16];
    v[0] = bf_lo(a.x); v[1] = bf_hi(a.x); v[2] = bf_lo(a.y); v[3] = bf_hi(a.y);
    v[4] = bf_lo(a.z); v[5] = bf_hi(a.z); v[6] = bf_lo(a.w); v[7] = bf_hi(a.w);
    v[8] = bf_lo(b.x); v[9] = bf_hi(b.x); v[10] = bf_lo(b.y); v[11] = bf_hi(b.y);
    v[12] = bf_lo(b.z); v[13] = bf_hi(b.z); v[14] = bf_lo(b.w); v[15] = bf_hi(b.w);
    float s = 0.f;
#pragma unroll
    for (int i = 0; i < 16; i++) s += v[i];
    float mean = warp_sum(s) * (1.0f / DM);
    float q = 0.f;
#pragma unroll
    for (int i = 0; i < 16; i++) { float d = v[i] - mean; q = fmaf(d, d, q); }
    float var = warp_sum(q) * (1.0f / DM);
    float rstd = rsqrtf(var + 1e-5f);
    return make_float2(rstd, -mean * rstd);
}
__device__ __forceinline__ float2 row_stats_x(const __nv_bfloat16* x, int row, int lane) {
    const uint4* p = (const uint4*)(x + (size_t)row * DM);
    return row_stats_regs(__ldg(p + lane), __ldg(p + 32 + lane));
}
__device__ __forceinline__ void colsum8(const __nv_bfloat16* w, int ld, int col, int k0, int nk, float (&s)[8]) {
#pragma unroll
    for (int i = 0; i < 8; i++) s[i] = 0.f;
    for (int k = k0; k < k0 + nk; k += 8) {
        uint4 u[8];
#pragma unroll
        for (int i = 0; i < 8; i++) u[i] = __ldg((const uint4*)(w + (size_t)(k + i) * ld + col));
#pragma unroll
        for (int i = 0; i < 8; i++) {
            s[0] += bf_lo(u[i].x); s[1] += bf_hi(u[i].x); s[2] += bf_lo(u[i].y); s[3] += bf_hi(u[i].y);
            s[4] += bf_lo(u[i].z); s[5] += bf_hi(u[i].z); s[6] += bf_lo(u[i].w); s[7] += bf_hi(u[i].w);
        }
    }
}
__device__ __forceinline__ bool wait_count(const unsigned int* p, unsigned int target, int lane) {
    int ok = 1;
    if (lane == 0) {
        int it = 0;
        while (ld_acquire(p) < target) { if (++it > (1 << 18)) { ok = 0; break; } }
    }
    ok = __shfl_sync(0xffffffffu, ok, 0);
    return ok != 0;
}

__global__ void __launch_bounds__(384, 1)
qkv_kernel(const __grid_constant__ CUtensorMap tm_x, const __grid_constant__ CUtensorMap tm_w,
           const __nv_bfloat16* __restrict__ x, const __nv_bfloat16* __restrict__ wqkv) {
    extern __shared__ __align__(1024) unsigned char smem[];
    const uint32_t sb = smem_u32(smem);
    const int tid = threadIdx.x, warp = __shfl_sync(0xffffffffu, tid >> 5, 0), lane = tid & 31;
    TLDECL
    TL(0);
    int mb, nt;
    tile_of(blockIdx.x, mb, nt);
    const uint32_t full = sb + K1_BAR, empty = full + 40, auxb = full + 80;
    if (tid == 0) {
        prefetch_tmap(&tm_x); prefetch_tmap(&tm_w);
        for (int i = 0; i < K1_STAGES; i++) { mbar_init(full + 8 * i, 1); mbar_init(empty + 8 * i, 8); }
        mbar_init(auxb, 3);
        fence_barrier_init();
    }
    __syncthreads();
    pdl_launch();
    if (warp == 0) {
        if (blockIdx.x == 0) { g_cnt2[lane] = 0; g_cnt2[32 + lane] = 0; }
        if (lane == 0) {
            for (int kb = 0; kb < 8; kb++) {
                int s = kb % K1_STAGES;
                if (kb >= K1_STAGES) mbar_wait(empty + 8 * s, 0);
                mbar_expect(full + 8 * s, K1_STAGE);
                tma2d(sb + s * K1_STAGE, &tm_x, kb * 64, mb * 128, full + 8 * s);
                tma3d(sb + s * K1_STAGE + 16384, &tm_w, 0, kb * 64, nt * 3, full + 8 * s);
            }
        }
    } else if (warp < 4) {
        float2* s_rs = (float2*)(smem + K1_RS);
        float* s_cs = (float*)(smem + K1_CS);
        if (warp < 3) {
            const int r0 = mb * 128 + nt * 16 + (warp - 1) * 8;
            uint4 u[16];
#pragma unroll
            for (int i = 0; i < 8; i++) {
                const uint4* p = (const uint4*)(x + (size_t)(r0 + i) * DM);
                u[2 * i] = __ldg(p + lane); u[2 * i + 1] = __ldg(p + 32 + lane);
            }
            float2 mine = make_float2(0.f, 0.f);
#pragma unroll
            for (int i = 0; i < 8; i++) {
                float2 st = row_stats_regs(u[2 * i], u[2 * i + 1]);
                if (lane == i) mine = st;
            }
            if (lane < 8) g_rowstat1[r0 + lane] = mine;
            __syncwarp();
            if (lane == 0) red_release(&g_cnt[mb]);
        } else {
            uint4 u[24];
#pragma unroll
            for (int c = 0; c < 3; c++)
#pragma unroll
                for (int i = 0; i < 8; i++)
                    u[c * 8 + i] = __ldg((const uint4*)(wqkv + (size_t)(mb * 32 + (lane >> 3) * 8 + i) * 1536 + nt * 192 + (c * 8 + (lane & 7)) * 8));
#pragma unroll
            for (int c = 0; c < 3; c++) {
                float cs[8];
#pragma unroll
                for (int i = 0; i < 8; i++) cs[i] = 0.f;
#pragma unroll
                for (int i = 0; i < 8; i++) {
                    const uint4 w = u[c * 8 + i];
                    cs[0] += bf_lo(w.x); cs[1] += bf_hi(w.x); cs[2] += bf_lo(w.y); cs[3] += bf_hi(w.y);
                    cs[4] += bf_lo(w.z); cs[5] += bf_hi(w.z); cs[6] += bf_lo(w.w); cs[7] += bf_hi(w.w);
                }
#pragma unroll
                for (int i = 0; i < 8; i++) {
                    cs[i] += __shfl_xor_sync(0xffffffffu, cs[i], 8);
                    cs[i] += __shfl_xor_sync(0xffffffffu, cs[i], 16);
                }
                if (lane < 8) {
                    float4* d = (float4*)(g_cs1_part + mb * 1536 + nt * 192 + (c * 8 + lane) * 8);
                    d[0] = make_float4(cs[0], cs[1], cs[2], cs[3]);
                    d[1] = make_float4(cs[4], cs[5], cs[6], cs[7]);
                }
            }
            __syncwarp();
            if (lane == 0) red_release(&g_cnt[16 + nt]);
        }
        TX(8 + warp);
        if (warp == 1) {
            if (wait_count(&g_cnt[mb], 16, lane)) {
#pragma unroll
                for (int i = 0; i < 4; i++) s_rs[lane + 32 * i] = __ldcg(&g_rowstat1[mb * 128 + lane + 32 * i]);
            } else {
                for (int i = 0; i < 128; i++) {
                    float2 st = row_stats_x(x, mb * 128 + i, lane);
                    if (lane == 0) s_rs[i] = st;
                }
            }
        } else {
            int c0 = (warp - 2) * 96;
            if (wait_count(&g_cnt[16 + nt], 16, lane)) {
#pragma unroll
                for (int i = 0; i < 3; i++) {
                    float s = 0.f;
#pragma unroll
                    for (int p = 0; p < 16; p++) s += __ldcg(&g_cs1_part[p * 1536 + nt * 192 + c0 + lane + 32 * i]);
                    s_cs[c0 + lane + 32 * i] = s;
                }
            } else if (lane < 12) {
                float s[8];
                colsum8(wqkv, 1536, nt * 192 + c0 + lane * 8, 0, 512, s);
#pragma unroll
                for (int i = 0; i < 8; i++) s_cs[c0 + lane * 8 + i] = s[i];
            }
        }
        __syncwarp();
        TX(12 + warp);
        if (lane == 0) mbar_arrive(auxb);
        bar_sync(2, 256 + 96);
        const int a = tid - 32;
        {
            const int hh = a >> 3, w = a & 7;
            const float4* p = (const float4*)(smem + 49152) + (hh * 256 + w * 32) / 2;
            float m = 0.f;
#pragma unroll
            for (int i = 0; i < 8; i++) {
                const int ii = (i + a) & 7;
                float4 u = p[2 * ii], v = p[2 * ii + 1];
                float n0 = u.x + u.z + v.x + v.z, n1 = u.y + u.w + v.y + v.w;
                if (!(n0 <= 3.0e38f) || !(n1 <= 3.0e38f)) m = __int_as_float(0x7f800000);
                m = fmaxf(m, fmaxf(n0, n1));
            }
            const int col0 = nt * 192 + hh * 16;
            g_nrm[((col0 >> 9) * NH + ((col0 & 511) >> 4)) * 128 + mb * 8 + w] = m;
        }
        if (a < 24) bulk_wait_all();
        TL(27);
        TLDUMP;
    } else {
        const int wgi = (warp >> 2) - 1, ww = warp & 3;
        float acc[96];
#pragma unroll 1
        for (int kb = 0; kb < 8; kb++) {
            int s = kb % K1_STAGES;
            mbar_wait(full + 8 * s, (kb / K1_STAGES) & 1);
            if (warp == 4) TX(kb);
            uint64_t ad = make_desc(sb + s * K1_STAGE + wgi * 8192, 16, 1024, 1);
            uint64_t bd = make_desc(sb + s * K1_STAGE + 16384, 8192, 1024, 1);
            WG_FENCE();
#pragma unroll
            for (int k = 0; k < 4; k++) wgmma_ss_n192(acc, ad + k * 2, bd + k * 128, (kb | k) != 0);
            WG_COMMIT();
            if (kb > 0) {
                wg_wait<1>();
                if (lane == 0) mbar_arrive(empty + 8 * ((kb - 1) % K1_STAGES));
            }
        }
        wg_wait<0>();
        fence_regs(acc);
        TL(1);
        if (warp == 4) TX(16);
        mbar_wait(auxb, 0);
        if (warp == 4) TX(17);
        bar_sync(1, 256);
        const float2* s_rs = (const float2*)(smem + K1_RS);
        const float* s_cs = (const float*)(smem + K1_CS);
        const int g = lane >> 2, t = lane & 3;
        const int rl = wgi * 64 + ww * 16 + g;
        const float2 st0 = s_rs[rl], st1 = s_rs[rl + 8];
        const float QS = 0.25f * 1.4426950408889634f;
        const uint32_t stg = sb + ((lane >> 4) * 16 + wgi * 8 + ww * 2 + ((lane >> 3) & 1)) * 128 + (lane & 7) * 16;
        float2* s_np = (float2*)(smem + 49152) + (warp - 4) * 32 + lane;
#pragma unroll
        for (int hh = 0; hh < 12; hh++) {
            const int which = (nt * 192 + hh * 16) >> 9;
            const float sc = (which == 0) ? QS : 1.0f;
            const float a0 = st0.x * sc, b0 = st0.y * sc, a1 = st1.x * sc, b1 = st1.y * sc;
            const float2 c0 = *(const float2*)(s_cs + 16 * hh + 2 * t), c1 = *(const float2*)(s_cs + 16 * hh + 8 + 2 * t);
            const float* a = acc + 8 * hh;
            float v0 = fmaf(a0, a[0], b0 * c0.x), v1 = fmaf(a0, a[1], b0 * c0.y), v2 = fmaf(a1, a[2], b1 * c0.x), v3 = fmaf(a1, a[3], b1 * c0.y);
            float v4 = fmaf(a0, a[4], b0 * c1.x), v5 = fmaf(a0, a[5], b0 * c1.y), v6 = fmaf(a1, a[6], b1 * c1.x), v7 = fmaf(a1, a[7], b1 * c1.y);
            {
                const int head = ((nt * 192 + hh * 16) & 511) >> 4;
                uint32_t* o = (uint32_t*)g_qkv + ((size_t)((which * NH + head) * 2) * 256 + mb * 16 + wgi * 8 + ww * 2) * 32 + lane;
                o[0] = pack_bf16(v0, v1); o[32] = pack_bf16(v2, v3); o[8192] = pack_bf16(v4, v5); o[8192 + 32] = pack_bf16(v6, v7);
            }
            s_np[hh * 256] = make_float2(fmaf(v0, v0, fmaf(v1, v1, fmaf(v4, v4, v5 * v5))), fmaf(v2, v2, fmaf(v3, v3, fmaf(v6, v6, v7 * v7))));
        }
        fence_proxy_async();
        bar_arrive(2, 256 + 96);
        TL(2);
        TLDUMP;
    }
}

constexpr int AT_K = 0, AT_V = 65536, AT_ONES = 131072, AT_BAR = 163840, AT_SMEM = AT_BAR + 128;
#define POLY_MASK 0xAD6A

__device__ __forceinline__ uint32_t exp2_pair_poly(float x0, float x1) {
    uint32_t t0 = __float_as_uint(x0 + 32895.0f);
    uint32_t t1 = __float_as_uint(x1 + 32895.0f);
    uint32_t gd = __byte_perm(t0, t1, 0x6420);
    uint32_t wm = __byte_perm(t0, t1, 0x5612);
    uint32_t v = hfma2(gd, 0x71477147u, 0x354f354fu);
    uint32_t z = hmul2(v, gd);
    return (wm >> 1) + z;
}
__device__ __forceinline__ uint32_t exp2_pair_mufu(float x0, float x1) { return pack_bf16(ex2f(x0), ex2f(x1)); }
template <uint32_t MASK>
__device__ __forceinline__ void exp_blocks(const float (&s)[32], uint32_t (&p)[16]) {
#pragma unroll
    for (int b = 0; b < 8; b++) {
        if ((MASK >> b) & 1) {
            p[2 * b] = exp2_pair_poly(s[4 * b], s[4 * b + 1]);
            p[2 * b + 1] = exp2_pair_poly(s[4 * b + 2], s[4 * b + 3]);
        } else {
            p[2 * b] = exp2_pair_mufu(s[4 * b], s[4 * b + 1]);
            p[2 * b + 1] = exp2_pair_mufu(s[4 * b + 2], s[4 * b + 3]);
        }
    }
}
#define PV4(P) _Pragma("unroll") for (int i = 0; i < 4; i++) { pv_wgmma(o, P[4 * i], P[4 * i + 1], P[4 * i + 2], P[4 * i + 3], vd); vd += 16; }

__device__ __forceinline__ void attn_store(float (&o)[12], int row0, int head, int lane) {
    float l0 = __shfl_sync(0xffffffffu, o[8], lane & 28);
    float l1 = __shfl_sync(0xffffffffu, o[10], lane & 28);
    float r0 = 1.0f / l0, r1 = 1.0f / l1;
    uint32_t* op = (uint32_t*)g_ao;
    int mb = row0 >> 7, rg = (row0 & 127) >> 3;
    int kb = head >> 2, kc = (head & 3) * 2;
    size_t base = (((size_t)(mb * 8 + kb) * 8 + kc) * 16 + rg) * 32 + lane;
    op[base] = pack_bf16(o[0] * r0, o[1] * r0);
    op[base + 32] = pack_bf16(o[2] * r1, o[3] * r1);
    op[base + 16 * 32] = pack_bf16(o[4] * r0, o[5] * r0);
    op[base + 16 * 32 + 32] = pack_bf16(o[6] * r1, o[7] * r1);
}

__device__ __forceinline__ void attn_load_q(uint32_t (&q)[4], const __nv_bfloat16* gq, int row0, int lane) {
    const uint32_t* qp = (const uint32_t*)gq;
    int j0 = row0 >> 3;
    q[0] = __ldcg(qp + (0 * 256 + j0) * 32 + lane);
    q[1] = __ldcg(qp + (0 * 256 + j0 + 1) * 32 + lane);
    q[2] = __ldcg(qp + (1 * 256 + j0) * 32 + lane);
    q[3] = __ldcg(qp + (1 * 256 + j0 + 1) * 32 + lane);
}

__device__ __forceinline__ void attn_tile_safe(const uint32_t (&q)[4], uint64_t kd, uint64_t vd, int row0, int head, int lane) {
    float o[12];
#pragma unroll
    for (int i = 0; i < 12; i++) o[i] = 0.f;
    float m0 = -INFINITY, m1 = -INFINITY;
    fence_regs(o);
#pragma unroll 1
    for (int j = 0; j < 32; j++) {
        float s[32];
        uint32_t p[16];
        WG_FENCE();
        qk_wgmma_n64(s, q, kd); kd += 64;
        WG_COMMIT();
        wg_wait<0>();
        fence_regs(s);
        fence_regs(o);
        float x0 = m0, x1 = m1;
#pragma unroll
        for (int b = 0; b < 8; b++) {
            x0 = fmaxf(x0, fmaxf(s[4 * b], s[4 * b + 1]));
            x1 = fmaxf(x1, fmaxf(s[4 * b + 2], s[4 * b + 3]));
        }
        x0 = fmaxf(x0, __shfl_xor_sync(0xffffffffu, x0, 1)); x0 = fmaxf(x0, __shfl_xor_sync(0xffffffffu, x0, 2));
        x1 = fmaxf(x1, __shfl_xor_sync(0xffffffffu, x1, 1)); x1 = fmaxf(x1, __shfl_xor_sync(0xffffffffu, x1, 2));
        float al0 = ex2f(m0 - x0), al1 = ex2f(m1 - x1);
        m0 = x0; m1 = x1;
#pragma unroll
        for (int i = 0; i < 3; i++) { o[4 * i] *= al0; o[4 * i + 1] *= al0; o[4 * i + 2] *= al1; o[4 * i + 3] *= al1; }
#pragma unroll
        for (int b = 0; b < 8; b++) {
            p[2 * b] = exp2_pair_mufu(s[4 * b] - m0, s[4 * b + 1] - m0);
            p[2 * b + 1] = exp2_pair_mufu(s[4 * b + 2] - m1, s[4 * b + 3] - m1);
        }
        fence_regs(o);
        WG_FENCE();
        PV4(p);
        WG_COMMIT();
        wg_wait<0>();
        fence_regs(o);
    }
    attn_store(o, row0, head, lane);
}

__global__ void __launch_bounds__(512, 1)
attn_kernel(const __nv_bfloat16* __restrict__ wg_, const __nv_bfloat16* __restrict__ wu_,
            const __nv_bfloat16* __restrict__ wo_, const __nv_bfloat16* __restrict__ wd_) {
    extern __shared__ __align__(1024) unsigned char smem[];
    const uint32_t sb = smem_u32(smem);
    const int tid = threadIdx.x, wg = tid >> 7, warp = (tid >> 5) & 3, lane = tid & 31;
    TLDECL
    pdl_launch();
    if (blockIdx.x >= 128) {
        const int e = blockIdx.x - 128;
        const __nv_bfloat16* w = (e < 2) ? wg_ : wu_;
        float* red = (float*)smem;
        const int cgrp = tid & 127, kq = tid >> 7;
        if (cgrp < 112) {
            float s[8];
            colsum8(w, FF, (e & 1) * 896 + cgrp * 8, kq * 128, 128, s);
#pragma unroll
            for (int i = 0; i < 8; i++) red[kq * 896 + cgrp * 8 + i] = s[i];
        }
        __syncthreads();
        for (int c = tid; c < 896; c += 512)
            g_cs2[(e >> 1) * FF + (e & 1) * 896 + c] = red[c] + red[896 + c] + red[1792 + c] + red[2688 + c];
        if (tid < 32) {
            const char* p0 = (const char*)wo_ + e * (DM * DM * 2 / 4);
            for (int i = lane; i < 32; i += 32)
                asm volatile("cp.async.bulk.prefetch.L2.global [%0], %1;" :: "l"(p0 + i * 4096), "r"(4096) : "memory");
            const char* p1 = (const char*)wd_ + e * (FF * DM * 2 / 4);
            for (int i = lane; i < 112; i += 32)
                asm volatile("cp.async.bulk.prefetch.L2.global [%0], %1;" :: "l"(p1 + i * 4096), "r"(4096) : "memory");
        }
        return;
    }
    const int head = blockIdx.x >> 2, qq = blockIdx.x & 3;
    const __nv_bfloat16* gq = g_qkv + (size_t)head * (S_LEN * 16);
    const __nv_bfloat16* gk = g_qkv + (size_t)(NH + head) * (S_LEN * 16);
    const __nv_bfloat16* gv = g_qkv + (size_t)(2 * NH + head) * (S_LEN * 16);
    if (tid == 0) {
        for (int i = 0; i < 8; i++) mbar_init(sb + AT_BAR + 8 * i, 1);
        fence_barrier_init();
    }
    {
        uint4 one = make_uint4(0x00003F80u, 0, 0, 0);
#pragma unroll
        for (int i = 0; i < 4; i++) *(uint4*)(smem + AT_ONES + (i * 512 + tid) * 16) = one;
        fence_proxy_async();
    }
    __syncthreads();
    TL(3);
    pdl_wait();
    TL(4);
    auto load_kv = [&](int i) {
        uint32_t bar = sb + AT_BAR + 8 * i;
        mbar_expect(bar, 16384);
        bulk_g2s(sb + AT_K + i * 4096, gk + i * 2048, 4096, bar);
        bulk_g2s(sb + AT_K + 32768 + i * 4096, gk + 16384 + i * 2048, 4096, bar);
        bulk_g2s(sb + AT_V + i * 4096, gv + i * 2048, 4096, bar);
        bulk_g2s(sb + AT_V + 32768 + i * 4096, gv + 16384 + i * 2048, 4096, bar);
    };
    if (tid == 0) { load_kv(0); load_kv(1); }
    uint32_t q[4], q2[4];
    attn_load_q(q, gq, qq * 512 + wg * 64 + warp * 16, lane);
    attn_load_q(q2, gq, qq * 512 + (4 + wg) * 64 + warp * 16, lane);
    bool fast;
    {
        const float* nq = g_nrm + (0 * NH + head) * 128 + qq * 32;
        const float* nk = g_nrm + (1 * NH + head) * 128;
        const float* nv = g_nrm + (2 * NH + head) * 128;
        float4 k4 = __ldcg((const float4*)nk + lane), v4 = __ldcg((const float4*)nv + lane);
        float qm = warp_max(__ldcg(nq + lane));
        float km = warp_max(fmaxf(fmaxf(k4.x, k4.y), fmaxf(k4.z, k4.w)));
        float vm = warp_max(fmaxf(fmaxf(v4.x, v4.y), fmaxf(v4.z, v4.w)));
        fast = __all_sync(0xffffffffu, (qm * km <= 3500.0f) && (vm <= 1.0e24f));
    }
    TL(24);
    const uint64_t kdesc0 = make_desc(sb + AT_K, 32768, 128, 0);
    const uint64_t vdesc0 = make_desc(sb + AT_V, 128, 32768, 0);
    if (!fast) {
        if (tid == 0) for (int i = 2; i < 8; i++) load_kv(i);
        for (int i = 0; i < 8; i++) mbar_wait(sb + AT_BAR + 8 * i, 0);
#pragma unroll 1
        for (int tile = 0; tile < 2; tile++) {
            const int row0 = qq * 512 + (tile * 4 + wg) * 64 + warp * 16;
            attn_tile_safe(q, kdesc0, vdesc0, row0, head, lane);
#pragma unroll
            for (int i = 0; i < 4; i++) q[i] = q2[i];
        }
        return;
    }
#pragma unroll 1
    for (int tile = 0; tile < 2; tile++) {
        const int row0 = qq * 512 + (tile * 4 + wg) * 64 + warp * 16;
        float o[12];
#pragma unroll
        for (int i = 0; i < 12; i++) o[i] = 0.f;
        fence_regs(o);
        float sa[32];
        uint32_t pa[16];
        uint64_t kd = kdesc0, vd = vdesc0;
        if (tile == 0) { mbar_wait(sb + AT_BAR, 0); TL(25); }
        WG_FENCE();
        qk_wgmma_n64(sa, q, kd); kd += 64;
        WG_COMMIT();
#pragma unroll 1
        for (int jj = 0; jj < 8; jj++) {
            if (tile == 0 && jj < 7) {
                if (tid == 0 && jj < 6) load_kv(jj + 2);
                mbar_wait(sb + AT_BAR + 8 * (jj + 1), 0);
            }
            if (wg == 0 && warp == 0) TX(128 + tile * 8 + jj);
#pragma unroll
            for (int j = 0; j < 4; j++) {
                wg_wait<0>();
                fence_regs(sa);
                if (j & 1) exp_blocks<(POLY_MASK >> 8)>(sa, pa); else exp_blocks<(POLY_MASK & 255)>(sa, pa);
                WG_FENCE();
                qk_wgmma_n64(sa, q, kd); kd += 64;
                PV4(pa);
                WG_COMMIT();
            }
        }
        wg_wait<0>();
        fence_regs(o);
        fence_regs(sa);
        if (tile == 0) TL(26);
        attn_store(o, row0, head, lane);
#pragma unroll
        for (int i = 0; i < 4; i++) q[i] = q2[i];
    }
    TL(5);
    TLDUMP;
}

constexpr int F_R2 = 131072, F_X = 196608, F_BAR = 229376;
constexpr int F_RS = F_BAR + 256, F_CS = F_RS + 1024, F_SMEM = F_CS + 1792;
enum { B_FA = 0, B_HF = 4, B_BF = 8, B_BE = 11, B_CF = 14, B_CE = 20, B_ADONE = 26, B_BDONE = 27, B_XC = 28, B_PRDY = 29, B_AUX = 30, B_NUM = 31 };

__device__ __forceinline__ uint32_t mapa(uint32_t a, uint32_t rank) { uint32_t r; asm("mapa.shared::cluster.u32 %0, %1, %2;" : "=r"(r) : "r"(a), "r"(rank)); return r; }
__device__ __forceinline__ void st_async4(uint32_t dst, float a, float b, float c, float d, uint32_t bar) {
    asm volatile("st.async.weak.shared::cluster.mbarrier::complete_tx::bytes.v4.f32 [%0], {%1,%2,%3,%4}, [%5];"
                 :: "r"(dst), "f"(a), "f"(b), "f"(c), "f"(d), "r"(bar) : "memory");
}
__device__ __forceinline__ void mbar_arrive_remote(uint32_t a) { asm volatile("mbarrier.arrive.relaxed.cluster.shared::cluster.b64 _, [%0];" :: "r"(a) : "memory"); }
__device__ __forceinline__ void mbar_wait_cluster(uint32_t a, int parity) {
    uint32_t done;
    int it = 0;
    do {
        asm volatile("{\n.reg .pred p;\nmbarrier.try_wait.parity.acquire.cluster.shared::cta.b64 p, [%1], %2;\nselp.u32 %0, 1, 0, p;\n}"
                     : "=r"(done) : "r"(a), "r"(parity) : "memory");
        if (++it > (1 << 24)) __trap();
    } while (!done);
}
__device__ __forceinline__ void poll_count(const unsigned int* p, unsigned int target) {
    int it = 0;
    while (ld_acquire(p) < target) { if (++it > (1 << 22)) __trap(); }
    asm volatile("fence.proxy.async.global;" ::: "memory");
}
__device__ __forceinline__ void tma2d_store(const CUtensorMap* m, uint32_t src, int c0, int c1) {
    asm volatile("cp.async.bulk.tensor.2d.global.shared::cta.bulk_group [%0, {%2, %3}], [%1];" :: "l"(m), "r"(src), "r"(c0), "r"(c1) : "memory");
}
template <int R>
__device__ __forceinline__ void xchg(float (&acc)[64], float (&o)[32], uint32_t sb, unsigned char* smem, int bar, int ctid) {
    const uint32_t dst = mapa(sb + F_X + ctid * 16, 1 - R), rb = mapa(sb + F_BAR + 8 * bar, 1 - R);
#pragma unroll
    for (int q = 0; q < 8; q++) {
        const int j = (1 - R) * 32 + 4 * q;
        st_async4(dst + q * 4096, acc[j], acc[j + 1], acc[j + 2], acc[j + 3], rb);
    }
    mbar_wait_cluster(sb + F_BAR + 8 * bar, 0);
#pragma unroll
    for (int q = 0; q < 8; q++) {
        float4 v = *(const float4*)(smem + F_X + q * 4096 + ctid * 16);
        const int j = R * 32 + 4 * q;
        o[4 * q] = acc[j] + v.x; o[4 * q + 1] = acc[j + 1] + v.y; o[4 * q + 2] = acc[j + 2] + v.z; o[4 * q + 3] = acc[j + 3] + v.w;
    }
}

template <int NB, bool STAGE>
__device__ __forceinline__ void ffn_epilogue(const float* ag, const float* au, const float* s_cs, int cs_off, uint32_t* gp, uint32_t stg,
                                             float2 st0, float2 st1, int lane) {
    const int t = lane & 3;
    const float C1 = 0.7978845608028654f, C2 = 0.044715f * 0.7978845608028654f;
    const float k10 = st0.x * C1, k20 = st0.x * st0.x * st0.x * C2, k11 = st1.x * C1, k21 = st1.x * st1.x * st1.x * C2;
#pragma unroll
    for (int j2 = 0; j2 < NB / 2; j2++) {
        uint32_t pk[4];
#pragma unroll
        for (int jj = 0; jj < 2; jj++) {
            const int j = 2 * j2 + jj;
            const float2 cg = *(const float2*)(s_cs + cs_off + 8 * j + 2 * t);
            const float2 cu = *(const float2*)(s_cs + 224 + cs_off + 8 * j + 2 * t);
            float r[4];
#pragma unroll
            for (int e = 0; e < 4; e++) {
                const float nm = (e < 2) ? st0.y : st1.y, k1 = (e < 2) ? k10 : k11, k2 = (e < 2) ? k20 : k21;
                const float tg = fmaf(nm, (e & 1) ? cg.y : cg.x, ag[4 * j + e]);
                const float tu = fmaf(nm, (e & 1) ? cu.y : cu.x, au[4 * j + e]);
                const float th = tanh_fast(tg * fmaf(tg * tg, k2, k1));
                const float p = tg * tu;
                r[e] = fmaf(p, th, p);
            }
            pk[2 * jj] = pack_bf16(r[0], r[1]);
            pk[2 * jj + 1] = pack_bf16(r[2], r[3]);
        }
        if (STAGE) {
            stsm4(stg + j2 * 4096, pk[0], pk[1], pk[2], pk[3]);
        } else {
            gp[j2 * 1024] = pk[0]; gp[j2 * 1024 + 32] = pk[1]; gp[j2 * 1024 + 512] = pk[2]; gp[j2 * 1024 + 544] = pk[3];
        }
    }
}

__global__ void __cluster_dims__(2, 1, 1) __launch_bounds__(384, 1)
tail_kernel(const __grid_constant__ CUtensorMap tm_o, const __grid_constant__ CUtensorMap tm_g,
            const __grid_constant__ CUtensorMap tm_u, const __grid_constant__ CUtensorMap tm_d,
            const __grid_constant__ CUtensorMap tm_out, const __nv_bfloat16* __restrict__ x) {
    extern __shared__ __align__(1024) unsigned char smem[];
    const uint32_t sb = smem_u32(smem);
    const uint32_t bars = sb + F_BAR;
    const int tid = threadIdx.x, warp = __shfl_sync(0xffffffffu, tid >> 5, 0), lane = tid & 31;
    TLDECL
    TL(6);
    if (warp == 4) TX(200);
    const int cl = blockIdx.x >> 1, r = blockIdx.x & 1;
    const int mb = ((cl & 7) >> 1) * 4 + (cl >> 4), ntA = (cl & 1) * 2 + ((cl >> 3) & 1);
    const int nt = ntA * 2 + r;
    if (tid < B_NUM) {
        const int i = tid;
        int cnt = 1;
        if ((i >= B_BE && i < B_BE + 3) || (i >= B_CE && i < B_CE + 6) || i == B_BDONE || i == B_PRDY) cnt = 8;
        if (i == B_AUX) cnt = 2;
        mbar_init(bars + 8 * i, cnt);
        if (i == B_XC) mbar_expect(bars + 8 * B_XC, 32768);
    }
    if (warp == 0) TX(201);
    if (warp == 0) { __syncwarp(); if (lane == 0) fence_barrier_init(); }
    if (warp == 0) TX(202);
    __syncthreads();
    if (warp == 4) TX(203);
    asm volatile("barrier.cluster.arrive.relaxed.aligned;" ::: "memory");
    if (warp == 4) TX(204);
    if (warp < 4) {
        asm volatile("setmaxnreg.dec.sync.aligned.u32 56;");
        if (warp == 0) TX(205);
        if (warp == 0) {
            if (lane == 0) {
                auto load_b = [&](int it) {
                    const int s = it % 3, pass = it >> 3, kb = it & 7;
                    const int ng = pass ? 3 : 4, c0 = nt * 224 + pass * 128;
                    const uint32_t bar = bars + 8 * (B_BF + s), dst = sb + F_R2 + s * 32768;
                    mbar_expect(bar, ng * 8192);
                    for (int i = 0; i < ng; i++) {
                        tma2d(dst + i * 4096, &tm_g, c0 + i * 32, kb * 64, bar);
                        tma2d(dst + 16384 + i * 4096, &tm_u, c0 + i * 32, kb * 64, bar);
                    }
                };
                for (int i = 0; i < 8; i++) {
                    const uint32_t bar = bars + 8 * (B_FA + (i >> 1));
                    if (!(i & 1)) mbar_expect(bar, 49152);
                    tma2d(sb + F_R2 + 32768 + i * 8192, &tm_o, nt * 64, i * 64, bar);
                }
                pdl_wait();
                TL(16);
                for (int i = 0; i < 8; i++)
                    bulk_g2s(sb + i * 16384, g_ao + (size_t)(mb * 8 + i) * 8192, 16384, bars + 8 * (B_FA + (i >> 1)));
                load_b(0);
                if (blockIdx.x == 0)
                    for (int i = 0; i < 32; i++) g_cnt[i] = 0;
                mbar_wait(bars + 8 * B_ADONE, 0);
                load_b(1); load_b(2);
                poll_count(&g_cnt2[mb], 8);
                TL(17);
                for (int kb = 0; kb < 8; kb++) {
                    const uint32_t bar = bars + 8 * (B_HF + (kb >> 1));
                    if (!(kb & 1)) mbar_expect(bar, (kb >> 1) == ntA ? 16384 : 32768);
                    if (kb != nt) bulk_g2s(sb + kb * 16384, g_h + (size_t)(mb * 8 + kb) * 8192, 16384, bar);
                }
                for (int it = 3; it < 16; it++) {
                    mbar_wait(bars + 8 * (B_BE + it % 3), (it / 3 - 1) & 1);
                    load_b(it);
                }
                mbar_wait(bars + 8 * B_BDONE, 0);
                for (int i = 0; i < 6; i++) {
                    const uint32_t bar = bars + 8 * (B_CF + i);
                    mbar_expect(bar, 32768);
                    tma2d(sb + i * 32768 + 16384, &tm_d, ntA * 128, (2 * i + r) * 64, bar);
                    tma2d(sb + i * 32768 + 24576, &tm_d, ntA * 128 + 64, (2 * i + r) * 64, bar);
                }
                poll_count(&g_cnt2[16 + mb], 8);
                TL(18);
                for (int kb = 0; kb < 14; kb++) {
                    const int s = kb % 6;
                    const uint32_t bar = bars + 8 * (B_CF + s);
                    if (kb >= 6) {
                        mbar_wait(bars + 8 * (B_CE + s), ((kb / 6) - 1) & 1);
                        mbar_expect(bar, 32768);
                        tma2d(sb + s * 32768 + 16384, &tm_d, ntA * 128, (2 * kb + r) * 64, bar);
                        tma2d(sb + s * 32768 + 24576, &tm_d, ntA * 128 + 64, (2 * kb + r) * 64, bar);
                    }
                    bulk_g2s(sb + s * 32768, g_g + (size_t)(mb * 28 + 2 * kb + r) * 8192, 16384, bar);
                }
            }
            TLDUMP;
            __syncwarp();
            asm volatile("barrier.cluster.wait.acquire.aligned;" ::: "memory");
        } else if (warp == 1) {
            asm volatile("barrier.cluster.wait.acquire.aligned;" ::: "memory");
            bar_sync(1, 288);
            if (lane == 0) {
                red_release(&g_cnt2[mb]);
                TL(9);
            }
            __syncwarp();
            bar_sync(2, 288);
            if (lane == 0) {
                red_release(&g_cnt2[16 + mb]);
                TL(13);
            }
            __syncwarp();
            bar_sync(3, 288);
            if (lane == 0) {
                tma2d_store(&tm_out, sb, nt * 64, mb * 128);
                bulk_commit();
                bulk_wait_all();
                TL(15);
            }
            TLDUMP;
        } else {
            asm volatile("barrier.cluster.wait.acquire.aligned;" ::: "memory");
            pdl_wait();
            float2* s_rs = (float2*)(smem + F_RS);
            float* s_cs = (float*)(smem + F_CS);
            for (int c = tid - 64; c < 448; c += 64)
                s_cs[c] = __ldcg(&g_cs2[(c >= 224 ? FF - 224 : 0) + nt * 224 + c]);
            if (lane == 0) poll_count(&g_cnt2[mb], 8);
            __syncwarp();
            for (int rr = tid - 64; rr < 128; rr += 64) {
                const float4* hp = (const float4*)(g_hstat + (size_t)(mb * 128 + rr) * 8);
                float4 a = __ldcg(hp), b = __ldcg(hp + 1), c = __ldcg(hp + 2), d = __ldcg(hp + 3);
                float mean = 0.125f * (a.x + a.z + b.x + b.z + c.x + c.z + d.x + d.z);
                float m2 = a.y + a.w + b.y + b.w + c.y + c.w + d.y + d.w;
                float e;
                e = a.x - mean; m2 = fmaf(64.f * e, e, m2); e = a.z - mean; m2 = fmaf(64.f * e, e, m2);
                e = b.x - mean; m2 = fmaf(64.f * e, e, m2); e = b.z - mean; m2 = fmaf(64.f * e, e, m2);
                e = c.x - mean; m2 = fmaf(64.f * e, e, m2); e = c.z - mean; m2 = fmaf(64.f * e, e, m2);
                e = d.x - mean; m2 = fmaf(64.f * e, e, m2); e = d.z - mean; m2 = fmaf(64.f * e, e, m2);
                s_rs[rr] = make_float2(rsqrtf(m2 * (1.0f / DM) + 1e-5f), -mean);
            }
            __syncwarp();
            if (lane == 0) mbar_arrive(bars + 8 * B_AUX);
        }
    } else {
        asm volatile("setmaxnreg.inc.sync.aligned.u32 216;");
        if (warp == 4) TX(206);
        const int wgi = (warp >> 2) - 1, ww = warp & 3, ctid = tid - 128;
        const int g = lane >> 2, t = lane & 3;
        const int rl = wgi * 64 + ww * 16 + g, row = mb * 128 + rl;
        const int rgl = wgi * 8 + ww * 2;
        const float2* s_rs = (const float2*)(smem + F_RS);
        const float* s_cs = (const float*)(smem + F_CS);
        const uint32_t stl = ((lane >> 4) * 16 + rgl + ((lane >> 3) & 1)) * 128 + (lane & 7) * 16;
        TL(23);
        {
            uint32_t xr[16];
            const uint32_t* xp = (const uint32_t*)(x + (size_t)row * DM + nt * 64) + t;
#pragma unroll
            for (int j = 0; j < 8; j++) { xr[2 * j] = __ldg(xp + 4 * j); xr[2 * j + 1] = __ldg(xp + 8 * (DM / 2) + 4 * j); }
            float acc[32];
#pragma unroll 1
            for (int i = 0; i < 8; i++) {
                if (!(i & 1)) { mbar_wait(bars + 8 * (B_FA + (i >> 1)), 0); if (i == 0) TL(19); }
                uint64_t ad = make_desc(sb + i * 16384 + wgi * 1024, 2048, 128, 0);
                uint64_t bd = make_desc(sb + F_R2 + 32768 + i * 8192, 8192, 1024, 1);
                WG_FENCE();
#pragma unroll
                for (int k = 0; k < 4; k++) wgmma_ss_n64(acc, ad + k * 256, bd + k * 128, (i | k) != 0);
                WG_COMMIT();
            }
            wg_wait<0>();
            fence_regs(acc);
            TL(7);
            bar_sync(4, 256);
            if (tid == 128) mbar_arrive(bars + 8 * B_ADONE);
            uint32_t* hp = (uint32_t*)g_h + ((size_t)(mb * 8 + nt) * 8 * 16 + rgl) * 32 + lane;
            float v0[16], v1[16];
            float s0 = 0.f, s1 = 0.f;
#pragma unroll
            for (int j2 = 0; j2 < 4; j2++) {
                uint32_t u[4];
#pragma unroll
                for (int jj = 0; jj < 2; jj++) {
                    const int j = 2 * j2 + jj;
                    u[2 * jj] = pack_bf16(bf_lo(xr[2 * j]) + acc[4 * j], bf_hi(xr[2 * j]) + acc[4 * j + 1]);
                    u[2 * jj + 1] = pack_bf16(bf_lo(xr[2 * j + 1]) + acc[4 * j + 2], bf_hi(xr[2 * j + 1]) + acc[4 * j + 3]);
                    v0[2 * j] = bf_lo(u[2 * jj]); v0[2 * j + 1] = bf_hi(u[2 * jj]);
                    v1[2 * j] = bf_lo(u[2 * jj + 1]); v1[2 * j + 1] = bf_hi(u[2 * jj + 1]);
                    s0 += v0[2 * j] + v0[2 * j + 1];
                    s1 += v1[2 * j] + v1[2 * j + 1];
                }
                stsm4(sb + nt * 16384 + stl + j2 * 4096, u[0], u[1], u[2], u[3]);
                hp[j2 * 1024] = u[0]; hp[j2 * 1024 + 32] = u[1]; hp[j2 * 1024 + 512] = u[2]; hp[j2 * 1024 + 544] = u[3];
            }
            fence_proxy_async();
            float m0 = s0 * (1.0f / 16), m1 = s1 * (1.0f / 16), q0 = 0.f, q1 = 0.f;
#pragma unroll
            for (int i = 0; i < 16; i++) {
                float d0 = v0[i] - m0, d1 = v1[i] - m1;
                q0 = fmaf(d0, d0, q0); q1 = fmaf(d1, d1, q1);
            }
#pragma unroll
            for (int st = 0; st < 2; st++) {
                float hn = st ? 16.f : 8.f;
                float om0 = __shfl_xor_sync(0xffffffffu, m0, 1 << st), oq0 = __shfl_xor_sync(0xffffffffu, q0, 1 << st);
                float om1 = __shfl_xor_sync(0xffffffffu, m1, 1 << st), oq1 = __shfl_xor_sync(0xffffffffu, q1, 1 << st);
                float d0 = om0 - m0, d1 = om1 - m1;
                q0 = q0 + oq0 + d0 * d0 * hn; q1 = q1 + oq1 + d1 * d1 * hn;
                m0 = 0.5f * (m0 + om0); m1 = 0.5f * (m1 + om1);
            }
            if (t == 0) {
                g_hstat[row * 8 + nt] = make_float2(m0, q0);
                g_hstat[(row + 8) * 8 + nt] = make_float2(m1, q1);
            }
            bar_arrive(1, 288);
            bar_sync(4, 256);
            TL(8);
        }
        uint32_t* gp = (uint32_t*)g_g + (((size_t)mb * 224 + nt * 28) * 16 + rgl) * 32 + lane;
        {
            float ag[64], au[64];
#pragma unroll 1
            for (int kb = 0; kb < 8; kb++) {
                const int s = kb % 3;
                if (!(kb & 1)) mbar_wait(bars + 8 * (B_HF + (kb >> 1)), 0);
                mbar_wait(bars + 8 * (B_BF + s), (kb / 3) & 1);
                if (warp == 4) TX(32 + kb);
                uint64_t ad = make_desc(sb + kb * 16384 + wgi * 1024, 2048, 128, 0);
                uint64_t bd = make_desc(sb + F_R2 + s * 32768, 4096, 512, 2);
                WG_FENCE();
#pragma unroll
                for (int k = 0; k < 4; k++) {
                    wgmma_ss_n128(ag, ad + k * 256, bd + k * 64, (kb | k) != 0);
                    wgmma_ss_n128(au, ad + k * 256, bd + 1024 + k * 64, (kb | k) != 0);
                }
                WG_COMMIT();
                if (kb > 0) {
                    wg_wait<1>();
                    if (lane == 0) mbar_arrive(bars + 8 * (B_BE + (kb - 1) % 3));
                }
            }
            wg_wait<0>();
            if (lane == 0) mbar_arrive(bars + 8 * (B_BE + 7 % 3));
            fence_regs(ag); fence_regs(au);
            TL(10);
            mbar_wait(bars + 8 * B_AUX, 0);
            ffn_epilogue<16, false>(ag, au, s_cs, 0, gp, 0, s_rs[rl], s_rs[rl + 8], lane);
        }
        uint32_t hr[16];
        {
            const uint32_t* hs = (const uint32_t*)(smem + nt * 16384) + rgl * 32 + lane;
#pragma unroll
            for (int j = 0; j < 8; j++) { hr[2 * j] = hs[j * 512]; hr[2 * j + 1] = hs[j * 512 + 32]; }
        }
        {
            float ag[48], au[48];
#pragma unroll 1
            for (int kb = 0; kb < 8; kb++) {
                const int it = 8 + kb, s = it % 3;
                mbar_wait(bars + 8 * (B_BF + s), (it / 3) & 1);
                if (warp == 4) TX(32 + it);
                uint64_t ad = make_desc(sb + kb * 16384 + wgi * 1024, 2048, 128, 0);
                uint64_t bd = make_desc(sb + F_R2 + s * 32768, 4096, 512, 2);
                WG_FENCE();
#pragma unroll
                for (int k = 0; k < 4; k++) {
                    wgmma_ss_n96(ag, ad + k * 256, bd + k * 64, (kb | k) != 0);
                    wgmma_ss_n96(au, ad + k * 256, bd + 1024 + k * 64, (kb | k) != 0);
                }
                WG_COMMIT();
                if (kb > 0) {
                    wg_wait<1>();
                    if (lane == 0) mbar_arrive(bars + 8 * (B_BE + (it - 1) % 3));
                }
            }
            wg_wait<0>();
            asm volatile("barrier.cluster.wait.acquire.aligned;" ::: "memory");
            if (lane == 0) {
                mbar_arrive(bars + 8 * B_BDONE);
                mbar_arrive_remote(mapa(bars + 8 * B_PRDY, 1 - r));
            }
            fence_regs(ag); fence_regs(au);
            TL(11);
            ffn_epilogue<12, false>(ag, au, s_cs, 128, gp + 16 * 512, 0, s_rs[rl], s_rs[rl + 8], lane);
            bar_arrive(2, 288);
            TL(12);
        }
        {
            float acc[64];
#pragma unroll 1
            for (int kb = 0; kb < 14; kb++) {
                const int s = kb % 6;
                mbar_wait(bars + 8 * (B_CF + s), (kb / 6) & 1);
                if (warp == 4) TX(96 + kb);
                uint64_t ad = make_desc(sb + s * 32768 + wgi * 1024, 2048, 128, 0);
                uint64_t bd = make_desc(sb + s * 32768 + 16384, 8192, 1024, 1);
                WG_FENCE();
#pragma unroll
                for (int k = 0; k < 4; k++) wgmma_ss_n128(acc, ad + k * 256, bd + k * 128, (kb | k) != 0);
                WG_COMMIT();
                if (kb > 0) {
                    wg_wait<1>();
                    if (lane == 0) mbar_arrive(bars + 8 * (B_CE + (kb - 1) % 6));
                }
            }
            wg_wait<0>();
            fence_regs(acc);
            TL(14);
            mbar_wait_cluster(bars + 8 * B_PRDY, 0);
            float o[32];
            if (r == 0) xchg<0>(acc, o, sb, smem, B_XC, ctid); else xchg<1>(acc, o, sb, smem, B_XC, ctid);
            TL(22);
            bar_sync(4, 256);
            const float a0 = s_rs[rl].x, a1 = s_rs[rl + 8].x;
            const float k0 = 0.5f * a0 * a0, k1 = 0.5f * a1 * a1;
            const int srow = wgi * 64 + ww * 16 + ((lane >> 3) & 1) * 8 + (lane & 7);
#pragma unroll
            for (int j2 = 0; j2 < 4; j2++) {
                uint32_t u[4];
#pragma unroll
                for (int jj = 0; jj < 2; jj++) {
                    const int j = 2 * j2 + jj;
                    u[2 * jj] = pack_bf16(fmaf(k0, o[4 * j], bf_lo(hr[2 * j])), fmaf(k0, o[4 * j + 1], bf_hi(hr[2 * j])));
                    u[2 * jj + 1] = pack_bf16(fmaf(k1, o[4 * j + 2], bf_lo(hr[2 * j + 1])), fmaf(k1, o[4 * j + 3], bf_hi(hr[2 * j + 1])));
                }
                const int chunk = 2 * j2 + (lane >> 4);
                stsm4(sb + srow * 128 + ((chunk ^ (lane & 7)) * 16), u[0], u[1], u[2], u[3]);
            }
            fence_proxy_async();
            bar_arrive(3, 288);
            TLDUMP;
        }
    }
}

typedef CUresult (*EncodeFn)(CUtensorMap*, CUtensorMapDataType, cuuint32_t, void*, const cuuint64_t*, const cuuint64_t*,
                             const cuuint32_t*, const cuuint32_t*, CUtensorMapInterleave, CUtensorMapSwizzle,
                             CUtensorMapL2promotion, CUtensorMapFloatOOBfill);

void encode(EncodeFn fn, CUtensorMap* m, const void* ptr, int rank, const cuuint64_t* dims, const cuuint64_t* strides,
            const cuuint32_t* box, CUtensorMapSwizzle swz) {
    cuuint32_t es[3] = {1, 1, 1};
    fn(m, CU_TENSOR_MAP_DATA_TYPE_BFLOAT16, rank, (void*)ptr, dims, strides, box, es, CU_TENSOR_MAP_INTERLEAVE_NONE, swz,
       CU_TENSOR_MAP_L2_PROMOTION_L2_256B, CU_TENSOR_MAP_FLOAT_OOB_FILL_NONE);
}

template <typename... KArgs, typename... Args>
void launch(void (*kern)(KArgs...), int grid, int block, int smem, bool pdl, Args... args) {
    cudaLaunchConfig_t cfg = {};
    cfg.gridDim = dim3(grid); cfg.blockDim = dim3(block); cfg.dynamicSmemBytes = smem;
    cfg.stream = cudaStreamPerThread;
    cudaLaunchAttribute at[1];
    at[0].id = cudaLaunchAttributeProgrammaticStreamSerialization;
    at[0].val.programmaticStreamSerializationAllowed = 1;
    cfg.attrs = at; cfg.numAttrs = pdl ? 1 : 0;
    cudaLaunchKernelEx(&cfg, kern, KArgs(args)...);
}

}

extern "C" void kernel_launch(void* const* d_in, const int* in_sizes, int n_in, void* d_out, int out_size) {
    const __nv_bfloat16* x = (const __nv_bfloat16*)d_in[0];
    const __nv_bfloat16* wqkv = (const __nv_bfloat16*)d_in[1];
    const __nv_bfloat16* wo = (const __nv_bfloat16*)d_in[2];
    const __nv_bfloat16* wgate = (const __nv_bfloat16*)d_in[4];
    const __nv_bfloat16* wup = (const __nv_bfloat16*)d_in[5];
    const __nv_bfloat16* wdown = (const __nv_bfloat16*)d_in[6];
    __nv_bfloat16* out = (__nv_bfloat16*)d_out;

    static CUtensorMap tm_x, tm_wqkv, tm_wo, tm_wg, tm_wu, tm_wd, tm_out;
    static const void* cached[7] = {nullptr, nullptr, nullptr, nullptr, nullptr, nullptr, nullptr};
    if (cached[0] != x || cached[1] != wqkv || cached[2] != wo || cached[3] != wgate || cached[4] != wup || cached[5] != wdown || cached[6] != out) {
        void* fp = nullptr;
        cudaDriverEntryPointQueryResult qr;
        cudaGetDriverEntryPoint("cuTensorMapEncodeTiled", &fp, cudaEnableDefault, &qr);
        EncodeFn fn = (EncodeFn)fp;
        { cuuint64_t d[2] = {512, 2048}, s[1] = {1024}; cuuint32_t b[2] = {64, 128};
          encode(fn, &tm_x, x, 2, d, s, b, CU_TENSOR_MAP_SWIZZLE_128B);
          encode(fn, &tm_out, out, 2, d, s, b, CU_TENSOR_MAP_SWIZZLE_128B); }
        { cuuint64_t d[3] = {64, 512, 24}, s[2] = {3072, 128}; cuuint32_t b[3] = {64, 64, 3};
          encode(fn, &tm_wqkv, wqkv, 3, d, s, b, CU_TENSOR_MAP_SWIZZLE_128B); }
        { cuuint64_t d[2] = {512, 512}, s[1] = {1024}; cuuint32_t b[2] = {64, 64};
          encode(fn, &tm_wo, wo, 2, d, s, b, CU_TENSOR_MAP_SWIZZLE_128B); }
        { cuuint64_t d[2] = {1792, 512}, s[1] = {3584}; cuuint32_t b[2] = {32, 64};
          encode(fn, &tm_wg, wgate, 2, d, s, b, CU_TENSOR_MAP_SWIZZLE_64B);
          encode(fn, &tm_wu, wup, 2, d, s, b, CU_TENSOR_MAP_SWIZZLE_64B); }
        { cuuint64_t d[2] = {512, 1792}, s[1] = {1024}; cuuint32_t b[2] = {64, 64};
          encode(fn, &tm_wd, wdown, 2, d, s, b, CU_TENSOR_MAP_SWIZZLE_128B); }
        cudaFuncSetAttribute(qkv_kernel, cudaFuncAttributeMaxDynamicSharedMemorySize, F_SMEM);
        cudaFuncSetAttribute(qkv_kernel, cudaFuncAttributePreferredSharedMemoryCarveout, 100);
        cudaFuncSetAttribute(attn_kernel, cudaFuncAttributeMaxDynamicSharedMemorySize, F_SMEM);
        cudaFuncSetAttribute(attn_kernel, cudaFuncAttributePreferredSharedMemoryCarveout, 100);
        cudaFuncSetAttribute(tail_kernel, cudaFuncAttributeMaxDynamicSharedMemorySize, F_SMEM);
        cudaFuncSetAttribute(tail_kernel, cudaFuncAttributePreferredSharedMemoryCarveout, 100);
        cached[0] = x; cached[1] = wqkv; cached[2] = wo; cached[3] = wgate; cached[4] = wup; cached[5] = wdown; cached[6] = out;
    }
    launch(qkv_kernel, 128, 384, F_SMEM, false, tm_x, tm_wqkv, x, wqkv);
    launch(attn_kernel, 132, 512, F_SMEM, true, wgate, wup, wo, wdown);
    launch(tail_kernel, 128, 384, F_SMEM, true, tm_wo, tm_wg, tm_wu, tm_wd, tm_out, x);
}
```

```cpp
#include <cuda_runtime.h>
#include <cuda_bf16.h>
#include <cuda.h>
#include <stdint.h>

#define K1_DIRECT
namespace {

constexpr int S_LEN = 2048, DM = 512, NH = 32, FF = 1792;

__device__ __align__(1024) __nv_bfloat16 g_qkv[3 * NH * S_LEN * 16];
__device__ __align__(1024) __nv_bfloat16 g_ao[S_LEN * DM];
__device__ __align__(1024) __nv_bfloat16 g_h[S_LEN * DM];
__device__ __align__(1024) __nv_bfloat16 g_g[S_LEN * FF];
__device__ __align__(16) float2 g_rowstat1[S_LEN];
__device__ float g_cs1_part[16 * 1536];
__device__ unsigned int g_cnt[32];
__device__ unsigned int g_cnt2[64];
__device__ float g_nrm[3 * NH * 128];
__device__ float2 g_hstat[S_LEN * 8];
__device__ float g_cs2[2 * FF];

#define TLDECL
#define TL(slot)
#define TLDUMP
#define TX(slot)
__device__ __forceinline__ uint32_t smem_u32(const void* p) { return (uint32_t)__cvta_generic_to_shared(p); }
__device__ __forceinline__ void mbar_init(uint32_t a, int c) { asm volatile("mbarrier.init.shared.b64 [%0], %1;" :: "r"(a), "r"(c)); }
__device__ __forceinline__ void mbar_expect(uint32_t a, int bytes) { asm volatile("mbarrier.arrive.expect_tx.shared.b64 _, [%0], %1;" :: "r"(a), "r"(bytes) : "memory"); }
__device__ __forceinline__ void mbar_arrive(uint32_t a) { asm volatile("mbarrier.arrive.shared.b64 _, [%0];" :: "r"(a) : "memory"); }
__device__ __forceinline__ void mbar_wait(uint32_t a, int parity) {
    uint32_t done;
    int it = 0;
    do {
        asm volatile("{\n.reg .pred p;\nmbarrier.try_wait.parity.shared.b64 p, [%1], %2;\nselp.u32 %0, 1, 0, p;\n}"
                     : "=r"(done) : "r"(a), "r"(parity) : "memory");
        if (++it > (1 << 24)) __trap();
    } while (!done);
}
__device__ __forceinline__ void bulk_g2s(uint32_t dst, const void* src, int bytes, uint32_t bar) {
    asm volatile("cp.async.bulk.shared::cluster.global.mbarrier::complete_tx::bytes [%0], [%1], %2, [%3];"
                 :: "r"(dst), "l"(src), "r"(bytes), "r"(bar) : "memory");
}
__device__ __forceinline__ void tma2d(uint32_t dst, const CUtensorMap* m, int c0, int c1, uint32_t bar) {
    asm volatile("cp.async.bulk.tensor.2d.shared::cluster.global.mbarrier::complete_tx::bytes [%0], [%1, {%3, %4}], [%2];"
                 :: "r"(dst), "l"(m), "r"(bar), "r"(c0), "r"(c1) : "memory");
}
__device__ __forceinline__ void tma3d(uint32_t dst, const CUtensorMap* m, int c0, int c1, int c2, uint32_t bar) {
    asm volatile("cp.async.bulk.tensor.3d.shared::cluster.global.mbarrier::complete_tx::bytes [%0], [%1, {%3, %4, %5}], [%2];"
                 :: "r"(dst), "l"(m), "r"(bar), "r"(c0), "r"(c1), "r"(c2) : "memory");
}
__device__ __forceinline__ void prefetch_tmap(const CUtensorMap* m) { asm volatile("prefetch.tensormap [%0];" :: "l"(m) : "memory"); }
__device__ __forceinline__ void pdl_wait() { asm volatile("griddepcontrol.wait;" ::: "memory"); }
__device__ __forceinline__ void pdl_launch() { asm volatile("griddepcontrol.launch_dependents;" ::: "memory"); }
__device__ __forceinline__ void fence_barrier_init() { asm volatile("fence.mbarrier_init.release.cluster;" ::: "memory"); }
__device__ __forceinline__ void fence_proxy_async() { asm volatile("fence.proxy.async.shared::cta;" ::: "memory"); }
__device__ __forceinline__ uint64_t make_desc(uint32_t saddr, uint32_t lbo, uint32_t sbo, uint32_t swz) {
    return (uint64_t)((saddr & 0x3FFFF) >> 4) | ((uint64_t)((lbo & 0x3FFFF) >> 4) << 16) |
           ((uint64_t)((sbo & 0x3FFFF) >> 4) << 32) | ((uint64_t)swz << 62);
}
#define WG_FENCE() asm volatile("wgmma.fence.sync.aligned;" ::: "memory")
#define WG_COMMIT() asm volatile("wgmma.commit_group.sync.aligned;" ::: "memory")
template <int N> __device__ __forceinline__ void wg_wait() { asm volatile("wgmma.wait_group.sync.aligned %0;" :: "n"(N) : "memory"); }
template <int N> __device__ __forceinline__ void fence_regs(float (&d)[N]) {
#pragma unroll
    for (int i = 0; i < N; i++) asm volatile("" : "+f"(d[i]) :: "memory");
}
__device__ __forceinline__ float ex2f(float x) { float y; asm("ex2.approx.ftz.f32 %0, %1;" : "=f"(y) : "f"(x)); return y; }
__device__ __forceinline__ float tanh_fast(float x) { float y; asm("tanh.approx.f32 %0, %1;" : "=f"(y) : "f"(x)); return y; }
__device__ __forceinline__ uint32_t pack_bf16(float lo, float hi) { uint32_t r; asm("cvt.rn.bf16x2.f32 %0, %1, %2;" : "=r"(r) : "f"(hi), "f"(lo)); return r; }
__device__ __forceinline__ float bf_lo(uint32_t u) { return __uint_as_float(u << 16); }
__device__ __forceinline__ float bf_hi(uint32_t u) { return __uint_as_float(u & 0xFFFF0000u); }
__device__ __forceinline__ uint32_t hfma2(uint32_t a, uint32_t b, uint32_t c) { uint32_t r; asm("fma.rn.f16x2 %0, %1, %2, %3;" : "=r"(r) : "r"(a), "r"(b), "r"(c)); return r; }
__device__ __forceinline__ uint32_t hmul2(uint32_t a, uint32_t b) { uint32_t r; asm("mul.rn.f16x2 %0, %1, %2;" : "=r"(r) : "r"(a), "r"(b)); return r; }
__device__ __forceinline__ unsigned int ld_acquire(const unsigned int* p) { unsigned int v; asm volatile("ld.acquire.gpu.u32 %0, [%1];" : "=r"(v) : "l"(p) : "memory"); return v; }
__device__ __forceinline__ void red_release(unsigned int* p) { asm volatile("red.release.gpu.global.add.u32 [%0], 1;" :: "l"(p) : "memory"); }
__device__ __forceinline__ void stsm4(uint32_t addr, uint32_t a, uint32_t b, uint32_t c, uint32_t d) {
    asm volatile("stmatrix.sync.aligned.m8n8.x4.shared.b16 [%0], {%1,%2,%3,%4};" :: "r"(addr), "r"(a), "r"(b), "r"(c), "r"(d) : "memory");
}
__device__ __forceinline__ void bulk_s2g(void* dst, uint32_t src, int bytes) {
    asm volatile("cp.async.bulk.global.shared::cta.bulk_group [%0], [%1], %2;" :: "l"(dst), "r"(src), "r"(bytes) : "memory");
}
__device__ __forceinline__ void bulk_commit() { asm volatile("cp.async.bulk.commit_group;" ::: "memory"); }
__device__ __forceinline__ void bulk_wait_all() { asm volatile("cp.async.bulk.wait_group 0;" ::: "memory"); }
__device__ __forceinline__ void bulk_wait_read() { asm volatile("cp.async.bulk.wait_group.read 0;" ::: "memory"); }
__device__ __forceinline__ void bar_sync(int id, int n) { asm volatile("bar.sync %0, %1;" :: "r"(id), "r"(n) : "memory"); }
__device__ __forceinline__ void bar_arrive(int id, int n) { asm volatile("bar.arrive %0, %1;" :: "r"(id), "r"(n) : "memory"); }
__device__ __forceinline__ float warp_sum(float v) {
#pragma unroll
    for (int o = 16; o; o >>= 1) v += __shfl_xor_sync(0xffffffffu, v, o);
    return v;
}
__device__ __forceinline__ float warp_max(float v) {
#pragma unroll
    for (int o = 16; o; o >>= 1) v = fmaxf(v, __shfl_xor_sync(0xffffffffu, v, o));
    return v;
}

__device__ __forceinline__ void wgmma_ss_n64(float (&d)[32], uint64_t adesc, uint64_t bdesc, int scale_d) {
    asm volatile("{\n.reg .pred p;\nsetp.ne.b32 p, %34, 0;\n"
      "wgmma.mma_async.sync.aligned.m64n64k16.f32.bf16.bf16 {%0,%1,%2,%3,%4,%5,%6,%7,%8,%9,%10,%11,%12,%13,%14,%15,%16,%17,%18,%19,%20,%21,%22,%23,%24,%25,%26,%27,%28,%29,%30,%31}, %32, %33, p, 1, 1, 0, 1;\n}"
      : "+f"(d[0]), "+f"(d[1]), "+f"(d[2]), "+f"(d[3]), "+f"(d[4]), "+f"(d[5]), "+f"(d[6]), "+f"(d[7]), "+f"(d[8]), "+f"(d[9]), "+f"(d[10]), "+f"(d[11]), "+f"(d[12]), "+f"(d[13]), "+f"(d[14]), "+f"(d[15]), "+f"(d[16]), "+f"(d[17]), "+f"(d[18]), "+f"(d[19]), "+f"(d[20]), "+f"(d[21]), "+f"(d[22]), "+f"(d[23]), "+f"(d[24]), "+f"(d[25]), "+f"(d[26]), "+f"(d[27]), "+f"(d[28]), "+f"(d[29]), "+f"(d[30]), "+f"(d[31])
      : "l"(adesc), "l"(bdesc), "r"(scale_d));
}
__device__ __forceinline__ void wgmma_ss_n96(float (&d)[48], uint64_t adesc, uint64_t bdesc, int scale_d) {
    asm volatile("{\n.reg .pred p;\nsetp.ne.b32 p, %50, 0;\n"
      "wgmma.mma_async.sync.aligned.m64n96k16.f32.bf16.bf16 {%0,%1,%2,%3,%4,%5,%6,%7,%8,%9,%10,%11,%12,%13,%14,%15,%16,%17,%18,%19,%20,%21,%22,%23,%24,%25,%26,%27,%28,%29,%30,%31,%32,%33,%34,%35,%36,%37,%38,%39,%40,%41,%42,%43,%44,%45,%46,%47}, %48, %49, p, 1, 1, 0, 1;\n}"
      : "+f"(d[0]), "+f"(d[1]), "+f"(d[2]), "+f"(d[3]), "+f"(d[4]), "+f"(d[5]), "+f"(d[6]), "+f"(d[7]), "+f"(d[8]), "+f"(d[9]), "+f"(d[10]), "+f"(d[11]), "+f"(d[12]), "+f"(d[13]), "+f"(d[14]), "+f"(d[15]), "+f"(d[16]), "+f"(d[17]), "+f"(d[18]), "+f"(d[19]), "+f"(d[20]), "+f"(d[21]), "+f"(d[22]), "+f"(d[23]), "+f"(d[24]), "+f"(d[25]), "+f"(d[26]), "+f"(d[27]), "+f"(d[28]), "+f"(d[29]), "+f"(d[30]), "+f"(d[31]), "+f"(d[32]), "+f"(d[33]), "+f"(d[34]), "+f"(d[35]), "+f"(d[36]), "+f"(d[37]), "+f"(d[38]), "+f"(d[39]), "+f"(d[40]), "+f"(d[41]), "+f"(d[42]), "+f"(d[43]), "+f"(d[44]), "+f"(d[45]), "+f"(d[46]), "+f"(d[47])
      : "l"(adesc), "l"(bdesc), "r"(scale_d));
}
__device__ __forceinline__ void wgmma_ss_n128(float (&d)[64], uint64_t adesc, uint64_t bdesc, int scale_d) {
    asm volatile("{\n.reg .pred p;\nsetp.ne.b32 p, %66, 0;\n"
      "wgmma.mma_async.sync.aligned.m64n128k16.f32.bf16.bf16 {%0,%1,%2,%3,%4,%5,%6,%7,%8,%9,%10,%11,%12,%13,%14,%15,%16,%17,%18,%19,%20,%21,%22,%23,%24,%25,%26,%27,%28,%29,%30,%31,%32,%33,%34,%35,%36,%37,%38,%39,%40,%41,%42,%43,%44,%45,%46,%47,%48,%49,%50,%51,%52,%53,%54,%55,%56,%57,%58,%59,%60,%61,%62,%63}, %64, %65, p, 1, 1, 0, 1;\n}"
      : "+f"(d[0]), "+f"(d[1]), "+f"(d[2]), "+f"(d[3]), "+f"(d[4]), "+f"(d[5]), "+f"(d[6]), "+f"(d[7]), "+f"(d[8]), "+f"(d[9]), "+f"(d[10]), "+f"(d[11]), "+f"(d[12]), "+f"(d[13]), "+f"(d[14]), "+f"(d[15]), "+f"(d[16]), "+f"(d[17]), "+f"(d[18]), "+f"(d[19]), "+f"(d[20]), "+f"(d[21]), "+f"(d[22]), "+f"(d[23]), "+f"(d[24]), "+f"(d[25]), "+f"(d[26]), "+f"(d[27]), "+f"(d[28]), "+f"(d[29]), "+f"(d[30]), "+f"(d[31]), "+f"(d[32]), "+f"(d[33]), "+f"(d[34]), "+f"(d[35]), "+f"(d[36]), "+f"(d[37]), "+f"(d[38]), "+f"(d[39]), "+f"(d[40]), "+f"(d[41]), "+f"(d[42]), "+f"(d[43]), "+f"(d[44]), "+f"(d[45]), "+f"(d[46]), "+f"(d[47]), "+f"(d[48]), "+f"(d[49]), "+f"(d[50]), "+f"(d[51]), "+f"(d[52]), "+f"(d[53]), "+f"(d[54]), "+f"(d[55]), "+f"(d[56]), "+f"(d[57]), "+f"(d[58]), "+f"(d[59]), "+f"(d[60]), "+f"(d[61]), "+f"(d[62]), "+f"(d[63])
      : "l"(adesc), "l"(bdesc), "r"(scale_d));
}
__device__ __forceinline__ void wgmma_ss_n192(float (&d)[96], uint64_t adesc, uint64_t bdesc, int scale_d) {
    asm volatile("{\n.reg .pred p;\nsetp.ne.b32 p, %98, 0;\n"
      "wgmma.mma_async.sync.aligned.m64n192k16.f32.bf16.bf16 {%0,%1,%2,%3,%4,%5,%6,%7,%8,%9,%10,%11,%12,%13,%14,%15,%16,%17,%18,%19,%20,%21,%22,%23,%24,%25,%26,%27,%28,%29,%30,%31,%32,%33,%34,%35,%36,%37,%38,%39,%40,%41,%42,%43,%44,%45,%46,%47,%48,%49,%50,%51,%52,%53,%54,%55,%56,%57,%58,%59,%60,%61,%62,%63,%64,%65,%66,%67,%68,%69,%70,%71,%72,%73,%74,%75,%76,%77,%78,%79,%80,%81,%82,%83,%84,%85,%86,%87,%88,%89,%90,%91,%92,%93,%94,%95}, %96, %97, p, 1, 1, 0, 1;\n}"
      : "+f"(d[0]), "+f"(d[1]), "+f"(d[2]), "+f"(d[3]), "+f"(d[4]), "+f"(d[5]), "+f"(d[6]), "+f"(d[7]), "+f"(d[8]), "+f"(d[9]), "+f"(d[10]), "+f"(d[11]), "+f"(d[12]), "+f"(d[13]), "+f"(d[14]), "+f"(d[15]), "+f"(d[16]), "+f"(d[17]), "+f"(d[18]), "+f"(d[19]), "+f"(d[20]), "+f"(d[21]), "+f"(d[22]), "+f"(d[23]), "+f"(d[24]), "+f"(d[25]), "+f"(d[26]), "+f"(d[27]), "+f"(d[28]), "+f"(d[29]), "+f"(d[30]), "+f"(d[31]), "+f"(d[32]), "+f"(d[33]), "+f"(d[34]), "+f"(d[35]), "+f"(d[36]), "+f"(d[37]), "+f"(d[38]), "+f"(d[39]), "+f"(d[40]), "+f"(d[41]), "+f"(d[42]), "+f"(d[43]), "+f"(d[44]), "+f"(d[45]), "+f"(d[46]), "+f"(d[47]), "+f"(d[48]), "+f"(d[49]), "+f"(d[50]), "+f"(d[51]), "+f"(d[52]), "+f"(d[53]), "+f"(d[54]), "+f"(d[55]), "+f"(d[56]), "+f"(d[57]), "+f"(d[58]), "+f"(d[59]), "+f"(d[60]), "+f"(d[61]), "+f"(d[62]), "+f"(d[63]), "+f"(d[64]), "+f"(d[65]), "+f"(d[66]), "+f"(d[67]), "+f"(d[68]), "+f"(d[69]), "+f"(d[70]), "+f"(d[71]), "+f"(d[72]), "+f"(d[73]), "+f"(d[74]), "+f"(d[75]), "+f"(d[76]), "+f"(d[77]), "+f"(d[78]), "+f"(d[79]), "+f"(d[80]), "+f"(d[81]), "+f"(d[82]), "+f"(d[83]), "+f"(d[84]), "+f"(d[85]), "+f"(d[86]), "+f"(d[87]), "+f"(d[88]), "+f"(d[89]), "+f"(d[90]), "+f"(d[91]), "+f"(d[92]), "+f"(d[93]), "+f"(d[94]), "+f"(d[95])
      : "l"(adesc), "l"(bdesc), "r"(scale_d));
}
__device__ __forceinline__ void qk_wgmma_n64(float (&d)[32], const uint32_t (&a)[4], uint64_t desc) {
    asm volatile("wgmma.mma_async.sync.aligned.m64n64k16.f32.bf16.bf16 {%0,%1,%2,%3,%4,%5,%6,%7,%8,%9,%10,%11,%12,%13,%14,%15,%16,%17,%18,%19,%20,%21,%22,%23,%24,%25,%26,%27,%28,%29,%30,%31}, {%32,%33,%34,%35}, %36, 0, 1, 1, 0;"
      : "=f"(d[0]), "=f"(d[1]), "=f"(d[2]), "=f"(d[3]), "=f"(d[4]), "=f"(d[5]), "=f"(d[6]), "=f"(d[7]), "=f"(d[8]), "=f"(d[9]), "=f"(d[10]), "=f"(d[11]), "=f"(d[12]), "=f"(d[13]), "=f"(d[14]), "=f"(d[15]), "=f"(d[16]), "=f"(d[17]), "=f"(d[18]), "=f"(d[19]), "=f"(d[20]), "=f"(d[21]), "=f"(d[22]), "=f"(d[23]), "=f"(d[24]), "=f"(d[25]), "=f"(d[26]), "=f"(d[27]), "=f"(d[28]), "=f"(d[29]), "=f"(d[30]), "=f"(d[31])
      : "r"(a[0]), "r"(a[1]), "r"(a[2]), "r"(a[3]), "l"(desc));
}

__device__ __forceinline__ void pv_wgmma(float (&d)[12], uint32_t a0, uint32_t a1, uint32_t a2, uint32_t a3, uint64_t desc) {
    asm volatile("wgmma.mma_async.sync.aligned.m64n24k16.f32.bf16.bf16 {%0,%1,%2,%3,%4,%5,%6,%7,%8,%9,%10,%11}, {%12,%13,%14,%15}, %16, 1, 1, 1, 1;"
      : "+f"(d[0]), "+f"(d[1]), "+f"(d[2]), "+f"(d[3]), "+f"(d[4]), "+f"(d[5]), "+f"(d[6]), "+f"(d[7]), "+f"(d[8]), "+f"(d[9]), "+f"(d[10]), "+f"(d[11])
      : "r"(a0), "r"(a1), "r"(a2), "r"(a3), "l"(desc));
}

__device__ __forceinline__ void tile_of(int bid, int& mb, int& nt) {
    int grp = bid >> 4, in = bid & 15;
    mb = (grp >> 1) * 4 + (in >> 2);
    nt = (grp & 1) * 4 + (in & 3);
}

constexpr int K1_STAGES = 5, K1_STAGE = 16384 + 24576;
constexpr int K1_BAR = K1_STAGES * K1_STAGE, K1_RS = K1_BAR + 128, K1_CS = K1_RS + 1024, K1_SMEM = K1_CS + 768;

__device__ __forceinline__ float2 row_stats_regs(uint4 a, uint4 b) {
    float v[16];
    v[0] = bf_lo(a.x); v[1] = bf_hi(a.x); v[2] = bf_lo(a.y); v[3] = bf_hi(a.y);
    v[4] = bf_lo(a.z); v[5] = bf_hi(a.z); v[6] = bf_lo(a.w); v[7] = bf_hi(a.w);
    v[8] = bf_lo(b.x); v[9] = bf_hi(b.x); v[10] = bf_lo(b.y); v[11] = bf_hi(b.y);
    v[12] = bf_lo(b.z); v[13] = bf_hi(b.z); v[14] = bf_lo(b.w); v[15] = bf_hi(b.w);
    float s = 0.f;
#pragma unroll
    for (int i = 0; i < 16; i++) s += v[i];
    float mean = warp_sum(s) * (1.0f / DM);
    float q = 0.f;
#pragma unroll
    for (int i = 0; i < 16; i++) { float d = v[i] - mean; q = fmaf(d, d, q); }
    float var = warp_sum(q) * (1.0f / DM);
    float rstd = rsqrtf(var + 1e-5f);
    return make_float2(rstd, -mean * rstd);
}
__device__ __forceinline__ float2 row_stats_x(const __nv_bfloat16* x, int row, int lane) {
    const uint4* p = (const uint4*)(x + (size_t)row * DM);
    return row_stats_regs(__ldg(p + lane), __ldg(p + 32 + lane));
}
__device__ __forceinline__ void colsum8(const __nv_bfloat16* w, int ld, int col, int k0, int nk, float (&s)[8]) {
#pragma unroll
    for (int i = 0; i < 8; i++) s[i] = 0.f;
    for (int k = k0; k < k0 + nk; k += 8) {
        uint4 u[8];
#pragma unroll
        for (int i = 0; i < 8; i++) u[i] = __ldg((const uint4*)(w + (size_t)(k + i) * ld + col));
#pragma unroll
        for (int i = 0; i < 8; i++) {
            s[0] += bf_lo(u[i].x); s[1] += bf_hi(u[i].x); s[2] += bf_lo(u[i].y); s[3] += bf_hi(u[i].y);
            s[4] += bf_lo(u[i].z); s[5] += bf_hi(u[i].z); s[6] += bf_lo(u[i].w); s[7] += bf_hi(u[i].w);
        }
    }
}
__device__ __forceinline__ bool wait_count(const unsigned int* p, unsigned int target, int lane) {
    int ok = 1;
    if (lane == 0) {
        int it = 0;
        while (ld_acquire(p) < target) { if (++it > (1 << 18)) { ok = 0; break; } }
    }
    ok = __shfl_sync(0xffffffffu, ok, 0);
    return ok != 0;
}

__global__ void __launch_bounds__(384, 1)
qkv_kernel(const __grid_constant__ CUtensorMap tm_x, const __grid_constant__ CUtensorMap tm_w,
           const __nv_bfloat16* __restrict__ x, const __nv_bfloat16* __restrict__ wqkv) {
    extern __shared__ __align__(1024) unsigned char smem[];
    const uint32_t sb = smem_u32(smem);
    const int tid = threadIdx.x, warp = __shfl_sync(0xffffffffu, tid >> 5, 0), lane = tid & 31;
    TLDECL
    TL(0);
    int mb, nt;
    tile_of(blockIdx.x, mb, nt);
    const uint32_t full = sb + K1_BAR, empty = full + 40, auxb = full + 80;
    if (tid == 0) {
        prefetch_tmap(&tm_x); prefetch_tmap(&tm_w);
        for (int i = 0; i < K1_STAGES; i++) { mbar_init(full + 8 * i, 1); mbar_init(empty + 8 * i, 8); }
        mbar_init(auxb, 3);
        fence_barrier_init();
    }
    __syncthreads();
    pdl_launch();
    if (warp == 0) {
        if (blockIdx.x == 0) { g_cnt2[lane] = 0; g_cnt2[32 + lane] = 0; }
        if (lane == 0) {
            for (int kb = 0; kb < 8; kb++) {
                int s = kb % K1_STAGES;
                if (kb >= K1_STAGES) mbar_wait(empty + 8 * s, 0);
                mbar_expect(full + 8 * s, K1_STAGE);
                tma2d(sb + s * K1_STAGE, &tm_x, kb * 64, mb * 128, full + 8 * s);
                tma3d(sb + s * K1_STAGE + 16384, &tm_w, 0, kb * 64, nt * 3, full + 8 * s);
            }
        }
    } else if (warp < 4) {
        float2* s_rs = (float2*)(smem + K1_RS);
        float* s_cs = (float*)(smem + K1_CS);
        if (warp < 3) {
            const int r0 = mb * 128 + nt * 16 + (warp - 1) * 8;
            uint4 u[16];
#pragma unroll
            for (int i = 0; i < 8; i++) {
                const uint4* p = (const uint4*)(x + (size_t)(r0 + i) * DM);
                u[2 * i] = __ldg(p + lane); u[2 * i + 1] = __ldg(p + 32 + lane);
            }
            float2 mine = make_float2(0.f, 0.f);
#pragma unroll
            for (int i = 0; i < 8; i++) {
                float2 st = row_stats_regs(u[2 * i], u[2 * i + 1]);
                if (lane == i) mine = st;
            }
            if (lane < 8) g_rowstat1[r0 + lane] = mine;
            __syncwarp();
            if (lane == 0) red_release(&g_cnt[mb]);
        } else {
            uint4 u[24];
#pragma unroll
            for (int c = 0; c < 3; c++)
#pragma unroll
                for (int i = 0; i < 8; i++)
                    u[c * 8 + i] = __ldg((const uint4*)(wqkv + (size_t)(mb * 32 + (lane >> 3) * 8 + i) * 1536 + nt * 192 + (c * 8 + (lane & 7)) * 8));
#pragma unroll
            for (int c = 0; c < 3; c++) {
                float cs[8];
#pragma unroll
                for (int i = 0; i < 8; i++) cs[i] = 0.f;
#pragma unroll
                for (int i = 0; i < 8; i++) {
                    const uint4 w = u[c * 8 + i];
                    cs[0] += bf_lo(w.x); cs[1] += bf_hi(w.x); cs[2] += bf_lo(w.y); cs[3] += bf_hi(w.y);
                    cs[4] += bf_lo(w.z); cs[5] += bf_hi(w.z); cs[6] += bf_lo(w.w); cs[7] += bf_hi(w.w);
                }
#pragma unroll
                for (int i = 0; i < 8; i++) {
                    cs[i] += __shfl_xor_sync(0xffffffffu, cs[i], 8);
                    cs[i] += __shfl_xor_sync(0xffffffffu, cs[i], 16);
                }
                if (lane < 8) {
                    float4* d = (float4*)(g_cs1_part + mb * 1536 + nt * 192 + (c * 8 + lane) * 8);
                    d[0] = make_float4(cs[0], cs[1], cs[2], cs[3]);
                    d[1] = make_float4(cs[4], cs[5], cs[6], cs[7]);
                }
            }
            __syncwarp();
            if (lane == 0) red_release(&g_cnt[16 + nt]);
        }
        TX(8 + warp);
        if (warp == 1) {
            if (wait_count(&g_cnt[mb], 16, lane)) {
#pragma unroll
                for (int i = 0; i < 4; i++) s_rs[lane + 32 * i] = __ldcg(&g_rowstat1[mb * 128 + lane + 32 * i]);
            } else {
                for (int i = 0; i < 128; i++) {
                    float2 st = row_stats_x(x, mb * 128 + i, lane);
                    if (lane == 0) s_rs[i] = st;
                }
            }
        } else {
            int c0 = (warp - 2) * 96;
            if (wait_count(&g_cnt[16 + nt], 16, lane)) {
#pragma unroll
                for (int i = 0; i < 3; i++) {
                    float s = 0.f;
#pragma unroll
                    for (int p = 0; p < 16; p++) s += __ldcg(&g_cs1_part[p * 1536 + nt * 192 + c0 + lane + 32 * i]);
                    s_cs[c0 + lane + 32 * i] = s;
                }
            } else if (lane < 12) {
                float s[8];
                colsum8(wqkv, 1536, nt * 192 + c0 + lane * 8, 0, 512, s);
#pragma unroll
                for (int i = 0; i < 8; i++) s_cs[c0 + lane * 8 + i] = s[i];
            }
        }
        __syncwarp();
        TX(12 + warp);
        if (lane == 0) mbar_arrive(auxb);
        bar_sync(2, 256 + 96);
        const int a = tid - 32;
        {
            const int hh = a >> 3, w = a & 7;
            const float4* p = (const float4*)(smem + 49152) + (hh * 256 + w * 32) / 2;
            float m = 0.f;
#pragma unroll
            for (int i = 0; i < 8; i++) {
                const int ii = (i + a) & 7;
                float4 u = p[2 * ii], v = p[2 * ii + 1];
                float n0 = u.x + u.z + v.x + v.z, n1 = u.y + u.w + v.y + v.w;
                if (!(n0 <= 3.0e38f) || !(n1 <= 3.0e38f)) m = __int_as_float(0x7f800000);
                m = fmaxf(m, fmaxf(n0, n1));
            }
            const int col0 = nt * 192 + hh * 16;
            g_nrm[((col0 >> 9) * NH + ((col0 & 511) >> 4)) * 128 + mb * 8 + w] = m;
        }
        if (a < 24) bulk_wait_all();
        TL(27);
        TLDUMP;
    } else {
        const int wgi = (warp >> 2) - 1, ww = warp & 3;
        float acc[96];
#pragma unroll 1
        for (int kb = 0; kb < 8; kb++) {
            int s = kb % K1_STAGES;
            mbar_wait(full + 8 * s, (kb / K1_STAGES) & 1);
            if (warp == 4) TX(kb);
            uint64_t ad = make_desc(sb + s * K1_STAGE + wgi * 8192, 16, 1024, 1);
            uint64_t bd = make_desc(sb + s * K1_STAGE + 16384, 8192, 1024, 1);
            WG_FENCE();
#pragma unroll
            for (int k = 0; k < 4; k++) wgmma_ss_n192(acc, ad + k * 2, bd + k * 128, (kb | k) != 0);
            WG_COMMIT();
            if (kb > 0) {
                wg_wait<1>();
                if (lane == 0) mbar_arrive(empty + 8 * ((kb - 1) % K1_STAGES));
            }
        }
        wg_wait<0>();
        fence_regs(acc);
        TL(1);
        if (warp == 4) TX(16);
        mbar_wait(auxb, 0);
        if (warp == 4) TX(17);
        bar_sync(1, 256);
        const float2* s_rs = (const float2*)(smem + K1_RS);
        const float* s_cs = (const float*)(smem + K1_CS);
        const int g = lane >> 2, t = lane & 3;
        const int rl = wgi * 64 + ww * 16 + g;
        const float2 st0 = s_rs[rl], st1 = s_rs[rl + 8];
        const float QS = 0.25f * 1.4426950408889634f;
        const uint32_t stg = sb + ((lane >> 4) * 16 + wgi * 8 + ww * 2 + ((lane >> 3) & 1)) * 128 + (lane & 7) * 16;
        float2* s_np = (float2*)(smem + 49152) + (warp - 4) * 32 + lane;
#pragma unroll
        for (int hh = 0; hh < 12; hh++) {
            const int which = (nt * 192 + hh * 16) >> 9;
            const float sc = (which == 0) ? QS : 1.0f;
            const float a0 = st0.x * sc, b0 = st0.y * sc, a1 = st1.x * sc, b1 = st1.y * sc;
            const float2 c0 = *(const float2*)(s_cs + 16 * hh + 2 * t), c1 = *(const float2*)(s_cs + 16 * hh + 8 + 2 * t);
            const float* a = acc + 8 * hh;
            float v0 = fmaf(a0, a[0], b0 * c0.x), v1 = fmaf(a0, a[1], b0 * c0.y), v2 = fmaf(a1, a[2], b1 * c0.x), v3 = fmaf(a1, a[3], b1 * c0.y);
            float v4 = fmaf(a0, a[4], b0 * c1.x), v5 = fmaf(a0, a[5], b0 * c1.y), v6 = fmaf(a1, a[6], b1 * c1.x), v7 = fmaf(a1, a[7], b1 * c1.y);
            {
                const int head = ((nt * 192 + hh * 16) & 511) >> 4;
                uint32_t* o = (uint32_t*)g_qkv + ((size_t)((which * NH + head) * 2) * 256 + mb * 16 + wgi * 8 + ww * 2) * 32 + lane;
                o[0] = pack_bf16(v0, v1); o[32] = pack_bf16(v2, v3); o[8192] = pack_bf16(v4, v5); o[8192 + 32] = pack_bf16(v6, v7);
            }
            s_np[hh * 256] = make_float2(fmaf(v0, v0, fmaf(v1, v1, fmaf(v4, v4, v5 * v5))), fmaf(v2, v2, fmaf(v3, v3, fmaf(v6, v6, v7 * v7))));
        }
        fence_proxy_async();
        bar_arrive(2, 256 + 96);
        TL(2);
        TLDUMP;
    }
}

constexpr int AT_K = 0, AT_V = 65536, AT_ONES = 131072, AT_BAR = 163840, AT_SMEM = AT_BAR + 128;
#define POLY_MASK 0xAD6A

__device__ __forceinline__ uint32_t exp2_pair_poly(float x0, float x1) {
    uint32_t t0 = __float_as_uint(x0 + 32895.0f);
    uint32_t t1 = __float_as_uint(x1 + 32895.0f);
    uint32_t gd = __byte_perm(t0, t1, 0x6420);
    uint32_t wm = __byte_perm(t0, t1, 0x5612);
    uint32_t v = hfma2(gd, 0x71477147u, 0x354f354fu);
    uint32_t z = hmul2(v, gd);
    return (wm >> 1) + z;
}
__device__ __forceinline__ uint32_t exp2_pair_mufu(float x0, float x1) { return pack_bf16(ex2f(x0), ex2f(x1)); }
template <uint32_t MASK>
__device__ __forceinline__ void exp_blocks(const float (&s)[32], uint32_t (&p)[16]) {
#pragma unroll
    for (int b = 0; b < 8; b++) {
        if ((MASK >> b) & 1) {
            p[2 * b] = exp2_pair_poly(s[4 * b], s[4 * b + 1]);
            p[2 * b + 1] = exp2_pair_poly(s[4 * b + 2], s[4 * b + 3]);
        } else {
            p[2 * b] = exp2_pair_mufu(s[4 * b], s[4 * b + 1]);
            p[2 * b + 1] = exp2_pair_mufu(s[4 * b + 2], s[4 * b + 3]);
        }
    }
}
#define PV4(P) _Pragma("unroll") for (int i = 0; i < 4; i++) { pv_wgmma(o, P[4 * i], P[4 * i + 1], P[4 * i + 2], P[4 * i + 3], vd); vd += 16; }

__device__ __forceinline__ void attn_store(float (&o)[12], int row0, int head, int lane) {
    float l0 = __shfl_sync(0xffffffffu, o[8], lane & 28);
    float l1 = __shfl_sync(0xffffffffu, o[10], lane & 28);
    float r0 = 1.0f / l0, r1 = 1.0f / l1;
    uint32_t* op = (uint32_t*)g_ao;
    int mb = row0 >> 7, rg = (row0 & 127) >> 3;
    int kb = head >> 2, kc = (head & 3) * 2;
    size_t base = (((size_t)(mb * 8 + kb) * 8 + kc) * 16 + rg) * 32 + lane;
    op[base] = pack_bf16(o[0] * r0, o[1] * r0);
    op[base + 32] = pack_bf16(o[2] * r1, o[3] * r1);
    op[base + 16 * 32] = pack_bf16(o[4] * r0, o[5] * r0);
    op[base + 16 * 32 + 32] = pack_bf16(o[6] * r1, o[7] * r1);
}

__device__ __forceinline__ void attn_load_q(uint32_t (&q)[4], const __nv_bfloat16* gq, int row0, int lane) {
    const uint32_t* qp = (const uint32_t*)gq;
    int j0 = row0 >> 3;
    q[0] = __ldcg(qp + (0 * 256 + j0) * 32 + lane);
    q[1] = __ldcg(qp + (0 * 256 + j0 + 1) * 32 + lane);
    q[2] = __ldcg(qp + (1 * 256 + j0) * 32 + lane);
    q[3] = __ldcg(qp + (1 * 256 + j0 + 1) * 32 + lane);
}

__device__ __forceinline__ void attn_tile_safe(const uint32_t (&q)[4], uint64_t kd, uint64_t vd, int row0, int head, int lane) {
    float o[12];
#pragma unroll
    for (int i = 0; i < 12; i++) o[i] = 0.f;
    float m0 = -INFINITY, m1 = -INFINITY;
    fence_regs(o);
#pragma unroll 1
    for (int j = 0; j < 32; j++) {
        float s[32];
        uint32_t p[16];
        WG_FENCE();
        qk_wgmma_n64(s, q, kd); kd += 64;
        WG_COMMIT();
        wg_wait<0>();
        fence_regs(s);
        fence_regs(o);
        float x0 = m0, x1 = m1;
#pragma unroll
        for (int b = 0; b < 8; b++) {
            x0 = fmaxf(x0, fmaxf(s[4 * b], s[4 * b + 1]));
            x1 = fmaxf(x1, fmaxf(s[4 * b + 2], s[4 * b + 3]));
        }
        x0 = fmaxf(x0, __shfl_xor_sync(0xffffffffu, x0, 1)); x0 = fmaxf(x0, __shfl_xor_sync(0xffffffffu, x0, 2));
        x1 = fmaxf(x1, __shfl_xor_sync(0xffffffffu, x1, 1)); x1 = fmaxf(x1, __shfl_xor_sync(0xffffffffu, x1, 2));
        float al0 = ex2f(m0 - x0), al1 = ex2f(m1 - x1);
        m0 = x0; m1 = x1;
#pragma unroll
        for (int i = 0; i < 3; i++) { o[4 * i] *= al0; o[4 * i + 1] *= al0; o[4 * i + 2] *= al1; o[4 * i + 3] *= al1; }
#pragma unroll
        for (int b = 0; b < 8; b++) {
            p[2 * b] = exp2_pair_mufu(s[4 * b] - m0, s[4 * b + 1] - m0);
            p[2 * b + 1] = exp2_pair_mufu(s[4 * b + 2] - m1, s[4 * b + 3] - m1);
        }
        fence_regs(o);
        WG_FENCE();
        PV4(p);
        WG_COMMIT();
        wg_wait<0>();
        fence_regs(o);
    }
    attn_store(o, row0, head, lane);
}

__global__ void __launch_bounds__(512, 1)
attn_kernel(const __nv_bfloat16* __restrict__ wg_, const __nv_bfloat16* __restrict__ wu_,
            const __nv_bfloat16* __restrict__ wo_, const __nv_bfloat16* __restrict__ wd_) {
    extern __shared__ __align__(1024) unsigned char smem[];
    const uint32_t sb = smem_u32(smem);
    const int tid = threadIdx.x, wg = tid >> 7, warp = (tid >> 5) & 3, lane = tid & 31;
    TLDECL
    pdl_launch();
    if (blockIdx.x >= 128) {
        const int e = blockIdx.x - 128;
        const __nv_bfloat16* w = (e < 2) ? wg_ : wu_;
        float* red = (float*)smem;
        const int cgrp = tid & 127, kq = tid >> 7;
        if (cgrp < 112) {
            float s[8];
            colsum8(w, FF, (e & 1) * 896 + cgrp * 8, kq * 128, 128, s);
#pragma unroll
            for (int i = 0; i < 8; i++) red[kq * 896 + cgrp * 8 + i] = s[i];
        }
        __syncthreads();
        for (int c = tid; c < 896; c += 512)
            g_cs2[(e >> 1) * FF + (e & 1) * 896 + c] = red[c] + red[896 + c] + red[1792 + c] + red[2688 + c];
        if (tid < 32) {
            const char* p0 = (const char*)wo_ + e * (DM * DM * 2 / 4);
            for (int i = lane; i < 32; i += 32)
                asm volatile("cp.async.bulk.prefetch.L2.global [%0], %1;" :: "l"(p0 + i * 4096), "r"(4096) : "memory");
            const char* p1 = (const char*)wd_ + e * (FF * DM * 2 / 4);
            for (int i = lane; i < 112; i += 32)
                asm volatile("cp.async.bulk.prefetch.L2.global [%0], %1;" :: "l"(p1 + i * 4096), "r"(4096) : "memory");
        }
        return;
    }
    const int head = blockIdx.x >> 2, qq = blockIdx.x & 3;
    const __nv_bfloat16* gq = g_qkv + (size_t)head * (S_LEN * 16);
    const __nv_bfloat16* gk = g_qkv + (size_t)(NH + head) * (S_LEN * 16);
    const __nv_bfloat16* gv = g_qkv + (size_t)(2 * NH + head) * (S_LEN * 16);
    if (tid == 0) {
        for (int i = 0; i < 8; i++) mbar_init(sb + AT_BAR + 8 * i, 1);
        fence_barrier_init();
    }
    {
        uint4 one = make_uint4(0x00003F80u, 0, 0, 0);
#pragma unroll
        for (int i = 0; i < 4; i++) *(uint4*)(smem + AT_ONES + (i * 512 + tid) * 16) = one;
        fence_proxy_async();
    }
    __syncthreads();
    TL(3);
    pdl_wait();
    TL(4);
    auto load_kv = [&](int i) {
        uint32_t bar = sb + AT_BAR + 8 * i;
        mbar_expect(bar, 16384);
        bulk_g2s(sb + AT_K + i * 4096, gk + i * 2048, 4096, bar);
        bulk_g2s(sb + AT_K + 32768 + i * 4096, gk + 16384 + i * 2048, 4096, bar);
        bulk_g2s(sb + AT_V + i * 4096, gv + i * 2048, 4096, bar);
        bulk_g2s(sb + AT_V + 32768 + i * 4096, gv + 16384 + i * 2048, 4096, bar);
    };
    if (tid == 0) { load_kv(0); load_kv(1); }
    uint32_t q[4], q2[4];
    attn_load_q(q, gq, qq * 512 + wg * 64 + warp * 16, lane);
    attn_load_q(q2, gq, qq * 512 + (4 + wg) * 64 + warp * 16, lane);
    bool fast;
    {
        const float* nq = g_nrm + (0 * NH + head) * 128 + qq * 32;
        const float* nk = g_nrm + (1 * NH + head) * 128;
        const float* nv = g_nrm + (2 * NH + head) * 128;
        float4 k4 = __ldcg((const float4*)nk + lane), v4 = __ldcg((const float4*)nv + lane);
        float qm = warp_max(__ldcg(nq + lane));
        float km = warp_max(fmaxf(fmaxf(k4.x, k4.y), fmaxf(k4.z, k4.w)));
        float vm = warp_max(fmaxf(fmaxf(v4.x, v4.y), fmaxf(v4.z, v4.w)));
        fast = __all_sync(0xffffffffu, (qm * km <= 3500.0f) && (vm <= 1.0e24f));
    }
    TL(24);
    const uint64_t kdesc0 = make_desc(sb + AT_K, 32768, 128, 0);
    const uint64_t vdesc0 = make_desc(sb + AT_V, 128, 32768, 0);
    if (!fast) {
        if (tid == 0) for (int i = 2; i < 8; i++) load_kv(i);
        for (int i = 0; i < 8; i++) mbar_wait(sb + AT_BAR + 8 * i, 0);
#pragma unroll 1
        for (int tile = 0; tile < 2; tile++) {
            const int row0 = qq * 512 + (tile * 4 + wg) * 64 + warp * 16;
            attn_tile_safe(q, kdesc0, vdesc0, row0, head, lane);
#pragma unroll
            for (int i = 0; i < 4; i++) q[i] = q2[i];
        }
        return;
    }
#pragma unroll 1
    for (int tile = 0; tile < 2; tile++) {
        const int row0 = qq * 512 + (tile * 4 + wg) * 64 + warp * 16;
        float o[12];
#pragma unroll
        for (int i = 0; i < 12; i++) o[i] = 0.f;
        fence_regs(o);
        float sa[32];
        uint32_t pa[16];
        uint64_t kd = kdesc0, vd = vdesc0;
        if (tile == 0) { mbar_wait(sb + AT_BAR, 0); TL(25); }
        WG_FENCE();
        qk_wgmma_n64(sa, q, kd); kd += 64;
        WG_COMMIT();
#pragma unroll 1
        for (int jj = 0; jj < 8; jj++) {
            if (tile == 0 && jj < 7) {
                if (tid == 0 && jj < 6) load_kv(jj + 2);
                mbar_wait(sb + AT_BAR + 8 * (jj + 1), 0);
            }
            if (wg == 0 && warp == 0) TX(128 + tile * 8 + jj);
#pragma unroll
            for (int j = 0; j < 4; j++) {
                wg_wait<0>();
                fence_regs(sa);
                if (j & 1) exp_blocks<(POLY_MASK >> 8)>(sa, pa); else exp_blocks<(POLY_MASK & 255)>(sa, pa);
                WG_FENCE();
                qk_wgmma_n64(sa, q, kd); kd += 64;
                PV4(pa);
                WG_COMMIT();
            }
        }
        wg_wait<0>();
        fence_regs(o);
        fence_regs(sa);
        if (tile == 0) TL(26);
        attn_store(o, row0, head, lane);
#pragma unroll
        for (int i = 0; i < 4; i++) q[i] = q2[i];
    }
    TL(5);
    TLDUMP;
}

constexpr int F_R2 = 131072, F_X = 196608, F_BAR = 229376;
constexpr int F_RS = F_BAR + 256, F_CS = F_RS + 1024, F_SMEM = F_CS + 1792;
enum { B_FA = 0, B_HF = 4, B_BF = 8, B_BE = 11, B_CF = 14, B_CE = 20, B_ADONE = 26, B_BDONE = 27, B_XC = 28, B_PRDY = 29, B_AUX = 30, B_NUM = 31 };

__device__ __forceinline__ uint32_t mapa(uint32_t a, uint32_t rank) { uint32_t r; asm("mapa.shared::cluster.u32 %0, %1, %2;" : "=r"(r) : "r"(a), "r"(rank)); return r; }
__device__ __forceinline__ void st_async4(uint32_t dst, float a, float b, float c, float d, uint32_t bar) {
    asm volatile("st.async.weak.shared::cluster.mbarrier::complete_tx::bytes.v4.f32 [%0], {%1,%2,%3,%4}, [%5];"
                 :: "r"(dst), "f"(a), "f"(b), "f"(c), "f"(d), "r"(bar) : "memory");
}
__device__ __forceinline__ void mbar_arrive_remote(uint32_t a) { asm volatile("mbarrier.arrive.relaxed.cluster.shared::cluster.b64 _, [%0];" :: "r"(a) : "memory"); }
__device__ __forceinline__ void mbar_wait_cluster(uint32_t a, int parity) {
    uint32_t done;
    int it = 0;
    do {
        asm volatile("{\n.reg .pred p;\nmbarrier.try_wait.parity.acquire.cluster.shared::cta.b64 p, [%1], %2;\nselp.u32 %0, 1, 0, p;\n}"
                     : "=r"(done) : "r"(a), "r"(parity) : "memory");
        if (++it > (1 << 24)) __trap();
    } while (!done);
}
__device__ __forceinline__ void poll_count(const unsigned int* p, unsigned int target) {
    int it = 0;
    while (ld_acquire(p) < target) { if (++it > (1 << 22)) __trap(); }
    asm volatile("fence.proxy.async.global;" ::: "memory");
}
__device__ __forceinline__ void tma2d_store(const CUtensorMap* m, uint32_t src, int c0, int c1) {
    asm volatile("cp.async.bulk.tensor.2d.global.shared::cta.bulk_group [%0, {%2, %3}], [%1];" :: "l"(m), "r"(src), "r"(c0), "r"(c1) : "memory");
}
template <int R>
__device__ __forceinline__ void xchg(float (&acc)[64], float (&o)[32], uint32_t sb, unsigned char* smem, int bar, int ctid) {
    const uint32_t dst = mapa(sb + F_X + ctid * 16, 1 - R), rb = mapa(sb + F_BAR + 8 * bar, 1 - R);
#pragma unroll
    for (int q = 0; q < 8; q++) {
        const int j = (1 - R) * 32 + 4 * q;
        st_async4(dst + q * 4096, acc[j], acc[j + 1], acc[j + 2], acc[j + 3], rb);
    }
    mbar_wait_cluster(sb + F_BAR + 8 * bar, 0);
#pragma unroll
    for (int q = 0; q < 8; q++) {
        float4 v = *(const float4*)(smem + F_X + q * 4096 + ctid * 16);
        const int j = R * 32 + 4 * q;
        o[4 * q] = acc[j] + v.x; o[4 * q + 1] = acc[j + 1] + v.y; o[4 * q + 2] = acc[j + 2] + v.z; o[4 * q + 3] = acc[j + 3] + v.w;
    }
}

template <int NB, bool STAGE>
__device__ __forceinline__ void ffn_epilogue(const float* ag, const float* au, const float* s_cs, int cs_off, uint32_t* gp, uint32_t stg,
                                             float2 st0, float2 st1, int lane) {
    const int t = lane & 3;
    const float C1 = 0.7978845608028654f, C2 = 0.044715f * 0.7978845608028654f;
    const float k10 = st0.x * C1, k20 = st0.x * st0.x * st0.x * C2, k11 = st1.x * C1, k21 = st1.x * st1.x * st1.x * C2;
#pragma unroll
    for (int j2 = 0; j2 < NB / 2; j2++) {
        uint32_t pk[4];
#pragma unroll
        for (int jj = 0; jj < 2; jj++) {
            const int j = 2 * j2 + jj;
            const float2 cg = *(const float2*)(s_cs + cs_off + 8 * j + 2 * t);
            const float2 cu = *(const float2*)(s_cs + 224 + cs_off + 8 * j + 2 * t);
            float r[4];
#pragma unroll
            for (int e = 0; e < 4; e++) {
                const float nm = (e < 2) ? st0.y : st1.y, k1 = (e < 2) ? k10 : k11, k2 = (e < 2) ? k20 : k21;
                const float tg = fmaf(nm, (e & 1) ? cg.y : cg.x, ag[4 * j + e]);
                const float tu = fmaf(nm, (e & 1) ? cu.y : cu.x, au[4 * j + e]);
                const float th = tanh_fast(tg * fmaf(tg * tg, k2, k1));
                const float p = tg * tu;
                r[e] = fmaf(p, th, p);
            }
            pk[2 * jj] = pack_bf16(r[0], r[1]);
            pk[2 * jj + 1] = pack_bf16(r[2], r[3]);
        }
        if (STAGE) {
            stsm4(stg + j2 * 4096, pk[0], pk[1], pk[2], pk[3]);
        } else {
            gp[j2 * 1024] = pk[0]; gp[j2 * 1024 + 32] = pk[1]; gp[j2 * 1024 + 512] = pk[2]; gp[j2 * 1024 + 544] = pk[3];
        }
    }
}

__global__ void __cluster_dims__(2, 1, 1) __launch_bounds__(384, 1)
tail_kernel(const __grid_constant__ CUtensorMap tm_o, const __grid_constant__ CUtensorMap tm_g,
            const __grid_constant__ CUtensorMap tm_u, const __grid_constant__ CUtensorMap tm_d,
            const __grid_constant__ CUtensorMap tm_out, const __nv_bfloat16* __restrict__ x) {
    extern __shared__ __align__(1024) unsigned char smem[];
    const uint32_t sb = smem_u32(smem);
    const uint32_t bars = sb + F_BAR;
    const int tid = threadIdx.x, warp = __shfl_sync(0xffffffffu, tid >> 5, 0), lane = tid & 31;
    TLDECL
    TL(6);
    if (warp == 4) TX(200);
    const int cl = blockIdx.x >> 1, r = blockIdx.x & 1;
    const int mb = ((cl & 7) >> 1) * 4 + (cl >> 4), ntA = (cl & 1) * 2 + ((cl >> 3) & 1);
    const int nt = ntA * 2 + r;
    if (tid == 0) {
#pragma unroll
        for (int i = 0; i < B_NUM; i++) {
            const int cnt = ((i >= B_BE && i < B_BE + 3) || (i >= B_CE && i < B_CE + 6) || i == B_BDONE || i == B_PRDY) ? 8 : (i == B_AUX) ? 2 : 1;
            mbar_init(bars + 8 * i, cnt);
        }
        mbar_expect(bars + 8 * B_XC, 32768);
        fence_barrier_init();
    }
    TL(28);
    __syncthreads();
    TL(29);
    asm volatile("barrier.cluster.arrive.relaxed.aligned;" ::: "memory");
    TL(30);
    if (warp < 4) {
        asm volatile("setmaxnreg.dec.sync.aligned.u32 56;");
        if (warp == 0) TX(205);
        if (warp == 0) {
            if (lane == 0) {
                auto load_b = [&](int it) {
                    const int s = it % 3, pass = it >> 3, kb = it & 7;
                    const int ng = pass ? 3 : 4, c0 = nt * 224 + pass * 128;
                    const uint32_t bar = bars + 8 * (B_BF + s), dst = sb + F_R2 + s * 32768;
                    mbar_expect(bar, ng * 8192);
                    for (int i = 0; i < ng; i++) {
                        tma2d(dst + i * 4096, &tm_g, c0 + i * 32, kb * 64, bar);
                        tma2d(dst + 16384 + i * 4096, &tm_u, c0 + i * 32, kb * 64, bar);
                    }
                };
                for (int i = 0; i < 8; i++) {
                    const uint32_t bar = bars + 8 * (B_FA + (i >> 1));
                    if (!(i & 1)) mbar_expect(bar, 49152);
                    tma2d(sb + F_R2 + 32768 + i * 8192, &tm_o, nt * 64, i * 64, bar);
                }
                pdl_wait();
                TL(16);
                for (int i = 0; i < 8; i++)
                    bulk_g2s(sb + i * 16384, g_ao + (size_t)(mb * 8 + i) * 8192, 16384, bars + 8 * (B_FA + (i >> 1)));
                load_b(0);
                if (blockIdx.x == 0)
                    for (int i = 0; i < 32; i++) g_cnt[i] = 0;
                mbar_wait(bars + 8 * B_ADONE, 0);
                load_b(1); load_b(2);
                poll_count(&g_cnt2[mb], 8);
                TL(17);
                for (int kb = 0; kb < 8; kb++) {
                    const uint32_t bar = bars + 8 * (B_HF + (kb >> 1));
                    if (!(kb & 1)) mbar_expect(bar, (kb >> 1) == ntA ? 16384 : 32768);
                    if (kb != nt) bulk_g2s(sb + kb * 16384, g_h + (size_t)(mb * 8 + kb) * 8192, 16384, bar);
                }
                for (int it = 3; it < 16; it++) {
                    mbar_wait(bars + 8 * (B_BE + it % 3), (it / 3 - 1) & 1);
                    load_b(it);
                }
                mbar_wait(bars + 8 * B_BDONE, 0);
                for (int i = 0; i < 6; i++) {
                    const uint32_t bar = bars + 8 * (B_CF + i);
                    mbar_expect(bar, 32768);
                    tma2d(sb + i * 32768 + 16384, &tm_d, ntA * 128, (2 * i + r) * 64, bar);
                    tma2d(sb + i * 32768 + 24576, &tm_d, ntA * 128 + 64, (2 * i + r) * 64, bar);
                }
                poll_count(&g_cnt2[16 + mb], 8);
                TL(18);
                for (int kb = 0; kb < 14; kb++) {
                    const int s = kb % 6;
                    const uint32_t bar = bars + 8 * (B_CF + s);
                    if (kb >= 6) {
                        mbar_wait(bars + 8 * (B_CE + s), ((kb / 6) - 1) & 1);
                        mbar_expect(bar, 32768);
                        tma2d(sb + s * 32768 + 16384, &tm_d, ntA * 128, (2 * kb + r) * 64, bar);
                        tma2d(sb + s * 32768 + 24576, &tm_d, ntA * 128 + 64, (2 * kb + r) * 64, bar);
                    }
                    bulk_g2s(sb + s * 32768, g_g + (size_t)(mb * 28 + 2 * kb + r) * 8192, 16384, bar);
                }
            }
            TLDUMP;
            __syncwarp();
            asm volatile("barrier.cluster.wait.acquire.aligned;" ::: "memory");
        } else if (warp == 1) {
            asm volatile("barrier.cluster.wait.acquire.aligned;" ::: "memory");
            bar_sync(1, 288);
            if (lane == 0) {
                red_release(&g_cnt2[mb]);
                TL(9);
            }
            __syncwarp();
            bar_sync(2, 288);
            if (lane == 0) {
                red_release(&g_cnt2[16 + mb]);
                TL(13);
            }
            __syncwarp();
            bar_sync(3, 288);
            if (lane == 0) {
                tma2d_store(&tm_out, sb, nt * 64, mb * 128);
                bulk_commit();
                bulk_wait_all();
                TL(15);
            }
            TLDUMP;
        } else {
            asm volatile("barrier.cluster.wait.acquire.aligned;" ::: "memory");
            pdl_wait();
            float2* s_rs = (float2*)(smem + F_RS);
            float* s_cs = (float*)(smem + F_CS);
            for (int c = tid - 64; c < 448; c += 64)
                s_cs[c] = __ldcg(&g_cs2[(c >= 224 ? FF - 224 : 0) + nt * 224 + c]);
            if (lane == 0) poll_count(&g_cnt2[mb], 8);
            __syncwarp();
            for (int rr = tid - 64; rr < 128; rr += 64) {
                const float4* hp = (const float4*)(g_hstat + (size_t)(mb * 128 + rr) * 8);
                float4 a = __ldcg(hp), b = __ldcg(hp + 1), c = __ldcg(hp + 2), d = __ldcg(hp + 3);
                float mean = 0.125f * (a.x + a.z + b.x + b.z + c.x + c.z + d.x + d.z);
                float m2 = a.y + a.w + b.y + b.w + c.y + c.w + d.y + d.w;
                float e;
                e = a.x - mean; m2 = fmaf(64.f * e, e, m2); e = a.z - mean; m2 = fmaf(64.f * e, e, m2);
                e = b.x - mean; m2 = fmaf(64.f * e, e, m2); e = b.z - mean; m2 = fmaf(64.f * e, e, m2);
                e = c.x - mean; m2 = fmaf(64.f * e, e, m2); e = c.z - mean; m2 = fmaf(64.f * e, e, m2);
                e = d.x - mean; m2 = fmaf(64.f * e, e, m2); e = d.z - mean; m2 = fmaf(64.f * e, e, m2);
                s_rs[rr] = make_float2(rsqrtf(m2 * (1.0f / DM) + 1e-5f), -mean);
            }
            __syncwarp();
            if (lane == 0) mbar_arrive(bars + 8 * B_AUX);
        }
    } else {
        asm volatile("setmaxnreg.inc.sync.aligned.u32 216;");
        if (warp == 4) TX(206);
        const int wgi = (warp >> 2) - 1, ww = warp & 3, ctid = tid - 128;
        const int g = lane >> 2, t = lane & 3;
        const int rl = wgi * 64 + ww * 16 + g, row = mb * 128 + rl;
        const int rgl = wgi * 8 + ww * 2;
        const float2* s_rs = (const float2*)(smem + F_RS);
        const float* s_cs = (const float*)(smem + F_CS);
        const uint32_t stl = ((lane >> 4) * 16 + rgl + ((lane >> 3) & 1)) * 128 + (lane & 7) * 16;
        TL(23);
        {
            uint32_t xr[16];
            const uint32_t* xp = (const uint32_t*)(x + (size_t)row * DM + nt * 64) + t;
#pragma unroll
            for (int j = 0; j < 8; j++) { xr[2 * j] = __ldg(xp + 4 * j); xr[2 * j + 1] = __ldg(xp + 8 * (DM / 2) + 4 * j); }
            float acc[32];
#pragma unroll 1
            for (int i = 0; i < 8; i++) {
                if (!(i & 1)) { mbar_wait(bars + 8 * (B_FA + (i >> 1)), 0); if (i == 0) TL(19); }
                uint64_t ad = make_desc(sb + i * 16384 + wgi * 1024, 2048, 128, 0);
                uint64_t bd = make_desc(sb + F_R2 + 32768 + i * 8192, 8192, 1024, 1);
                WG_FENCE();
#pragma unroll
                for (int k = 0; k < 4; k++) wgmma_ss_n64(acc, ad + k * 256, bd + k * 128, (i | k) != 0);
                WG_COMMIT();
            }
            wg_wait<0>();
            fence_regs(acc);
            TL(7);
            bar_sync(4, 256);
            if (tid == 128) mbar_arrive(bars + 8 * B_ADONE);
            uint32_t* hp = (uint32_t*)g_h + ((size_t)(mb * 8 + nt) * 8 * 16 + rgl) * 32 + lane;
            float v0[16], v1[16];
            float s0 = 0.f, s1 = 0.f;
#pragma unroll
            for (int j2 = 0; j2 < 4; j2++) {
                uint32_t u[4];
#pragma unroll
                for (int jj = 0; jj < 2; jj++) {
                    const int j = 2 * j2 + jj;
                    u[2 * jj] = pack_bf16(bf_lo(xr[2 * j]) + acc[4 * j], bf_hi(xr[2 * j]) + acc[4 * j + 1]);
                    u[2 * jj + 1] = pack_bf16(bf_lo(xr[2 * j + 1]) + acc[4 * j + 2], bf_hi(xr[2 * j + 1]) + acc[4 * j + 3]);
                    v0[2 * j] = bf_lo(u[2 * jj]); v0[2 * j + 1] = bf_hi(u[2 * jj]);
                    v1[2 * j] = bf_lo(u[2 * jj + 1]); v1[2 * j + 1] = bf_hi(u[2 * jj + 1]);
                    s0 += v0[2 * j] + v0[2 * j + 1];
                    s1 += v1[2 * j] + v1[2 * j + 1];
                }
                stsm4(sb + nt * 16384 + stl + j2 * 4096, u[0], u[1], u[2], u[3]);
                hp[j2 * 1024] = u[0]; hp[j2 * 1024 + 32] = u[1]; hp[j2 * 1024 + 512] = u[2]; hp[j2 * 1024 + 544] = u[3];
            }
            fence_proxy_async();
            float m0 = s0 * (1.0f / 16), m1 = s1 * (1.0f / 16), q0 = 0.f, q1 = 0.f;
#pragma unroll
            for (int i = 0; i < 16; i++) {
                float d0 = v0[i] - m0, d1 = v1[i] - m1;
                q0 = fmaf(d0, d0, q0); q1 = fmaf(d1, d1, q1);
            }
#pragma unroll
            for (int st = 0; st < 2; st++) {
                float hn = st ? 16.f : 8.f;
                float om0 = __shfl_xor_sync(0xffffffffu, m0, 1 << st), oq0 = __shfl_xor_sync(0xffffffffu, q0, 1 << st);
                float om1 = __shfl_xor_sync(0xffffffffu, m1, 1 << st), oq1 = __shfl_xor_sync(0xffffffffu, q1, 1 << st);
                float d0 = om0 - m0, d1 = om1 - m1;
                q0 = q0 + oq0 + d0 * d0 * hn; q1 = q1 + oq1 + d1 * d1 * hn;
                m0 = 0.5f * (m0 + om0); m1 = 0.5f * (m1 + om1);
            }
            if (t == 0) {
                g_hstat[row * 8 + nt] = make_float2(m0, q0);
                g_hstat[(row + 8) * 8 + nt] = make_float2(m1, q1);
            }
            bar_arrive(1, 288);
            bar_sync(4, 256);
            TL(8);
        }
        uint32_t* gp = (uint32_t*)g_g + (((size_t)mb * 224 + nt * 28) * 16 + rgl) * 32 + lane;
        {
            float ag[64], au[64];
#pragma unroll 1
            for (int kb = 0; kb < 8; kb++) {
                const int s = kb % 3;
                if (!(kb & 1)) mbar_wait(bars + 8 * (B_HF + (kb >> 1)), 0);
                mbar_wait(bars + 8 * (B_BF + s), (kb / 3) & 1);
                if (warp == 4) TX(32 + kb);
                uint64_t ad = make_desc(sb + kb * 16384 + wgi * 1024, 2048, 128, 0);
                uint64_t bd = make_desc(sb + F_R2 + s * 32768, 4096, 512, 2);
                WG_FENCE();
#pragma unroll
                for (int k = 0; k < 4; k++) {
                    wgmma_ss_n128(ag, ad + k * 256, bd + k * 64, (kb | k) != 0);
                    wgmma_ss_n128(au, ad + k * 256, bd + 1024 + k * 64, (kb | k) != 0);
                }
                WG_COMMIT();
                if (kb > 0) {
                    wg_wait<1>();
                    if (lane == 0) mbar_arrive(bars + 8 * (B_BE + (kb - 1) % 3));
                }
            }
            wg_wait<0>();
            if (lane == 0) mbar_arrive(bars + 8 * (B_BE + 7 % 3));
            fence_regs(ag); fence_regs(au);
            TL(10);
            mbar_wait(bars + 8 * B_AUX, 0);
            ffn_epilogue<16, false>(ag, au, s_cs, 0, gp, 0, s_rs[rl], s_rs[rl + 8], lane);
        }
        uint32_t hr[16];
        {
            const uint32_t* hs = (const uint32_t*)(smem + nt * 16384) + rgl * 32 + lane;
#pragma unroll
            for (int j = 0; j < 8; j++) { hr[2 * j] = hs[j * 512]; hr[2 * j + 1] = hs[j * 512 + 32]; }
        }
        {
            float ag[48], au[48];
#pragma unroll 1
            for (int kb = 0; kb < 8; kb++) {
                const int it = 8 + kb, s = it % 3;
                mbar_wait(bars + 8 * (B_BF + s), (it / 3) & 1);
                if (warp == 4) TX(32 + it);
                uint64_t ad = make_desc(sb + kb * 16384 + wgi * 1024, 2048, 128, 0);
                uint64_t bd = make_desc(sb + F_R2 + s * 32768, 4096, 512, 2);
                WG_FENCE();
#pragma unroll
                for (int k = 0; k < 4; k++) {
                    wgmma_ss_n96(ag, ad + k * 256, bd + k * 64, (kb | k) != 0);
                    wgmma_ss_n96(au, ad + k * 256, bd + 1024 + k * 64, (kb | k) != 0);
                }
                WG_COMMIT();
                if (kb > 0) {
                    wg_wait<1>();
                    if (lane == 0) mbar_arrive(bars + 8 * (B_BE + (it - 1) % 3));
                }
            }
            wg_wait<0>();
            asm volatile("barrier.cluster.wait.acquire.aligned;" ::: "memory");
            if (lane == 0) {
                mbar_arrive(bars + 8 * B_BDONE);
                mbar_arrive_remote(mapa(bars + 8 * B_PRDY, 1 - r));
            }
            fence_regs(ag); fence_regs(au);
            TL(11);
            ffn_epilogue<12, false>(ag, au, s_cs, 128, gp + 16 * 512, 0, s_rs[rl], s_rs[rl + 8], lane);
            bar_arrive(2, 288);
            TL(12);
        }
        {
            float acc[64];
#pragma unroll 1
            for (int kb = 0; kb < 14; kb++) {
                const int s = kb % 6;
                mbar_wait(bars + 8 * (B_CF + s), (kb / 6) & 1);
                if (warp == 4) TX(96 + kb);
                uint64_t ad = make_desc(sb + s * 32768 + wgi * 1024, 2048, 128, 0);
                uint64_t bd = make_desc(sb + s * 32768 + 16384, 8192, 1024, 1);
                WG_FENCE();
#pragma unroll
                for (int k = 0; k < 4; k++) wgmma_ss_n128(acc, ad + k * 256, bd + k * 128, (kb | k) != 0);
                WG_COMMIT();
                if (kb > 0) {
                    wg_wait<1>();
                    if (lane == 0) mbar_arrive(bars + 8 * (B_CE + (kb - 1) % 6));
                }
            }
            wg_wait<0>();
            fence_regs(acc);
            TL(14);
            mbar_wait_cluster(bars + 8 * B_PRDY, 0);
            float o[32];
            if (r == 0) xchg<0>(acc, o, sb, smem, B_XC, ctid); else xchg<1>(acc, o, sb, smem, B_XC, ctid);
            TL(22);
            bar_sync(4, 256);
            const float a0 = s_rs[rl].x, a1 = s_rs[rl + 8].x;
            const float k0 = 0.5f * a0 * a0, k1 = 0.5f * a1 * a1;
            const int srow = wgi * 64 + ww * 16 + ((lane >> 3) & 1) * 8 + (lane & 7);
#pragma unroll
            for (int j2 = 0; j2 < 4; j2++) {
                uint32_t u[4];
#pragma unroll
                for (int jj = 0; jj < 2; jj++) {
                    const int j = 2 * j2 + jj;
                    u[2 * jj] = pack_bf16(fmaf(k0, o[4 * j], bf_lo(hr[2 * j])), fmaf(k0, o[4 * j + 1], bf_hi(hr[2 * j])));
                    u[2 * jj + 1] = pack_bf16(fmaf(k1, o[4 * j + 2], bf_lo(hr[2 * j + 1])), fmaf(k1, o[4 * j + 3], bf_hi(hr[2 * j + 1])));
                }
                const int chunk = 2 * j2 + (lane >> 4);
                stsm4(sb + srow * 128 + ((chunk ^ (lane & 7)) * 16), u[0], u[1], u[2], u[3]);
            }
            fence_proxy_async();
            bar_arrive(3, 288);
            TLDUMP;
        }
    }
}

typedef CUresult (*EncodeFn)(CUtensorMap*, CUtensorMapDataType, cuuint32_t, void*, const cuuint64_t*, const cuuint64_t*,
                             const cuuint32_t*, const cuuint32_t*, CUtensorMapInterleave, CUtensorMapSwizzle,
                             CUtensorMapL2promotion, CUtensorMapFloatOOBfill);

void encode(EncodeFn fn, CUtensorMap* m, const void* ptr, int rank, const cuuint64_t* dims, const cuuint64_t* strides,
            const cuuint32_t* box, CUtensorMapSwizzle swz) {
    cuuint32_t es[3] = {1, 1, 1};
    fn(m, CU_TENSOR_MAP_DATA_TYPE_BFLOAT16, rank, (void*)ptr, dims, strides, box, es, CU_TENSOR_MAP_INTERLEAVE_NONE, swz,
       CU_TENSOR_MAP_L2_PROMOTION_L2_256B, CU_TENSOR_MAP_FLOAT_OOB_FILL_NONE);
}

template <typename... KArgs, typename... Args>
void launch(void (*kern)(KArgs...), int grid, int block, int smem, bool pdl, Args... args) {
    cudaLaunchConfig_t cfg = {};
    cfg.gridDim = dim3(grid); cfg.blockDim = dim3(block); cfg.dynamicSmemBytes = smem;
    cfg.stream = cudaStreamPerThread;
    cudaLaunchAttribute at[1];
    at[0].id = cudaLaunchAttributeProgrammaticStreamSerialization;
    at[0].val.programmaticStreamSerializationAllowed = 1;
    cfg.attrs = at; cfg.numAttrs = pdl ? 1 : 0;
    cudaLaunchKernelEx(&cfg, kern, KArgs(args)...);
}

}

extern "C" void kernel_launch(void* const* d_in, const int* in_sizes, int n_in, void* d_out, int out_size) {
    const __nv_bfloat16* x = (const __nv_bfloat16*)d_in[0];
    const __nv_bfloat16* wqkv = (const __nv_bfloat16*)d_in[1];
    const __nv_bfloat16* wo = (const __nv_bfloat16*)d_in[2];
    const __nv_bfloat16* wgate = (const __nv_bfloat16*)d_in[4];
    const __nv_bfloat16* wup = (const __nv_bfloat16*)d_in[5];
    const __nv_bfloat16* wdown = (const __nv_bfloat16*)d_in[6];
    __nv_bfloat16* out = (__nv_bfloat16*)d_out;

    static CUtensorMap tm_x, tm_wqkv, tm_wo, tm_wg, tm_wu, tm_wd, tm_out;
    static const void* cached[7] = {nullptr, nullptr, nullptr, nullptr, nullptr, nullptr, nullptr};
    if (cached[0] != x || cached[1] != wqkv || cached[2] != wo || cached[3] != wgate || cached[4] != wup || cached[5] != wdown || cached[6] != out) {
        void* fp = nullptr;
        cudaDriverEntryPointQueryResult qr;
        cudaGetDriverEntryPoint("cuTensorMapEncodeTiled", &fp, cudaEnableDefault, &qr);
        EncodeFn fn = (EncodeFn)fp;
        { cuuint64_t d[2] = {512, 2048}, s[1] = {1024}; cuuint32_t b[2] = {64, 128};
          encode(fn, &tm_x, x, 2, d, s, b, CU_TENSOR_MAP_SWIZZLE_128B);
          encode(fn, &tm_out, out, 2, d, s, b, CU_TENSOR_MAP_SWIZZLE_128B); }
        { cuuint64_t d[3] = {64, 512, 24}, s[2] = {3072, 128}; cuuint32_t b[3] = {64, 64, 3};
          encode(fn, &tm_wqkv, wqkv, 3, d, s, b, CU_TENSOR_MAP_SWIZZLE_128B); }
        { cuuint64_t d[2] = {512, 512}, s[1] = {1024}; cuuint32_t b[2] = {64, 64};
          encode(fn, &tm_wo, wo, 2, d, s, b, CU_TENSOR_MAP_SWIZZLE_128B); }
        { cuuint64_t d[2] = {1792, 512}, s[1] = {3584}; cuuint32_t b[2] = {32, 64};
          encode(fn, &tm_wg, wgate, 2, d, s, b, CU_TENSOR_MAP_SWIZZLE_64B);
          encode(fn, &tm_wu, wup, 2, d, s, b, CU_TENSOR_MAP_SWIZZLE_64B); }
        { cuuint64_t d[2] = {512, 1792}, s[1] = {1024}; cuuint32_t b[2] = {64, 64};
          encode(fn, &tm_wd, wdown, 2, d, s, b, CU_TENSOR_MAP_SWIZZLE_128B); }
        cudaFuncSetAttribute(qkv_kernel, cudaFuncAttributeMaxDynamicSharedMemorySize, F_SMEM);
        cudaFuncSetAttribute(qkv_kernel, cudaFuncAttributePreferredSharedMemoryCarveout, 100);
        cudaFuncSetAttribute(attn_kernel, cudaFuncAttributeMaxDynamicSharedMemorySize, F_SMEM);
        cudaFuncSetAttribute(attn_kernel, cudaFuncAttributePreferredSharedMemoryCarveout, 100);
        cudaFuncSetAttribute(tail_kernel, cudaFuncAttributeMaxDynamicSharedMemorySize, F_SMEM);
        cudaFuncSetAttribute(tail_kernel, cudaFuncAttributePreferredSharedMemoryCarveout, 100);
        cached[0] = x; cached[1] = wqkv; cached[2] = wo; cached[3] = wgate; cached[4] = wup; cached[5] = wdown; cached[6] = out;
    }
    launch(qkv_kernel, 128, 384, F_SMEM, false, tm_x, tm_wqkv, x, wqkv);
    launch(attn_kernel, 132, 512, F_SMEM, true, wgate, wup, wo, wdown);
    launch(tail_kernel, 128, 384, F_SMEM, true, tm_wo, tm_wg, tm_wu, tm_wd, tm_out, x);
}
```

```cpp
#include <cuda_runtime.h>
#include <cuda_bf16.h>
#include <cuda.h>
#include <stdint.h>

#define K1_DIRECT
namespace {

constexpr int S_LEN = 2048, DM = 512, NH = 32, FF = 1792;

__device__ __align__(1024) __nv_bfloat16 g_qkv[3 * NH * S_LEN * 16];
__device__ __align__(1024) __nv_bfloat16 g_ao[S_LEN * DM];
__device__ __align__(1024) __nv_bfloat16 g_h[S_LEN * DM];
__device__ __align__(1024) __nv_bfloat16 g_g[S_LEN * FF];
__device__ __align__(16) float2 g_rowstat1[S_LEN];
__device__ float g_cs1_part[16 * 1536];
__device__ unsigned int g_cnt[32];
__device__ unsigned int g_cnt2[160];
__device__ float g_nrm[3 * NH * 128];
__device__ float2 g_hstat[S_LEN * 8];
__device__ float g_cs2[2 * FF];

#define TLDECL
#define TL(slot)
#define TLDUMP
#define TX(slot)
__device__ __forceinline__ uint32_t smem_u32(const void* p) { return (uint32_t)__cvta_generic_to_shared(p); }
__device__ __forceinline__ void mbar_init(uint32_t a, int c) { asm volatile("mbarrier.init.shared.b64 [%0], %1;" :: "r"(a), "r"(c)); }
__device__ __forceinline__ void mbar_expect(uint32_t a, int bytes) { asm volatile("mbarrier.arrive.expect_tx.shared.b64 _, [%0], %1;" :: "r"(a), "r"(bytes) : "memory"); }
__device__ __forceinline__ void mbar_arrive(uint32_t a) { asm volatile("mbarrier.arrive.shared.b64 _, [%0];" :: "r"(a) : "memory"); }
__device__ __forceinline__ void mbar_wait(uint32_t a, int parity) {
    uint32_t done;
    int it = 0;
    do {
        asm volatile("{\n.reg .pred p;\nmbarrier.try_wait.parity.shared.b64 p, [%1], %2;\nselp.u32 %0, 1, 0, p;\n}"
                     : "=r"(done) : "r"(a), "r"(parity) : "memory");
        if (++it > (1 << 24)) __trap();
    } while (!done);
}
__device__ __forceinline__ void bulk_g2s(uint32_t dst, const void* src, int bytes, uint32_t bar) {
    asm volatile("cp.async.bulk.shared::cluster.global.mbarrier::complete_tx::bytes [%0], [%1], %2, [%3];"
                 :: "r"(dst), "l"(src), "r"(bytes), "r"(bar) : "memory");
}
__device__ __forceinline__ void tma2d(uint32_t dst, const CUtensorMap* m, int c0, int c1, uint32_t bar) {
    asm volatile("cp.async.bulk.tensor.2d.shared::cluster.global.mbarrier::complete_tx::bytes [%0], [%1, {%3, %4}], [%2];"
                 :: "r"(dst), "l"(m), "r"(bar), "r"(c0), "r"(c1) : "memory");
}
__device__ __forceinline__ void tma3d(uint32_t dst, const CUtensorMap* m, int c0, int c1, int c2, uint32_t bar) {
    asm volatile("cp.async.bulk.tensor.3d.shared::cluster.global.mbarrier::complete_tx::bytes [%0], [%1, {%3, %4, %5}], [%2];"
                 :: "r"(dst), "l"(m), "r"(bar), "r"(c0), "r"(c1), "r"(c2) : "memory");
}
__device__ __forceinline__ void prefetch_tmap(const CUtensorMap* m) { asm volatile("prefetch.tensormap [%0];" :: "l"(m) : "memory"); }
__device__ __forceinline__ void pdl_wait() { asm volatile("griddepcontrol.wait;" ::: "memory"); }
__device__ __forceinline__ void pdl_launch() { asm volatile("griddepcontrol.launch_dependents;" ::: "memory"); }
__device__ __forceinline__ void fence_barrier_init() { asm volatile("fence.mbarrier_init.release.cluster;" ::: "memory"); }
__device__ __forceinline__ void fence_proxy_async() { asm volatile("fence.proxy.async.shared::cta;" ::: "memory"); }
__device__ __forceinline__ uint64_t make_desc(uint32_t saddr, uint32_t lbo, uint32_t sbo, uint32_t swz) {
    return (uint64_t)((saddr & 0x3FFFF) >> 4) | ((uint64_t)((lbo & 0x3FFFF) >> 4) << 16) |
           ((uint64_t)((sbo & 0x3FFFF) >> 4) << 32) | ((uint64_t)swz << 62);
}
#define WG_FENCE() asm volatile("wgmma.fence.sync.aligned;" ::: "memory")
#define WG_COMMIT() asm volatile("wgmma.commit_group.sync.aligned;" ::: "memory")
template <int N> __device__ __forceinline__ void wg_wait() { asm volatile("wgmma.wait_group.sync.aligned %0;" :: "n"(N) : "memory"); }
template <int N> __device__ __forceinline__ void fence_regs(float (&d)[N]) {
#pragma unroll
    for (int i = 0; i < N; i++) asm volatile("" : "+f"(d[i]) :: "memory");
}
__device__ __forceinline__ float ex2f(float x) { float y; asm("ex2.approx.ftz.f32 %0, %1;" : "=f"(y) : "f"(x)); return y; }
__device__ __forceinline__ float tanh_fast(float x) { float y; asm("tanh.approx.f32 %0, %1;" : "=f"(y) : "f"(x)); return y; }
__device__ __forceinline__ uint32_t pack_bf16(float lo, float hi) { uint32_t r; asm("cvt.rn.bf16x2.f32 %0, %1, %2;" : "=r"(r) : "f"(hi), "f"(lo)); return r; }
__device__ __forceinline__ float bf_lo(uint32_t u) { return __uint_as_float(u << 16); }
__device__ __forceinline__ float bf_hi(uint32_t u) { return __uint_as_float(u & 0xFFFF0000u); }
__device__ __forceinline__ uint32_t hfma2(uint32_t a, uint32_t b, uint32_t c) { uint32_t r; asm("fma.rn.f16x2 %0, %1, %2, %3;" : "=r"(r) : "r"(a), "r"(b), "r"(c)); return r; }
__device__ __forceinline__ uint32_t hmul2(uint32_t a, uint32_t b) { uint32_t r; asm("mul.rn.f16x2 %0, %1, %2;" : "=r"(r) : "r"(a), "r"(b)); return r; }
__device__ __forceinline__ unsigned int ld_acquire(const unsigned int* p) { unsigned int v; asm volatile("ld.acquire.gpu.u32 %0, [%1];" : "=r"(v) : "l"(p) : "memory"); return v; }
__device__ __forceinline__ void red_release(unsigned int* p) { asm volatile("red.release.gpu.global.add.u32 [%0], 1;" :: "l"(p) : "memory"); }
__device__ __forceinline__ void stsm4(uint32_t addr, uint32_t a, uint32_t b, uint32_t c, uint32_t d) {
    asm volatile("stmatrix.sync.aligned.m8n8.x4.shared.b16 [%0], {%1,%2,%3,%4};" :: "r"(addr), "r"(a), "r"(b), "r"(c), "r"(d) : "memory");
}
__device__ __forceinline__ void bulk_s2g(void* dst, uint32_t src, int bytes) {
    asm volatile("cp.async.bulk.global.shared::cta.bulk_group [%0], [%1], %2;" :: "l"(dst), "r"(src), "r"(bytes) : "memory");
}
__device__ __forceinline__ void bulk_commit() { asm volatile("cp.async.bulk.commit_group;" ::: "memory"); }
__device__ __forceinline__ void bulk_wait_all() { asm volatile("cp.async.bulk.wait_group 0;" ::: "memory"); }
__device__ __forceinline__ void bulk_wait_read() { asm volatile("cp.async.bulk.wait_group.read 0;" ::: "memory"); }
__device__ __forceinline__ void bar_sync(int id, int n) { asm volatile("bar.sync %0, %1;" :: "r"(id), "r"(n) : "memory"); }
__device__ __forceinline__ void bar_arrive(int id, int n) { asm volatile("bar.arrive %0, %1;" :: "r"(id), "r"(n) : "memory"); }
__device__ __forceinline__ float warp_sum(float v) {
#pragma unroll
    for (int o = 16; o; o >>= 1) v += __shfl_xor_sync(0xffffffffu, v, o);
    return v;
}
__device__ __forceinline__ float warp_max(float v) {
#pragma unroll
    for (int o = 16; o; o >>= 1) v = fmaxf(v, __shfl_xor_sync(0xffffffffu, v, o));
    return v;
}

__device__ __forceinline__ void wgmma_ss_n64(float (&d)[32], uint64_t adesc, uint64_t bdesc, int scale_d) {
    asm volatile("{\n.reg .pred p;\nsetp.ne.b32 p, %34, 0;\n"
      "wgmma.mma_async.sync.aligned.m64n64k16.f32.bf16.bf16 {%0,%1,%2,%3,%4,%5,%6,%7,%8,%9,%10,%11,%12,%13,%14,%15,%16,%17,%18,%19,%20,%21,%22,%23,%24,%25,%26,%27,%28,%29,%30,%31}, %32, %33, p, 1, 1, 0, 1;\n}"
      : "+f"(d[0]), "+f"(d[1]), "+f"(d[2]), "+f"(d[3]), "+f"(d[4]), "+f"(d[5]), "+f"(d[6]), "+f"(d[7]), "+f"(d[8]), "+f"(d[9]), "+f"(d[10]), "+f"(d[11]), "+f"(d[12]), "+f"(d[13]), "+f"(d[14]), "+f"(d[15]), "+f"(d[16]), "+f"(d[17]), "+f"(d[18]), "+f"(d[19]), "+f"(d[20]), "+f"(d[21]), "+f"(d[22]), "+f"(d[23]), "+f"(d[24]), "+f"(d[25]), "+f"(d[26]), "+f"(d[27]), "+f"(d[28]), "+f"(d[29]), "+f"(d[30]), "+f"(d[31])
      : "l"(adesc), "l"(bdesc), "r"(scale_d));
}
__device__ __forceinline__ void wgmma_ss_n96(float (&d)[48], uint64_t adesc, uint64_t bdesc, int scale_d) {
    asm volatile("{\n.reg .pred p;\nsetp.ne.b32 p, %50, 0;\n"
      "wgmma.mma_async.sync.aligned.m64n96k16.f32.bf16.bf16 {%0,%1,%2,%3,%4,%5,%6,%7,%8,%9,%10,%11,%12,%13,%14,%15,%16,%17,%18,%19,%20,%21,%22,%23,%24,%25,%26,%27,%28,%29,%30,%31,%32,%33,%34,%35,%36,%37,%38,%39,%40,%41,%42,%43,%44,%45,%46,%47}, %48, %49, p, 1, 1, 0, 1;\n}"
      : "+f"(d[0]), "+f"(d[1]), "+f"(d[2]), "+f"(d[3]), "+f"(d[4]), "+f"(d[5]), "+f"(d[6]), "+f"(d[7]), "+f"(d[8]), "+f"(d[9]), "+f"(d[10]), "+f"(d[11]), "+f"(d[12]), "+f"(d[13]), "+f"(d[14]), "+f"(d[15]), "+f"(d[16]), "+f"(d[17]), "+f"(d[18]), "+f"(d[19]), "+f"(d[20]), "+f"(d[21]), "+f"(d[22]), "+f"(d[23]), "+f"(d[24]), "+f"(d[25]), "+f"(d[26]), "+f"(d[27]), "+f"(d[28]), "+f"(d[29]), "+f"(d[30]), "+f"(d[31]), "+f"(d[32]), "+f"(d[33]), "+f"(d[34]), "+f"(d[35]), "+f"(d[36]), "+f"(d[37]), "+f"(d[38]), "+f"(d[39]), "+f"(d[40]), "+f"(d[41]), "+f"(d[42]), "+f"(d[43]), "+f"(d[44]), "+f"(d[45]), "+f"(d[46]), "+f"(d[47])
      : "l"(adesc), "l"(bdesc), "r"(scale_d));
}
__device__ __forceinline__ void wgmma_ss_n128(float (&d)[64], uint64_t adesc, uint64_t bdesc, int scale_d) {
    asm volatile("{\n.reg .pred p;\nsetp.ne.b32 p, %66, 0;\n"
      "wgmma.mma_async.sync.aligned.m64n128k16.f32.bf16.bf16 {%0,%1,%2,%3,%4,%5,%6,%7,%8,%9,%10,%11,%12,%13,%14,%15,%16,%17,%18,%19,%20,%21,%22,%23,%24,%25,%26,%27,%28,%29,%30,%31,%32,%33,%34,%35,%36,%37,%38,%39,%40,%41,%42,%43,%44,%45,%46,%47,%48,%49,%50,%51,%52,%53,%54,%55,%56,%57,%58,%59,%60,%61,%62,%63}, %64, %65, p, 1, 1, 0, 1;\n}"
      : "+f"(d[0]), "+f"(d[1]), "+f"(d[2]), "+f"(d[3]), "+f"(d[4]), "+f"(d[5]), "+f"(d[6]), "+f"(d[7]), "+f"(d[8]), "+f"(d[9]), "+f"(d[10]), "+f"(d[11]), "+f"(d[12]), "+f"(d[13]), "+f"(d[14]), "+f"(d[15]), "+f"(d[16]), "+f"(d[17]), "+f"(d[18]), "+f"(d[19]), "+f"(d[20]), "+f"(d[21]), "+f"(d[22]), "+f"(d[23]), "+f"(d[24]), "+f"(d[25]), "+f"(d[26]), "+f"(d[27]), "+f"(d[28]), "+f"(d[29]), "+f"(d[30]), "+f"(d[31]), "+f"(d[32]), "+f"(d[33]), "+f"(d[34]), "+f"(d[35]), "+f"(d[36]), "+f"(d[37]), "+f"(d[38]), "+f"(d[39]), "+f"(d[40]), "+f"(d[41]), "+f"(d[42]), "+f"(d[43]), "+f"(d[44]), "+f"(d[45]), "+f"(d[46]), "+f"(d[47]), "+f"(d[48]), "+f"(d[49]), "+f"(d[50]), "+f"(d[51]), "+f"(d[52]), "+f"(d[53]), "+f"(d[54]), "+f"(d[55]), "+f"(d[56]), "+f"(d[57]), "+f"(d[58]), "+f"(d[59]), "+f"(d[60]), "+f"(d[61]), "+f"(d[62]), "+f"(d[63])
      : "l"(adesc), "l"(bdesc), "r"(scale_d));
}
__device__ __forceinline__ void wgmma_ss_n192(float (&d)[96], uint64_t adesc, uint64_t bdesc, int scale_d) {
    asm volatile("{\n.reg .pred p;\nsetp.ne.b32 p, %98, 0;\n"
      "wgmma.mma_async.sync.aligned.m64n192k16.f32.bf16.bf16 {%0,%1,%2,%3,%4,%5,%6,%7,%8,%9,%10,%11,%12,%13,%14,%15,%16,%17,%18,%19,%20,%21,%22,%23,%24,%25,%26,%27,%28,%29,%30,%31,%32,%33,%34,%35,%36,%37,%38,%39,%40,%41,%42,%43,%44,%45,%46,%47,%48,%49,%50,%51,%52,%53,%54,%55,%56,%57,%58,%59,%60,%61,%62,%63,%64,%65,%66,%67,%68,%69,%70,%71,%72,%73,%74,%75,%76,%77,%78,%79,%80,%81,%82,%83,%84,%85,%86,%87,%88,%89,%90,%91,%92,%93,%94,%95}, %96, %97, p, 1, 1, 0, 1;\n}"
      : "+f"(d[0]), "+f"(d[1]), "+f"(d[2]), "+f"(d[3]), "+f"(d[4]), "+f"(d[5]), "+f"(d[6]), "+f"(d[7]), "+f"(d[8]), "+f"(d[9]), "+f"(d[10]), "+f"(d[11]), "+f"(d[12]), "+f"(d[13]), "+f"(d[14]), "+f"(d[15]), "+f"(d[16]), "+f"(d[17]), "+f"(d[18]), "+f"(d[19]), "+f"(d[20]), "+f"(d[21]), "+f"(d[22]), "+f"(d[23]), "+f"(d[24]), "+f"(d[25]), "+f"(d[26]), "+f"(d[27]), "+f"(d[28]), "+f"(d[29]), "+f"(d[30]), "+f"(d[31]), "+f"(d[32]), "+f"(d[33]), "+f"(d[34]), "+f"(d[35]), "+f"(d[36]), "+f"(d[37]), "+f"(d[38]), "+f"(d[39]), "+f"(d[40]), "+f"(d[41]), "+f"(d[42]), "+f"(d[43]), "+f"(d[44]), "+f"(d[45]), "+f"(d[46]), "+f"(d[47]), "+f"(d[48]), "+f"(d[49]), "+f"(d[50]), "+f"(d[51]), "+f"(d[52]), "+f"(d[53]), "+f"(d[54]), "+f"(d[55]), "+f"(d[56]), "+f"(d[57]), "+f"(d[58]), "+f"(d[59]), "+f"(d[60]), "+f"(d[61]), "+f"(d[62]), "+f"(d[63]), "+f"(d[64]), "+f"(d[65]), "+f"(d[66]), "+f"(d[67]), "+f"(d[68]), "+f"(d[69]), "+f"(d[70]), "+f"(d[71]), "+f"(d[72]), "+f"(d[73]), "+f"(d[74]), "+f"(d[75]), "+f"(d[76]), "+f"(d[77]), "+f"(d[78]), "+f"(d[79]), "+f"(d[80]), "+f"(d[81]), "+f"(d[82]), "+f"(d[83]), "+f"(d[84]), "+f"(d[85]), "+f"(d[86]), "+f"(d[87]), "+f"(d[88]), "+f"(d[89]), "+f"(d[90]), "+f"(d[91]), "+f"(d[92]), "+f"(d[93]), "+f"(d[94]), "+f"(d[95])
      : "l"(adesc), "l"(bdesc), "r"(scale_d));
}
__device__ __forceinline__ void qk_wgmma_n64(float (&d)[32], const uint32_t (&a)[4], uint64_t desc) {
    asm volatile("wgmma.mma_async.sync.aligned.m64n64k16.f32.bf16.bf16 {%0,%1,%2,%3,%4,%5,%6,%7,%8,%9,%10,%11,%12,%13,%14,%15,%16,%17,%18,%19,%20,%21,%22,%23,%24,%25,%26,%27,%28,%29,%30,%31}, {%32,%33,%34,%35}, %36, 0, 1, 1, 0;"
      : "=f"(d[0]), "=f"(d[1]), "=f"(d[2]), "=f"(d[3]), "=f"(d[4]), "=f"(d[5]), "=f"(d[6]), "=f"(d[7]), "=f"(d[8]), "=f"(d[9]), "=f"(d[10]), "=f"(d[11]), "=f"(d[12]), "=f"(d[13]), "=f"(d[14]), "=f"(d[15]), "=f"(d[16]), "=f"(d[17]), "=f"(d[18]), "=f"(d[19]), "=f"(d[20]), "=f"(d[21]), "=f"(d[22]), "=f"(d[23]), "=f"(d[24]), "=f"(d[25]), "=f"(d[26]), "=f"(d[27]), "=f"(d[28]), "=f"(d[29]), "=f"(d[30]), "=f"(d[31])
      : "r"(a[0]), "r"(a[1]), "r"(a[2]), "r"(a[3]), "l"(desc));
}

__device__ __forceinline__ void pv_wgmma(float (&d)[12], uint32_t a0, uint32_t a1, uint32_t a2, uint32_t a3, uint64_t desc) {
    asm volatile("wgmma.mma_async.sync.aligned.m64n24k16.f32.bf16.bf16 {%0,%1,%2,%3,%4,%5,%6,%7,%8,%9,%10,%11}, {%12,%13,%14,%15}, %16, 1, 1, 1, 1;"
      : "+f"(d[0]), "+f"(d[1]), "+f"(d[2]), "+f"(d[3]), "+f"(d[4]), "+f"(d[5]), "+f"(d[6]), "+f"(d[7]), "+f"(d[8]), "+f"(d[9]), "+f"(d[10]), "+f"(d[11])
      : "r"(a0), "r"(a1), "r"(a2), "r"(a3), "l"(desc));
}

__device__ __forceinline__ void tile_of(int bid, int& mb, int& nt) {
    int grp = bid >> 4, in = bid & 15;
    mb = (grp >> 1) * 4 + (in >> 2);
    nt = (grp & 1) * 4 + (in & 3);
}

constexpr int K1_STAGES = 5, K1_STAGE = 16384 + 24576;
constexpr int K1_BAR = K1_STAGES * K1_STAGE, K1_RS = K1_BAR + 128, K1_CS = K1_RS + 1024, K1_SMEM = K1_CS + 768;

__device__ __forceinline__ float2 row_stats_regs(uint4 a, uint4 b) {
    float v[16];
    v[0] = bf_lo(a.x); v[1] = bf_hi(a.x); v[2] = bf_lo(a.y); v[3] = bf_hi(a.y);
    v[4] = bf_lo(a.z); v[5] = bf_hi(a.z); v[6] = bf_lo(a.w); v[7] = bf_hi(a.w);
    v[8] = bf_lo(b.x); v[9] = bf_hi(b.x); v[10] = bf_lo(b.y); v[11] = bf_hi(b.y);
    v[12] = bf_lo(b.z); v[13] = bf_hi(b.z); v[14] = bf_lo(b.w); v[15] = bf_hi(b.w);
    float s = 0.f;
#pragma unroll
    for (int i = 0; i < 16; i++) s += v[i];
    float mean = warp_sum(s) * (1.0f / DM);
    float q = 0.f;
#pragma unroll
    for (int i = 0; i < 16; i++) { float d = v[i] - mean; q = fmaf(d, d, q); }
    float var = warp_sum(q) * (1.0f / DM);
    float rstd = rsqrtf(var + 1e-5f);
    return make_float2(rstd, -mean * rstd);
}
__device__ __forceinline__ float2 row_stats_x(const __nv_bfloat16* x, int row, int lane) {
    const uint4* p = (const uint4*)(x + (size_t)row * DM);
    return row_stats_regs(__ldg(p + lane), __ldg(p + 32 + lane));
}
__device__ __forceinline__ void colsum8(const __nv_bfloat16* w, int ld, int col, int k0, int nk, float (&s)[8]) {
#pragma unroll
    for (int i = 0; i < 8; i++) s[i] = 0.f;
    for (int k = k0; k < k0 + nk; k += 8) {
        uint4 u[8];
#pragma unroll
        for (int i = 0; i < 8; i++) u[i] = __ldg((const uint4*)(w + (size_t)(k + i) * ld + col));
#pragma unroll
        for (int i = 0; i < 8; i++) {
            s[0] += bf_lo(u[i].x); s[1] += bf_hi(u[i].x); s[2] += bf_lo(u[i].y); s[3] += bf_hi(u[i].y);
            s[4] += bf_lo(u[i].z); s[5] += bf_hi(u[i].z); s[6] += bf_lo(u[i].w); s[7] += bf_hi(u[i].w);
        }
    }
}
__device__ __forceinline__ bool wait_count(const unsigned int* p, unsigned int target, int lane) {
    int ok = 1;
    if (lane == 0) {
        int it = 0;
        while (ld_acquire(p) < target) { if (++it > (1 << 18)) { ok = 0; break; } }
    }
    ok = __shfl_sync(0xffffffffu, ok, 0);
    return ok != 0;
}

__global__ void __launch_bounds__(384, 1)
qkv_kernel(const __grid_constant__ CUtensorMap tm_x, const __grid_constant__ CUtensorMap tm_w,
           const __nv_bfloat16* __restrict__ x, const __nv_bfloat16* __restrict__ wqkv) {
    extern __shared__ __align__(1024) unsigned char smem[];
    const uint32_t sb = smem_u32(smem);
    const int tid = threadIdx.x, warp = __shfl_sync(0xffffffffu, tid >> 5, 0), lane = tid & 31;
    TLDECL
    TL(0);
    int mb, nt;
    tile_of(blockIdx.x, mb, nt);
    const uint32_t full = sb + K1_BAR, empty = full + 40, auxb = full + 80;
    if (tid == 0) {
        prefetch_tmap(&tm_x); prefetch_tmap(&tm_w);
        for (int i = 0; i < K1_STAGES; i++) { mbar_init(full + 8 * i, 1); mbar_init(empty + 8 * i, 8); }
        mbar_init(auxb, 3);
        fence_barrier_init();
    }
    __syncthreads();
    pdl_launch();
    if (warp == 0) {
        if (blockIdx.x == 0) for (int i = lane; i < 160; i += 32) g_cnt2[i] = 0;
        if (lane == 0) {
            for (int kb = 0; kb < 8; kb++) {
                int s = kb % K1_STAGES;
                if (kb >= K1_STAGES) mbar_wait(empty + 8 * s, 0);
                mbar_expect(full + 8 * s, K1_STAGE);
                tma2d(sb + s * K1_STAGE, &tm_x, kb * 64, mb * 128, full + 8 * s);
                tma3d(sb + s * K1_STAGE + 16384, &tm_w, 0, kb * 64, nt * 3, full + 8 * s);
            }
        }
    } else if (warp < 4) {
        float2* s_rs = (float2*)(smem + K1_RS);
        float* s_cs = (float*)(smem + K1_CS);
        if (warp < 3) {
            const int r0 = mb * 128 + nt * 16 + (warp - 1) * 8;
            uint4 u[16];
#pragma unroll
            for (int i = 0; i < 8; i++) {
                const uint4* p = (const uint4*)(x + (size_t)(r0 + i) * DM);
                u[2 * i] = __ldg(p + lane); u[2 * i + 1] = __ldg(p + 32 + lane);
            }
            float2 mine = make_float2(0.f, 0.f);
#pragma unroll
            for (int i = 0; i < 8; i++) {
                float2 st = row_stats_regs(u[2 * i], u[2 * i + 1]);
                if (lane == i) mine = st;
            }
            if (lane < 8) g_rowstat1[r0 + lane] = mine;
            __syncwarp();
            if (lane == 0) red_release(&g_cnt[mb]);
        } else {
            uint4 u[24];
#pragma unroll
            for (int c = 0; c < 3; c++)
#pragma unroll
                for (int i = 0; i < 8; i++)
                    u[c * 8 + i] = __ldg((const uint4*)(wqkv + (size_t)(mb * 32 + (lane >> 3) * 8 + i) * 1536 + nt * 192 + (c * 8 + (lane & 7)) * 8));
#pragma unroll
            for (int c = 0; c < 3; c++) {
                float cs[8];
#pragma unroll
                for (int i = 0; i < 8; i++) cs[i] = 0.f;
#pragma unroll
                for (int i = 0; i < 8; i++) {
                    const uint4 w = u[c * 8 + i];
                    cs[0] += bf_lo(w.x); cs[1] += bf_hi(w.x); cs[2] += bf_lo(w.y); cs[3] += bf_hi(w.y);
                    cs[4] += bf_lo(w.z); cs[5] += bf_hi(w.z); cs[6] += bf_lo(w.w); cs[7] += bf_hi(w.w);
                }
#pragma unroll
                for (int i = 0; i < 8; i++) {
                    cs[i] += __shfl_xor_sync(0xffffffffu, cs[i], 8);
                    cs[i] += __shfl_xor_sync(0xffffffffu, cs[i], 16);
                }
                if (lane < 8) {
                    float4* d = (float4*)(g_cs1_part + mb * 1536 + nt * 192 + (c * 8 + lane) * 8);
                    d[0] = make_float4(cs[0], cs[1], cs[2], cs[3]);
                    d[1] = make_float4(cs[4], cs[5], cs[6], cs[7]);
                }
            }
            __syncwarp();
            if (lane == 0) red_release(&g_cnt[16 + nt]);
        }
        TX(8 + warp);
        if (warp == 1) {
            if (wait_count(&g_cnt[mb], 16, lane)) {
#pragma unroll
                for (int i = 0; i < 4; i++) s_rs[lane + 32 * i] = __ldcg(&g_rowstat1[mb * 128 + lane + 32 * i]);
            } else {
                for (int i = 0; i < 128; i++) {
                    float2 st = row_stats_x(x, mb * 128 + i, lane);
                    if (lane == 0) s_rs[i] = st;
                }
            }
        } else {
            int c0 = (warp - 2) * 96;
            if (wait_count(&g_cnt[16 + nt], 16, lane)) {
#pragma unroll
                for (int i = 0; i < 3; i++) {
                    float s = 0.f;
#pragma unroll
                    for (int p = 0; p < 16; p++) s += __ldcg(&g_cs1_part[p * 1536 + nt * 192 + c0 + lane + 32 * i]);
                    s_cs[c0 + lane + 32 * i] = s;
                }
            } else if (lane < 12) {
                float s[8];
                colsum8(wqkv, 1536, nt * 192 + c0 + lane * 8, 0, 512, s);
#pragma unroll
                for (int i = 0; i < 8; i++) s_cs[c0 + lane * 8 + i] = s[i];
            }
        }
        __syncwarp();
        TX(12 + warp);
        if (lane == 0) mbar_arrive(auxb);
        bar_sync(2, 256 + 96);
        const int a = tid - 32;
        {
            const int hh = a >> 3, w = a & 7;
            const float4* p = (const float4*)(smem + 49152) + (hh * 256 + w * 32) / 2;
            float m = 0.f;
#pragma unroll
            for (int i = 0; i < 8; i++) {
                const int ii = (i + a) & 7;
                float4 u = p[2 * ii], v = p[2 * ii + 1];
                float n0 = u.x + u.z + v.x + v.z, n1 = u.y + u.w + v.y + v.w;
                if (!(n0 <= 3.0e38f) || !(n1 <= 3.0e38f)) m = __int_as_float(0x7f800000);
                m = fmaxf(m, fmaxf(n0, n1));
            }
            const int col0 = nt * 192 + hh * 16;
            g_nrm[((col0 >> 9) * NH + ((col0 & 511) >> 4)) * 128 + mb * 8 + w] = m;
        }
        if (a < 24) bulk_wait_all();
        TL(27);
        TLDUMP;
    } else {
        const int wgi = (warp >> 2) - 1, ww = warp & 3;
        float acc[96];
#pragma unroll 1
        for (int kb = 0; kb < 8; kb++) {
            int s = kb % K1_STAGES;
            mbar_wait(full + 8 * s, (kb / K1_STAGES) & 1);
            if (warp == 4) TX(kb);
            uint64_t ad = make_desc(sb + s * K1_STAGE + wgi * 8192, 16, 1024, 1);
            uint64_t bd = make_desc(sb + s * K1_STAGE + 16384, 8192, 1024, 1);
            WG_FENCE();
#pragma unroll
            for (int k = 0; k < 4; k++) wgmma_ss_n192(acc, ad + k * 2, bd + k * 128, (kb | k) != 0);
            WG_COMMIT();
            if (kb > 0) {
                wg_wait<1>();
                if (lane == 0) mbar_arrive(empty + 8 * ((kb - 1) % K1_STAGES));
            }
        }
        wg_wait<0>();
        fence_regs(acc);
        TL(1);
        if (warp == 4) TX(16);
        mbar_wait(auxb, 0);
        if (warp == 4) TX(17);
        bar_sync(1, 256);
        const float2* s_rs = (const float2*)(smem + K1_RS);
        const float* s_cs = (const float*)(smem + K1_CS);
        const int g = lane >> 2, t = lane & 3;
        const int rl = wgi * 64 + ww * 16 + g;
        const float2 st0 = s_rs[rl], st1 = s_rs[rl + 8];
        const float QS = 0.25f * 1.4426950408889634f;
        const uint32_t stg = sb + ((lane >> 4) * 16 + wgi * 8 + ww * 2 + ((lane >> 3) & 1)) * 128 + (lane & 7) * 16;
        float2* s_np = (float2*)(smem + 49152) + (warp - 4) * 32 + lane;
#pragma unroll
        for (int hh = 0; hh < 12; hh++) {
            const int which = (nt * 192 + hh * 16) >> 9;
            const float sc = (which == 0) ? QS : 1.0f;
            const float a0 = st0.x * sc, b0 = st0.y * sc, a1 = st1.x * sc, b1 = st1.y * sc;
            const float2 c0 = *(const float2*)(s_cs + 16 * hh + 2 * t), c1 = *(const float2*)(s_cs + 16 * hh + 8 + 2 * t);
            const float* a = acc + 8 * hh;
            float v0 = fmaf(a0, a[0], b0 * c0.x), v1 = fmaf(a0, a[1], b0 * c0.y), v2 = fmaf(a1, a[2], b1 * c0.x), v3 = fmaf(a1, a[3], b1 * c0.y);
            float v4 = fmaf(a0, a[4], b0 * c1.x), v5 = fmaf(a0, a[5], b0 * c1.y), v6 = fmaf(a1, a[6], b1 * c1.x), v7 = fmaf(a1, a[7], b1 * c1.y);
            {
                const int head = ((nt * 192 + hh * 16) & 511) >> 4;
                uint32_t* o = (uint32_t*)g_qkv + ((size_t)((which * NH + head) * 2) * 256 + mb * 16 + wgi * 8 + ww * 2) * 32 + lane;
                o[0] = pack_bf16(v0, v1); o[32] = pack_bf16(v2, v3); o[8192] = pack_bf16(v4, v5); o[8192 + 32] = pack_bf16(v6, v7);
            }
            s_np[hh * 256] = make_float2(fmaf(v0, v0, fmaf(v1, v1, fmaf(v4, v4, v5 * v5))), fmaf(v2, v2, fmaf(v3, v3, fmaf(v6, v6, v7 * v7))));
        }
        fence_proxy_async();
        bar_arrive(2, 256 + 96);
        TL(2);
        TLDUMP;
    }
}

constexpr int AT_K = 0, AT_V = 65536, AT_ONES = 131072, AT_BAR = 163840, AT_SMEM = AT_BAR + 128;
#define POLY_MASK 0xAD6A

__device__ __forceinline__ uint32_t exp2_pair_poly(float x0, float x1) {
    uint32_t t0 = __float_as_uint(x0 + 32895.0f);
    uint32_t t1 = __float_as_uint(x1 + 32895.0f);
    uint32_t gd = __byte_perm(t0, t1, 0x6420);
    uint32_t wm = __byte_perm(t0, t1, 0x5612);
    uint32_t v = hfma2(gd, 0x71477147u, 0x354f354fu);
    uint32_t z = hmul2(v, gd);
    return (wm >> 1) + z;
}
__device__ __forceinline__ uint32_t exp2_pair_mufu(float x0, float x1) { return pack_bf16(ex2f(x0), ex2f(x1)); }
template <uint32_t MASK>
__device__ __forceinline__ void exp_blocks(const float (&s)[32], uint32_t (&p)[16]) {
#pragma unroll
    for (int b = 0; b < 8; b++) {
        if ((MASK >> b) & 1) {
            p[2 * b] = exp2_pair_poly(s[4 * b], s[4 * b + 1]);
            p[2 * b + 1] = exp2_pair_poly(s[4 * b + 2], s[4 * b + 3]);
        } else {
            p[2 * b] = exp2_pair_mufu(s[4 * b], s[4 * b + 1]);
            p[2 * b + 1] = exp2_pair_mufu(s[4 * b + 2], s[4 * b + 3]);
        }
    }
}
#define PV4(P) _Pragma("unroll") for (int i = 0; i < 4; i++) { pv_wgmma(o, P[4 * i], P[4 * i + 1], P[4 * i + 2], P[4 * i + 3], vd); vd += 16; }

__device__ __forceinline__ void attn_store(float (&o)[12], int row0, int head, int lane) {
    float l0 = __shfl_sync(0xffffffffu, o[8], lane & 28);
    float l1 = __shfl_sync(0xffffffffu, o[10], lane & 28);
    float r0 = 1.0f / l0, r1 = 1.0f / l1;
    uint32_t* op = (uint32_t*)g_ao;
    int mb = row0 >> 7, rg = (row0 & 127) >> 3;
    int kb = head >> 2, kc = (head & 3) * 2;
    size_t base = (((size_t)(mb * 8 + kb) * 8 + kc) * 16 + rg) * 32 + lane;
    op[base] = pack_bf16(o[0] * r0, o[1] * r0);
    op[base + 32] = pack_bf16(o[2] * r1, o[3] * r1);
    op[base + 16 * 32] = pack_bf16(o[4] * r0, o[5] * r0);
    op[base + 16 * 32 + 32] = pack_bf16(o[6] * r1, o[7] * r1);
}

__device__ __forceinline__ void attn_load_q(uint32_t (&q)[4], const __nv_bfloat16* gq, int row0, int lane) {
    const uint32_t* qp = (const uint32_t*)gq;
    int j0 = row0 >> 3;
    q[0] = __ldcg(qp + (0 * 256 + j0) * 32 + lane);
    q[1] = __ldcg(qp + (0 * 256 + j0 + 1) * 32 + lane);
    q[2] = __ldcg(qp + (1 * 256 + j0) * 32 + lane);
    q[3] = __ldcg(qp + (1 * 256 + j0 + 1) * 32 + lane);
}

__device__ __forceinline__ void attn_tile_safe(const uint32_t (&q)[4], uint64_t kd, uint64_t vd, int row0, int head, int lane) {
    float o[12];
#pragma unroll
    for (int i = 0; i < 12; i++) o[i] = 0.f;
    float m0 = -INFINITY, m1 = -INFINITY;
    fence_regs(o);
#pragma unroll 1
    for (int j = 0; j < 32; j++) {
        float s[32];
        uint32_t p[16];
        WG_FENCE();
        qk_wgmma_n64(s, q, kd); kd += 64;
        WG_COMMIT();
        wg_wait<0>();
        fence_regs(s);
        fence_regs(o);
        float x0 = m0, x1 = m1;
#pragma unroll
        for (int b = 0; b < 8; b++) {
            x0 = fmaxf(x0, fmaxf(s[4 * b], s[4 * b + 1]));
            x1 = fmaxf(x1, fmaxf(s[4 * b + 2], s[4 * b + 3]));
        }
        x0 = fmaxf(x0, __shfl_xor_sync(0xffffffffu, x0, 1)); x0 = fmaxf(x0, __shfl_xor_sync(0xffffffffu, x0, 2));
        x1 = fmaxf(x1, __shfl_xor_sync(0xffffffffu, x1, 1)); x1 = fmaxf(x1, __shfl_xor_sync(0xffffffffu, x1, 2));
        float al0 = ex2f(m0 - x0), al1 = ex2f(m1 - x1);
        m0 = x0; m1 = x1;
#pragma unroll
        for (int i = 0; i < 3; i++) { o[4 * i] *= al0; o[4 * i + 1] *= al0; o[4 * i + 2] *= al1; o[4 * i + 3] *= al1; }
#pragma unroll
        for (int b = 0; b < 8; b++) {
            p[2 * b] = exp2_pair_mufu(s[4 * b] - m0, s[4 * b + 1] - m0);
            p[2 * b + 1] = exp2_pair_mufu(s[4 * b + 2] - m1, s[4 * b + 3] - m1);
        }
        fence_regs(o);
        WG_FENCE();
        PV4(p);
        WG_COMMIT();
        wg_wait<0>();
        fence_regs(o);
    }
    attn_store(o, row0, head, lane);
}

__global__ void __launch_bounds__(512, 1)
attn_kernel(const __nv_bfloat16* __restrict__ wg_, const __nv_bfloat16* __restrict__ wu_,
            const __nv_bfloat16* __restrict__ wo_, const __nv_bfloat16* __restrict__ wd_) {
    extern __shared__ __align__(1024) unsigned char smem[];
    const uint32_t sb = smem_u32(smem);
    const int tid = threadIdx.x, wg = tid >> 7, warp = (tid >> 5) & 3, lane = tid & 31;
    TLDECL
    pdl_launch();
    if (blockIdx.x >= 128) {
        const int e = blockIdx.x - 128;
        const __nv_bfloat16* w = (e < 2) ? wg_ : wu_;
        float* red = (float*)smem;
        const int cgrp = tid & 127, kq = tid >> 7;
        if (cgrp < 112) {
            float s[8];
            colsum8(w, FF, (e & 1) * 896 + cgrp * 8, kq * 128, 128, s);
#pragma unroll
            for (int i = 0; i < 8; i++) red[kq * 896 + cgrp * 8 + i] = s[i];
        }
        __syncthreads();
        for (int c = tid; c < 896; c += 512)
            g_cs2[(e >> 1) * FF + (e & 1) * 896 + c] = red[c] + red[896 + c] + red[1792 + c] + red[2688 + c];
        if (tid < 32) {
            const char* p0 = (const char*)wo_ + e * (DM * DM * 2 / 4);
            for (int i = lane; i < 32; i += 32)
                asm volatile("cp.async.bulk.prefetch.L2.global [%0], %1;" :: "l"(p0 + i * 4096), "r"(4096) : "memory");
            const char* p1 = (const char*)wd_ + e * (FF * DM * 2 / 4);
            for (int i = lane; i < 112; i += 32)
                asm volatile("cp.async.bulk.prefetch.L2.global [%0], %1;" :: "l"(p1 + i * 4096), "r"(4096) : "memory");
        }
        return;
    }
    const int head = blockIdx.x >> 2, qq = blockIdx.x & 3;
    const __nv_bfloat16* gq = g_qkv + (size_t)head * (S_LEN * 16);
    const __nv_bfloat16* gk = g_qkv + (size_t)(NH + head) * (S_LEN * 16);
    const __nv_bfloat16* gv = g_qkv + (size_t)(2 * NH + head) * (S_LEN * 16);
    if (tid == 0) {
        for (int i = 0; i < 8; i++) mbar_init(sb + AT_BAR + 8 * i, 1);
        fence_barrier_init();
    }
    {
        uint4 one = make_uint4(0x00003F80u, 0, 0, 0);
#pragma unroll
        for (int i = 0; i < 4; i++) *(uint4*)(smem + AT_ONES + (i * 512 + tid) * 16) = one;
        fence_proxy_async();
    }
    __syncthreads();
    TL(3);
    pdl_wait();
    TL(4);
    auto load_kv = [&](int i) {
        uint32_t bar = sb + AT_BAR + 8 * i;
        mbar_expect(bar, 16384);
        bulk_g2s(sb + AT_K + i * 4096, gk + i * 2048, 4096, bar);
        bulk_g2s(sb + AT_K + 32768 + i * 4096, gk + 16384 + i * 2048, 4096, bar);
        bulk_g2s(sb + AT_V + i * 4096, gv + i * 2048, 4096, bar);
        bulk_g2s(sb + AT_V + 32768 + i * 4096, gv + 16384 + i * 2048, 4096, bar);
    };
    if (tid == 0) { load_kv(0); load_kv(1); }
    uint32_t q[4], q2[4];
    attn_load_q(q, gq, qq * 512 + wg * 64 + warp * 16, lane);
    attn_load_q(q2, gq, qq * 512 + (4 + wg) * 64 + warp * 16, lane);
    bool fast;
    {
        const float* nq = g_nrm + (0 * NH + head) * 128 + qq * 32;
        const float* nk = g_nrm + (1 * NH + head) * 128;
        const float* nv = g_nrm + (2 * NH + head) * 128;
        float4 k4 = __ldcg((const float4*)nk + lane), v4 = __ldcg((const float4*)nv + lane);
        float qm = warp_max(__ldcg(nq + lane));
        float km = warp_max(fmaxf(fmaxf(k4.x, k4.y), fmaxf(k4.z, k4.w)));
        float vm = warp_max(fmaxf(fmaxf(v4.x, v4.y), fmaxf(v4.z, v4.w)));
        fast = __all_sync(0xffffffffu, (qm * km <= 3500.0f) && (vm <= 1.0e24f));
    }
    TL(24);
    const uint64_t kdesc0 = make_desc(sb + AT_K, 32768, 128, 0);
    const uint64_t vdesc0 = make_desc(sb + AT_V, 128, 32768, 0);
    if (!fast) {
        if (tid == 0) for (int i = 2; i < 8; i++) load_kv(i);
        for (int i = 0; i < 8; i++) mbar_wait(sb + AT_BAR + 8 * i, 0);
#pragma unroll 1
        for (int tile = 0; tile < 2; tile++) {
            const int row0 = qq * 512 + (tile * 4 + wg) * 64 + warp * 16;
            attn_tile_safe(q, kdesc0, vdesc0, row0, head, lane);
#pragma unroll
            for (int i = 0; i < 4; i++) q[i] = q2[i];
        }
        return;
    }
#pragma unroll 1
    for (int tile = 0; tile < 2; tile++) {
        const int row0 = qq * 512 + (tile * 4 + wg) * 64 + warp * 16;
        float o[12];
#pragma unroll
        for (int i = 0; i < 12; i++) o[i] = 0.f;
        fence_regs(o);
        float sa[32];
        uint32_t pa[16];
        uint64_t kd = kdesc0, vd = vdesc0;
        if (tile == 0) { mbar_wait(sb + AT_BAR, 0); TL(25); }
        WG_FENCE();
        qk_wgmma_n64(sa, q, kd); kd += 64;
        WG_COMMIT();
#pragma unroll 1
        for (int jj = 0; jj < 8; jj++) {
            if (tile == 0 && jj < 7) {
                if (tid == 0 && jj < 6) load_kv(jj + 2);
                mbar_wait(sb + AT_BAR + 8 * (jj + 1), 0);
            }
            if (wg == 0 && warp == 0) TX(128 + tile * 8 + jj);
#pragma unroll
            for (int j = 0; j < 4; j++) {
                wg_wait<0>();
                fence_regs(sa);
                if (j & 1) exp_blocks<(POLY_MASK >> 8)>(sa, pa); else exp_blocks<(POLY_MASK & 255)>(sa, pa);
                WG_FENCE();
                qk_wgmma_n64(sa, q, kd); kd += 64;
                PV4(pa);
                WG_COMMIT();
            }
        }
        wg_wait<0>();
        fence_regs(o);
        fence_regs(sa);
        if (tile == 0) TL(26);
        attn_store(o, row0, head, lane);
#pragma unroll
        for (int i = 0; i < 4; i++) q[i] = q2[i];
    }
    TL(5);
    TLDUMP;
}

constexpr int F_R2 = 131072, F_X = 196608, F_BAR = 229376;
constexpr int F_RS = F_BAR + 256, F_CS = F_RS + 1024, F_SMEM = F_CS + 1792;
enum { B_FA = 0, B_HF = 4, B_BF = 8, B_BE = 11, B_CF = 14, B_CE = 20, B_ADONE = 26, B_BDONE = 27, B_XC = 28, B_PRDY = 29, B_AUX = 30, B_NUM = 31 };

__device__ __forceinline__ uint32_t mapa(uint32_t a, uint32_t rank) { uint32_t r; asm("mapa.shared::cluster.u32 %0, %1, %2;" : "=r"(r) : "r"(a), "r"(rank)); return r; }
__device__ __forceinline__ void st_async4(uint32_t dst, float a, float b, float c, float d, uint32_t bar) {
    asm volatile("st.async.weak.shared::cluster.mbarrier::complete_tx::bytes.v4.f32 [%0], {%1,%2,%3,%4}, [%5];"
                 :: "r"(dst), "f"(a), "f"(b), "f"(c), "f"(d), "r"(bar) : "memory");
}
__device__ __forceinline__ void mbar_arrive_remote(uint32_t a) { asm volatile("mbarrier.arrive.relaxed.cluster.shared::cluster.b64 _, [%0];" :: "r"(a) : "memory"); }
__device__ __forceinline__ void mbar_wait_cluster(uint32_t a, int parity) {
    uint32_t done;
    int it = 0;
    do {
        asm volatile("{\n.reg .pred p;\nmbarrier.try_wait.parity.acquire.cluster.shared::cta.b64 p, [%1], %2;\nselp.u32 %0, 1, 0, p;\n}"
                     : "=r"(done) : "r"(a), "r"(parity) : "memory");
        if (++it > (1 << 24)) __trap();
    } while (!done);
}
__device__ __forceinline__ void poll_count(const unsigned int* p, unsigned int target) {
    int it = 0;
    while (ld_acquire(p) < target) { if (++it > (1 << 22)) __trap(); }
    asm volatile("fence.proxy.async.global;" ::: "memory");
}
__device__ __forceinline__ void tma2d_store(const CUtensorMap* m, uint32_t src, int c0, int c1) {
    asm volatile("cp.async.bulk.tensor.2d.global.shared::cta.bulk_group [%0, {%2, %3}], [%1];" :: "l"(m), "r"(src), "r"(c0), "r"(c1) : "memory");
}
__device__ __forceinline__ int c_kblock(int i, int r) {
    if (i < 6) { const int e = 2 * i + r, m = e / 3, k = e - 3 * m; return 7 * m + (k == 2 ? 4 : k); }
    const int l = 2 * (i - 6) + r, m = l >> 2, k = l & 3;
    return 7 * m + (k < 2 ? 2 + k : 3 + k);
}
template <int R>
__device__ __forceinline__ void xchg(float (&acc)[64], float (&o)[32], uint32_t sb, unsigned char* smem, int bar, int ctid) {
    const uint32_t dst = mapa(sb + F_X + ctid * 16, 1 - R), rb = mapa(sb + F_BAR + 8 * bar, 1 - R);
#pragma unroll
    for (int q = 0; q < 8; q++) {
        const int j = (1 - R) * 32 + 4 * q;
        st_async4(dst + q * 4096, acc[j], acc[j + 1], acc[j + 2], acc[j + 3], rb);
    }
    mbar_wait_cluster(sb + F_BAR + 8 * bar, 0);
#pragma unroll
    for (int q = 0; q < 8; q++) {
        float4 v = *(const float4*)(smem + F_X + q * 4096 + ctid * 16);
        const int j = R * 32 + 4 * q;
        o[4 * q] = acc[j] + v.x; o[4 * q + 1] = acc[j + 1] + v.y; o[4 * q + 2] = acc[j + 2] + v.z; o[4 * q + 3] = acc[j + 3] + v.w;
    }
}

template <int NB, bool STAGE>
__device__ __forceinline__ void ffn_epilogue(const float* ag, const float* au, const float* s_cs, int cs_off, uint32_t* gp, uint32_t stg,
                                             float2 st0, float2 st1, int lane) {
    const int t = lane & 3;
    const float C1 = 0.7978845608028654f, C2 = 0.044715f * 0.7978845608028654f;
    const float k10 = st0.x * C1, k20 = st0.x * st0.x * st0.x * C2, k11 = st1.x * C1, k21 = st1.x * st1.x * st1.x * C2;
#pragma unroll
    for (int j2 = 0; j2 < NB / 2; j2++) {
        uint32_t pk[4];
#pragma unroll
        for (int jj = 0; jj < 2; jj++) {
            const int j = 2 * j2 + jj;
            const float2 cg = *(const float2*)(s_cs + cs_off + 8 * j + 2 * t);
            const float2 cu = *(const float2*)(s_cs + 224 + cs_off + 8 * j + 2 * t);
            float r[4];
#pragma unroll
            for (int e = 0; e < 4; e++) {
                const float nm = (e < 2) ? st0.y : st1.y, k1 = (e < 2) ? k10 : k11, k2 = (e < 2) ? k20 : k21;
                const float tg = fmaf(nm, (e & 1) ? cg.y : cg.x, ag[4 * j + e]);
                const float tu = fmaf(nm, (e & 1) ? cu.y : cu.x, au[4 * j + e]);
                const float th = tanh_fast(tg * fmaf(tg * tg, k2, k1));
                const float p = tg * tu;
                r[e] = fmaf(p, th, p);
            }
            pk[2 * jj] = pack_bf16(r[0], r[1]);
            pk[2 * jj + 1] = pack_bf16(r[2], r[3]);
        }
        if (STAGE) {
            stsm4(stg + j2 * 4096, pk[0], pk[1], pk[2], pk[3]);
        } else {
            gp[j2 * 1024] = pk[0]; gp[j2 * 1024 + 32] = pk[1]; gp[j2 * 1024 + 512] = pk[2]; gp[j2 * 1024 + 544] = pk[3];
        }
    }
}

__global__ void __cluster_dims__(2, 1, 1) __launch_bounds__(384, 1)
tail_kernel(const __grid_constant__ CUtensorMap tm_o, const __grid_constant__ CUtensorMap tm_g,
            const __grid_constant__ CUtensorMap tm_u, const __grid_constant__ CUtensorMap tm_d,
            const __grid_constant__ CUtensorMap tm_out, const __nv_bfloat16* __restrict__ x) {
    extern __shared__ __align__(1024) unsigned char smem[];
    const uint32_t sb = smem_u32(smem);
    const uint32_t bars = sb + F_BAR;
    const int tid = threadIdx.x, warp = __shfl_sync(0xffffffffu, tid >> 5, 0), lane = tid & 31;
    TLDECL
    TL(6);
    if (warp == 4) TX(200);
    const int cl = blockIdx.x >> 1, r = blockIdx.x & 1;
    const int mb = ((cl & 7) >> 1) * 4 + (cl >> 4), ntA = (cl & 1) * 2 + ((cl >> 3) & 1);
    const int nt = ntA * 2 + r;
    if (tid == 0) {
#pragma unroll
        for (int i = 0; i < B_NUM; i++) {
            const int cnt = ((i >= B_BE && i < B_BE + 3) || (i >= B_CE && i < B_CE + 6) || i == B_BDONE || i == B_PRDY) ? 8 : (i == B_AUX) ? 2 : 1;
            mbar_init(bars + 8 * i, cnt);
        }
        mbar_expect(bars + 8 * B_XC, 32768);
        fence_barrier_init();
    }
    TL(28);
    __syncthreads();
    TL(29);
    asm volatile("barrier.cluster.arrive.relaxed.aligned;" ::: "memory");
    TL(30);
    if (warp < 4) {
        asm volatile("setmaxnreg.dec.sync.aligned.u32 56;");
        if (warp == 0) TX(205);
        if (warp == 0) {
            if (lane == 0) {
                auto load_b = [&](int it) {
                    const int s = it % 3, pass = it >> 3, kb = (nt + it) & 7;
                    const int ng = pass ? 3 : 4, c0 = nt * 224 + pass * 128;
                    const uint32_t bar = bars + 8 * (B_BF + s), dst = sb + F_R2 + s * 32768;
                    mbar_expect(bar, ng * 8192);
                    for (int i = 0; i < ng; i++) {
                        tma2d(dst + i * 4096, &tm_g, c0 + i * 32, kb * 64, bar);
                        tma2d(dst + 16384 + i * 4096, &tm_u, c0 + i * 32, kb * 64, bar);
                    }
                };
                for (int i = 0; i < 8; i++) {
                    const uint32_t bar = bars + 8 * (B_FA + (i >> 1));
                    if (!(i & 1)) mbar_expect(bar, 49152);
                    tma2d(sb + F_R2 + 32768 + i * 8192, &tm_o, nt * 64, i * 64, bar);
                }
                pdl_wait();
                TL(16);
                for (int i = 0; i < 8; i++)
                    bulk_g2s(sb + i * 16384, g_ao + (size_t)(mb * 8 + i) * 8192, 16384, bars + 8 * (B_FA + (i >> 1)));
                load_b(0);
                if (blockIdx.x == 0)
                    for (int i = 0; i < 32; i++) g_cnt[i] = 0;
                mbar_wait(bars + 8 * B_ADONE, 0);
                load_b(1); load_b(2);
                for (int it = 3; it < 16; it++) {
                    mbar_wait(bars + 8 * (B_BE + it % 3), (it / 3 - 1) & 1);
                    load_b(it);
                }
                mbar_wait(bars + 8 * B_BDONE, 0);
                poll_count(&g_cnt2[mb], 8);
                for (int i = 0; i < 14; i++) {
                    const int s = i % 6, kb = c_kblock(i, r);
                    const uint32_t bar = bars + 8 * (B_CF + s);
                    if (i >= 6) mbar_wait(bars + 8 * (B_CE + s), ((i / 6) - 1) & 1);
                    mbar_expect(bar, 32768);
                    tma2d(sb + s * 32768 + 16384, &tm_d, ntA * 128, kb * 64, bar);
                    tma2d(sb + s * 32768 + 24576, &tm_d, ntA * 128 + 64, kb * 64, bar);
                    if (i == 6) { poll_count(&g_cnt2[16 + mb], 8); TL(18); }
                    bulk_g2s(sb + s * 32768, g_g + (size_t)(mb * 28 + kb) * 8192, 16384, bar);
                }
            }
            TLDUMP;
            __syncwarp();
            asm volatile("barrier.cluster.wait.acquire.aligned;" ::: "memory");
        } else if (warp == 1) {
            asm volatile("barrier.cluster.wait.acquire.aligned;" ::: "memory");
            bar_sync(1, 288);
            if (lane == 0) red_release(&g_cnt2[mb]);
            __syncwarp();
            bar_sync(2, 288);
            if (lane == 0) {
                red_release(&g_cnt2[16 + mb]);
                TL(13);
            }
            __syncwarp();
            bar_sync(3, 288);
            if (lane == 0) {
                tma2d_store(&tm_out, sb, nt * 64, mb * 128);
                bulk_commit();
                bulk_wait_all();
                TL(15);
            }
            TLDUMP;
        } else {
            asm volatile("barrier.cluster.wait.acquire.aligned;" ::: "memory");
            pdl_wait();
            float2* s_rs = (float2*)(smem + F_RS);
            float* s_cs = (float*)(smem + F_CS);
            for (int c = tid - 64; c < 448; c += 64)
                s_cs[c] = __ldcg(&g_cs2[(c >= 224 ? FF - 224 : 0) + nt * 224 + c]);
            if (tid == 96) {
                mbar_wait(bars + 8 * B_ADONE, 0);
                for (int i = 1; i < 8; i++) {
                    const int kb = (nt + i) & 7;
                    const uint32_t bar = bars + 8 * (i < 5 ? B_HF + i - 1 : B_FA + i - 5);
                    poll_count(&g_cnt2[32 + mb * 8 + kb], 8);
                    mbar_expect(bar, 16384);
                    bulk_g2s(sb + kb * 16384, g_h + (size_t)(mb * 8 + kb) * 8192, 16384, bar);
                }
                TL(17);
            }
            __syncwarp();
            if (lane < 8) poll_count(&g_cnt2[32 + mb * 8 + lane], 8);
            __syncwarp();
            for (int rr = tid - 64; rr < 128; rr += 64) {
                const float4* hp = (const float4*)(g_hstat + (size_t)(mb * 128 + rr) * 8);
                float4 a = __ldcg(hp), b = __ldcg(hp + 1), c = __ldcg(hp + 2), d = __ldcg(hp + 3);
                float mean = 0.125f * (a.x + a.z + b.x + b.z + c.x + c.z + d.x + d.z);
                float m2 = a.y + a.w + b.y + b.w + c.y + c.w + d.y + d.w;
                float e;
                e = a.x - mean; m2 = fmaf(64.f * e, e, m2); e = a.z - mean; m2 = fmaf(64.f * e, e, m2);
                e = b.x - mean; m2 = fmaf(64.f * e, e, m2); e = b.z - mean; m2 = fmaf(64.f * e, e, m2);
                e = c.x - mean; m2 = fmaf(64.f * e, e, m2); e = c.z - mean; m2 = fmaf(64.f * e, e, m2);
                e = d.x - mean; m2 = fmaf(64.f * e, e, m2); e = d.z - mean; m2 = fmaf(64.f * e, e, m2);
                s_rs[rr] = make_float2(rsqrtf(m2 * (1.0f / DM) + 1e-5f), -mean);
            }
            __syncwarp();
            if (lane == 0) mbar_arrive(bars + 8 * B_AUX);
            TLDUMP;
        }
    } else {
        asm volatile("setmaxnreg.inc.sync.aligned.u32 216;");
        if (warp == 4) TX(206);
        const int wgi = (warp >> 2) - 1, ww = warp & 3, ctid = tid - 128;
        const int g = lane >> 2, t = lane & 3;
        const int rl = wgi * 64 + ww * 16 + g, row = mb * 128 + rl;
        const int rgl = wgi * 8 + ww * 2;
        const float2* s_rs = (const float2*)(smem + F_RS);
        const float* s_cs = (const float*)(smem + F_CS);
        const uint32_t stl = ((lane >> 4) * 16 + rgl + ((lane >> 3) & 1)) * 128 + (lane & 7) * 16;
        TL(23);
        {
            uint32_t xr[16];
            const uint32_t* xp = (const uint32_t*)(x + (size_t)row * DM + nt * 64) + t;
#pragma unroll
            for (int j = 0; j < 8; j++) { xr[2 * j] = __ldg(xp + 4 * j); xr[2 * j + 1] = __ldg(xp + 8 * (DM / 2) + 4 * j); }
            float acc[32];
#pragma unroll 1
            for (int i = 0; i < 8; i++) {
                if (!(i & 1)) { mbar_wait(bars + 8 * (B_FA + (i >> 1)), 0); if (i == 0) TL(19); }
                uint64_t ad = make_desc(sb + i * 16384 + wgi * 1024, 2048, 128, 0);
                uint64_t bd = make_desc(sb + F_R2 + 32768 + i * 8192, 8192, 1024, 1);
                WG_FENCE();
#pragma unroll
                for (int k = 0; k < 4; k++) wgmma_ss_n64(acc, ad + k * 256, bd + k * 128, (i | k) != 0);
                WG_COMMIT();
            }
            wg_wait<0>();
            fence_regs(acc);
            TL(7);
            bar_sync(4, 256);
            if (tid == 128) mbar_arrive(bars + 8 * B_ADONE);
            uint32_t* hp = (uint32_t*)g_h + ((size_t)(mb * 8 + nt) * 8 * 16 + rgl) * 32 + lane;
            float v0[16], v1[16];
            float s0 = 0.f, s1 = 0.f;
#pragma unroll
            for (int j2 = 0; j2 < 4; j2++) {
                uint32_t u[4];
#pragma unroll
                for (int jj = 0; jj < 2; jj++) {
                    const int j = 2 * j2 + jj;
                    u[2 * jj] = pack_bf16(bf_lo(xr[2 * j]) + acc[4 * j], bf_hi(xr[2 * j]) + acc[4 * j + 1]);
                    u[2 * jj + 1] = pack_bf16(bf_lo(xr[2 * j + 1]) + acc[4 * j + 2], bf_hi(xr[2 * j + 1]) + acc[4 * j + 3]);
                    v0[2 * j] = bf_lo(u[2 * jj]); v0[2 * j + 1] = bf_hi(u[2 * jj]);
                    v1[2 * j] = bf_lo(u[2 * jj + 1]); v1[2 * j + 1] = bf_hi(u[2 * jj + 1]);
                    s0 += v0[2 * j] + v0[2 * j + 1];
                    s1 += v1[2 * j] + v1[2 * j + 1];
                }
                stsm4(sb + nt * 16384 + stl + j2 * 4096, u[0], u[1], u[2], u[3]);
                hp[j2 * 1024] = u[0]; hp[j2 * 1024 + 32] = u[1]; hp[j2 * 1024 + 512] = u[2]; hp[j2 * 1024 + 544] = u[3];
            }
            fence_proxy_async();
            float m0 = s0 * (1.0f / 16), m1 = s1 * (1.0f / 16), q0 = 0.f, q1 = 0.f;
#pragma unroll
            for (int i = 0; i < 16; i++) {
                float d0 = v0[i] - m0, d1 = v1[i] - m1;
                q0 = fmaf(d0, d0, q0); q1 = fmaf(d1, d1, q1);
            }
#pragma unroll
            for (int st = 0; st < 2; st++) {
                float hn = st ? 16.f : 8.f;
                float om0 = __shfl_xor_sync(0xffffffffu, m0, 1 << st), oq0 = __shfl_xor_sync(0xffffffffu, q0, 1 << st);
                float om1 = __shfl_xor_sync(0xffffffffu, m1, 1 << st), oq1 = __shfl_xor_sync(0xffffffffu, q1, 1 << st);
                float d0 = om0 - m0, d1 = om1 - m1;
                q0 = q0 + oq0 + d0 * d0 * hn; q1 = q1 + oq1 + d1 * d1 * hn;
                m0 = 0.5f * (m0 + om0); m1 = 0.5f * (m1 + om1);
            }
            if (t == 0) {
                g_hstat[row * 8 + nt] = make_float2(m0, q0);
                g_hstat[(row + 8) * 8 + nt] = make_float2(m1, q1);
            }
            __syncwarp();
            if (lane == 0) red_release(&g_cnt2[32 + mb * 8 + nt]);
            TL(9);
            bar_sync(4, 256);
            TL(8);
        }
        uint32_t* gp = (uint32_t*)g_g + (((size_t)mb * 224 + nt * 28) * 16 + rgl) * 32 + lane;
        {
            float ag[64], au[64];
#pragma unroll 1
            for (int kb = 0; kb < 8; kb++) {
                const int s = kb % 3;
                if (kb) mbar_wait(bars + 8 * (kb < 5 ? B_HF + kb - 1 : B_FA + kb - 5), kb < 5 ? 0 : 1);
                mbar_wait(bars + 8 * (B_BF + s), (kb / 3) & 1);
                uint64_t ad = make_desc(sb + ((nt + kb) & 7) * 16384 + wgi * 1024, 2048, 128, 0);
                uint64_t bd = make_desc(sb + F_R2 + s * 32768, 4096, 512, 2);
                WG_FENCE();
#pragma unroll
                for (int k = 0; k < 4; k++) {
                    wgmma_ss_n128(ag, ad + k * 256, bd + k * 64, (kb | k) != 0);
                    wgmma_ss_n128(au, ad + k * 256, bd + 1024 + k * 64, (kb | k) != 0);
                }
                WG_COMMIT();
                if (kb > 0) {
                    wg_wait<1>();
                    if (lane == 0) mbar_arrive(bars + 8 * (B_BE + (kb - 1) % 3));
                }
            }
            wg_wait<0>();
            if (lane == 0) mbar_arrive(bars + 8 * (B_BE + 7 % 3));
            fence_regs(ag); fence_regs(au);
            TL(10);
            mbar_wait(bars + 8 * B_AUX, 0);
            ffn_epilogue<16, false>(ag, au, s_cs, 0, gp, 0, s_rs[rl], s_rs[rl + 8], lane);
            bar_arrive(1, 288);
        }
        uint32_t hr[16];
        {
            const uint32_t* hs = (const uint32_t*)(smem + nt * 16384) + rgl * 32 + lane;
#pragma unroll
            for (int j = 0; j < 8; j++) { hr[2 * j] = hs[j * 512]; hr[2 * j + 1] = hs[j * 512 + 32]; }
        }
        {
            float ag[48], au[48];
#pragma unroll 1
            for (int kb = 0; kb < 8; kb++) {
                const int it = 8 + kb, s = it % 3;
                mbar_wait(bars + 8 * (B_BF + s), (it / 3) & 1);
                uint64_t ad = make_desc(sb + ((nt + kb) & 7) * 16384 + wgi * 1024, 2048, 128, 0);
                uint64_t bd = make_desc(sb + F_R2 + s * 32768, 4096, 512, 2);
                WG_FENCE();
#pragma unroll
                for (int k = 0; k < 4; k++) {
                    wgmma_ss_n96(ag, ad + k * 256, bd + k * 64, (kb | k) != 0);
                    wgmma_ss_n96(au, ad + k * 256, bd + 1024 + k * 64, (kb | k) != 0);
                }
                WG_COMMIT();
                if (kb > 0) {
                    wg_wait<1>();
                    if (lane == 0) mbar_arrive(bars + 8 * (B_BE + (it - 1) % 3));
                }
            }
            wg_wait<0>();
            asm volatile("barrier.cluster.wait.acquire.aligned;" ::: "memory");
            if (lane == 0) {
                mbar_arrive(bars + 8 * B_BDONE);
                mbar_arrive_remote(mapa(bars + 8 * B_PRDY, 1 - r));
            }
            fence_regs(ag); fence_regs(au);
            TL(11);
            ffn_epilogue<12, false>(ag, au, s_cs, 128, gp + 16 * 512, 0, s_rs[rl], s_rs[rl + 8], lane);
            bar_arrive(2, 288);
            TL(12);
        }
        {
            float acc[64];
#pragma unroll 1
            for (int kb = 0; kb < 14; kb++) {
                const int s = kb % 6;
                mbar_wait(bars + 8 * (B_CF + s), (kb / 6) & 1);
                if (warp == 4) TX(96 + kb);
                uint64_t ad = make_desc(sb + s * 32768 + wgi * 1024, 2048, 128, 0);
                uint64_t bd = make_desc(sb + s * 32768 + 16384, 8192, 1024, 1);
                WG_FENCE();
#pragma unroll
                for (int k = 0; k < 4; k++) wgmma_ss_n128(acc, ad + k * 256, bd + k * 128, (kb | k) != 0);
                WG_COMMIT();
                if (kb > 0) {
                    wg_wait<1>();
                    if (lane == 0) mbar_arrive(bars + 8 * (B_CE + (kb - 1) % 6));
                }
            }
            wg_wait<0>();
            fence_regs(acc);
            TL(14);
            mbar_wait_cluster(bars + 8 * B_PRDY, 0);
            float o[32];
            if (r == 0) xchg<0>(acc, o, sb, smem, B_XC, ctid); else xchg<1>(acc, o, sb, smem, B_XC, ctid);
            TL(22);
            bar_sync(4, 256);
            const float a0 = s_rs[rl].x, a1 = s_rs[rl + 8].x;
            const float k0 = 0.5f * a0 * a0, k1 = 0.5f * a1 * a1;
            const int srow = wgi * 64 + ww * 16 + ((lane >> 3) & 1) * 8 + (lane & 7);
#pragma unroll
            for (int j2 = 0; j2 < 4; j2++) {
                uint32_t u[4];
#pragma unroll
                for (int jj = 0; jj < 2; jj++) {
                    const int j = 2 * j2 + jj;
                    u[2 * jj] = pack_bf16(fmaf(k0, o[4 * j], bf_lo(hr[2 * j])), fmaf(k0, o[4 * j + 1], bf_hi(hr[2 * j])));
                    u[2 * jj + 1] = pack_bf16(fmaf(k1, o[4 * j + 2], bf_lo(hr[2 * j + 1])), fmaf(k1, o[4 * j + 3], bf_hi(hr[2 * j + 1])));
                }
                const int chunk = 2 * j2 + (lane >> 4);
                stsm4(sb + srow * 128 + ((chunk ^ (lane & 7)) * 16), u[0], u[1], u[2], u[3]);
            }
            fence_proxy_async();
            bar_arrive(3, 288);
            TLDUMP;
        }
    }
}

typedef CUresult (*EncodeFn)(CUtensorMap*, CUtensorMapDataType, cuuint32_t, void*, const cuuint64_t*, const cuuint64_t*,
                             const cuuint32_t*, const cuuint32_t*, CUtensorMapInterleave, CUtensorMapSwizzle,
                             CUtensorMapL2promotion, CUtensorMapFloatOOBfill);

void encode(EncodeFn fn, CUtensorMap* m, const void* ptr, int rank, const cuuint64_t* dims, const cuuint64_t* strides,
            const cuuint32_t* box, CUtensorMapSwizzle swz) {
    cuuint32_t es[3] = {1, 1, 1};
    fn(m, CU_TENSOR_MAP_DATA_TYPE_BFLOAT16, rank, (void*)ptr, dims, strides, box, es, CU_TENSOR_MAP_INTERLEAVE_NONE, swz,
       CU_TENSOR_MAP_L2_PROMOTION_L2_256B, CU_TENSOR_MAP_FLOAT_OOB_FILL_NONE);
}

template <typename... KArgs, typename... Args>
void launch(void (*kern)(KArgs...), int grid, int block, int smem, bool pdl, Args... args) {
    cudaLaunchConfig_t cfg = {};
    cfg.gridDim = dim3(grid); cfg.blockDim = dim3(block); cfg.dynamicSmemBytes = smem;
    cfg.stream = cudaStreamPerThread;
    cudaLaunchAttribute at[1];
    at[0].id = cudaLaunchAttributeProgrammaticStreamSerialization;
    at[0].val.programmaticStreamSerializationAllowed = 1;
    cfg.attrs = at; cfg.numAttrs = pdl ? 1 : 0;
    cudaLaunchKernelEx(&cfg, kern, KArgs(args)...);
}

}

extern "C" void kernel_launch(void* const* d_in, const int* in_sizes, int n_in, void* d_out, int out_size) {
    const __nv_bfloat16* x = (const __nv_bfloat16*)d_in[0];
    const __nv_bfloat16* wqkv = (const __nv_bfloat16*)d_in[1];
    const __nv_bfloat16* wo = (const __nv_bfloat16*)d_in[2];
    const __nv_bfloat16* wgate = (const __nv_bfloat16*)d_in[4];
    const __nv_bfloat16* wup = (const __nv_bfloat16*)d_in[5];
    const __nv_bfloat16* wdown = (const __nv_bfloat16*)d_in[6];
    __nv_bfloat16* out = (__nv_bfloat16*)d_out;

    static CUtensorMap tm_x, tm_wqkv, tm_wo, tm_wg, tm_wu, tm_wd, tm_out;
    static const void* cached[7] = {nullptr, nullptr, nullptr, nullptr, nullptr, nullptr, nullptr};
    if (cached[0] != x || cached[1] != wqkv || cached[2] != wo || cached[3] != wgate || cached[4] != wup || cached[5] != wdown || cached[6] != out) {
        void* fp = nullptr;
        cudaDriverEntryPointQueryResult qr;
        cudaGetDriverEntryPoint("cuTensorMapEncodeTiled", &fp, cudaEnableDefault, &qr);
        EncodeFn fn = (EncodeFn)fp;
        { cuuint64_t d[2] = {512, 2048}, s[1] = {1024}; cuuint32_t b[2] = {64, 128};
          encode(fn, &tm_x, x, 2, d, s, b, CU_TENSOR_MAP_SWIZZLE_128B);
          encode(fn, &tm_out, out, 2, d, s, b, CU_TENSOR_MAP_SWIZZLE_128B); }
        { cuuint64_t d[3] = {64, 512, 24}, s[2] = {3072, 128}; cuuint32_t b[3] = {64, 64, 3};
          encode(fn, &tm_wqkv, wqkv, 3, d, s, b, CU_TENSOR_MAP_SWIZZLE_128B); }
        { cuuint64_t d[2] = {512, 512}, s[1] = {1024}; cuuint32_t b[2] = {64, 64};
          encode(fn, &tm_wo, wo, 2, d, s, b, CU_TENSOR_MAP_SWIZZLE_128B); }
        { cuuint64_t d[2] = {1792, 512}, s[1] = {3584}; cuuint32_t b[2] = {32, 64};
          encode(fn, &tm_wg, wgate, 2, d, s, b, CU_TENSOR_MAP_SWIZZLE_64B);
          encode(fn, &tm_wu, wup, 2, d, s, b, CU_TENSOR_MAP_SWIZZLE_64B); }
        { cuuint64_t d[2] = {512, 1792}, s[1] = {1024}; cuuint32_t b[2] = {64, 64};
          encode(fn, &tm_wd, wdown, 2, d, s, b, CU_TENSOR_MAP_SWIZZLE_128B); }
        cudaFuncSetAttribute(qkv_kernel, cudaFuncAttributeMaxDynamicSharedMemorySize, F_SMEM);
        cudaFuncSetAttribute(qkv_kernel, cudaFuncAttributePreferredSharedMemoryCarveout, 100);
        cudaFuncSetAttribute(attn_kernel, cudaFuncAttributeMaxDynamicSharedMemorySize, F_SMEM);
        cudaFuncSetAttribute(attn_kernel, cudaFuncAttributePreferredSharedMemoryCarveout, 100);
        cudaFuncSetAttribute(tail_kernel, cudaFuncAttributeMaxDynamicSharedMemorySize, F_SMEM);
        cudaFuncSetAttribute(tail_kernel, cudaFuncAttributePreferredSharedMemoryCarveout, 100);
        cached[0] = x; cached[1] = wqkv; cached[2] = wo; cached[3] = wgate; cached[4] = wup; cached[5] = wdown; cached[6] = out;
    }
    launch(qkv_kernel, 128, 384, F_SMEM, false, tm_x, tm_wqkv, x, wqkv);
    launch(attn_kernel, 132, 512, F_SMEM, true, wgate, wup, wo, wdown);
    launch(tail_kernel, 128, 384, F_SMEM, true, tm_wo, tm_wg, tm_wu, tm_wd, tm_out, x);
}
```

```cpp
#include <cuda_runtime.h>
#include <cuda_bf16.h>
#include <cuda.h>
#include <stdint.h>

#define K1_DIRECT
namespace {

constexpr int S_LEN = 2048, DM = 512, NH = 32, FF = 1792;

__device__ __align__(1024) __nv_bfloat16 g_qkv[3 * NH * S_LEN * 16];
__device__ __align__(1024) __nv_bfloat16 g_ao[S_LEN * DM];
__device__ __align__(1024) __nv_bfloat16 g_h[S_LEN * DM];
__device__ __align__(1024) __nv_bfloat16 g_g[S_LEN * FF];
__device__ __align__(16) float2 g_rowstat1[S_LEN];
__device__ float g_cs1_part[16 * 1536];
__device__ unsigned int g_cnt[32];
__device__ unsigned int g_cnt2[160];
__device__ float g_nrm[3 * NH * 128];
__device__ float2 g_hstat[S_LEN * 8];
__device__ float g_cs2[2 * FF];

#define TLDECL
#define TL(slot)
#define TLDUMP
#define TX(slot)
__device__ __forceinline__ uint32_t smem_u32(const void* p) { return (uint32_t)__cvta_generic_to_shared(p); }
__device__ __forceinline__ void mbar_init(uint32_t a, int c) { asm volatile("mbarrier.init.shared.b64 [%0], %1;" :: "r"(a), "r"(c)); }
__device__ __forceinline__ void mbar_expect(uint32_t a, int bytes) { asm volatile("mbarrier.arrive.expect_tx.shared.b64 _, [%0], %1;" :: "r"(a), "r"(bytes) : "memory"); }
__device__ __forceinline__ void mbar_arrive(uint32_t a) { asm volatile("mbarrier.arrive.shared.b64 _, [%0];" :: "r"(a) : "memory"); }
__device__ __forceinline__ void mbar_wait(uint32_t a, int parity) {
    uint32_t done;
    int it = 0;
    do {
        asm volatile("{\n.reg .pred p;\nmbarrier.try_wait.parity.shared.b64 p, [%1], %2;\nselp.u32 %0, 1, 0, p;\n}"
                     : "=r"(done) : "r"(a), "r"(parity) : "memory");
        if (++it > (1 << 24)) __trap();
    } while (!done);
}
__device__ __forceinline__ void bulk_g2s(uint32_t dst, const void* src, int bytes, uint32_t bar) {
    asm volatile("cp.async.bulk.shared::cluster.global.mbarrier::complete_tx::bytes [%0], [%1], %2, [%3];"
                 :: "r"(dst), "l"(src), "r"(bytes), "r"(bar) : "memory");
}
__device__ __forceinline__ void tma2d(uint32_t dst, const CUtensorMap* m, int c0, int c1, uint32_t bar) {
    asm volatile("cp.async.bulk.tensor.2d.shared::cluster.global.mbarrier::complete_tx::bytes [%0], [%1, {%3, %4}], [%2];"
                 :: "r"(dst), "l"(m), "r"(bar), "r"(c0), "r"(c1) : "memory");
}
__device__ __forceinline__ void tma3d(uint32_t dst, const CUtensorMap* m, int c0, int c1, int c2, uint32_t bar) {
    asm volatile("cp.async.bulk.tensor.3d.shared::cluster.global.mbarrier::complete_tx::bytes [%0], [%1, {%3, %4, %5}], [%2];"
                 :: "r"(dst), "l"(m), "r"(bar), "r"(c0), "r"(c1), "r"(c2) : "memory");
}
__device__ __forceinline__ void prefetch_tmap(const CUtensorMap* m) { asm volatile("prefetch.tensormap [%0];" :: "l"(m) : "memory"); }
__device__ __forceinline__ void pdl_wait() { asm volatile("griddepcontrol.wait;" ::: "memory"); }
__device__ __forceinline__ void pdl_launch() { asm volatile("griddepcontrol.launch_dependents;" ::: "memory"); }
__device__ __forceinline__ void fence_barrier_init() { asm volatile("fence.mbarrier_init.release.cluster;" ::: "memory"); }
__device__ __forceinline__ void fence_proxy_async() { asm volatile("fence.proxy.async.shared::cta;" ::: "memory"); }
__device__ __forceinline__ uint64_t make_desc(uint32_t saddr, uint32_t lbo, uint32_t sbo, uint32_t swz) {
    return (uint64_t)((saddr & 0x3FFFF) >> 4) | ((uint64_t)((lbo & 0x3FFFF) >> 4) << 16) |
           ((uint64_t)((sbo & 0x3FFFF) >> 4) << 32) | ((uint64_t)swz << 62);
}
#define WG_FENCE() asm volatile("wgmma.fence.sync.aligned;" ::: "memory")
#define WG_COMMIT() asm volatile("wgmma.commit_group.sync.aligned;" ::: "memory")
template <int N> __device__ __forceinline__ void wg_wait() { asm volatile("wgmma.wait_group.sync.aligned %0;" :: "n"(N) : "memory"); }
template <int N> __device__ __forceinline__ void fence_regs(float (&d)[N]) {
#pragma unroll
    for (int i = 0; i < N; i++) asm volatile("" : "+f"(d[i]) :: "memory");
}
__device__ __forceinline__ float ex2f(float x) { float y; asm("ex2.approx.ftz.f32 %0, %1;" : "=f"(y) : "f"(x)); return y; }
__device__ __forceinline__ float tanh_fast(float x) { float y; asm("tanh.approx.f32 %0, %1;" : "=f"(y) : "f"(x)); return y; }
__device__ __forceinline__ uint32_t pack_bf16(float lo, float hi) { uint32_t r; asm("cvt.rn.bf16x2.f32 %0, %1, %2;" : "=r"(r) : "f"(hi), "f"(lo)); return r; }
__device__ __forceinline__ float bf_lo(uint32_t u) { return __uint_as_float(u << 16); }
__device__ __forceinline__ float bf_hi(uint32_t u) { return __uint_as_float(u & 0xFFFF0000u); }
__device__ __forceinline__ uint32_t hfma2(uint32_t a, uint32_t b, uint32_t c) { uint32_t r; asm("fma.rn.f16x2 %0, %1, %2, %3;" : "=r"(r) : "r"(a), "r"(b), "r"(c)); return r; }
__device__ __forceinline__ uint32_t hmul2(uint32_t a, uint32_t b) { uint32_t r; asm("mul.rn.f16x2 %0, %1, %2;" : "=r"(r) : "r"(a), "r"(b)); return r; }
__device__ __forceinline__ unsigned int ld_acquire(const unsigned int* p) { unsigned int v; asm volatile("ld.acquire.gpu.u32 %0, [%1];" : "=r"(v) : "l"(p) : "memory"); return v; }
__device__ __forceinline__ void red_release(unsigned int* p) { asm volatile("red.release.gpu.global.add.u32 [%0], 1;" :: "l"(p) : "memory"); }
__device__ __forceinline__ void stsm4(uint32_t addr, uint32_t a, uint32_t b, uint32_t c, uint32_t d) {
    asm volatile("stmatrix.sync.aligned.m8n8.x4.shared.b16 [%0], {%1,%2,%3,%4};" :: "r"(addr), "r"(a), "r"(b), "r"(c), "r"(d) : "memory");
}
__device__ __forceinline__ void bulk_s2g(void* dst, uint32_t src, int bytes) {
    asm volatile("cp.async.bulk.global.shared::cta.bulk_group [%0], [%1], %2;" :: "l"(dst), "r"(src), "r"(bytes) : "memory");
}
__device__ __forceinline__ void bulk_commit() { asm volatile("cp.async.bulk.commit_group;" ::: "memory"); }
__device__ __forceinline__ void bulk_wait_all() { asm volatile("cp.async.bulk.wait_group 0;" ::: "memory"); }
__device__ __forceinline__ void bulk_wait_read() { asm volatile("cp.async.bulk.wait_group.read 0;" ::: "memory"); }
__device__ __forceinline__ void bar_sync(int id, int n) { asm volatile("bar.sync %0, %1;" :: "r"(id), "r"(n) : "memory"); }
__device__ __forceinline__ void bar_arrive(int id, int n) { asm volatile("bar.arrive %0, %1;" :: "r"(id), "r"(n) : "memory"); }
__device__ __forceinline__ float warp_sum(float v) {
#pragma unroll
    for (int o = 16; o; o >>= 1) v += __shfl_xor_sync(0xffffffffu, v, o);
    return v;
}
__device__ __forceinline__ float warp_max(float v) {
#pragma unroll
    for (int o = 16; o; o >>= 1) v = fmaxf(v, __shfl_xor_sync(0xffffffffu, v, o));
    return v;
}

__device__ __forceinline__ void wgmma_ss_n64(float (&d)[32], uint64_t adesc, uint64_t bdesc, int scale_d) {
    asm volatile("{\n.reg .pred p;\nsetp.ne.b32 p, %34, 0;\n"
      "wgmma.mma_async.sync.aligned.m64n64k16.f32.bf16.bf16 {%0,%1,%2,%3,%4,%5,%6,%7,%8,%9,%10,%11,%12,%13,%14,%15,%16,%17,%18,%19,%20,%21,%22,%23,%24,%25,%26,%27,%28,%29,%30,%31}, %32, %33, p, 1, 1, 0, 1;\n}"
      : "+f"(d[0]), "+f"(d[1]), "+f"(d[2]), "+f"(d[3]), "+f"(d[4]), "+f"(d[5]), "+f"(d[6]), "+f"(d[7]), "+f"(d[8]), "+f"(d[9]), "+f"(d[10]), "+f"(d[11]), "+f"(d[12]), "+f"(d[13]), "+f"(d[14]), "+f"(d[15]), "+f"(d[16]), "+f"(d[17]), "+f"(d[18]), "+f"(d[19]), "+f"(d[20]), "+f"(d[21]), "+f"(d[22]), "+f"(d[23]), "+f"(d[24]), "+f"(d[25]), "+f"(d[26]), "+f"(d[27]), "+f"(d[28]), "+f"(d[29]), "+f"(d[30]), "+f"(d[31])
      : "l"(adesc), "l"(bdesc), "r"(scale_d));
}
__device__ __forceinline__ void wgmma_ss_n96(float (&d)[48], uint64_t adesc, uint64_t bdesc, int scale_d) {
    asm volatile("{\n.reg .pred p;\nsetp.ne.b32 p, %50, 0;\n"
      "wgmma.mma_async.sync.aligned.m64n96k16.f32.bf16.bf16 {%0,%1,%2,%3,%4,%5,%6,%7,%8,%9,%10,%11,%12,%13,%14,%15,%16,%17,%18,%19,%20,%21,%22,%23,%24,%25,%26,%27,%28,%29,%30,%31,%32,%33,%34,%35,%36,%37,%38,%39,%40,%41,%42,%43,%44,%45,%46,%47}, %48, %49, p, 1, 1, 0, 1;\n}"
      : "+f"(d[0]), "+f"(d[1]), "+f"(d[2]), "+f"(d[3]), "+f"(d[4]), "+f"(d[5]), "+f"(d[6]), "+f"(d[7]), "+f"(d[8]), "+f"(d[9]), "+f"(d[10]), "+f"(d[11]), "+f"(d[12]), "+f"(d[13]), "+f"(d[14]), "+f"(d[15]), "+f"(d[16]), "+f"(d[17]), "+f"(d[18]), "+f"(d[19]), "+f"(d[20]), "+f"(d[21]), "+f"(d[22]), "+f"(d[23]), "+f"(d[24]), "+f"(d[25]), "+f"(d[26]), "+f"(d[27]), "+f"(d[28]), "+f"(d[29]), "+f"(d[30]), "+f"(d[31]), "+f"(d[32]), "+f"(d[33]), "+f"(d[34]), "+f"(d[35]), "+f"(d[36]), "+f"(d[37]), "+f"(d[38]), "+f"(d[39]), "+f"(d[40]), "+f"(d[41]), "+f"(d[42]), "+f"(d[43]), "+f"(d[44]), "+f"(d[45]), "+f"(d[46]), "+f"(d[47])
      : "l"(adesc), "l"(bdesc), "r"(scale_d));
}
__device__ __forceinline__ void wgmma_ss_n128(float (&d)[64], uint64_t adesc, uint64_t bdesc, int scale_d) {
    asm volatile("{\n.reg .pred p;\nsetp.ne.b32 p, %66, 0;\n"
      "wgmma.mma_async.sync.aligned.m64n128k16.f32.bf16.bf16 {%0,%1,%2,%3,%4,%5,%6,%7,%8,%9,%10,%11,%12,%13,%14,%15,%16,%17,%18,%19,%20,%21,%22,%23,%24,%25,%26,%27,%28,%29,%30,%31,%32,%33,%34,%35,%36,%37,%38,%39,%40,%41,%42,%43,%44,%45,%46,%47,%48,%49,%50,%51,%52,%53,%54,%55,%56,%57,%58,%59,%60,%61,%62,%63}, %64, %65, p, 1, 1, 0, 1;\n}"
      : "+f"(d[0]), "+f"(d[1]), "+f"(d[2]), "+f"(d[3]), "+f"(d[4]), "+f"(d[5]), "+f"(d[6]), "+f"(d[7]), "+f"(d[8]), "+f"(d[9]), "+f"(d[10]), "+f"(d[11]), "+f"(d[12]), "+f"(d[13]), "+f"(d[14]), "+f"(d[15]), "+f"(d[16]), "+f"(d[17]), "+f"(d[18]), "+f"(d[19]), "+f"(d[20]), "+f"(d[21]), "+f"(d[22]), "+f"(d[23]), "+f"(d[24]), "+f"(d[25]), "+f"(d[26]), "+f"(d[27]), "+f"(d[28]), "+f"(d[29]), "+f"(d[30]), "+f"(d[31]), "+f"(d[32]), "+f"(d[33]), "+f"(d[34]), "+f"(d[35]), "+f"(d[36]), "+f"(d[37]), "+f"(d[38]), "+f"(d[39]), "+f"(d[40]), "+f"(d[41]), "+f"(d[42]), "+f"(d[43]), "+f"(d[44]), "+f"(d[45]), "+f"(d[46]), "+f"(d[47]), "+f"(d[48]), "+f"(d[49]), "+f"(d[50]), "+f"(d[51]), "+f"(d[52]), "+f"(d[53]), "+f"(d[54]), "+f"(d[55]), "+f"(d[56]), "+f"(d[57]), "+f"(d[58]), "+f"(d[59]), "+f"(d[60]), "+f"(d[61]), "+f"(d[62]), "+f"(d[63])
      : "l"(adesc), "l"(bdesc), "r"(scale_d));
}
__device__ __forceinline__ void wgmma_ss_n192(float (&d)[96], uint64_t adesc, uint64_t bdesc, int scale_d) {
    asm volatile("{\n.reg .pred p;\nsetp.ne.b32 p, %98, 0;\n"
      "wgmma.mma_async.sync.aligned.m64n192k16.f32.bf16.bf16 {%0,%1,%2,%3,%4,%5,%6,%7,%8,%9,%10,%11,%12,%13,%14,%15,%16,%17,%18,%19,%20,%21,%22,%23,%24,%25,%26,%27,%28,%29,%30,%31,%32,%33,%34,%35,%36,%37,%38,%39,%40,%41,%42,%43,%44,%45,%46,%47,%48,%49,%50,%51,%52,%53,%54,%55,%56,%57,%58,%59,%60,%61,%62,%63,%64,%65,%66,%67,%68,%69,%70,%71,%72,%73,%74,%75,%76,%77,%78,%79,%80,%81,%82,%83,%84,%85,%86,%87,%88,%89,%90,%91,%92,%93,%94,%95}, %96, %97, p, 1, 1, 0, 1;\n}"
      : "+f"(d[0]), "+f"(d[1]), "+f"(d[2]), "+f"(d[3]), "+f"(d[4]), "+f"(d[5]), "+f"(d[6]), "+f"(d[7]), "+f"(d[8]), "+f"(d[9]), "+f"(d[10]), "+f"(d[11]), "+f"(d[12]), "+f"(d[13]), "+f"(d[14]), "+f"(d[15]), "+f"(d[16]), "+f"(d[17]), "+f"(d[18]), "+f"(d[19]), "+f"(d[20]), "+f"(d[21]), "+f"(d[22]), "+f"(d[23]), "+f"(d[24]), "+f"(d[25]), "+f"(d[26]), "+f"(d[27]), "+f"(d[28]), "+f"(d[29]), "+f"(d[30]), "+f"(d[31]), "+f"(d[32]), "+f"(d[33]), "+f"(d[34]), "+f"(d[35]), "+f"(d[36]), "+f"(d[37]), "+f"(d[38]), "+f"(d[39]), "+f"(d[40]), "+f"(d[41]), "+f"(d[42]), "+f"(d[43]), "+f"(d[44]), "+f"(d[45]), "+f"(d[46]), "+f"(d[47]), "+f"(d[48]), "+f"(d[49]), "+f"(d[50]), "+f"(d[51]), "+f"(d[52]), "+f"(d[53]), "+f"(d[54]), "+f"(d[55]), "+f"(d[56]), "+f"(d[57]), "+f"(d[58]), "+f"(d[59]), "+f"(d[60]), "+f"(d[61]), "+f"(d[62]), "+f"(d[63]), "+f"(d[64]), "+f"(d[65]), "+f"(d[66]), "+f"(d[67]), "+f"(d[68]), "+f"(d[69]), "+f"(d[70]), "+f"(d[71]), "+f"(d[72]), "+f"(d[73]), "+f"(d[74]), "+f"(d[75]), "+f"(d[76]), "+f"(d[77]), "+f"(d[78]), "+f"(d[79]), "+f"(d[80]), "+f"(d[81]), "+f"(d[82]), "+f"(d[83]), "+f"(d[84]), "+f"(d[85]), "+f"(d[86]), "+f"(d[87]), "+f"(d[88]), "+f"(d[89]), "+f"(d[90]), "+f"(d[91]), "+f"(d[92]), "+f"(d[93]), "+f"(d[94]), "+f"(d[95])
      : "l"(adesc), "l"(bdesc), "r"(scale_d));
}
__device__ __forceinline__ void qk_wgmma_n64(float (&d)[32], const uint32_t (&a)[4], uint64_t desc) {
    asm volatile("wgmma.mma_async.sync.aligned.m64n64k16.f32.bf16.bf16 {%0,%1,%2,%3,%4,%5,%6,%7,%8,%9,%10,%11,%12,%13,%14,%15,%16,%17,%18,%19,%20,%21,%22,%23,%24,%25,%26,%27,%28,%29,%30,%31}, {%32,%33,%34,%35}, %36, 0, 1, 1, 0;"
      : "=f"(d[0]), "=f"(d[1]), "=f"(d[2]), "=f"(d[3]), "=f"(d[4]), "=f"(d[5]), "=f"(d[6]), "=f"(d[7]), "=f"(d[8]), "=f"(d[9]), "=f"(d[10]), "=f"(d[11]), "=f"(d[12]), "=f"(d[13]), "=f"(d[14]), "=f"(d[15]), "=f"(d[16]), "=f"(d[17]), "=f"(d[18]), "=f"(d[19]), "=f"(d[20]), "=f"(d[21]), "=f"(d[22]), "=f"(d[23]), "=f"(d[24]), "=f"(d[25]), "=f"(d[26]), "=f"(d[27]), "=f"(d[28]), "=f"(d[29]), "=f"(d[30]), "=f"(d[31])
      : "r"(a[0]), "r"(a[1]), "r"(a[2]), "r"(a[3]), "l"(desc));
}

__device__ __forceinline__ void pv_wgmma(float (&d)[12], uint32_t a0, uint32_t a1, uint32_t a2, uint32_t a3, uint64_t desc) {
    asm volatile("wgmma.mma_async.sync.aligned.m64n24k16.f32.bf16.bf16 {%0,%1,%2,%3,%4,%5,%6,%7,%8,%9,%10,%11}, {%12,%13,%14,%15}, %16, 1, 1, 1, 1;"
      : "+f"(d[0]), "+f"(d[1]), "+f"(d[2]), "+f"(d[3]), "+f"(d[4]), "+f"(d[5]), "+f"(d[6]), "+f"(d[7]), "+f"(d[8]), "+f"(d[9]), "+f"(d[10]), "+f"(d[11])
      : "r"(a0), "r"(a1), "r"(a2), "r"(a3), "l"(desc));
}

__device__ __forceinline__ void tile_of(int bid, int& mb, int& nt) {
    int grp = bid >> 4, in = bid & 15;
    mb = (grp >> 1) * 4 + (in >> 2);
    nt = (grp & 1) * 4 + (in & 3);
}

constexpr int K1_STAGES = 5, K1_STAGE = 16384 + 24576;
constexpr int K1_BAR = K1_STAGES * K1_STAGE, K1_RS = K1_BAR + 128, K1_CS = K1_RS + 1024, K1_SMEM = K1_CS + 768;

__device__ __forceinline__ float2 row_stats_regs(uint4 a, uint4 b) {
    float v[16];
    v[0] = bf_lo(a.x); v[1] = bf_hi(a.x); v[2] = bf_lo(a.y); v[3] = bf_hi(a.y);
    v[4] = bf_lo(a.z); v[5] = bf_hi(a.z); v[6] = bf_lo(a.w); v[7] = bf_hi(a.w);
    v[8] = bf_lo(b.x); v[9] = bf_hi(b.x); v[10] = bf_lo(b.y); v[11] = bf_hi(b.y);
    v[12] = bf_lo(b.z); v[13] = bf_hi(b.z); v[14] = bf_lo(b.w); v[15] = bf_hi(b.w);
    float s = 0.f;
#pragma unroll
    for (int i = 0; i < 16; i++) s += v[i];
    float mean = warp_sum(s) * (1.0f / DM);
    float q = 0.f;
#pragma unroll
    for (int i = 0; i < 16; i++) { float d = v[i] - mean; q = fmaf(d, d, q); }
    float var = warp_sum(q) * (1.0f / DM);
    float rstd = rsqrtf(var + 1e-5f);
    return make_float2(rstd, -mean * rstd);
}
__device__ __forceinline__ float2 row_stats_x(const __nv_bfloat16* x, int row, int lane) {
    const uint4* p = (const uint4*)(x + (size_t)row * DM);
    return row_stats_regs(__ldg(p + lane), __ldg(p + 32 + lane));
}
__device__ __forceinline__ void colsum8(const __nv_bfloat16* w, int ld, int col, int k0, int nk, float (&s)[8]) {
#pragma unroll
    for (int i = 0; i < 8; i++) s[i] = 0.f;
    for (int k = k0; k < k0 + nk; k += 8) {
        uint4 u[8];
#pragma unroll
        for (int i = 0; i < 8; i++) u[i] = __ldg((const uint4*)(w + (size_t)(k + i) * ld + col));
#pragma unroll
        for (int i = 0; i < 8; i++) {
            s[0] += bf_lo(u[i].x); s[1] += bf_hi(u[i].x); s[2] += bf_lo(u[i].y); s[3] += bf_hi(u[i].y);
            s[4] += bf_lo(u[i].z); s[5] += bf_hi(u[i].z); s[6] += bf_lo(u[i].w); s[7] += bf_hi(u[i].w);
        }
    }
}
__device__ __forceinline__ bool wait_count(const unsigned int* p, unsigned int target, int lane) {
    int ok = 1;
    if (lane == 0) {
        int it = 0;
        while (ld_acquire(p) < target) { if (++it > (1 << 18)) { ok = 0; break; } }
    }
    ok = __shfl_sync(0xffffffffu, ok, 0);
    return ok != 0;
}

__global__ void __launch_bounds__(384, 1)
qkv_kernel(const __grid_constant__ CUtensorMap tm_x, const __grid_constant__ CUtensorMap tm_w,
           const __nv_bfloat16* __restrict__ x, const __nv_bfloat16* __restrict__ wqkv) {
    extern __shared__ __align__(1024) unsigned char smem[];
    const uint32_t sb = smem_u32(smem);
    const int tid = threadIdx.x, warp = __shfl_sync(0xffffffffu, tid >> 5, 0), lane = tid & 31;
    TLDECL
    TL(0);
    int mb, nt;
    tile_of(blockIdx.x, mb, nt);
    const uint32_t full = sb + K1_BAR, empty = full + 40, auxb = full + 80;
    if (tid == 0) {
        prefetch_tmap(&tm_x); prefetch_tmap(&tm_w);
        for (int i = 0; i < K1_STAGES; i++) { mbar_init(full + 8 * i, 1); mbar_init(empty + 8 * i, 8); }
        mbar_init(auxb, 3);
        fence_barrier_init();
    }
    __syncthreads();
    pdl_launch();
    if (warp == 0) {
        if (blockIdx.x == 0) for (int i = lane; i < 160; i += 32) g_cnt2[i] = 0;
        if (lane == 0) {
            for (int kb = 0; kb < 8; kb++) {
                int s = kb % K1_STAGES;
                if (kb >= K1_STAGES) mbar_wait(empty + 8 * s, 0);
                mbar_expect(full + 8 * s, K1_STAGE);
                tma2d(sb + s * K1_STAGE, &tm_x, kb * 64, mb * 128, full + 8 * s);
                tma3d(sb + s * K1_STAGE + 16384, &tm_w, 0, kb * 64, nt * 3, full + 8 * s);
            }
        }
    } else if (warp < 4) {
        float2* s_rs = (float2*)(smem + K1_RS);
        float* s_cs = (float*)(smem + K1_CS);
        if (warp < 3) {
            const int r0 = mb * 128 + nt * 16 + (warp - 1) * 8;
            uint4 u[16];
#pragma unroll
            for (int i = 0; i < 8; i++) {
                const uint4* p = (const uint4*)(x + (size_t)(r0 + i) * DM);
                u[2 * i] = __ldg(p + lane); u[2 * i + 1] = __ldg(p + 32 + lane);
            }
            float2 mine = make_float2(0.f, 0.f);
#pragma unroll
            for (int i = 0; i < 8; i++) {
                float2 st = row_stats_regs(u[2 * i], u[2 * i + 1]);
                if (lane == i) mine = st;
            }
            if (lane < 8) g_rowstat1[r0 + lane] = mine;
            __syncwarp();
            if (lane == 0) red_release(&g_cnt[mb]);
        } else {
            uint4 u[24];
#pragma unroll
            for (int c = 0; c < 3; c++)
#pragma unroll
                for (int i = 0; i < 8; i++)
                    u[c * 8 + i] = __ldg((const uint4*)(wqkv + (size_t)(mb * 32 + (lane >> 3) * 8 + i) * 1536 + nt * 192 + (c * 8 + (lane & 7)) * 8));
#pragma unroll
            for (int c = 0; c < 3; c++) {
                float cs[8];
#pragma unroll
                for (int i = 0; i < 8; i++) cs[i] = 0.f;
#pragma unroll
                for (int i = 0; i < 8; i++) {
                    const uint4 w = u[c * 8 + i];
                    cs[0] += bf_lo(w.x); cs[1] += bf_hi(w.x); cs[2] += bf_lo(w.y); cs[3] += bf_hi(w.y);
                    cs[4] += bf_lo(w.z); cs[5] += bf_hi(w.z); cs[6] += bf_lo(w.w); cs[7] += bf_hi(w.w);
                }
#pragma unroll
                for (int i = 0; i < 8; i++) {
                    cs[i] += __shfl_xor_sync(0xffffffffu, cs[i], 8);
                    cs[i] += __shfl_xor_sync(0xffffffffu, cs[i], 16);
                }
                if (lane < 8) {
                    float4* d = (float4*)(g_cs1_part + mb * 1536 + nt * 192 + (c * 8 + lane) * 8);
                    d[0] = make_float4(cs[0], cs[1], cs[2], cs[3]);
                    d[1] = make_float4(cs[4], cs[5], cs[6], cs[7]);
                }
            }
            __syncwarp();
            if (lane == 0) red_release(&g_cnt[16 + nt]);
        }
        TX(8 + warp);
        if (warp == 1) {
            if (wait_count(&g_cnt[mb], 16, lane)) {
#pragma unroll
                for (int i = 0; i < 4; i++) s_rs[lane + 32 * i] = __ldcg(&g_rowstat1[mb * 128 + lane + 32 * i]);
            } else {
                for (int i = 0; i < 128; i++) {
                    float2 st = row_stats_x(x, mb * 128 + i, lane);
                    if (lane == 0) s_rs[i] = st;
                }
            }
        } else {
            int c0 = (warp - 2) * 96;
            if (wait_count(&g_cnt[16 + nt], 16, lane)) {
#pragma unroll
                for (int i = 0; i < 3; i++) {
                    float s = 0.f;
#pragma unroll
                    for (int p = 0; p < 16; p++) s += __ldcg(&g_cs1_part[p * 1536 + nt * 192 + c0 + lane + 32 * i]);
                    s_cs[c0 + lane + 32 * i] = s;
                }
            } else if (lane < 12) {
                float s[8];
                colsum8(wqkv, 1536, nt * 192 + c0 + lane * 8, 0, 512, s);
#pragma unroll
                for (int i = 0; i < 8; i++) s_cs[c0 + lane * 8 + i] = s[i];
            }
        }
        __syncwarp();
        TX(12 + warp);
        if (lane == 0) mbar_arrive(auxb);
        bar_sync(2, 256 + 96);
        const int a = tid - 32;
        {
            const int hh = a >> 3, w = a & 7;
            const float4* p = (const float4*)(smem + 49152) + (hh * 256 + w * 32) / 2;
            float m = 0.f;
#pragma unroll
            for (int i = 0; i < 8; i++) {
                const int ii = (i + a) & 7;
                float4 u = p[2 * ii], v = p[2 * ii + 1];
                float n0 = u.x + u.z + v.x + v.z, n1 = u.y + u.w + v.y + v.w;
                if (!(n0 <= 3.0e38f) || !(n1 <= 3.0e38f)) m = __int_as_float(0x7f800000);
                m = fmaxf(m, fmaxf(n0, n1));
            }
            const int col0 = nt * 192 + hh * 16;
            g_nrm[((col0 >> 9) * NH + ((col0 & 511) >> 4)) * 128 + mb * 8 + w] = m;
        }
        if (a < 24) bulk_wait_all();
        TL(27);
        TLDUMP;
    } else {
        const int wgi = (warp >> 2) - 1, ww = warp & 3;
        float acc[96];
#pragma unroll 1
        for (int kb = 0; kb < 8; kb++) {
            int s = kb % K1_STAGES;
            mbar_wait(full + 8 * s, (kb / K1_STAGES) & 1);
            if (warp == 4) TX(kb);
            uint64_t ad = make_desc(sb + s * K1_STAGE + wgi * 8192, 16, 1024, 1);
            uint64_t bd = make_desc(sb + s * K1_STAGE + 16384, 8192, 1024, 1);
            WG_FENCE();
#pragma unroll
            for (int k = 0; k < 4; k++) wgmma_ss_n192(acc, ad + k * 2, bd + k * 128, (kb | k) != 0);
            WG_COMMIT();
            if (kb > 0) {
                wg_wait<1>();
                if (lane == 0) mbar_arrive(empty + 8 * ((kb - 1) % K1_STAGES));
            }
        }
        wg_wait<0>();
        fence_regs(acc);
        TL(1);
        if (warp == 4) TX(16);
        mbar_wait(auxb, 0);
        if (warp == 4) TX(17);
        bar_sync(1, 256);
        const float2* s_rs = (const float2*)(smem + K1_RS);
        const float* s_cs = (const float*)(smem + K1_CS);
        const int g = lane >> 2, t = lane & 3;
        const int rl = wgi * 64 + ww * 16 + g;
        const float2 st0 = s_rs[rl], st1 = s_rs[rl + 8];
        const float QS = 0.25f * 1.4426950408889634f;
        const uint32_t stg = sb + ((lane >> 4) * 16 + wgi * 8 + ww * 2 + ((lane >> 3) & 1)) * 128 + (lane & 7) * 16;
        float2* s_np = (float2*)(smem + 49152) + (warp - 4) * 32 + lane;
#pragma unroll
        for (int hh = 0; hh < 12; hh++) {
            const int which = (nt * 192 + hh * 16) >> 9;
            const float sc = (which == 0) ? QS : 1.0f;
            const float a0 = st0.x * sc, b0 = st0.y * sc, a1 = st1.x * sc, b1 = st1.y * sc;
            const float2 c0 = *(const float2*)(s_cs + 16 * hh + 2 * t), c1 = *(const float2*)(s_cs + 16 * hh + 8 + 2 * t);
            const float* a = acc + 8 * hh;
            float v0 = fmaf(a0, a[0], b0 * c0.x), v1 = fmaf(a0, a[1], b0 * c0.y), v2 = fmaf(a1, a[2], b1 * c0.x), v3 = fmaf(a1, a[3], b1 * c0.y);
            float v4 = fmaf(a0, a[4], b0 * c1.x), v5 = fmaf(a0, a[5], b0 * c1.y), v6 = fmaf(a1, a[6], b1 * c1.x), v7 = fmaf(a1, a[7], b1 * c1.y);
            {
                const int head = ((nt * 192 + hh * 16) & 511) >> 4;
                uint32_t* o = (uint32_t*)g_qkv + ((size_t)((which * NH + head) * 2) * 256 + mb * 16 + wgi * 8 + ww * 2) * 32 + lane;
                o[0] = pack_bf16(v0, v1); o[32] = pack_bf16(v2, v3); o[8192] = pack_bf16(v4, v5); o[8192 + 32] = pack_bf16(v6, v7);
            }
            s_np[hh * 256] = make_float2(fmaf(v0, v0, fmaf(v1, v1, fmaf(v4, v4, v5 * v5))), fmaf(v2, v2, fmaf(v3, v3, fmaf(v6, v6, v7 * v7))));
        }
        fence_proxy_async();
        bar_arrive(2, 256 + 96);
        TL(2);
        TLDUMP;
    }
}

constexpr int AT_K = 0, AT_V = 65536, AT_ONES = 131072, AT_BAR = 163840, AT_SMEM = AT_BAR + 128;
#define POLY_MASK 0xAD6A

__device__ __forceinline__ uint32_t exp2_pair_poly(float x0, float x1) {
    uint32_t t0 = __float_as_uint(x0 + 32895.0f);
    uint32_t t1 = __float_as_uint(x1 + 32895.0f);
    uint32_t gd = __byte_perm(t0, t1, 0x6420);
    uint32_t wm = __byte_perm(t0, t1, 0x5612);
    uint32_t v = hfma2(gd, 0x71477147u, 0x354f354fu);
    uint32_t z = hmul2(v, gd);
    return (wm >> 1) + z;
}
__device__ __forceinline__ uint32_t exp2_pair_mufu(float x0, float x1) { return pack_bf16(ex2f(x0), ex2f(x1)); }
template <uint32_t MASK>
__device__ __forceinline__ void exp_blocks(const float (&s)[32], uint32_t (&p)[16]) {
#pragma unroll
    for (int b = 0; b < 8; b++) {
        if ((MASK >> b) & 1) {
            p[2 * b] = exp2_pair_poly(s[4 * b], s[4 * b + 1]);
            p[2 * b + 1] = exp2_pair_poly(s[4 * b + 2], s[4 * b + 3]);
        } else {
            p[2 * b] = exp2_pair_mufu(s[4 * b], s[4 * b + 1]);
            p[2 * b + 1] = exp2_pair_mufu(s[4 * b + 2], s[4 * b + 3]);
        }
    }
}
#define PV4(P) _Pragma("unroll") for (int i = 0; i < 4; i++) { pv_wgmma(o, P[4 * i], P[4 * i + 1], P[4 * i + 2], P[4 * i + 3], vd); vd += 16; }

__device__ __forceinline__ void attn_store(float (&o)[12], int row0, int head, int lane) {
    float l0 = __shfl_sync(0xffffffffu, o[8], lane & 28);
    float l1 = __shfl_sync(0xffffffffu, o[10], lane & 28);
    float r0 = 1.0f / l0, r1 = 1.0f / l1;
    uint32_t* op = (uint32_t*)g_ao;
    int mb = row0 >> 7, rg = (row0 & 127) >> 3;
    int kb = head >> 2, kc = (head & 3) * 2;
    size_t base = (((size_t)(mb * 8 + kb) * 8 + kc) * 16 + rg) * 32 + lane;
    op[base] = pack_bf16(o[0] * r0, o[1] * r0);
    op[base + 32] = pack_bf16(o[2] * r1, o[3] * r1);
    op[base + 16 * 32] = pack_bf16(o[4] * r0, o[5] * r0);
    op[base + 16 * 32 + 32] = pack_bf16(o[6] * r1, o[7] * r1);
}

__device__ __forceinline__ void attn_load_q(uint32_t (&q)[4], const __nv_bfloat16* gq, int row0, int lane) {
    const uint32_t* qp = (const uint32_t*)gq;
    int j0 = row0 >> 3;
    q[0] = __ldcg(qp + (0 * 256 + j0) * 32 + lane);
    q[1] = __ldcg(qp + (0 * 256 + j0 + 1) * 32 + lane);
    q[2] = __ldcg(qp + (1 * 256 + j0) * 32 + lane);
    q[3] = __ldcg(qp + (1 * 256 + j0 + 1) * 32 + lane);
}

__device__ __forceinline__ void attn_tile_safe(const uint32_t (&q)[4], uint64_t kd, uint64_t vd, int row0, int head, int lane) {
    float o[12];
#pragma unroll
    for (int i = 0; i < 12; i++) o[i] = 0.f;
    float m0 = -INFINITY, m1 = -INFINITY;
    fence_regs(o);
#pragma unroll 1
    for (int j = 0; j < 32; j++) {
        float s[32];
        uint32_t p[16];
        WG_FENCE();
        qk_wgmma_n64(s, q, kd); kd += 64;
        WG_COMMIT();
        wg_wait<0>();
        fence_regs(s);
        fence_regs(o);
        float x0 = m0, x1 = m1;
#pragma unroll
        for (int b = 0; b < 8; b++) {
            x0 = fmaxf(x0, fmaxf(s[4 * b], s[4 * b + 1]));
            x1 = fmaxf(x1, fmaxf(s[4 * b + 2], s[4 * b + 3]));
        }
        x0 = fmaxf(x0, __shfl_xor_sync(0xffffffffu, x0, 1)); x0 = fmaxf(x0, __shfl_xor_sync(0xffffffffu, x0, 2));
        x1 = fmaxf(x1, __shfl_xor_sync(0xffffffffu, x1, 1)); x1 = fmaxf(x1, __shfl_xor_sync(0xffffffffu, x1, 2));
        float al0 = ex2f(m0 - x0), al1 = ex2f(m1 - x1);
        m0 = x0; m1 = x1;
#pragma unroll
        for (int i = 0; i < 3; i++) { o[4 * i] *= al0; o[4 * i + 1] *= al0; o[4 * i + 2] *= al1; o[4 * i + 3] *= al1; }
#pragma unroll
        for (int b = 0; b < 8; b++) {
            p[2 * b] = exp2_pair_mufu(s[4 * b] - m0, s[4 * b + 1] - m0);
            p[2 * b + 1] = exp2_pair_mufu(s[4 * b + 2] - m1, s[4 * b + 3] - m1);
        }
        fence_regs(o);
        WG_FENCE();
        PV4(p);
        WG_COMMIT();
        wg_wait<0>();
        fence_regs(o);
    }
    attn_store(o, row0, head, lane);
}

__global__ void __launch_bounds__(512, 1)
attn_kernel(const __nv_bfloat16* __restrict__ wg_, const __nv_bfloat16* __restrict__ wu_,
            const __nv_bfloat16* __restrict__ wo_, const __nv_bfloat16* __restrict__ wd_) {
    extern __shared__ __align__(1024) unsigned char smem[];
    const uint32_t sb = smem_u32(smem);
    const int tid = threadIdx.x, wg = tid >> 7, warp = (tid >> 5) & 3, lane = tid & 31;
    TLDECL
    pdl_launch();
    if (blockIdx.x >= 128) {
        const int e = blockIdx.x - 128;
        const __nv_bfloat16* w = (e < 2) ? wg_ : wu_;
        float* red = (float*)smem;
        const int cgrp = tid & 127, kq = tid >> 7;
        if (cgrp < 112) {
            float s[8];
            colsum8(w, FF, (e & 1) * 896 + cgrp * 8, kq * 128, 128, s);
#pragma unroll
            for (int i = 0; i < 8; i++) red[kq * 896 + cgrp * 8 + i] = s[i];
        }
        __syncthreads();
        for (int c = tid; c < 896; c += 512)
            g_cs2[(e >> 1) * FF + (e & 1) * 896 + c] = red[c] + red[896 + c] + red[1792 + c] + red[2688 + c];
        if (tid < 32) {
            const char* p0 = (const char*)wo_ + e * (DM * DM * 2 / 4);
            for (int i = lane; i < 32; i += 32)
                asm volatile("cp.async.bulk.prefetch.L2.global [%0], %1;" :: "l"(p0 + i * 4096), "r"(4096) : "memory");
            const char* p1 = (const char*)wd_ + e * (FF * DM * 2 / 4);
            for (int i = lane; i < 112; i += 32)
                asm volatile("cp.async.bulk.prefetch.L2.global [%0], %1;" :: "l"(p1 + i * 4096), "r"(4096) : "memory");
        }
        return;
    }
    const int head = blockIdx.x >> 2, qq = blockIdx.x & 3;
    const __nv_bfloat16* gq = g_qkv + (size_t)head * (S_LEN * 16);
    const __nv_bfloat16* gk = g_qkv + (size_t)(NH + head) * (S_LEN * 16);
    const __nv_bfloat16* gv = g_qkv + (size_t)(2 * NH + head) * (S_LEN * 16);
    if (tid == 0) {
        for (int i = 0; i < 8; i++) mbar_init(sb + AT_BAR + 8 * i, 1);
        fence_barrier_init();
    }
    {
        uint4 one = make_uint4(0x00003F80u, 0, 0, 0);
#pragma unroll
        for (int i = 0; i < 4; i++) *(uint4*)(smem + AT_ONES + (i * 512 + tid) * 16) = one;
        fence_proxy_async();
    }
    __syncthreads();
    TL(3);
    pdl_wait();
    TL(4);
    auto load_kv = [&](int i) {
        uint32_t bar = sb + AT_BAR + 8 * i;
        mbar_expect(bar, 16384);
        bulk_g2s(sb + AT_K + i * 4096, gk + i * 2048, 4096, bar);
        bulk_g2s(sb + AT_K + 32768 + i * 4096, gk + 16384 + i * 2048, 4096, bar);
        bulk_g2s(sb + AT_V + i * 4096, gv + i * 2048, 4096, bar);
        bulk_g2s(sb + AT_V + 32768 + i * 4096, gv + 16384 + i * 2048, 4096, bar);
    };
    if (tid == 0) { load_kv(0); load_kv(1); }
    uint32_t q[4], q2[4];
    attn_load_q(q, gq, qq * 512 + wg * 64 + warp * 16, lane);
    attn_load_q(q2, gq, qq * 512 + (4 + wg) * 64 + warp * 16, lane);
    bool fast;
    {
        const float* nq = g_nrm + (0 * NH + head) * 128 + qq * 32;
        const float* nk = g_nrm + (1 * NH + head) * 128;
        const float* nv = g_nrm + (2 * NH + head) * 128;
        float4 k4 = __ldcg((const float4*)nk + lane), v4 = __ldcg((const float4*)nv + lane);
        float qm = warp_max(__ldcg(nq + lane));
        float km = warp_max(fmaxf(fmaxf(k4.x, k4.y), fmaxf(k4.z, k4.w)));
        float vm = warp_max(fmaxf(fmaxf(v4.x, v4.y), fmaxf(v4.z, v4.w)));
        fast = __all_sync(0xffffffffu, (qm * km <= 3500.0f) && (vm <= 1.0e24f));
    }
    TL(24);
    const uint64_t kdesc0 = make_desc(sb + AT_K, 32768, 128, 0);
    const uint64_t vdesc0 = make_desc(sb + AT_V, 128, 32768, 0);
    if (!fast) {
        if (tid == 0) for (int i = 2; i < 8; i++) load_kv(i);
        for (int i = 0; i < 8; i++) mbar_wait(sb + AT_BAR + 8 * i, 0);
#pragma unroll 1
        for (int tile = 0; tile < 2; tile++) {
            const int row0 = qq * 512 + (tile * 4 + wg) * 64 + warp * 16;
            attn_tile_safe(q, kdesc0, vdesc0, row0, head, lane);
#pragma unroll
            for (int i = 0; i < 4; i++) q[i] = q2[i];
        }
        return;
    }
#pragma unroll 1
    for (int tile = 0; tile < 2; tile++) {
        const int row0 = qq * 512 + (tile * 4 + wg) * 64 + warp * 16;
        float o[12];
#pragma unroll
        for (int i = 0; i < 12; i++) o[i] = 0.f;
        fence_regs(o);
        float sa[32];
        uint32_t pa[16];
        uint64_t kd = kdesc0, vd = vdesc0;
        if (tile == 0) { mbar_wait(sb + AT_BAR, 0); TL(25); }
        WG_FENCE();
        qk_wgmma_n64(sa, q, kd); kd += 64;
        WG_COMMIT();
#pragma unroll 1
        for (int jj = 0; jj < 8; jj++) {
            if (tile == 0 && jj < 7) {
                if (tid == 0 && jj < 6) load_kv(jj + 2);
                mbar_wait(sb + AT_BAR + 8 * (jj + 1), 0);
            }
            if (wg == 0 && warp == 0) TX(128 + tile * 8 + jj);
#pragma unroll
            for (int j = 0; j < 4; j++) {
                wg_wait<0>();
                fence_regs(sa);
                if (j & 1) exp_blocks<(POLY_MASK >> 8)>(sa, pa); else exp_blocks<(POLY_MASK & 255)>(sa, pa);
                WG_FENCE();
                qk_wgmma_n64(sa, q, kd); kd += 64;
                PV4(pa);
                WG_COMMIT();
            }
        }
        wg_wait<0>();
        fence_regs(o);
        fence_regs(sa);
        if (tile == 0) TL(26);
        attn_store(o, row0, head, lane);
#pragma unroll
        for (int i = 0; i < 4; i++) q[i] = q2[i];
    }
    TL(5);
    TLDUMP;
}

constexpr int F_R2 = 131072, F_X = 196608, F_BAR = 229376;
constexpr int F_RS = F_BAR + 256, F_CS = F_RS + 1024, F_SMEM = F_CS + 1792;
enum { B_FA = 0, B_HF = 4, B_BF = 8, B_BE = 11, B_CF = 14, B_CE = 20, B_ADONE = 26, B_BDONE = 27, B_XC = 28, B_PRDY = 29, B_AUX = 30, B_NUM = 31 };

__device__ __forceinline__ uint32_t mapa(uint32_t a, uint32_t rank) { uint32_t r; asm("mapa.shared::cluster.u32 %0, %1, %2;" : "=r"(r) : "r"(a), "r"(rank)); return r; }
__device__ __forceinline__ void st_async4(uint32_t dst, float a, float b, float c, float d, uint32_t bar) {
    asm volatile("st.async.weak.shared::cluster.mbarrier::complete_tx::bytes.v4.f32 [%0], {%1,%2,%3,%4}, [%5];"
                 :: "r"(dst), "f"(a), "f"(b), "f"(c), "f"(d), "r"(bar) : "memory");
}
__device__ __forceinline__ void mbar_arrive_remote(uint32_t a) { asm volatile("mbarrier.arrive.relaxed.cluster.shared::cluster.b64 _, [%0];" :: "r"(a) : "memory"); }
__device__ __forceinline__ void mbar_wait_cluster(uint32_t a, int parity) {
    uint32_t done;
    int it = 0;
    do {
        asm volatile("{\n.reg .pred p;\nmbarrier.try_wait.parity.acquire.cluster.shared::cta.b64 p, [%1], %2;\nselp.u32 %0, 1, 0, p;\n}"
                     : "=r"(done) : "r"(a), "r"(parity) : "memory");
        if (++it > (1 << 24)) __trap();
    } while (!done);
}
__device__ __forceinline__ void poll_count(const unsigned int* p, unsigned int target) {
    int it = 0;
    while (ld_acquire(p) < target) { if (++it > (1 << 22)) __trap(); }
    asm volatile("fence.proxy.async.global;" ::: "memory");
}
__device__ __forceinline__ void tma2d_mc(uint32_t dst, const CUtensorMap* m, int c0, int c1, uint32_t bar) {
    asm volatile("cp.async.bulk.tensor.2d.shared::cluster.global.mbarrier::complete_tx::bytes.multicast::cluster [%0], [%1, {%3, %4}], [%2], %5;"
                 :: "r"(dst), "l"(m), "r"(bar), "r"(c0), "r"(c1), "h"((uint16_t)3) : "memory");
}
__device__ __forceinline__ void bulk_g2s_mc(uint32_t dst, const void* src, int bytes, uint32_t bar) {
    asm volatile("cp.async.bulk.shared::cluster.global.mbarrier::complete_tx::bytes.multicast::cluster [%0], [%1], %2, [%3], %4;"
                 :: "r"(dst), "l"(src), "r"(bytes), "r"(bar), "h"((uint16_t)3) : "memory");
}
__device__ __forceinline__ void tma2d_store(const CUtensorMap* m, uint32_t src, int c0, int c1) {
    asm volatile("cp.async.bulk.tensor.2d.global.shared::cta.bulk_group [%0, {%2, %3}], [%1];" :: "l"(m), "r"(src), "r"(c0), "r"(c1) : "memory");
}
__device__ __forceinline__ float2 h_row_stats(int row) {
    const float4* hp = (const float4*)(g_hstat + (size_t)row * 8);
    float4 a = __ldcg(hp), b = __ldcg(hp + 1), c = __ldcg(hp + 2), d = __ldcg(hp + 3);
    float mean = 0.125f * (a.x + a.z + b.x + b.z + c.x + c.z + d.x + d.z);
    float m2 = a.y + a.w + b.y + b.w + c.y + c.w + d.y + d.w;
    float e;
    e = a.x - mean; m2 = fmaf(64.f * e, e, m2); e = a.z - mean; m2 = fmaf(64.f * e, e, m2);
    e = b.x - mean; m2 = fmaf(64.f * e, e, m2); e = b.z - mean; m2 = fmaf(64.f * e, e, m2);
    e = c.x - mean; m2 = fmaf(64.f * e, e, m2); e = c.z - mean; m2 = fmaf(64.f * e, e, m2);
    e = d.x - mean; m2 = fmaf(64.f * e, e, m2); e = d.z - mean; m2 = fmaf(64.f * e, e, m2);
    return make_float2(rsqrtf(m2 * (1.0f / DM) + 1e-5f), -mean);
}
__device__ __forceinline__ int c_kblock(int i, int r) {
    if (i < 6) { const int e = 2 * i + r, m = e / 3, k = e - 3 * m; return 7 * m + (k == 2 ? 4 : k); }
    const int l = 2 * (i - 6) + r, m = l >> 2, k = l & 3;
    return 7 * m + (k < 2 ? 2 + k : 3 + k);
}
template <int R>
__device__ __forceinline__ void xchg(float (&acc)[64], float (&o)[32], uint32_t sb, unsigned char* smem, int bar, int ctid) {
    const uint32_t dst = mapa(sb + F_X + ctid * 16, 1 - R), rb = mapa(sb + F_BAR + 8 * bar, 1 - R);
#pragma unroll
    for (int q = 0; q < 8; q++) {
        const int j = (1 - R) * 32 + 4 * q;
        st_async4(dst + q * 4096, acc[j], acc[j + 1], acc[j + 2], acc[j + 3], rb);
    }
    mbar_wait_cluster(sb + F_BAR + 8 * bar, 0);
#pragma unroll
    for (int q = 0; q < 8; q++) {
        float4 v = *(const float4*)(smem + F_X + q * 4096 + ctid * 16);
        const int j = R * 32 + 4 * q;
        o[4 * q] = acc[j] + v.x; o[4 * q + 1] = acc[j + 1] + v.y; o[4 * q + 2] = acc[j + 2] + v.z; o[4 * q + 3] = acc[j + 3] + v.w;
    }
}

template <int NB, bool STAGE>
__device__ __forceinline__ void ffn_epilogue(const float* ag, const float* au, const float* s_cs, int cs_off, uint32_t* gp, uint32_t stg,
                                             float2 st0, float2 st1, int lane) {
    const int t = lane & 3;
    const float C1 = 0.7978845608028654f, C2 = 0.044715f * 0.7978845608028654f;
    const float k10 = st0.x * C1, k20 = st0.x * st0.x * st0.x * C2, k11 = st1.x * C1, k21 = st1.x * st1.x * st1.x * C2;
#pragma unroll
    for (int j2 = 0; j2 < NB / 2; j2++) {
        uint32_t pk[4];
#pragma unroll
        for (int jj = 0; jj < 2; jj++) {
            const int j = 2 * j2 + jj;
            const float2 cg = *(const float2*)(s_cs + cs_off + 8 * j + 2 * t);
            const float2 cu = *(const float2*)(s_cs + 224 + cs_off + 8 * j + 2 * t);
            float r[4];
#pragma unroll
            for (int e = 0; e < 4; e++) {
                const float nm = (e < 2) ? st0.y : st1.y, k1 = (e < 2) ? k10 : k11, k2 = (e < 2) ? k20 : k21;
                const float tg = fmaf(nm, (e & 1) ? cg.y : cg.x, ag[4 * j + e]);
                const float tu = fmaf(nm, (e & 1) ? cu.y : cu.x, au[4 * j + e]);
                const float th = tanh_fast(tg * fmaf(tg * tg, k2, k1));
                const float p = tg * tu;
                r[e] = fmaf(p, th, p);
            }
            pk[2 * jj] = pack_bf16(r[0], r[1]);
            pk[2 * jj + 1] = pack_bf16(r[2], r[3]);
        }
        if (STAGE) {
            stsm4(stg + j2 * 4096, pk[0], pk[1], pk[2], pk[3]);
        } else {
            gp[j2 * 1024] = pk[0]; gp[j2 * 1024 + 32] = pk[1]; gp[j2 * 1024 + 512] = pk[2]; gp[j2 * 1024 + 544] = pk[3];
        }
    }
}

__global__ void __cluster_dims__(2, 1, 1) __launch_bounds__(384, 1)
tail_kernel(const __grid_constant__ CUtensorMap tm_o, const __grid_constant__ CUtensorMap tm_g,
            const __grid_constant__ CUtensorMap tm_u, const __grid_constant__ CUtensorMap tm_d,
            const __grid_constant__ CUtensorMap tm_out, const __nv_bfloat16* __restrict__ x) {
    extern __shared__ __align__(1024) unsigned char smem[];
    const uint32_t sb = smem_u32(smem);
    const uint32_t bars = sb + F_BAR;
    const int tid = threadIdx.x, warp = __shfl_sync(0xffffffffu, tid >> 5, 0), lane = tid & 31;
    TLDECL
    TL(6);
    if (warp == 4) TX(200);
    const int cl = blockIdx.x >> 1, r = blockIdx.x & 1;
    const int mb = ((cl & 7) >> 1) * 4 + (cl >> 4), ntA = (cl & 1) * 2 + ((cl >> 3) & 1);
    const int nt = ntA * 2 + r;
    const int mbB = (mb & ~1) + r, ntB = (mb & 1) * 4 + ntA;
    if (tid == 0) {
#pragma unroll
        for (int i = 0; i < B_NUM; i++) {
            const int cnt = (i >= B_BE && i < B_BE + 3) ? 16 : ((i >= B_CE && i < B_CE + 6) || i == B_BDONE || i == B_PRDY) ? 8 : (i == B_AUX || i == B_ADONE) ? 2 : 1;
            mbar_init(bars + 8 * i, cnt);
        }
        mbar_expect(bars + 8 * B_XC, 32768);
        fence_barrier_init();
    }
    TL(28);
    __syncthreads();
    TL(29);
    asm volatile("barrier.cluster.arrive.relaxed.aligned;" ::: "memory");
    TL(30);
    if (warp < 4) {
        asm volatile("setmaxnreg.dec.sync.aligned.u32 56;");
        if (warp == 0) TX(205);
        if (warp == 0) {
            if (lane == 0) {
                auto load_b = [&](int it) {
                    const int s = it % 3, pass = it >> 3, kb = (ntB + it) & 7;
                    const int ng = pass ? 3 : 4, c0 = ntB * 224 + pass * 128;
                    const uint32_t bar = bars + 8 * (B_BF + s), dst = sb + F_R2 + s * 32768 + r * 16384;
                    mbar_expect(bar, ng * 8192);
                    for (int i = 0; i < ng; i++) tma2d_mc(dst + i * 4096, r ? &tm_u : &tm_g, c0 + i * 32, kb * 64, bar);
                };
                for (int i = 0; i < 8; i++) {
                    const uint32_t bar = bars + 8 * (B_FA + (i >> 1));
                    if (!(i & 1)) mbar_expect(bar, 49152);
                    tma2d(sb + F_R2 + 32768 + i * 8192, &tm_o, nt * 64, i * 64, bar);
                }
                asm volatile("barrier.cluster.wait.acquire;" ::: "memory");
                pdl_wait();
                TL(16);
                for (int i = 0; i < 4; i++)
                    bulk_g2s_mc(sb + (2 * i + r) * 16384, g_ao + (size_t)(mb * 8 + 2 * i + r) * 8192, 16384, bars + 8 * (B_FA + i));
                load_b(0);
                if (blockIdx.x == 0)
                    for (int i = 0; i < 32; i++) g_cnt[i] = 0;
                mbar_wait_cluster(bars + 8 * B_ADONE, 0);
                load_b(1); load_b(2);
                for (int it = 3; it < 16; it++) {
                    mbar_wait_cluster(bars + 8 * (B_BE + it % 3), (it / 3 - 1) & 1);
                    load_b(it);
                }
                mbar_wait(bars + 8 * B_BDONE, 0);
                poll_count(&g_cnt2[mb], 8);
                for (int i = 0; i < 14; i++) {
                    const int s = i % 6, kb = c_kblock(i, r);
                    const uint32_t bar = bars + 8 * (B_CF + s);
                    if (i >= 6) mbar_wait(bars + 8 * (B_CE + s), ((i / 6) - 1) & 1);
                    mbar_expect(bar, 32768);
                    tma2d(sb + s * 32768 + 16384, &tm_d, ntA * 128, kb * 64, bar);
                    tma2d(sb + s * 32768 + 24576, &tm_d, ntA * 128 + 64, kb * 64, bar);
                    if (i == 6) { poll_count(&g_cnt2[16 + mb], 8); TL(18); }
                    bulk_g2s(sb + s * 32768, g_g + (size_t)(mb * 28 + kb) * 8192, 16384, bar);
                }
            }
            else asm volatile("barrier.cluster.wait.acquire;" ::: "memory");
            TLDUMP;
        } else if (warp == 1) {
            asm volatile("barrier.cluster.wait.acquire.aligned;" ::: "memory");
            bar_sync(5, 288);
            if (lane == 0) { red_release(&g_cnt2[32 + mb * 8 + nt]); TL(9); }
            __syncwarp();
            bar_sync(1, 288);
            if (lane == 0) red_release(&g_cnt2[mbB]);
            __syncwarp();
            bar_sync(2, 288);
            if (lane == 0) {
                red_release(&g_cnt2[16 + mbB]);
                TL(13);
            }
            __syncwarp();
            bar_sync(3, 288);
            if (lane == 0) {
                tma2d_store(&tm_out, sb, nt * 64, mb * 128);
                bulk_commit();
                bulk_wait_all();
                TL(15);
            }
            TLDUMP;
        } else {
            asm volatile("barrier.cluster.wait.acquire.aligned;" ::: "memory");
            pdl_wait();
            float2* s_rs = (float2*)(smem + F_RS);
            float* s_cs = (float*)(smem + F_CS);
            for (int c = tid - 64; c < 448; c += 64)
                s_cs[c] = __ldcg(&g_cs2[(c >= 224 ? FF - 224 : 0) + ntB * 224 + c]);
            if (tid == 96) {
                mbar_wait_cluster(bars + 8 * B_ADONE, 0);
                for (int i = 0; i < 8; i++) {
                    const int kb = (ntB + i) & 7;
                    const uint32_t bar = bars + 8 * (i < 4 ? B_HF + i : B_FA + i - 4);
                    poll_count(&g_cnt2[32 + mbB * 8 + kb], 1);
                    mbar_expect(bar, 16384);
                    bulk_g2s(sb + kb * 16384, g_h + (size_t)(mbB * 8 + kb) * 8192, 16384, bar);
                }
                TL(17);
            }
            __syncwarp();
            if (lane < 8) poll_count(&g_cnt2[32 + mbB * 8 + lane], 1);
            __syncwarp();
            for (int rr = tid - 64; rr < 128; rr += 64) {
                s_rs[rr] = h_row_stats(mbB * 128 + rr);
            }
            __syncwarp();
            if (lane == 0) mbar_arrive(bars + 8 * B_AUX);
            TLDUMP;
        }
    } else {
        asm volatile("setmaxnreg.inc.sync.aligned.u32 216;");
        if (warp == 4) TX(206);
        const int wgi = (warp >> 2) - 1, ww = warp & 3, ctid = tid - 128;
        const int g = lane >> 2, t = lane & 3;
        const int rl = wgi * 64 + ww * 16 + g, row = mb * 128 + rl;
        const int rgl = wgi * 8 + ww * 2;
        const float2* s_rs = (const float2*)(smem + F_RS);
        const float* s_cs = (const float*)(smem + F_CS);
        const uint32_t stl = ((lane >> 4) * 16 + rgl + ((lane >> 3) & 1)) * 128 + (lane & 7) * 16;
        uint32_t* hp = (uint32_t*)g_h + ((size_t)(mb * 8 + nt) * 8 * 16 + rgl) * 32 + lane;
        const uint32_t rbars = mapa(bars, 1 - r);
        TL(23);
        {
            uint32_t xr[16];
            const uint32_t* xp = (const uint32_t*)(x + (size_t)row * DM + nt * 64) + t;
#pragma unroll
            for (int j = 0; j < 8; j++) { xr[2 * j] = __ldg(xp + 4 * j); xr[2 * j + 1] = __ldg(xp + 8 * (DM / 2) + 4 * j); }
            float acc[32];
#pragma unroll 1
            for (int i = 0; i < 8; i++) {
                if (!(i & 1)) { mbar_wait(bars + 8 * (B_FA + (i >> 1)), 0); if (i == 0) TL(19); }
                uint64_t ad = make_desc(sb + i * 16384 + wgi * 1024, 2048, 128, 0);
                uint64_t bd = make_desc(sb + F_R2 + 32768 + i * 8192, 8192, 1024, 1);
                WG_FENCE();
#pragma unroll
                for (int k = 0; k < 4; k++) wgmma_ss_n64(acc, ad + k * 256, bd + k * 128, (i | k) != 0);
                WG_COMMIT();
            }
            wg_wait<0>();
            fence_regs(acc);
            TL(7);
            asm volatile("barrier.cluster.wait.acquire.aligned;" ::: "memory");
            bar_sync(4, 256);
            if (tid == 128) { mbar_arrive(bars + 8 * B_ADONE); mbar_arrive_remote(mapa(bars + 8 * B_ADONE, 1 - r)); }
            float v0[16], v1[16];
            float s0 = 0.f, s1 = 0.f;
#pragma unroll
            for (int j2 = 0; j2 < 4; j2++) {
                uint32_t u[4];
#pragma unroll
                for (int jj = 0; jj < 2; jj++) {
                    const int j = 2 * j2 + jj;
                    u[2 * jj] = pack_bf16(bf_lo(xr[2 * j]) + acc[4 * j], bf_hi(xr[2 * j]) + acc[4 * j + 1]);
                    u[2 * jj + 1] = pack_bf16(bf_lo(xr[2 * j + 1]) + acc[4 * j + 2], bf_hi(xr[2 * j + 1]) + acc[4 * j + 3]);
                    v0[2 * j] = bf_lo(u[2 * jj]); v0[2 * j + 1] = bf_hi(u[2 * jj]);
                    v1[2 * j] = bf_lo(u[2 * jj + 1]); v1[2 * j + 1] = bf_hi(u[2 * jj + 1]);
                    s0 += v0[2 * j] + v0[2 * j + 1];
                    s1 += v1[2 * j] + v1[2 * j + 1];
                }
                hp[j2 * 1024] = u[0]; hp[j2 * 1024 + 32] = u[1]; hp[j2 * 1024 + 512] = u[2]; hp[j2 * 1024 + 544] = u[3];
            }
            float m0 = s0 * (1.0f / 16), m1 = s1 * (1.0f / 16), q0 = 0.f, q1 = 0.f;
#pragma unroll
            for (int i = 0; i < 16; i++) {
                float d0 = v0[i] - m0, d1 = v1[i] - m1;
                q0 = fmaf(d0, d0, q0); q1 = fmaf(d1, d1, q1);
            }
#pragma unroll
            for (int st = 0; st < 2; st++) {
                float hn = st ? 16.f : 8.f;
                float om0 = __shfl_xor_sync(0xffffffffu, m0, 1 << st), oq0 = __shfl_xor_sync(0xffffffffu, q0, 1 << st);
                float om1 = __shfl_xor_sync(0xffffffffu, m1, 1 << st), oq1 = __shfl_xor_sync(0xffffffffu, q1, 1 << st);
                float d0 = om0 - m0, d1 = om1 - m1;
                q0 = q0 + oq0 + d0 * d0 * hn; q1 = q1 + oq1 + d1 * d1 * hn;
                m0 = 0.5f * (m0 + om0); m1 = 0.5f * (m1 + om1);
            }
            if (t == 0) {
                g_hstat[row * 8 + nt] = make_float2(m0, q0);
                g_hstat[(row + 8) * 8 + nt] = make_float2(m1, q1);
            }
            bar_arrive(5, 288);
            TL(8);
        }
        uint32_t* gp = (uint32_t*)g_g + (((size_t)mbB * 224 + ntB * 28) * 16 + rgl) * 32 + lane;
        {
            float ag[64], au[64];
#pragma unroll 1
            for (int kb = 0; kb < 8; kb++) {
                const int s = kb % 3;
                mbar_wait(bars + 8 * (kb < 4 ? B_HF + kb : B_FA + kb - 4), kb < 4 ? 0 : 1);
                mbar_wait(bars + 8 * (B_BF + s), (kb / 3) & 1);
                uint64_t ad = make_desc(sb + ((ntB + kb) & 7) * 16384 + wgi * 1024, 2048, 128, 0);
                uint64_t bd = make_desc(sb + F_R2 + s * 32768, 4096, 512, 2);
                WG_FENCE();
#pragma unroll
                for (int k = 0; k < 4; k++) {
                    wgmma_ss_n128(ag, ad + k * 256, bd + k * 64, (kb | k) != 0);
                    wgmma_ss_n128(au, ad + k * 256, bd + 1024 + k * 64, (kb | k) != 0);
                }
                WG_COMMIT();
                if (kb > 0) {
                    wg_wait<1>();
                    if (lane == 0) { mbar_arrive(bars + 8 * (B_BE + (kb - 1) % 3)); mbar_arrive_remote(rbars + 8 * (B_BE + (kb - 1) % 3)); }
                }
            }
            wg_wait<0>();
            if (lane == 0) { mbar_arrive(bars + 8 * (B_BE + 7 % 3)); mbar_arrive_remote(rbars + 8 * (B_BE + 7 % 3)); }
            fence_regs(ag); fence_regs(au);
            TL(10);
            mbar_wait(bars + 8 * B_AUX, 0);
            ffn_epilogue<16, false>(ag, au, s_cs, 0, gp, 0, s_rs[rl], s_rs[rl + 8], lane);
            bar_arrive(1, 288);
        }
        {
            float ag[48], au[48];
#pragma unroll 1
            for (int kb = 0; kb < 8; kb++) {
                const int it = 8 + kb, s = it % 3;
                mbar_wait(bars + 8 * (B_BF + s), (it / 3) & 1);
                uint64_t ad = make_desc(sb + ((ntB + kb) & 7) * 16384 + wgi * 1024, 2048, 128, 0);
                uint64_t bd = make_desc(sb + F_R2 + s * 32768, 4096, 512, 2);
                WG_FENCE();
#pragma unroll
                for (int k = 0; k < 4; k++) {
                    wgmma_ss_n96(ag, ad + k * 256, bd + k * 64, (kb | k) != 0);
                    wgmma_ss_n96(au, ad + k * 256, bd + 1024 + k * 64, (kb | k) != 0);
                }
                WG_COMMIT();
                if (kb > 0) {
                    wg_wait<1>();
                    if (lane == 0 && it + 2 < 16) { mbar_arrive(bars + 8 * (B_BE + (it - 1) % 3)); mbar_arrive_remote(rbars + 8 * (B_BE + (it - 1) % 3)); }
                }
            }
            wg_wait<0>();
            if (lane == 0) {
                mbar_arrive(bars + 8 * B_BDONE);
                mbar_arrive_remote(rbars + 8 * B_PRDY);
            }
            fence_regs(ag); fence_regs(au);
            TL(11);
            ffn_epilogue<12, false>(ag, au, s_cs, 128, gp + 16 * 512, 0, s_rs[rl], s_rs[rl + 8], lane);
            bar_arrive(2, 288);
            TL(12);
        }
        {
            uint32_t hr[16];
#pragma unroll
            for (int j = 0; j < 8; j++) { hr[2 * j] = __ldcg(hp + j * 512); hr[2 * j + 1] = __ldcg(hp + j * 512 + 32); }
            mbar_wait(bars + 8 * (B_CF + 0), 0);
            const float a0 = h_row_stats(row).x, a1 = h_row_stats(row + 8).x;
            float acc[64];
#pragma unroll 1
            for (int kb = 0; kb < 14; kb++) {
                const int s = kb % 6;
                mbar_wait(bars + 8 * (B_CF + s), (kb / 6) & 1);
                if (warp == 4) TX(96 + kb);
                uint64_t ad = make_desc(sb + s * 32768 + wgi * 1024, 2048, 128, 0);
                uint64_t bd = make_desc(sb + s * 32768 + 16384, 8192, 1024, 1);
                WG_FENCE();
#pragma unroll
                for (int k = 0; k < 4; k++) wgmma_ss_n128(acc, ad + k * 256, bd + k * 128, (kb | k) != 0);
                WG_COMMIT();
                if (kb > 0) {
                    wg_wait<1>();
                    if (lane == 0) mbar_arrive(bars + 8 * (B_CE + (kb - 1) % 6));
                }
            }
            wg_wait<0>();
            fence_regs(acc);
            TL(14);
            mbar_wait_cluster(bars + 8 * B_PRDY, 0);
            float o[32];
            if (r == 0) xchg<0>(acc, o, sb, smem, B_XC, ctid); else xchg<1>(acc, o, sb, smem, B_XC, ctid);
            TL(22);
            bar_sync(4, 256);
            const float k0 = 0.5f * a0 * a0, k1 = 0.5f * a1 * a1;
            const int srow = wgi * 64 + ww * 16 + ((lane >> 3) & 1) * 8 + (lane & 7);
#pragma unroll
            for (int j2 = 0; j2 < 4; j2++) {
                uint32_t u[4];
#pragma unroll
                for (int jj = 0; jj < 2; jj++) {
                    const int j = 2 * j2 + jj;
                    u[2 * jj] = pack_bf16(fmaf(k0, o[4 * j], bf_lo(hr[2 * j])), fmaf(k0, o[4 * j + 1], bf_hi(hr[2 * j])));
                    u[2 * jj + 1] = pack_bf16(fmaf(k1, o[4 * j + 2], bf_lo(hr[2 * j + 1])), fmaf(k1, o[4 * j + 3], bf_hi(hr[2 * j + 1])));
                }
                const int chunk = 2 * j2 + (lane >> 4);
                stsm4(sb + srow * 128 + ((chunk ^ (lane & 7)) * 16), u[0], u[1], u[2], u[3]);
            }
            fence_proxy_async();
            bar_arrive(3, 288);
            TLDUMP;
        }
    }
}

typedef CUresult (*EncodeFn)(CUtensorMap*, CUtensorMapDataType, cuuint32_t, void*, const cuuint64_t*, const cuuint64_t*,
                             const cuuint32_t*, const cuuint32_t*, CUtensorMapInterleave, CUtensorMapSwizzle,
                             CUtensorMapL2promotion, CUtensorMapFloatOOBfill);

void encode(EncodeFn fn, CUtensorMap* m, const void* ptr, int rank, const cuuint64_t* dims, const cuuint64_t* strides,
            const cuuint32_t* box, CUtensorMapSwizzle swz) {
    cuuint32_t es[3] = {1, 1, 1};
    fn(m, CU_TENSOR_MAP_DATA_TYPE_BFLOAT16, rank, (void*)ptr, dims, strides, box, es, CU_TENSOR_MAP_INTERLEAVE_NONE, swz,
       CU_TENSOR_MAP_L2_PROMOTION_L2_256B, CU_TENSOR_MAP_FLOAT_OOB_FILL_NONE);
}

template <typename... KArgs, typename... Args>
void launch(void (*kern)(KArgs...), int grid, int block, int smem, bool pdl, Args... args) {
    cudaLaunchConfig_t cfg = {};
    cfg.gridDim = dim3(grid); cfg.blockDim = dim3(block); cfg.dynamicSmemBytes = smem;
    cfg.stream = cudaStreamPerThread;
    cudaLaunchAttribute at[1];
    at[0].id = cudaLaunchAttributeProgrammaticStreamSerialization;
    at[0].val.programmaticStreamSerializationAllowed = 1;
    cfg.attrs = at; cfg.numAttrs = pdl ? 1 : 0;
    cudaLaunchKernelEx(&cfg, kern, KArgs(args)...);
}

}

extern "C" void kernel_launch(void* const* d_in, const int* in_sizes, int n_in, void* d_out, int out_size) {
    const __nv_bfloat16* x = (const __nv_bfloat16*)d_in[0];
    const __nv_bfloat16* wqkv = (const __nv_bfloat16*)d_in[1];
    const __nv_bfloat16* wo = (const __nv_bfloat16*)d_in[2];
    const __nv_bfloat16* wgate = (const __nv_bfloat16*)d_in[4];
    const __nv_bfloat16* wup = (const __nv_bfloat16*)d_in[5];
    const __nv_bfloat16* wdown = (const __nv_bfloat16*)d_in[6];
    __nv_bfloat16* out = (__nv_bfloat16*)d_out;

    static CUtensorMap tm_x, tm_wqkv, tm_wo, tm_wg, tm_wu, tm_wd, tm_out;
    static const void* cached[7] = {nullptr, nullptr, nullptr, nullptr, nullptr, nullptr, nullptr};
    if (cached[0] != x || cached[1] != wqkv || cached[2] != wo || cached[3] != wgate || cached[4] != wup || cached[5] != wdown || cached[6] != out) {
        void* fp = nullptr;
        cudaDriverEntryPointQueryResult qr;
        cudaGetDriverEntryPoint("cuTensorMapEncodeTiled", &fp, cudaEnableDefault, &qr);
        EncodeFn fn = (EncodeFn)fp;
        { cuuint64_t d[2] = {512, 2048}, s[1] = {1024}; cuuint32_t b[2] = {64, 128};
          encode(fn, &tm_x, x, 2, d, s, b, CU_TENSOR_MAP_SWIZZLE_128B);
          encode(fn, &tm_out, out, 2, d, s, b, CU_TENSOR_MAP_SWIZZLE_128B); }
        { cuuint64_t d[3] = {64, 512, 24}, s[2] = {3072, 128}; cuuint32_t b[3] = {64, 64, 3};
          encode(fn, &tm_wqkv, wqkv, 3, d, s, b, CU_TENSOR_MAP_SWIZZLE_128B); }
        { cuuint64_t d[2] = {512, 512}, s[1] = {1024}; cuuint32_t b[2] = {64, 64};
          encode(fn, &tm_wo, wo, 2, d, s, b, CU_TENSOR_MAP_SWIZZLE_128B); }
        { cuuint64_t d[2] = {1792, 512}, s[1] = {3584}; cuuint32_t b[2] = {32, 64};
          encode(fn, &tm_wg, wgate, 2, d, s, b, CU_TENSOR_MAP_SWIZZLE_64B);
          encode(fn, &tm_wu, wup, 2, d, s, b, CU_TENSOR_MAP_SWIZZLE_64B); }
        { cuuint64_t d[2] = {512, 1792}, s[1] = {1024}; cuuint32_t b[2] = {64, 64};
          encode(fn, &tm_wd, wdown, 2, d, s, b, CU_TENSOR_MAP_SWIZZLE_128B); }
        cudaFuncSetAttribute(qkv_kernel, cudaFuncAttributeMaxDynamicSharedMemorySize, F_SMEM);
        cudaFuncSetAttribute(qkv_kernel, cudaFuncAttributePreferredSharedMemoryCarveout, 100);
        cudaFuncSetAttribute(attn_kernel, cudaFuncAttributeMaxDynamicSharedMemorySize, F_SMEM);
        cudaFuncSetAttribute(attn_kernel, cudaFuncAttributePreferredSharedMemoryCarveout, 100);
        cudaFuncSetAttribute(tail_kernel, cudaFuncAttributeMaxDynamicSharedMemorySize, F_SMEM);
        cudaFuncSetAttribute(tail_kernel, cudaFuncAttributePreferredSharedMemoryCarveout, 100);
        cached[0] = x; cached[1] = wqkv; cached[2] = wo; cached[3] = wgate; cached[4] = wup; cached[5] = wdown; cached[6] = out;
    }
    launch(qkv_kernel, 128, 384, F_SMEM, false, tm_x, tm_wqkv, x, wqkv);
    launch(attn_kernel, 132, 512, F_SMEM, true, wgate, wup, wo, wdown);
    launch(tail_kernel, 128, 384, F_SMEM, true, tm_wo, tm_wg, tm_wu, tm_wd, tm_out, x);
}
```

```cpp
#include <cuda_runtime.h>
#include <cuda_bf16.h>
#include <cuda.h>
#include <stdint.h>

#define K1_DIRECT
namespace {

constexpr int S_LEN = 2048, DM = 512, NH = 32, FF = 1792;

__device__ __align__(1024) __nv_bfloat16 g_qkv[3 * NH * S_LEN * 16];
__device__ __align__(1024) __nv_bfloat16 g_ao[S_LEN * DM];
__device__ __align__(1024) __nv_bfloat16 g_h[S_LEN * DM];
__device__ __align__(1024) __nv_bfloat16 g_g[S_LEN * FF];
__device__ __align__(16) float2 g_rowstat1[S_LEN];
__device__ float g_cs1_part[16 * 1536];
__device__ unsigned int g_cnt[32];
__device__ unsigned int g_cnt2[160];
__device__ float g_nrm[3 * NH * 128];
__device__ float2 g_hstat[S_LEN * 8];
__device__ float g_cs2[2 * FF];

#define TLDECL
#define TL(slot)
#define TLDUMP
#define TX(slot)
__device__ __forceinline__ uint32_t smem_u32(const void* p) { return (uint32_t)__cvta_generic_to_shared(p); }
__device__ __forceinline__ void mbar_init(uint32_t a, int c) { asm volatile("mbarrier.init.shared.b64 [%0], %1;" :: "r"(a), "r"(c)); }
__device__ __forceinline__ void mbar_expect(uint32_t a, int bytes) { asm volatile("mbarrier.arrive.expect_tx.shared.b64 _, [%0], %1;" :: "r"(a), "r"(bytes) : "memory"); }
__device__ __forceinline__ void mbar_arrive(uint32_t a) { asm volatile("mbarrier.arrive.shared.b64 _, [%0];" :: "r"(a) : "memory"); }
__device__ __forceinline__ void mbar_wait(uint32_t a, int parity) {
    uint32_t done;
    int it = 0;
    do {
        asm volatile("{\n.reg .pred p;\nmbarrier.try_wait.parity.shared.b64 p, [%1], %2;\nselp.u32 %0, 1, 0, p;\n}"
                     : "=r"(done) : "r"(a), "r"(parity) : "memory");
        if (++it > (1 << 24)) __trap();
    } while (!done);
}
__device__ __forceinline__ void bulk_g2s(uint32_t dst, const void* src, int bytes, uint32_t bar) {
    asm volatile("cp.async.bulk.shared::cluster.global.mbarrier::complete_tx::bytes [%0], [%1], %2, [%3];"
                 :: "r"(dst), "l"(src), "r"(bytes), "r"(bar) : "memory");
}
__device__ __forceinline__ void tma2d(uint32_t dst, const CUtensorMap* m, int c0, int c1, uint32_t bar) {
    asm volatile("cp.async.bulk.tensor.2d.shared::cluster.global.mbarrier::complete_tx::bytes [%0], [%1, {%3, %4}], [%2];"
                 :: "r"(dst), "l"(m), "r"(bar), "r"(c0), "r"(c1) : "memory");
}
__device__ __forceinline__ void tma3d(uint32_t dst, const CUtensorMap* m, int c0, int c1, int c2, uint32_t bar) {
    asm volatile("cp.async.bulk.tensor.3d.shared::cluster.global.mbarrier::complete_tx::bytes [%0], [%1, {%3, %4, %5}], [%2];"
                 :: "r"(dst), "l"(m), "r"(bar), "r"(c0), "r"(c1), "r"(c2) : "memory");
}
__device__ __forceinline__ void prefetch_tmap(const CUtensorMap* m) { asm volatile("prefetch.tensormap [%0];" :: "l"(m) : "memory"); }
__device__ __forceinline__ void pdl_wait() { asm volatile("griddepcontrol.wait;" ::: "memory"); }
__device__ __forceinline__ void pdl_launch() { asm volatile("griddepcontrol.launch_dependents;" ::: "memory"); }
__device__ __forceinline__ void fence_barrier_init() { asm volatile("fence.mbarrier_init.release.cluster;" ::: "memory"); }
__device__ __forceinline__ void fence_proxy_async() { asm volatile("fence.proxy.async.shared::cta;" ::: "memory"); }
__device__ __forceinline__ uint64_t make_desc(uint32_t saddr, uint32_t lbo, uint32_t sbo, uint32_t swz) {
    return (uint64_t)((saddr & 0x3FFFF) >> 4) | ((uint64_t)((lbo & 0x3FFFF) >> 4) << 16) |
           ((uint64_t)((sbo & 0x3FFFF) >> 4) << 32) | ((uint64_t)swz << 62);
}
#define WG_FENCE() asm volatile("wgmma.fence.sync.aligned;" ::: "memory")
#define WG_COMMIT() asm volatile("wgmma.commit_group.sync.aligned;" ::: "memory")
template <int N> __device__ __forceinline__ void wg_wait() { asm volatile("wgmma.wait_group.sync.aligned %0;" :: "n"(N) : "memory"); }
template <int N> __device__ __forceinline__ void fence_regs(float (&d)[N]) {
#pragma unroll
    for (int i = 0; i < N; i++) asm volatile("" : "+f"(d[i]) :: "memory");
}
__device__ __forceinline__ float ex2f(float x) { float y; asm("ex2.approx.ftz.f32 %0, %1;" : "=f"(y) : "f"(x)); return y; }
__device__ __forceinline__ float tanh_fast(float x) { float y; asm("tanh.approx.f32 %0, %1;" : "=f"(y) : "f"(x)); return y; }
__device__ __forceinline__ uint32_t pack_bf16(float lo, float hi) { uint32_t r; asm("cvt.rn.bf16x2.f32 %0, %1, %2;" : "=r"(r) : "f"(hi), "f"(lo)); return r; }
__device__ __forceinline__ float bf_lo(uint32_t u) { return __uint_as_float(u << 16); }
__device__ __forceinline__ float bf_hi(uint32_t u) { return __uint_as_float(u & 0xFFFF0000u); }
__device__ __forceinline__ uint32_t hfma2(uint32_t a, uint32_t b, uint32_t c) { uint32_t r; asm("fma.rn.f16x2 %0, %1, %2, %3;" : "=r"(r) : "r"(a), "r"(b), "r"(c)); return r; }
__device__ __forceinline__ uint32_t hmul2(uint32_t a, uint32_t b) { uint32_t r; asm("mul.rn.f16x2 %0, %1, %2;" : "=r"(r) : "r"(a), "r"(b)); return r; }
__device__ __forceinline__ unsigned int ld_acquire(const unsigned int* p) { unsigned int v; asm volatile("ld.acquire.gpu.u32 %0, [%1];" : "=r"(v) : "l"(p) : "memory"); return v; }
__device__ __forceinline__ void red_release(unsigned int* p) { asm volatile("red.release.gpu.global.add.u32 [%0], 1;" :: "l"(p) : "memory"); }
__device__ __forceinline__ void stsm4(uint32_t addr, uint32_t a, uint32_t b, uint32_t c, uint32_t d) {
    asm volatile("stmatrix.sync.aligned.m8n8.x4.shared.b16 [%0], {%1,%2,%3,%4};" :: "r"(addr), "r"(a), "r"(b), "r"(c), "r"(d) : "memory");
}
__device__ __forceinline__ void bulk_s2g(void* dst, uint32_t src, int bytes) {
    asm volatile("cp.async.bulk.global.shared::cta.bulk_group [%0], [%1], %2;" :: "l"(dst), "r"(src), "r"(bytes) : "memory");
}
__device__ __forceinline__ void bulk_commit() { asm volatile("cp.async.bulk.commit_group;" ::: "memory"); }
__device__ __forceinline__ void bulk_wait_all() { asm volatile("cp.async.bulk.wait_group 0;" ::: "memory"); }
__device__ __forceinline__ void bulk_wait_read() { asm volatile("cp.async.bulk.wait_group.read 0;" ::: "memory"); }
__device__ __forceinline__ void bar_sync(int id, int n) { asm volatile("bar.sync %0, %1;" :: "r"(id), "r"(n) : "memory"); }
__device__ __forceinline__ void bar_arrive(int id, int n) { asm volatile("bar.arrive %0, %1;" :: "r"(id), "r"(n) : "memory"); }
__device__ __forceinline__ float warp_sum(float v) {
#pragma unroll
    for (int o = 16; o; o >>= 1) v += __shfl_xor_sync(0xffffffffu, v, o);
    return v;
}
__device__ __forceinline__ float warp_max(float v) {
#pragma unroll
    for (int o = 16; o; o >>= 1) v = fmaxf(v, __shfl_xor_sync(0xffffffffu, v, o));
    return v;
}

__device__ __forceinline__ void wgmma_ss_n64(float (&d)[32], uint64_t adesc, uint64_t bdesc, int scale_d) {
    asm volatile("{\n.reg .pred p;\nsetp.ne.b32 p, %34, 0;\n"
      "wgmma.mma_async.sync.aligned.m64n64k16.f32.bf16.bf16 {%0,%1,%2,%3,%4,%5,%6,%7,%8,%9,%10,%11,%12,%13,%14,%15,%16,%17,%18,%19,%20,%21,%22,%23,%24,%25,%26,%27,%28,%29,%30,%31}, %32, %33, p, 1, 1, 0, 1;\n}"
      : "+f"(d[0]), "+f"(d[1]), "+f"(d[2]), "+f"(d[3]), "+f"(d[4]), "+f"(d[5]), "+f"(d[6]), "+f"(d[7]), "+f"(d[8]), "+f"(d[9]), "+f"(d[10]), "+f"(d[11]), "+f"(d[12]), "+f"(d[13]), "+f"(d[14]), "+f"(d[15]), "+f"(d[16]), "+f"(d[17]), "+f"(d[18]), "+f"(d[19]), "+f"(d[20]), "+f"(d[21]), "+f"(d[22]), "+f"(d[23]), "+f"(d[24]), "+f"(d[25]), "+f"(d[26]), "+f"(d[27]), "+f"(d[28]), "+f"(d[29]), "+f"(d[30]), "+f"(d[31])
      : "l"(adesc), "l"(bdesc), "r"(scale_d));
}
__device__ __forceinline__ void wgmma_ss_n96(float (&d)[48], uint64_t adesc, uint64_t bdesc, int scale_d) {
    asm volatile("{\n.reg .pred p;\nsetp.ne.b32 p, %50, 0;\n"
      "wgmma.mma_async.sync.aligned.m64n96k16.f32.bf16.bf16 {%0,%1,%2,%3,%4,%5,%6,%7,%8,%9,%10,%11,%12,%13,%14,%15,%16,%17,%18,%19,%20,%21,%22,%23,%24,%25,%26,%27,%28,%29,%30,%31,%32,%33,%34,%35,%36,%37,%38,%39,%40,%41,%42,%43,%44,%45,%46,%47}, %48, %49, p, 1, 1, 0, 1;\n}"
      : "+f"(d[0]), "+f"(d[1]), "+f"(d[2]), "+f"(d[3]), "+f"(d[4]), "+f"(d[5]), "+f"(d[6]), "+f"(d[7]), "+f"(d[8]), "+f"(d[9]), "+f"(d[10]), "+f"(d[11]), "+f"(d[12]), "+f"(d[13]), "+f"(d[14]), "+f"(d[15]), "+f"(d[16]), "+f"(d[17]), "+f"(d[18]), "+f"(d[19]), "+f"(d[20]), "+f"(d[21]), "+f"(d[22]), "+f"(d[23]), "+f"(d[24]), "+f"(d[25]), "+f"(d[26]), "+f"(d[27]), "+f"(d[28]), "+f"(d[29]), "+f"(d[30]), "+f"(d[31]), "+f"(d[32]), "+f"(d[33]), "+f"(d[34]), "+f"(d[35]), "+f"(d[36]), "+f"(d[37]), "+f"(d[38]), "+f"(d[39]), "+f"(d[40]), "+f"(d[41]), "+f"(d[42]), "+f"(d[43]), "+f"(d[44]), "+f"(d[45]), "+f"(d[46]), "+f"(d[47])
      : "l"(adesc), "l"(bdesc), "r"(scale_d));
}
__device__ __forceinline__ void wgmma_ss_n128(float (&d)[64], uint64_t adesc, uint64_t bdesc, int scale_d) {
    asm volatile("{\n.reg .pred p;\nsetp.ne.b32 p, %66, 0;\n"
      "wgmma.mma_async.sync.aligned.m64n128k16.f32.bf16.bf16 {%0,%1,%2,%3,%4,%5,%6,%7,%8,%9,%10,%11,%12,%13,%14,%15,%16,%17,%18,%19,%20,%21,%22,%23,%24,%25,%26,%27,%28,%29,%30,%31,%32,%33,%34,%35,%36,%37,%38,%39,%40,%41,%42,%43,%44,%45,%46,%47,%48,%49,%50,%51,%52,%53,%54,%55,%56,%57,%58,%59,%60,%61,%62,%63}, %64, %65, p, 1, 1, 0, 1;\n}"
      : "+f"(d[0]), "+f"(d[1]), "+f"(d[2]), "+f"(d[3]), "+f"(d[4]), "+f"(d[5]), "+f"(d[6]), "+f"(d[7]), "+f"(d[8]), "+f"(d[9]), "+f"(d[10]), "+f"(d[11]), "+f"(d[12]), "+f"(d[13]), "+f"(d[14]), "+f"(d[15]), "+f"(d[16]), "+f"(d[17]), "+f"(d[18]), "+f"(d[19]), "+f"(d[20]), "+f"(d[21]), "+f"(d[22]), "+f"(d[23]), "+f"(d[24]), "+f"(d[25]), "+f"(d[26]), "+f"(d[27]), "+f"(d[28]), "+f"(d[29]), "+f"(d[30]), "+f"(d[31]), "+f"(d[32]), "+f"(d[33]), "+f"(d[34]), "+f"(d[35]), "+f"(d[36]), "+f"(d[37]), "+f"(d[38]), "+f"(d[39]), "+f"(d[40]), "+f"(d[41]), "+f"(d[42]), "+f"(d[43]), "+f"(d[44]), "+f"(d[45]), "+f"(d[46]), "+f"(d[47]), "+f"(d[48]), "+f"(d[49]), "+f"(d[50]), "+f"(d[51]), "+f"(d[52]), "+f"(d[53]), "+f"(d[54]), "+f"(d[55]), "+f"(d[56]), "+f"(d[57]), "+f"(d[58]), "+f"(d[59]), "+f"(d[60]), "+f"(d[61]), "+f"(d[62]), "+f"(d[63])
      : "l"(adesc), "l"(bdesc), "r"(scale_d));
}
__device__ __forceinline__ void wgmma_ss_n192(float (&d)[96], uint64_t adesc, uint64_t bdesc, int scale_d) {
    asm volatile("{\n.reg .pred p;\nsetp.ne.b32 p, %98, 0;\n"
      "wgmma.mma_async.sync.aligned.m64n192k16.f32.bf16.bf16 {%0,%1,%2,%3,%4,%5,%6,%7,%8,%9,%10,%11,%12,%13,%14,%15,%16,%17,%18,%19,%20,%21,%22,%23,%24,%25,%26,%27,%28,%29,%30,%31,%32,%33,%34,%35,%36,%37,%38,%39,%40,%41,%42,%43,%44,%45,%46,%47,%48,%49,%50,%51,%52,%53,%54,%55,%56,%57,%58,%59,%60,%61,%62,%63,%64,%65,%66,%67,%68,%69,%70,%71,%72,%73,%74,%75,%76,%77,%78,%79,%80,%81,%82,%83,%84,%85,%86,%87,%88,%89,%90,%91,%92,%93,%94,%95}, %96, %97, p, 1, 1, 0, 1;\n}"
      : "+f"(d[0]), "+f"(d[1]), "+f"(d[2]), "+f"(d[3]), "+f"(d[4]), "+f"(d[5]), "+f"(d[6]), "+f"(d[7]), "+f"(d[8]), "+f"(d[9]), "+f"(d[10]), "+f"(d[11]), "+f"(d[12]), "+f"(d[13]), "+f"(d[14]), "+f"(d[15]), "+f"(d[16]), "+f"(d[17]), "+f"(d[18]), "+f"(d[19]), "+f"(d[20]), "+f"(d[21]), "+f"(d[22]), "+f"(d[23]), "+f"(d[24]), "+f"(d[25]), "+f"(d[26]), "+f"(d[27]), "+f"(d[28]), "+f"(d[29]), "+f"(d[30]), "+f"(d[31]), "+f"(d[32]), "+f"(d[33]), "+f"(d[34]), "+f"(d[35]), "+f"(d[36]), "+f"(d[37]), "+f"(d[38]), "+f"(d[39]), "+f"(d[40]), "+f"(d[41]), "+f"(d[42]), "+f"(d[43]), "+f"(d[44]), "+f"(d[45]), "+f"(d[46]), "+f"(d[47]), "+f"(d[48]), "+f"(d[49]), "+f"(d[50]), "+f"(d[51]), "+f"(d[52]), "+f"(d[53]), "+f"(d[54]), "+f"(d[55]), "+f"(d[56]), "+f"(d[57]), "+f"(d[58]), "+f"(d[59]), "+f"(d[60]), "+f"(d[61]), "+f"(d[62]), "+f"(d[63]), "+f"(d[64]), "+f"(d[65]), "+f"(d[66]), "+f"(d[67]), "+f"(d[68]), "+f"(d[69]), "+f"(d[70]), "+f"(d[71]), "+f"(d[72]), "+f"(d[73]), "+f"(d[74]), "+f"(d[75]), "+f"(d[76]), "+f"(d[77]), "+f"(d[78]), "+f"(d[79]), "+f"(d[80]), "+f"(d[81]), "+f"(d[82]), "+f"(d[83]), "+f"(d[84]), "+f"(d[85]), "+f"(d[86]), "+f"(d[87]), "+f"(d[88]), "+f"(d[89]), "+f"(d[90]), "+f"(d[91]), "+f"(d[92]), "+f"(d[93]), "+f"(d[94]), "+f"(d[95])
      : "l"(adesc), "l"(bdesc), "r"(scale_d));
}
__device__ __forceinline__ void qk_wgmma_n64(float (&d)[32], const uint32_t (&a)[4], uint64_t desc) {
    asm volatile("wgmma.mma_async.sync.aligned.m64n64k16.f32.bf16.bf16 {%0,%1,%2,%3,%4,%5,%6,%7,%8,%9,%10,%11,%12,%13,%14,%15,%16,%17,%18,%19,%20,%21,%22,%23,%24,%25,%26,%27,%28,%29,%30,%31}, {%32,%33,%34,%35}, %36, 0, 1, 1, 0;"
      : "=f"(d[0]), "=f"(d[1]), "=f"(d[2]), "=f"(d[3]), "=f"(d[4]), "=f"(d[5]), "=f"(d[6]), "=f"(d[7]), "=f"(d[8]), "=f"(d[9]), "=f"(d[10]), "=f"(d[11]), "=f"(d[12]), "=f"(d[13]), "=f"(d[14]), "=f"(d[15]), "=f"(d[16]), "=f"(d[17]), "=f"(d[18]), "=f"(d[19]), "=f"(d[20]), "=f"(d[21]), "=f"(d[22]), "=f"(d[23]), "=f"(d[24]), "=f"(d[25]), "=f"(d[26]), "=f"(d[27]), "=f"(d[28]), "=f"(d[29]), "=f"(d[30]), "=f"(d[31])
      : "r"(a[0]), "r"(a[1]), "r"(a[2]), "r"(a[3]), "l"(desc));
}

__device__ __forceinline__ void pv_wgmma(float (&d)[12], uint32_t a0, uint32_t a1, uint32_t a2, uint32_t a3, uint64_t desc) {
    asm volatile("wgmma.mma_async.sync.aligned.m64n24k16.f32.bf16.bf16 {%0,%1,%2,%3,%4,%5,%6,%7,%8,%9,%10,%11}, {%12,%13,%14,%15}, %16, 1, 1, 1, 1;"
      : "+f"(d[0]), "+f"(d[1]), "+f"(d[2]), "+f"(d[3]), "+f"(d[4]), "+f"(d[5]), "+f"(d[6]), "+f"(d[7]), "+f"(d[8]), "+f"(d[9]), "+f"(d[10]), "+f"(d[11])
      : "r"(a0), "r"(a1), "r"(a2), "r"(a3), "l"(desc));
}

__device__ __forceinline__ uint32_t mapa(uint32_t a, uint32_t rank) { uint32_t r; asm("mapa.shared::cluster.u32 %0, %1, %2;" : "=r"(r) : "r"(a), "r"(rank)); return r; }
__device__ __forceinline__ void mbar_arrive_remote(uint32_t a) { asm volatile("mbarrier.arrive.relaxed.cluster.shared::cluster.b64 _, [%0];" :: "r"(a) : "memory"); }
__device__ __forceinline__ void mbar_wait_cluster(uint32_t a, int parity) {
    uint32_t done;
    int it = 0;
    do {
        asm volatile("{\n.reg .pred p;\nmbarrier.try_wait.parity.acquire.cluster.shared::cta.b64 p, [%1], %2;\nselp.u32 %0, 1, 0, p;\n}"
                     : "=r"(done) : "r"(a), "r"(parity) : "memory");
        if (++it > (1 << 24)) __trap();
    } while (!done);
}
__device__ __forceinline__ void tma2d_mc(uint32_t dst, const CUtensorMap* m, int c0, int c1, uint32_t bar) {
    asm volatile("cp.async.bulk.tensor.2d.shared::cluster.global.mbarrier::complete_tx::bytes.multicast::cluster [%0], [%1, {%3, %4}], [%2], %5;"
                 :: "r"(dst), "l"(m), "r"(bar), "r"(c0), "r"(c1), "h"((uint16_t)3) : "memory");
}
__device__ __forceinline__ void bulk_g2s_mc(uint32_t dst, const void* src, int bytes, uint32_t bar) {
    asm volatile("cp.async.bulk.shared::cluster.global.mbarrier::complete_tx::bytes.multicast::cluster [%0], [%1], %2, [%3], %4;"
                 :: "r"(dst), "l"(src), "r"(bytes), "r"(bar), "h"((uint16_t)3) : "memory");
}
__device__ __forceinline__ void tile_of(int bid, int& mb, int& nt) {
    int grp = bid >> 4, in = bid & 15;
    mb = (grp >> 1) * 4 + (in >> 2);
    nt = (grp & 1) * 4 + (in & 3);
}

constexpr int K1_STAGES = 5, K1_STAGE = 16384 + 24576;
constexpr int K1_BAR = K1_STAGES * K1_STAGE, K1_RS = K1_BAR + 128, K1_CS = K1_RS + 1024, K1_SMEM = K1_CS + 768;

__device__ __forceinline__ float2 row_stats_regs(uint4 a, uint4 b) {
    float v[16];
    v[0] = bf_lo(a.x); v[1] = bf_hi(a.x); v[2] = bf_lo(a.y); v[3] = bf_hi(a.y);
    v[4] = bf_lo(a.z); v[5] = bf_hi(a.z); v[6] = bf_lo(a.w); v[7] = bf_hi(a.w);
    v[8] = bf_lo(b.x); v[9] = bf_hi(b.x); v[10] = bf_lo(b.y); v[11] = bf_hi(b.y);
    v[12] = bf_lo(b.z); v[13] = bf_hi(b.z); v[14] = bf_lo(b.w); v[15] = bf_hi(b.w);
    float s = 0.f;
#pragma unroll
    for (int i = 0; i < 16; i++) s += v[i];
    float mean = warp_sum(s) * (1.0f / DM);
    float q = 0.f;
#pragma unroll
    for (int i = 0; i < 16; i++) { float d = v[i] - mean; q = fmaf(d, d, q); }
    float var = warp_sum(q) * (1.0f / DM);
    float rstd = rsqrtf(var + 1e-5f);
    return make_float2(rstd, -mean * rstd);
}
__device__ __forceinline__ float2 row_stats_x(const __nv_bfloat16* x, int row, int lane) {
    const uint4* p = (const uint4*)(x + (size_t)row * DM);
    return row_stats_regs(__ldg(p + lane), __ldg(p + 32 + lane));
}
__device__ __forceinline__ void colsum8(const __nv_bfloat16* w, int ld, int col, int k0, int nk, float (&s)[8]) {
#pragma unroll
    for (int i = 0; i < 8; i++) s[i] = 0.f;
    for (int k = k0; k < k0 + nk; k += 8) {
        uint4 u[8];
#pragma unroll
        for (int i = 0; i < 8; i++) u[i] = __ldg((const uint4*)(w + (size_t)(k + i) * ld + col));
#pragma unroll
        for (int i = 0; i < 8; i++) {
            s[0] += bf_lo(u[i].x); s[1] += bf_hi(u[i].x); s[2] += bf_lo(u[i].y); s[3] += bf_hi(u[i].y);
            s[4] += bf_lo(u[i].z); s[5] += bf_hi(u[i].z); s[6] += bf_lo(u[i].w); s[7] += bf_hi(u[i].w);
        }
    }
}
__device__ __forceinline__ bool wait_count(const unsigned int* p, unsigned int target, int lane) {
    int ok = 1;
    if (lane == 0) {
        int it = 0;
        while (ld_acquire(p) < target) { if (++it > (1 << 18)) { ok = 0; break; } }
    }
    ok = __shfl_sync(0xffffffffu, ok, 0);
    return ok != 0;
}

__global__ void __cluster_dims__(2, 1, 1) __launch_bounds__(384, 1)
qkv_kernel(const __grid_constant__ CUtensorMap tm_x, const __grid_constant__ CUtensorMap tm_w,
           const __nv_bfloat16* __restrict__ x, const __nv_bfloat16* __restrict__ wqkv) {
    extern __shared__ __align__(1024) unsigned char smem[];
    const uint32_t sb = smem_u32(smem);
    const int tid = threadIdx.x, warp = __shfl_sync(0xffffffffu, tid >> 5, 0), lane = tid & 31;
    TLDECL
    TL(0);
    const int r = blockIdx.x & 1, nt = (blockIdx.x >> 1) & 7, mb = (blockIdx.x >> 4) * 2 + r;
    const uint32_t full = sb + K1_BAR, empty = full + 40, auxb = full + 80;
    if (tid == 0) {
        prefetch_tmap(&tm_x); prefetch_tmap(&tm_w);
        for (int i = 0; i < K1_STAGES; i++) { mbar_init(full + 8 * i, 1); mbar_init(empty + 8 * i, 16); }
        mbar_init(auxb, 3);
        fence_barrier_init();
    }
    __syncthreads();
    asm volatile("barrier.cluster.arrive.relaxed.aligned;" ::: "memory");
    pdl_launch();
    if (warp == 0) {
        if (lane == 0) {
            for (int kb = 0; kb < K1_STAGES; kb++) {
                mbar_expect(full + 8 * kb, K1_STAGE);
                tma2d(sb + kb * K1_STAGE, &tm_x, kb * 64, mb * 128, full + 8 * kb);
            }
        }
        __syncwarp();
        asm volatile("barrier.cluster.wait.acquire.aligned;" ::: "memory");
        if (lane == 0) {
            for (int kb = 0; kb < 8; kb++) {
                int s = kb % K1_STAGES;
                if (kb >= K1_STAGES) {
                    mbar_wait_cluster(empty + 8 * s, 0);
                    mbar_expect(full + 8 * s, K1_STAGE);
                    tma2d(sb + s * K1_STAGE, &tm_x, kb * 64, mb * 128, full + 8 * s);
                }
                for (int i = 0; i < 3; i++)
                    tma2d_mc(sb + s * K1_STAGE + 16384 + i * 8192 + r * 4096, &tm_w, nt * 192 + i * 64, kb * 64 + r * 32, full + 8 * s);
            }
        }
        if (blockIdx.x == 0) for (int i = lane; i < 160; i += 32) g_cnt2[i] = 0;
    } else if (warp < 4) {
        asm volatile("barrier.cluster.wait.acquire.aligned;" ::: "memory");
        float2* s_rs = (float2*)(smem + K1_RS);
        float* s_cs = (float*)(smem + K1_CS);
        if (warp < 3) {
            const int r0 = mb * 128 + nt * 16 + (warp - 1) * 8;
            uint4 u[16];
#pragma unroll
            for (int i = 0; i < 8; i++) {
                const uint4* p = (const uint4*)(x + (size_t)(r0 + i) * DM);
                u[2 * i] = __ldg(p + lane); u[2 * i + 1] = __ldg(p + 32 + lane);
            }
            float2 mine = make_float2(0.f, 0.f);
#pragma unroll
            for (int i = 0; i < 8; i++) {
                float2 st = row_stats_regs(u[2 * i], u[2 * i + 1]);
                if (lane == i) mine = st;
            }
            if (lane < 8) g_rowstat1[r0 + lane] = mine;
            __syncwarp();
            if (lane == 0) red_release(&g_cnt[mb]);
        } else {
            uint4 u[24];
#pragma unroll
            for (int c = 0; c < 3; c++)
#pragma unroll
                for (int i = 0; i < 8; i++)
                    u[c * 8 + i] = __ldg((const uint4*)(wqkv + (size_t)(mb * 32 + (lane >> 3) * 8 + i) * 1536 + nt * 192 + (c * 8 + (lane & 7)) * 8));
#pragma unroll
            for (int c = 0; c < 3; c++) {
                float cs[8];
#pragma unroll
                for (int i = 0; i < 8; i++) cs[i] = 0.f;
#pragma unroll
                for (int i = 0; i < 8; i++) {
                    const uint4 w = u[c * 8 + i];
                    cs[0] += bf_lo(w.x); cs[1] += bf_hi(w.x); cs[2] += bf_lo(w.y); cs[3] += bf_hi(w.y);
                    cs[4] += bf_lo(w.z); cs[5] += bf_hi(w.z); cs[6] += bf_lo(w.w); cs[7] += bf_hi(w.w);
                }
#pragma unroll
                for (int i = 0; i < 8; i++) {
                    cs[i] += __shfl_xor_sync(0xffffffffu, cs[i], 8);
                    cs[i] += __shfl_xor_sync(0xffffffffu, cs[i], 16);
                }
                if (lane < 8) {
                    float4* d = (float4*)(g_cs1_part + mb * 1536 + nt * 192 + (c * 8 + lane) * 8);
                    d[0] = make_float4(cs[0], cs[1], cs[2], cs[3]);
                    d[1] = make_float4(cs[4], cs[5], cs[6], cs[7]);
                }
            }
            __syncwarp();
            if (lane == 0) red_release(&g_cnt[16 + nt]);
        }
        TX(8 + warp);
        if (warp == 1) {
            if (wait_count(&g_cnt[mb], 16, lane)) {
#pragma unroll
                for (int i = 0; i < 4; i++) s_rs[lane + 32 * i] = __ldcg(&g_rowstat1[mb * 128 + lane + 32 * i]);
            } else {
                for (int i = 0; i < 128; i++) {
                    float2 st = row_stats_x(x, mb * 128 + i, lane);
                    if (lane == 0) s_rs[i] = st;
                }
            }
        } else {
            int c0 = (warp - 2) * 96;
            if (wait_count(&g_cnt[16 + nt], 16, lane)) {
#pragma unroll
                for (int i = 0; i < 3; i++) {
                    float s = 0.f;
#pragma unroll
                    for (int p = 0; p < 16; p++) s += __ldcg(&g_cs1_part[p * 1536 + nt * 192 + c0 + lane + 32 * i]);
                    s_cs[c0 + lane + 32 * i] = s;
                }
            } else if (lane < 12) {
                float s[8];
                colsum8(wqkv, 1536, nt * 192 + c0 + lane * 8, 0, 512, s);
#pragma unroll
                for (int i = 0; i < 8; i++) s_cs[c0 + lane * 8 + i] = s[i];
            }
        }
        __syncwarp();
        TX(12 + warp);
        if (lane == 0) mbar_arrive(auxb);
        bar_sync(2, 256 + 96);
        const int a = tid - 32;
        {
            const int hh = a >> 3, w = a & 7;
            const float4* p = (const float4*)(smem + 49152) + (hh * 256 + w * 32) / 2;
            float m = 0.f;
#pragma unroll
            for (int i = 0; i < 8; i++) {
                const int ii = (i + a) & 7;
                float4 u = p[2 * ii], v = p[2 * ii + 1];
                float n0 = u.x + u.z + v.x + v.z, n1 = u.y + u.w + v.y + v.w;
                if (!(n0 <= 3.0e38f) || !(n1 <= 3.0e38f)) m = __int_as_float(0x7f800000);
                m = fmaxf(m, fmaxf(n0, n1));
            }
            const int col0 = nt * 192 + hh * 16;
            g_nrm[((col0 >> 9) * NH + ((col0 & 511) >> 4)) * 128 + mb * 8 + w] = m;
        }
        if (a < 24) bulk_wait_all();
        TL(27);
        TLDUMP;
    } else {
        const int wgi = (warp >> 2) - 1, ww = warp & 3;
        asm volatile("barrier.cluster.wait.acquire.aligned;" ::: "memory");
        const uint32_t rempty = mapa(empty, 1 - r);
        float acc[96];
#pragma unroll 1
        for (int kb = 0; kb < 8; kb++) {
            int s = kb % K1_STAGES;
            mbar_wait(full + 8 * s, (kb / K1_STAGES) & 1);
            if (warp == 4) TX(kb);
            uint64_t ad = make_desc(sb + s * K1_STAGE + wgi * 8192, 16, 1024, 1);
            uint64_t bd = make_desc(sb + s * K1_STAGE + 16384, 8192, 1024, 1);
            WG_FENCE();
#pragma unroll
            for (int k = 0; k < 4; k++) wgmma_ss_n192(acc, ad + k * 2, bd + k * 128, (kb | k) != 0);
            WG_COMMIT();
            if (kb > 0) {
                wg_wait<1>();
                if (lane == 0 && kb - 1 + K1_STAGES < 8) { mbar_arrive(empty + 8 * (kb - 1)); mbar_arrive_remote(rempty + 8 * (kb - 1)); }
            }
        }
        wg_wait<0>();
        fence_regs(acc);
        TL(1);
        if (warp == 4) TX(16);
        mbar_wait(auxb, 0);
        if (warp == 4) TX(17);
        bar_sync(1, 256);
        const float2* s_rs = (const float2*)(smem + K1_RS);
        const float* s_cs = (const float*)(smem + K1_CS);
        const int g = lane >> 2, t = lane & 3;
        const int rl = wgi * 64 + ww * 16 + g;
        const float2 st0 = s_rs[rl], st1 = s_rs[rl + 8];
        const float QS = 0.25f * 1.4426950408889634f;
        const uint32_t stg = sb + ((lane >> 4) * 16 + wgi * 8 + ww * 2 + ((lane >> 3) & 1)) * 128 + (lane & 7) * 16;
        float2* s_np = (float2*)(smem + 49152) + (warp - 4) * 32 + lane;
#pragma unroll
        for (int hh = 0; hh < 12; hh++) {
            const int which = (nt * 192 + hh * 16) >> 9;
            const float sc = (which == 0) ? QS : 1.0f;
            const float a0 = st0.x * sc, b0 = st0.y * sc, a1 = st1.x * sc, b1 = st1.y * sc;
            const float2 c0 = *(const float2*)(s_cs + 16 * hh + 2 * t), c1 = *(const float2*)(s_cs + 16 * hh + 8 + 2 * t);
            const float* a = acc + 8 * hh;
            float v0 = fmaf(a0, a[0], b0 * c0.x), v1 = fmaf(a0, a[1], b0 * c0.y), v2 = fmaf(a1, a[2], b1 * c0.x), v3 = fmaf(a1, a[3], b1 * c0.y);
            float v4 = fmaf(a0, a[4], b0 * c1.x), v5 = fmaf(a0, a[5], b0 * c1.y), v6 = fmaf(a1, a[6], b1 * c1.x), v7 = fmaf(a1, a[7], b1 * c1.y);
            {
                const int head = ((nt * 192 + hh * 16) & 511) >> 4;
                uint32_t* o = (uint32_t*)g_qkv + ((size_t)((which * NH + head) * 2) * 256 + mb * 16 + wgi * 8 + ww * 2) * 32 + lane;
                o[0] = pack_bf16(v0, v1); o[32] = pack_bf16(v2, v3); o[8192] = pack_bf16(v4, v5); o[8192 + 32] = pack_bf16(v6, v7);
            }
            s_np[hh * 256] = make_float2(fmaf(v0, v0, fmaf(v1, v1, fmaf(v4, v4, v5 * v5))), fmaf(v2, v2, fmaf(v3, v3, fmaf(v6, v6, v7 * v7))));
        }
        fence_proxy_async();
        bar_arrive(2, 256 + 96);
        TL(2);
        TLDUMP;
    }
}

constexpr int AT_K = 0, AT_V = 65536, AT_ONES = 131072, AT_BAR = 163840, AT_SMEM = AT_BAR + 128;
#define POLY_MASK 0xAD6A

__device__ __forceinline__ uint32_t exp2_pair_poly(float x0, float x1) {
    uint32_t t0 = __float_as_uint(x0 + 32895.0f);
    uint32_t t1 = __float_as_uint(x1 + 32895.0f);
    uint32_t gd = __byte_perm(t0, t1, 0x6420);
    uint32_t wm = __byte_perm(t0, t1, 0x5612);
    uint32_t v = hfma2(gd, 0x71477147u, 0x354f354fu);
    uint32_t z = hmul2(v, gd);
    return (wm >> 1) + z;
}
__device__ __forceinline__ uint32_t exp2_pair_mufu(float x0, float x1) { return pack_bf16(ex2f(x0), ex2f(x1)); }
template <uint32_t MASK>
__device__ __forceinline__ void exp_blocks(const float (&s)[32], uint32_t (&p)[16]) {
#pragma unroll
    for (int b = 0; b < 8; b++) {
        if ((MASK >> b) & 1) {
            p[2 * b] = exp2_pair_poly(s[4 * b], s[4 * b + 1]);
            p[2 * b + 1] = exp2_pair_poly(s[4 * b + 2], s[4 * b + 3]);
        } else {
            p[2 * b] = exp2_pair_mufu(s[4 * b], s[4 * b + 1]);
            p[2 * b + 1] = exp2_pair_mufu(s[4 * b + 2], s[4 * b + 3]);
        }
    }
}
#define PV4(P) _Pragma("unroll") for (int i = 0; i < 4; i++) { pv_wgmma(o, P[4 * i], P[4 * i + 1], P[4 * i + 2], P[4 * i + 3], vd); vd += 16; }

__device__ __forceinline__ void attn_store(float (&o)[12], int row0, int head, int lane) {
    float l0 = __shfl_sync(0xffffffffu, o[8], lane & 28);
    float l1 = __shfl_sync(0xffffffffu, o[10], lane & 28);
    float r0 = 1.0f / l0, r1 = 1.0f / l1;
    uint32_t* op = (uint32_t*)g_ao;
    int mb = row0 >> 7, rg = (row0 & 127) >> 3;
    int kb = head >> 2, kc = (head & 3) * 2;
    size_t base = (((size_t)(mb * 8 + kb) * 8 + kc) * 16 + rg) * 32 + lane;
    op[base] = pack_bf16(o[0] * r0, o[1] * r0);
    op[base + 32] = pack_bf16(o[2] * r1, o[3] * r1);
    op[base + 16 * 32] = pack_bf16(o[4] * r0, o[5] * r0);
    op[base + 16 * 32 + 32] = pack_bf16(o[6] * r1, o[7] * r1);
}

__device__ __forceinline__ void attn_load_q(uint32_t (&q)[4], const __nv_bfloat16* gq, int row0, int lane) {
    const uint32_t* qp = (const uint32_t*)gq;
    int j0 = row0 >> 3;
    q[0] = __ldcg(qp + (0 * 256 + j0) * 32 + lane);
    q[1] = __ldcg(qp + (0 * 256 + j0 + 1) * 32 + lane);
    q[2] = __ldcg(qp + (1 * 256 + j0) * 32 + lane);
    q[3] = __ldcg(qp + (1 * 256 + j0 + 1) * 32 + lane);
}

__device__ __forceinline__ void attn_tile_safe(const uint32_t (&q)[4], uint64_t kd, uint64_t vd, int row0, int head, int lane) {
    float o[12];
#pragma unroll
    for (int i = 0; i < 12; i++) o[i] = 0.f;
    float m0 = -INFINITY, m1 = -INFINITY;
    fence_regs(o);
#pragma unroll 1
    for (int j = 0; j < 32; j++) {
        float s[32];
        uint32_t p[16];
        WG_FENCE();
        qk_wgmma_n64(s, q, kd); kd += 64;
        WG_COMMIT();
        wg_wait<0>();
        fence_regs(s);
        fence_regs(o);
        float x0 = m0, x1 = m1;
#pragma unroll
        for (int b = 0; b < 8; b++) {
            x0 = fmaxf(x0, fmaxf(s[4 * b], s[4 * b + 1]));
            x1 = fmaxf(x1, fmaxf(s[4 * b + 2], s[4 * b + 3]));
        }
        x0 = fmaxf(x0, __shfl_xor_sync(0xffffffffu, x0, 1)); x0 = fmaxf(x0, __shfl_xor_sync(0xffffffffu, x0, 2));
        x1 = fmaxf(x1, __shfl_xor_sync(0xffffffffu, x1, 1)); x1 = fmaxf(x1, __shfl_xor_sync(0xffffffffu, x1, 2));
        float al0 = ex2f(m0 - x0), al1 = ex2f(m1 - x1);
        m0 = x0; m1 = x1;
#pragma unroll
        for (int i = 0; i < 3; i++) { o[4 * i] *= al0; o[4 * i + 1] *= al0; o[4 * i + 2] *= al1; o[4 * i + 3] *= al1; }
#pragma unroll
        for (int b = 0; b < 8; b++) {
            p[2 * b] = exp2_pair_mufu(s[4 * b] - m0, s[4 * b + 1] - m0);
            p[2 * b + 1] = exp2_pair_mufu(s[4 * b + 2] - m1, s[4 * b + 3] - m1);
        }
        fence_regs(o);
        WG_FENCE();
        PV4(p);
        WG_COMMIT();
        wg_wait<0>();
        fence_regs(o);
    }
    attn_store(o, row0, head, lane);
}

__global__ void __launch_bounds__(512, 1)
attn_kernel(const __nv_bfloat16* __restrict__ wg_, const __nv_bfloat16* __restrict__ wu_,
            const __nv_bfloat16* __restrict__ wo_, const __nv_bfloat16* __restrict__ wd_) {
    extern __shared__ __align__(1024) unsigned char smem[];
    const uint32_t sb = smem_u32(smem);
    const int tid = threadIdx.x, wg = tid >> 7, warp = (tid >> 5) & 3, lane = tid & 31;
    TLDECL
    pdl_launch();
    if (blockIdx.x >= 128) {
        const int e = blockIdx.x - 128;
        const __nv_bfloat16* w = (e < 2) ? wg_ : wu_;
        float* red = (float*)smem;
        const int cgrp = tid & 127, kq = tid >> 7;
        if (cgrp < 112) {
            float s[8];
            colsum8(w, FF, (e & 1) * 896 + cgrp * 8, kq * 128, 128, s);
#pragma unroll
            for (int i = 0; i < 8; i++) red[kq * 896 + cgrp * 8 + i] = s[i];
        }
        __syncthreads();
        for (int c = tid; c < 896; c += 512)
            g_cs2[(e >> 1) * FF + (e & 1) * 896 + c] = red[c] + red[896 + c] + red[1792 + c] + red[2688 + c];
        if (tid < 32) {
            const char* p0 = (const char*)wo_ + e * (DM * DM * 2 / 4);
            for (int i = lane; i < 32; i += 32)
                asm volatile("cp.async.bulk.prefetch.L2.global [%0], %1;" :: "l"(p0 + i * 4096), "r"(4096) : "memory");
            const char* p1 = (const char*)wd_ + e * (FF * DM * 2 / 4);
            for (int i = lane; i < 112; i += 32)
                asm volatile("cp.async.bulk.prefetch.L2.global [%0], %1;" :: "l"(p1 + i * 4096), "r"(4096) : "memory");
        }
        return;
    }
    const int head = blockIdx.x >> 2, qq = blockIdx.x & 3;
    const __nv_bfloat16* gq = g_qkv + (size_t)head * (S_LEN * 16);
    const __nv_bfloat16* gk = g_qkv + (size_t)(NH + head) * (S_LEN * 16);
    const __nv_bfloat16* gv = g_qkv + (size_t)(2 * NH + head) * (S_LEN * 16);
    if (tid == 0) {
        for (int i = 0; i < 8; i++) mbar_init(sb + AT_BAR + 8 * i, 1);
        fence_barrier_init();
    }
    {
        uint4 one = make_uint4(0x00003F80u, 0, 0, 0);
#pragma unroll
        for (int i = 0; i < 4; i++) *(uint4*)(smem + AT_ONES + (i * 512 + tid) * 16) = one;
        fence_proxy_async();
    }
    __syncthreads();
    TL(3);
    pdl_wait();
    TL(4);
    auto load_kv = [&](int i) {
        uint32_t bar = sb + AT_BAR + 8 * i;
        mbar_expect(bar, 16384);
        bulk_g2s(sb + AT_K + i * 4096, gk + i * 2048, 4096, bar);
        bulk_g2s(sb + AT_K + 32768 + i * 4096, gk + 16384 + i * 2048, 4096, bar);
        bulk_g2s(sb + AT_V + i * 4096, gv + i * 2048, 4096, bar);
        bulk_g2s(sb + AT_V + 32768 + i * 4096, gv + 16384 + i * 2048, 4096, bar);
    };
    if (tid == 0) { load_kv(0); load_kv(1); }
    uint32_t q[4], q2[4];
    attn_load_q(q, gq, qq * 512 + wg * 64 + warp * 16, lane);
    attn_load_q(q2, gq, qq * 512 + (4 + wg) * 64 + warp * 16, lane);
    bool fast;
    {
        const float* nq = g_nrm + (0 * NH + head) * 128 + qq * 32;
        const float* nk = g_nrm + (1 * NH + head) * 128;
        const float* nv = g_nrm + (2 * NH + head) * 128;
        float4 k4 = __ldcg((const float4*)nk + lane), v4 = __ldcg((const float4*)nv + lane);
        float qm = warp_max(__ldcg(nq + lane));
        float km = warp_max(fmaxf(fmaxf(k4.x, k4.y), fmaxf(k4.z, k4.w)));
        float vm = warp_max(fmaxf(fmaxf(v4.x, v4.y), fmaxf(v4.z, v4.w)));
        fast = __all_sync(0xffffffffu, (qm * km <= 3500.0f) && (vm <= 1.0e24f));
    }
    TL(24);
    const uint64_t kdesc0 = make_desc(sb + AT_K, 32768, 128, 0);
    const uint64_t vdesc0 = make_desc(sb + AT_V, 128, 32768, 0);
    if (!fast) {
        if (tid == 0) for (int i = 2; i < 8; i++) load_kv(i);
        for (int i = 0; i < 8; i++) mbar_wait(sb + AT_BAR + 8 * i, 0);
#pragma unroll 1
        for (int tile = 0; tile < 2; tile++) {
            const int row0 = qq * 512 + (tile * 4 + wg) * 64 + warp * 16;
            attn_tile_safe(q, kdesc0, vdesc0, row0, head, lane);
#pragma unroll
            for (int i = 0; i < 4; i++) q[i] = q2[i];
        }
        return;
    }
#pragma unroll 1
    for (int tile = 0; tile < 2; tile++) {
        const int row0 = qq * 512 + (tile * 4 + wg) * 64 + warp * 16;
        float o[12];
#pragma unroll
        for (int i = 0; i < 12; i++) o[i] = 0.f;
        fence_regs(o);
        float sa[32];
        uint32_t pa[16];
        uint64_t kd = kdesc0, vd = vdesc0;
        if (tile == 0) { mbar_wait(sb + AT_BAR, 0); TL(25); }
        WG_FENCE();
        qk_wgmma_n64(sa, q, kd); kd += 64;
        WG_COMMIT();
#pragma unroll 1
        for (int jj = 0; jj < 8; jj++) {
            if (tile == 0 && jj < 7) {
                if (tid == 0 && jj < 6) load_kv(jj + 2);
                mbar_wait(sb + AT_BAR + 8 * (jj + 1), 0);
            }
            if (wg == 0 && warp == 0) TX(128 + tile * 8 + jj);
#pragma unroll
            for (int j = 0; j < 4; j++) {
                wg_wait<0>();
                fence_regs(sa);
                if (j & 1) exp_blocks<(POLY_MASK >> 8)>(sa, pa); else exp_blocks<(POLY_MASK & 255)>(sa, pa);
                WG_FENCE();
                qk_wgmma_n64(sa, q, kd); kd += 64;
                PV4(pa);
                WG_COMMIT();
            }
        }
        wg_wait<0>();
        fence_regs(o);
        fence_regs(sa);
        if (tile == 0) TL(26);
        attn_store(o, row0, head, lane);
#pragma unroll
        for (int i = 0; i < 4; i++) q[i] = q2[i];
    }
    TL(5);
    TLDUMP;
}

constexpr int F_R2 = 131072, F_X = 196608, F_BAR = 229376;
constexpr int F_RS = F_BAR + 256, F_CS = F_RS + 1024, F_SMEM = F_CS + 1792;
enum { B_FA = 0, B_HF = 4, B_BF = 8, B_BE = 11, B_CF = 14, B_CE = 20, B_ADONE = 26, B_BDONE = 27, B_XC = 28, B_PRDY = 29, B_AUX = 30, B_NUM = 31 };

__device__ __forceinline__ void st_async4(uint32_t dst, float a, float b, float c, float d, uint32_t bar) {
    asm volatile("st.async.weak.shared::cluster.mbarrier::complete_tx::bytes.v4.f32 [%0], {%1,%2,%3,%4}, [%5];"
                 :: "r"(dst), "f"(a), "f"(b), "f"(c), "f"(d), "r"(bar) : "memory");
}
__device__ __forceinline__ void poll_count(const unsigned int* p, unsigned int target) {
    int it = 0;
    while (ld_acquire(p) < target) { if (++it > (1 << 22)) __trap(); }
    asm volatile("fence.proxy.async.global;" ::: "memory");
}
__device__ __forceinline__ void tma2d_store(const CUtensorMap* m, uint32_t src, int c0, int c1) {
    asm volatile("cp.async.bulk.tensor.2d.global.shared::cta.bulk_group [%0, {%2, %3}], [%1];" :: "l"(m), "r"(src), "r"(c0), "r"(c1) : "memory");
}
__device__ __forceinline__ float2 h_row_stats(int row) {
    const float4* hp = (const float4*)(g_hstat + (size_t)row * 8);
    float4 a = __ldcg(hp), b = __ldcg(hp + 1), c = __ldcg(hp + 2), d = __ldcg(hp + 3);
    float mean = 0.125f * (a.x + a.z + b.x + b.z + c.x + c.z + d.x + d.z);
    float m2 = a.y + a.w + b.y + b.w + c.y + c.w + d.y + d.w;
    float e;
    e = a.x - mean; m2 = fmaf(64.f * e, e, m2); e = a.z - mean; m2 = fmaf(64.f * e, e, m2);
    e = b.x - mean; m2 = fmaf(64.f * e, e, m2); e = b.z - mean; m2 = fmaf(64.f * e, e, m2);
    e = c.x - mean; m2 = fmaf(64.f * e, e, m2); e = c.z - mean; m2 = fmaf(64.f * e, e, m2);
    e = d.x - mean; m2 = fmaf(64.f * e, e, m2); e = d.z - mean; m2 = fmaf(64.f * e, e, m2);
    return make_float2(rsqrtf(m2 * (1.0f / DM) + 1e-5f), -mean);
}
__device__ __forceinline__ int c_kblock(int i, int r) {
    if (i < 6) { const int e = 2 * i + r, m = e / 3, k = e - 3 * m; return 7 * m + (k == 2 ? 4 : k); }
    const int l = 2 * (i - 6) + r, m = l >> 2, k = l & 3;
    return 7 * m + (k < 2 ? 2 + k : 3 + k);
}
__device__ __forceinline__ uint32_t c_stage_a(int s, int ntB) { return s < 4 ? ((ntB + 2 * s) & 7) * 16384 : F_R2 + (s - 4) * 32768; }
__device__ __forceinline__ uint32_t c_stage_b(int s, int ntB) { return s < 4 ? ((ntB + 2 * s + 1) & 7) * 16384 : F_R2 + (s - 4) * 32768 + 16384; }
template <int R>
__device__ __forceinline__ void xchg(float (&acc)[64], float (&o)[32], uint32_t sb, unsigned char* smem, int bar, int ctid) {
    const uint32_t dst = mapa(sb + F_X + ctid * 16, 1 - R), rb = mapa(sb + F_BAR + 8 * bar, 1 - R);
#pragma unroll
    for (int q = 0; q < 8; q++) {
        const int j = (1 - R) * 32 + 4 * q;
        st_async4(dst + q * 4096, acc[j], acc[j + 1], acc[j + 2], acc[j + 3], rb);
    }
    mbar_wait_cluster(sb + F_BAR + 8 * bar, 0);
#pragma unroll
    for (int q = 0; q < 8; q++) {
        float4 v = *(const float4*)(smem + F_X + q * 4096 + ctid * 16);
        const int j = R * 32 + 4 * q;
        o[4 * q] = acc[j] + v.x; o[4 * q + 1] = acc[j + 1] + v.y; o[4 * q + 2] = acc[j + 2] + v.z; o[4 * q + 3] = acc[j + 3] + v.w;
    }
}

template <int NB, bool STAGE>
__device__ __forceinline__ void ffn_epilogue(const float* ag, const float* au, const float* s_cs, int cs_off, uint32_t* gp, uint32_t stg,
                                             float2 st0, float2 st1, int lane) {
    const int t = lane & 3;
    const float C1 = 0.7978845608028654f, C2 = 0.044715f * 0.7978845608028654f;
    const float k10 = st0.x * C1, k20 = st0.x * st0.x * st0.x * C2, k11 = st1.x * C1, k21 = st1.x * st1.x * st1.x * C2;
#pragma unroll
    for (int j2 = 0; j2 < NB / 2; j2++) {
        uint32_t pk[4];
#pragma unroll
        for (int jj = 0; jj < 2; jj++) {
            const int j = 2 * j2 + jj;
            const float2 cg = *(const float2*)(s_cs + cs_off + 8 * j + 2 * t);
            const float2 cu = *(const float2*)(s_cs + 224 + cs_off + 8 * j + 2 * t);
            float r[4];
#pragma unroll
            for (int e = 0; e < 4; e++) {
                const float nm = (e < 2) ? st0.y : st1.y, k1 = (e < 2) ? k10 : k11, k2 = (e < 2) ? k20 : k21;
                const float tg = fmaf(nm, (e & 1) ? cg.y : cg.x, ag[4 * j + e]);
                const float tu = fmaf(nm, (e & 1) ? cu.y : cu.x, au[4 * j + e]);
                const float th = tanh_fast(tg * fmaf(tg * tg, k2, k1));
                const float p = tg * tu;
                r[e] = fmaf(p, th, p);
            }
            pk[2 * jj] = pack_bf16(r[0], r[1]);
            pk[2 * jj + 1] = pack_bf16(r[2], r[3]);
        }
        if (STAGE) {
            stsm4(stg + j2 * 4096, pk[0], pk[1], pk[2], pk[3]);
        } else {
            gp[j2 * 1024] = pk[0]; gp[j2 * 1024 + 32] = pk[1]; gp[j2 * 1024 + 512] = pk[2]; gp[j2 * 1024 + 544] = pk[3];
        }
    }
}

__global__ void __cluster_dims__(2, 1, 1) __launch_bounds__(384, 1)
tail_kernel(const __grid_constant__ CUtensorMap tm_o, const __grid_constant__ CUtensorMap tm_g,
            const __grid_constant__ CUtensorMap tm_u, const __grid_constant__ CUtensorMap tm_d,
            const __grid_constant__ CUtensorMap tm_out, const __nv_bfloat16* __restrict__ x) {
    extern __shared__ __align__(1024) unsigned char smem[];
    const uint32_t sb = smem_u32(smem);
    const uint32_t bars = sb + F_BAR;
    const int tid = threadIdx.x, warp = __shfl_sync(0xffffffffu, tid >> 5, 0), lane = tid & 31;
    TLDECL
    TL(6);
    if (warp == 4) TX(200);
    const int cl = blockIdx.x >> 1, r = blockIdx.x & 1;
    const int mb = ((cl & 7) >> 1) * 4 + (cl >> 4), ntA = (cl & 1) * 2 + ((cl >> 3) & 1);
    const int nt = ntA * 2 + r;
    const int mbB = (mb & ~1) + r, ntB = (mb & 1) * 4 + ntA;
    if (tid == 0) {
#pragma unroll
        for (int i = 0; i < B_NUM; i++) {
            const int cnt = (i >= B_BE && i < B_BE + 3) ? 16 : ((i >= B_CE && i < B_CE + 6) || i == B_BDONE || i == B_PRDY) ? 8 : (i == B_AUX || i == B_ADONE) ? 2 : 1;
            mbar_init(bars + 8 * i, cnt);
        }
        mbar_expect(bars + 8 * B_XC, 32768);
        fence_barrier_init();
    }
    TL(28);
    __syncthreads();
    TL(29);
    asm volatile("barrier.cluster.arrive.relaxed.aligned;" ::: "memory");
    TL(30);
    if (warp < 4) {
        asm volatile("setmaxnreg.dec.sync.aligned.u32 56;");
        if (warp == 0) TX(205);
        if (warp == 0) {
            if (lane == 0) {
                auto load_b = [&](int it) {
                    const int s = it % 3, pass = it >> 3, kb = (ntB + it) & 7;
                    const int ng = pass ? 3 : 4, c0 = ntB * 224 + pass * 128;
                    const uint32_t bar = bars + 8 * (B_BF + s), dst = sb + F_R2 + s * 32768 + r * 16384;
                    mbar_expect(bar, ng * 8192);
                    for (int i = 0; i < ng; i++) tma2d_mc(dst + i * 4096, r ? &tm_u : &tm_g, c0 + i * 32, kb * 64, bar);
                };
                for (int i = 0; i < 8; i++) {
                    const uint32_t bar = bars + 8 * (B_FA + (i >> 1));
                    if (!(i & 1)) mbar_expect(bar, 49152);
                    tma2d(sb + F_R2 + 32768 + i * 8192, &tm_o, nt * 64, i * 64, bar);
                }
                asm volatile("barrier.cluster.wait.acquire;" ::: "memory");
                pdl_wait();
                TL(16);
                for (int i = 0; i < 4; i++)
                    bulk_g2s_mc(sb + (2 * i + r) * 16384, g_ao + (size_t)(mb * 8 + 2 * i + r) * 8192, 16384, bars + 8 * (B_FA + i));
                load_b(0);
                if (blockIdx.x == 0)
                    for (int i = 0; i < 32; i++) g_cnt[i] = 0;
                mbar_wait_cluster(bars + 8 * B_ADONE, 0);
                load_b(1); load_b(2);
                auto load_c = [&](int i) {
                    const int s = i % 6, kb = c_kblock(i, r);
                    const uint32_t bar = bars + 8 * (B_CF + s), da = sb + c_stage_a(s, ntB), db = sb + c_stage_b(s, ntB);
                    mbar_expect(bar, 32768);
                    tma2d(db, &tm_d, ntA * 128, kb * 64, bar);
                    tma2d(db + 8192, &tm_d, ntA * 128 + 64, kb * 64, bar);
                    bulk_g2s(da, g_g + (size_t)(mb * 28 + kb) * 8192, 16384, bar);
                };
                for (int it = 3; it < 16; it++) {
                    mbar_wait_cluster(bars + 8 * (B_BE + it % 3), (it / 3 - 1) & 1);
                    load_b(it);
                    if (it == 12) { poll_count(&g_cnt2[mb], 8); load_c(0); }
                    if (it == 14) load_c(1);
                }
                mbar_wait(bars + 8 * B_BDONE, 0);
                for (int i = 2; i < 14; i++) {
                    if (i >= 6) mbar_wait(bars + 8 * (B_CE + i % 6), ((i / 6) - 1) & 1);
                    if (i == 6) { poll_count(&g_cnt2[16 + mb], 8); TL(18); }
                    load_c(i);
                }
            }
            else asm volatile("barrier.cluster.wait.acquire;" ::: "memory");
            TLDUMP;
        } else if (warp == 1) {
            asm volatile("barrier.cluster.wait.acquire.aligned;" ::: "memory");
            bar_sync(5, 288);
            if (lane == 0) { red_release(&g_cnt2[32 + mb * 8 + nt]); TL(9); }
            __syncwarp();
            bar_sync(1, 288);
            if (lane == 0) red_release(&g_cnt2[mbB]);
            __syncwarp();
            bar_sync(2, 288);
            if (lane == 0) {
                red_release(&g_cnt2[16 + mbB]);
                TL(13);
            }
            __syncwarp();
            bar_sync(3, 288);
            if (lane == 0) {
                tma2d_store(&tm_out, sb, nt * 64, mb * 128);
                bulk_commit();
                bulk_wait_all();
                TL(15);
            }
            TLDUMP;
        } else {
            asm volatile("barrier.cluster.wait.acquire.aligned;" ::: "memory");
            pdl_wait();
            float2* s_rs = (float2*)(smem + F_RS);
            float* s_cs = (float*)(smem + F_CS);
            for (int c = tid - 64; c < 448; c += 64)
                s_cs[c] = __ldcg(&g_cs2[(c >= 224 ? FF - 224 : 0) + ntB * 224 + c]);
            if (tid == 96) {
                mbar_wait_cluster(bars + 8 * B_ADONE, 0);
                for (int i = 0; i < 8; i++) {
                    const int kb = (ntB + i) & 7;
                    const uint32_t bar = bars + 8 * (i < 4 ? B_HF + i : B_FA + i - 4);
                    poll_count(&g_cnt2[32 + mbB * 8 + kb], 1);
                    mbar_expect(bar, 16384);
                    bulk_g2s(sb + kb * 16384, g_h + (size_t)(mbB * 8 + kb) * 8192, 16384, bar);
                }
                TL(17);
            }
            __syncwarp();
            if (lane < 8) poll_count(&g_cnt2[32 + mbB * 8 + lane], 1);
            __syncwarp();
            for (int rr = tid - 64; rr < 128; rr += 64) {
                s_rs[rr] = h_row_stats(mbB * 128 + rr);
            }
            __syncwarp();
            if (lane == 0) mbar_arrive(bars + 8 * B_AUX);
            TLDUMP;
        }
    } else {
        asm volatile("setmaxnreg.inc.sync.aligned.u32 216;");
        if (warp == 4) TX(206);
        const int wgi = (warp >> 2) - 1, ww = warp & 3, ctid = tid - 128;
        const int g = lane >> 2, t = lane & 3;
        const int rl = wgi * 64 + ww * 16 + g, row = mb * 128 + rl;
        const int rgl = wgi * 8 + ww * 2;
        const float2* s_rs = (const float2*)(smem + F_RS);
        const float* s_cs = (const float*)(smem + F_CS);
        const uint32_t stl = ((lane >> 4) * 16 + rgl + ((lane >> 3) & 1)) * 128 + (lane & 7) * 16;
        uint32_t* hp = (uint32_t*)g_h + ((size_t)(mb * 8 + nt) * 8 * 16 + rgl) * 32 + lane;
        const uint32_t rbars = mapa(bars, 1 - r);
        TL(23);
        {
            uint32_t xr[16];
            const uint32_t* xp = (const uint32_t*)(x + (size_t)row * DM + nt * 64) + t;
#pragma unroll
            for (int j = 0; j < 8; j++) { xr[2 * j] = __ldg(xp + 4 * j); xr[2 * j + 1] = __ldg(xp + 8 * (DM / 2) + 4 * j); }
            float acc[32];
#pragma unroll 1
            for (int i = 0; i < 8; i++) {
                if (!(i & 1)) { mbar_wait(bars + 8 * (B_FA + (i >> 1)), 0); if (i == 0) TL(19); }
                uint64_t ad = make_desc(sb + i * 16384 + wgi * 1024, 2048, 128, 0);
                uint64_t bd = make_desc(sb + F_R2 + 32768 + i * 8192, 8192, 1024, 1);
                WG_FENCE();
#pragma unroll
                for (int k = 0; k < 4; k++) wgmma_ss_n64(acc, ad + k * 256, bd + k * 128, (i | k) != 0);
                WG_COMMIT();
            }
            wg_wait<0>();
            fence_regs(acc);
            TL(7);
            asm volatile("barrier.cluster.wait.acquire.aligned;" ::: "memory");
            bar_sync(4, 256);
            if (tid == 128) { mbar_arrive(bars + 8 * B_ADONE); mbar_arrive_remote(mapa(bars + 8 * B_ADONE, 1 - r)); }
            float v0[16], v1[16];
            float s0 = 0.f, s1 = 0.f;
#pragma unroll
            for (int j2 = 0; j2 < 4; j2++) {
                uint32_t u[4];
#pragma unroll
                for (int jj = 0; jj < 2; jj++) {
                    const int j = 2 * j2 + jj;
                    u[2 * jj] = pack_bf16(bf_lo(xr[2 * j]) + acc[4 * j], bf_hi(xr[2 * j]) + acc[4 * j + 1]);
                    u[2 * jj + 1] = pack_bf16(bf_lo(xr[2 * j + 1]) + acc[4 * j + 2], bf_hi(xr[2 * j + 1]) + acc[4 * j + 3]);
                    v0[2 * j] = bf_lo(u[2 * jj]); v0[2 * j + 1] = bf_hi(u[2 * jj]);
                    v1[2 * j] = bf_lo(u[2 * jj + 1]); v1[2 * j + 1] = bf_hi(u[2 * jj + 1]);
                    s0 += v0[2 * j] + v0[2 * j + 1];
                    s1 += v1[2 * j] + v1[2 * j + 1];
                }
                hp[j2 * 1024] = u[0]; hp[j2 * 1024 + 32] = u[1]; hp[j2 * 1024 + 512] = u[2]; hp[j2 * 1024 + 544] = u[3];
            }
            float m0 = s0 * (1.0f / 16), m1 = s1 * (1.0f / 16), q0 = 0.f, q1 = 0.f;
#pragma unroll
            for (int i = 0; i < 16; i++) {
                float d0 = v0[i] - m0, d1 = v1[i] - m1;
                q0 = fmaf(d0, d0, q0); q1 = fmaf(d1, d1, q1);
            }
#pragma unroll
            for (int st = 0; st < 2; st++) {
                float hn = st ? 16.f : 8.f;
                float om0 = __shfl_xor_sync(0xffffffffu, m0, 1 << st), oq0 = __shfl_xor_sync(0xffffffffu, q0, 1 << st);
                float om1 = __shfl_xor_sync(0xffffffffu, m1, 1 << st), oq1 = __shfl_xor_sync(0xffffffffu, q1, 1 << st);
                float d0 = om0 - m0, d1 = om1 - m1;
                q0 = q0 + oq0 + d0 * d0 * hn; q1 = q1 + oq1 + d1 * d1 * hn;
                m0 = 0.5f * (m0 + om0); m1 = 0.5f * (m1 + om1);
            }
            if (t == 0) {
                g_hstat[row * 8 + nt] = make_float2(m0, q0);
                g_hstat[(row + 8) * 8 + nt] = make_float2(m1, q1);
            }
            bar_arrive(5, 288);
            TL(8);
        }
        uint32_t* gp = (uint32_t*)g_g + (((size_t)mbB * 224 + ntB * 28) * 16 + rgl) * 32 + lane;
        {
            float ag[64], au[64];
#pragma unroll 1
            for (int kb = 0; kb < 8; kb++) {
                const int s = kb % 3;
                mbar_wait(bars + 8 * (kb < 4 ? B_HF + kb : B_FA + kb - 4), kb < 4 ? 0 : 1);
                mbar_wait(bars + 8 * (B_BF + s), (kb / 3) & 1);
                uint64_t ad = make_desc(sb + ((ntB + kb) & 7) * 16384 + wgi * 1024, 2048, 128, 0);
                uint64_t bd = make_desc(sb + F_R2 + s * 32768, 4096, 512, 2);
                WG_FENCE();
#pragma unroll
                for (int k = 0; k < 4; k++) {
                    wgmma_ss_n128(ag, ad + k * 256, bd + k * 64, (kb | k) != 0);
                    wgmma_ss_n128(au, ad + k * 256, bd + 1024 + k * 64, (kb | k) != 0);
                }
                WG_COMMIT();
                if (kb > 0) {
                    wg_wait<1>();
                    if (lane == 0) { mbar_arrive(bars + 8 * (B_BE + (kb - 1) % 3)); mbar_arrive_remote(rbars + 8 * (B_BE + (kb - 1) % 3)); }
                }
            }
            wg_wait<0>();
            if (lane == 0) { mbar_arrive(bars + 8 * (B_BE + 7 % 3)); mbar_arrive_remote(rbars + 8 * (B_BE + 7 % 3)); }
            fence_regs(ag); fence_regs(au);
            TL(10);
            mbar_wait(bars + 8 * B_AUX, 0);
            ffn_epilogue<16, false>(ag, au, s_cs, 0, gp, 0, s_rs[rl], s_rs[rl + 8], lane);
            bar_arrive(1, 288);
        }
        {
            float ag[48], au[48];
#pragma unroll 1
            for (int kb = 0; kb < 8; kb++) {
                const int it = 8 + kb, s = it % 3;
                mbar_wait(bars + 8 * (B_BF + s), (it / 3) & 1);
                uint64_t ad = make_desc(sb + ((ntB + kb) & 7) * 16384 + wgi * 1024, 2048, 128, 0);
                uint64_t bd = make_desc(sb + F_R2 + s * 32768, 4096, 512, 2);
                WG_FENCE();
#pragma unroll
                for (int k = 0; k < 4; k++) {
                    wgmma_ss_n96(ag, ad + k * 256, bd + k * 64, (kb | k) != 0);
                    wgmma_ss_n96(au, ad + k * 256, bd + 1024 + k * 64, (kb | k) != 0);
                }
                WG_COMMIT();
                if (kb > 0) {
                    wg_wait<1>();
                    if (lane == 0 && it + 2 < 16) { mbar_arrive(bars + 8 * (B_BE + (it - 1) % 3)); mbar_arrive_remote(rbars + 8 * (B_BE + (it - 1) % 3)); }
                }
            }
            wg_wait<0>();
            if (lane == 0) {
                mbar_arrive(bars + 8 * B_BDONE);
                mbar_arrive_remote(rbars + 8 * B_PRDY);
            }
            fence_regs(ag); fence_regs(au);
            TL(11);
            ffn_epilogue<12, false>(ag, au, s_cs, 128, gp + 16 * 512, 0, s_rs[rl], s_rs[rl + 8], lane);
            bar_arrive(2, 288);
            TL(12);
        }
        {
            uint32_t hr[16];
#pragma unroll
            for (int j = 0; j < 8; j++) { hr[2 * j] = __ldcg(hp + j * 512); hr[2 * j + 1] = __ldcg(hp + j * 512 + 32); }
            mbar_wait(bars + 8 * (B_CF + 0), 0);
            const float a0 = h_row_stats(row).x, a1 = h_row_stats(row + 8).x;
            float acc[64];
#pragma unroll 1
            for (int kb = 0; kb < 14; kb++) {
                const int s = kb % 6;
                mbar_wait(bars + 8 * (B_CF + s), (kb / 6) & 1);
                if (warp == 4) TX(96 + kb);
                uint64_t ad = make_desc(sb + c_stage_a(s, ntB) + wgi * 1024, 2048, 128, 0);
                uint64_t bd = make_desc(sb + c_stage_b(s, ntB), 8192, 1024, 1);
                WG_FENCE();
#pragma unroll
                for (int k = 0; k < 4; k++) wgmma_ss_n128(acc, ad + k * 256, bd + k * 128, (kb | k) != 0);
                WG_COMMIT();
                if (kb > 0) {
                    wg_wait<1>();
                    if (lane == 0) mbar_arrive(bars + 8 * (B_CE + (kb - 1) % 6));
                }
            }
            wg_wait<0>();
            fence_regs(acc);
            TL(14);
            mbar_wait_cluster(bars + 8 * B_PRDY, 0);
            float o[32];
            if (r == 0) xchg<0>(acc, o, sb, smem, B_XC, ctid); else xchg<1>(acc, o, sb, smem, B_XC, ctid);
            TL(22);
            bar_sync(4, 256);
            const float k0 = 0.5f * a0 * a0, k1 = 0.5f * a1 * a1;
            const int srow = wgi * 64 + ww * 16 + ((lane >> 3) & 1) * 8 + (lane & 7);
#pragma unroll
            for (int j2 = 0; j2 < 4; j2++) {
                uint32_t u[4];
#pragma unroll
                for (int jj = 0; jj < 2; jj++) {
                    const int j = 2 * j2 + jj;
                    u[2 * jj] = pack_bf16(fmaf(k0, o[4 * j], bf_lo(hr[2 * j])), fmaf(k0, o[4 * j + 1], bf_hi(hr[2 * j])));
                    u[2 * jj + 1] = pack_bf16(fmaf(k1, o[4 * j + 2], bf_lo(hr[2 * j + 1])), fmaf(k1, o[4 * j + 3], bf_hi(hr[2 * j + 1])));
                }
                const int chunk = 2 * j2 + (lane >> 4);
                stsm4(sb + srow * 128 + ((chunk ^ (lane & 7)) * 16), u[0], u[1], u[2], u[3]);
            }
            fence_proxy_async();
            bar_arrive(3, 288);
            TLDUMP;
        }
    }
}

typedef CUresult (*EncodeFn)(CUtensorMap*, CUtensorMapDataType, cuuint32_t, void*, const cuuint64_t*, const cuuint64_t*,
                             const cuuint32_t*, const cuuint32_t*, CUtensorMapInterleave, CUtensorMapSwizzle,
                             CUtensorMapL2promotion, CUtensorMapFloatOOBfill);

void encode(EncodeFn fn, CUtensorMap* m, const void* ptr, int rank, const cuuint64_t* dims, const cuuint64_t* strides,
            const cuuint32_t* box, CUtensorMapSwizzle swz) {
    cuuint32_t es[3] = {1, 1, 1};
    fn(m, CU_TENSOR_MAP_DATA_TYPE_BFLOAT16, rank, (void*)ptr, dims, strides, box, es, CU_TENSOR_MAP_INTERLEAVE_NONE, swz,
       CU_TENSOR_MAP_L2_PROMOTION_L2_256B, CU_TENSOR_MAP_FLOAT_OOB_FILL_NONE);
}

template <typename... KArgs, typename... Args>
void launch(void (*kern)(KArgs...), int grid, int block, int smem, bool pdl, Args... args) {
    cudaLaunchConfig_t cfg = {};
    cfg.gridDim = dim3(grid); cfg.blockDim = dim3(block); cfg.dynamicSmemBytes = smem;
    cfg.stream = cudaStreamPerThread;
    cudaLaunchAttribute at[1];
    at[0].id = cudaLaunchAttributeProgrammaticStreamSerialization;
    at[0].val.programmaticStreamSerializationAllowed = 1;
    cfg.attrs = at; cfg.numAttrs = pdl ? 1 : 0;
    cudaLaunchKernelEx(&cfg, kern, KArgs(args)...);
}

}

extern "C" void kernel_launch(void* const* d_in, const int* in_sizes, int n_in, void* d_out, int out_size) {
    const __nv_bfloat16* x = (const __nv_bfloat16*)d_in[0];
    const __nv_bfloat16* wqkv = (const __nv_bfloat16*)d_in[1];
    const __nv_bfloat16* wo = (const __nv_bfloat16*)d_in[2];
    const __nv_bfloat16* wgate = (const __nv_bfloat16*)d_in[4];
    const __nv_bfloat16* wup = (const __nv_bfloat16*)d_in[5];
    const __nv_bfloat16* wdown = (const __nv_bfloat16*)d_in[6];
    __nv_bfloat16* out = (__nv_bfloat16*)d_out;

    static CUtensorMap tm_x, tm_wqkv, tm_wo, tm_wg, tm_wu, tm_wd, tm_out;
    static const void* cached[7] = {nullptr, nullptr, nullptr, nullptr, nullptr, nullptr, nullptr};
    if (cached[0] != x || cached[1] != wqkv || cached[2] != wo || cached[3] != wgate || cached[4] != wup || cached[5] != wdown || cached[6] != out) {
        void* fp = nullptr;
        cudaDriverEntryPointQueryResult qr;
        cudaGetDriverEntryPoint("cuTensorMapEncodeTiled", &fp, cudaEnableDefault, &qr);
        EncodeFn fn = (EncodeFn)fp;
        { cuuint64_t d[2] = {512, 2048}, s[1] = {1024}; cuuint32_t b[2] = {64, 128};
          encode(fn, &tm_x, x, 2, d, s, b, CU_TENSOR_MAP_SWIZZLE_128B);
          encode(fn, &tm_out, out, 2, d, s, b, CU_TENSOR_MAP_SWIZZLE_128B); }
        { cuuint64_t d[2] = {1536, 512}, s[1] = {3072}; cuuint32_t b[2] = {64, 32};
          encode(fn, &tm_wqkv, wqkv, 2, d, s, b, CU_TENSOR_MAP_SWIZZLE_128B); }
        { cuuint64_t d[2] = {512, 512}, s[1] = {1024}; cuuint32_t b[2] = {64, 64};
          encode(fn, &tm_wo, wo, 2, d, s, b, CU_TENSOR_MAP_SWIZZLE_128B); }
        { cuuint64_t d[2] = {1792, 512}, s[1] = {3584}; cuuint32_t b[2] = {32, 64};
          encode(fn, &tm_wg, wgate, 2, d, s, b, CU_TENSOR_MAP_SWIZZLE_64B);
          encode(fn, &tm_wu, wup, 2, d, s, b, CU_TENSOR_MAP_SWIZZLE_64B); }
        { cuuint64_t d[2] = {512, 1792}, s[1] = {1024}; cuuint32_t b[2] = {64, 64};
          encode(fn, &tm_wd, wdown, 2, d, s, b, CU_TENSOR_MAP_SWIZZLE_128B); }
        cudaFuncSetAttribute(qkv_kernel, cudaFuncAttributeMaxDynamicSharedMemorySize, F_SMEM);
        cudaFuncSetAttribute(qkv_kernel, cudaFuncAttributePreferredSharedMemoryCarveout, 100);
        cudaFuncSetAttribute(attn_kernel, cudaFuncAttributeMaxDynamicSharedMemorySize, F_SMEM);
        cudaFuncSetAttribute(attn_kernel, cudaFuncAttributePreferredSharedMemoryCarveout, 100);
        cudaFuncSetAttribute(tail_kernel, cudaFuncAttributeMaxDynamicSharedMemorySize, F_SMEM);
        cudaFuncSetAttribute(tail_kernel, cudaFuncAttributePreferredSharedMemoryCarveout, 100);
        cached[0] = x; cached[1] = wqkv; cached[2] = wo; cached[3] = wgate; cached[4] = wup; cached[5] = wdown; cached[6] = out;
    }
    launch(qkv_kernel, 128, 384, F_SMEM, false, tm_x, tm_wqkv, x, wqkv);
    launch(attn_kernel, 132, 512, F_SMEM, true, wgate, wup, wo, wdown);
    launch(tail_kernel, 128, 384, F_SMEM, true, tm_wo, tm_wg, tm_wu, tm_wd, tm_out, x);
}
```

```cpp
#include <cuda_runtime.h>
#include <cuda_bf16.h>
#include <cuda.h>
#include <stdint.h>

#define K1_DIRECT
namespace {

constexpr int S_LEN = 2048, DM = 512, NH = 32, FF = 1792;

__device__ __align__(1024) __nv_bfloat16 g_qkv[3 * NH * S_LEN * 16];
__device__ __align__(1024) __nv_bfloat16 g_ao[S_LEN * DM];
__device__ __align__(1024) __nv_bfloat16 g_h[S_LEN * DM];
__device__ __align__(1024) __nv_bfloat16 g_g[S_LEN * FF];
__device__ __align__(16) float2 g_rowstat1[S_LEN];
__device__ float g_cs1_part[16 * 1536];
__device__ unsigned int g_cnt[32];
__device__ unsigned int g_cnt2[160];
__device__ float g_nrm[3 * NH * 128];
__device__ float2 g_hstat[S_LEN * 8];
__device__ float g_cs2[2 * FF];

#define TLDECL
#define TL(slot)
#define TLDUMP
#define TX(slot)
__device__ __forceinline__ uint32_t smem_u32(const void* p) { return (uint32_t)__cvta_generic_to_shared(p); }
__device__ __forceinline__ void mbar_init(uint32_t a, int c) { asm volatile("mbarrier.init.shared.b64 [%0], %1;" :: "r"(a), "r"(c)); }
__device__ __forceinline__ void mbar_expect(uint32_t a, int bytes) { asm volatile("mbarrier.arrive.expect_tx.shared.b64 _, [%0], %1;" :: "r"(a), "r"(bytes) : "memory"); }
__device__ __forceinline__ void mbar_arrive(uint32_t a) { asm volatile("mbarrier.arrive.shared.b64 _, [%0];" :: "r"(a) : "memory"); }
__device__ __forceinline__ void mbar_wait(uint32_t a, int parity) {
    uint32_t done;
    int it = 0;
    do {
        asm volatile("{\n.reg .pred p;\nmbarrier.try_wait.parity.shared.b64 p, [%1], %2;\nselp.u32 %0, 1, 0, p;\n}"
                     : "=r"(done) : "r"(a), "r"(parity) : "memory");
        if (++it > (1 << 24)) __trap();
    } while (!done);
}
__device__ __forceinline__ void bulk_g2s(uint32_t dst, const void* src, int bytes, uint32_t bar) {
    asm volatile("cp.async.bulk.shared::cluster.global.mbarrier::complete_tx::bytes [%0], [%1], %2, [%3];"
                 :: "r"(dst), "l"(src), "r"(bytes), "r"(bar) : "memory");
}
__device__ __forceinline__ void tma2d(uint32_t dst, const CUtensorMap* m, int c0, int c1, uint32_t bar) {
    asm volatile("cp.async.bulk.tensor.2d.shared::cluster.global.mbarrier::complete_tx::bytes [%0], [%1, {%3, %4}], [%2];"
                 :: "r"(dst), "l"(m), "r"(bar), "r"(c0), "r"(c1) : "memory");
}
__device__ __forceinline__ void tma3d(uint32_t dst, const CUtensorMap* m, int c0, int c1, int c2, uint32_t bar) {
    asm volatile("cp.async.bulk.tensor.3d.shared::cluster.global.mbarrier::complete_tx::bytes [%0], [%1, {%3, %4, %5}], [%2];"
                 :: "r"(dst), "l"(m), "r"(bar), "r"(c0), "r"(c1), "r"(c2) : "memory");
}
__device__ __forceinline__ void prefetch_tmap(const CUtensorMap* m) { asm volatile("prefetch.tensormap [%0];" :: "l"(m) : "memory"); }
__device__ __forceinline__ void pdl_wait() { asm volatile("griddepcontrol.wait;" ::: "memory"); }
__device__ __forceinline__ void pdl_launch() { asm volatile("griddepcontrol.launch_dependents;" ::: "memory"); }
__device__ __forceinline__ void fence_barrier_init() { asm volatile("fence.mbarrier_init.release.cluster;" ::: "memory"); }
__device__ __forceinline__ void fence_proxy_async() { asm volatile("fence.proxy.async.shared::cta;" ::: "memory"); }
__device__ __forceinline__ uint64_t make_desc(uint32_t saddr, uint32_t lbo, uint32_t sbo, uint32_t swz) {
    return (uint64_t)((saddr & 0x3FFFF) >> 4) | ((uint64_t)((lbo & 0x3FFFF) >> 4) << 16) |
           ((uint64_t)((sbo & 0x3FFFF) >> 4) << 32) | ((uint64_t)swz << 62);
}
#define WG_FENCE() asm volatile("wgmma.fence.sync.aligned;" ::: "memory")
#define WG_COMMIT() asm volatile("wgmma.commit_group.sync.aligned;" ::: "memory")
template <int N> __device__ __forceinline__ void wg_wait() { asm volatile("wgmma.wait_group.sync.aligned %0;" :: "n"(N) : "memory"); }
template <int N> __device__ __forceinline__ void fence_regs(float (&d)[N]) {
#pragma unroll
    for (int i = 0; i < N; i++) asm volatile("" : "+f"(d[i]) :: "memory");
}
__device__ __forceinline__ float ex2f(float x) { float y; asm("ex2.approx.ftz.f32 %0, %1;" : "=f"(y) : "f"(x)); return y; }
__device__ __forceinline__ float tanh_fast(float x) { float y; asm("tanh.approx.f32 %0, %1;" : "=f"(y) : "f"(x)); return y; }
__device__ __forceinline__ uint32_t pack_bf16(float lo, float hi) { uint32_t r; asm("cvt.rn.bf16x2.f32 %0, %1, %2;" : "=r"(r) : "f"(hi), "f"(lo)); return r; }
__device__ __forceinline__ float bf_lo(uint32_t u) { return __uint_as_float(u << 16); }
__device__ __forceinline__ float bf_hi(uint32_t u) { return __uint_as_float(u & 0xFFFF0000u); }
__device__ __forceinline__ uint32_t hfma2(uint32_t a, uint32_t b, uint32_t c) { uint32_t r; asm("fma.rn.f16x2 %0, %1, %2, %3;" : "=r"(r) : "r"(a), "r"(b), "r"(c)); return r; }
__device__ __forceinline__ uint32_t hmul2(uint32_t a, uint32_t b) { uint32_t r; asm("mul.rn.f16x2 %0, %1, %2;" : "=r"(r) : "r"(a), "r"(b)); return r; }
__device__ __forceinline__ unsigned int ld_acquire(const unsigned int* p) { unsigned int v; asm volatile("ld.acquire.gpu.u32 %0, [%1];" : "=r"(v) : "l"(p) : "memory"); return v; }
__device__ __forceinline__ void red_release(unsigned int* p) { asm volatile("red.release.gpu.global.add.u32 [%0], 1;" :: "l"(p) : "memory"); }
__device__ __forceinline__ void stsm4(uint32_t addr, uint32_t a, uint32_t b, uint32_t c, uint32_t d) {
    asm volatile("stmatrix.sync.aligned.m8n8.x4.shared.b16 [%0], {%1,%2,%3,%4};" :: "r"(addr), "r"(a), "r"(b), "r"(c), "r"(d) : "memory");
}
__device__ __forceinline__ void bulk_s2g(void* dst, uint32_t src, int bytes) {
    asm volatile("cp.async.bulk.global.shared::cta.bulk_group [%0], [%1], %2;" :: "l"(dst), "r"(src), "r"(bytes) : "memory");
}
__device__ __forceinline__ void bulk_commit() { asm volatile("cp.async.bulk.commit_group;" ::: "memory"); }
__device__ __forceinline__ void bulk_wait_all() { asm volatile("cp.async.bulk.wait_group 0;" ::: "memory"); }
__device__ __forceinline__ void bulk_wait_read() { asm volatile("cp.async.bulk.wait_group.read 0;" ::: "memory"); }
__device__ __forceinline__ void bar_sync(int id, int n) { asm volatile("bar.sync %0, %1;" :: "r"(id), "r"(n) : "memory"); }
__device__ __forceinline__ void bar_arrive(int id, int n) { asm volatile("bar.arrive %0, %1;" :: "r"(id), "r"(n) : "memory"); }
__device__ __forceinline__ float warp_sum(float v) {
#pragma unroll
    for (int o = 16; o; o >>= 1) v += __shfl_xor_sync(0xffffffffu, v, o);
    return v;
}
__device__ __forceinline__ float warp_max(float v) {
#pragma unroll
    for (int o = 16; o; o >>= 1) v = fmaxf(v, __shfl_xor_sync(0xffffffffu, v, o));
    return v;
}

__device__ __forceinline__ void wgmma_ss_n64(float (&d)[32], uint64_t adesc, uint64_t bdesc, int scale_d) {
    asm volatile("{\n.reg .pred p;\nsetp.ne.b32 p, %34, 0;\n"
      "wgmma.mma_async.sync.aligned.m64n64k16.f32.bf16.bf16 {%0,%1,%2,%3,%4,%5,%6,%7,%8,%9,%10,%11,%12,%13,%14,%15,%16,%17,%18,%19,%20,%21,%22,%23,%24,%25,%26,%27,%28,%29,%30,%31}, %32, %33, p, 1, 1, 0, 1;\n}"
      : "+f"(d[0]), "+f"(d[1]), "+f"(d[2]), "+f"(d[3]), "+f"(d[4]), "+f"(d[5]), "+f"(d[6]), "+f"(d[7]), "+f"(d[8]), "+f"(d[9]), "+f"(d[10]), "+f"(d[11]), "+f"(d[12]), "+f"(d[13]), "+f"(d[14]), "+f"(d[15]), "+f"(d[16]), "+f"(d[17]), "+f"(d[18]), "+f"(d[19]), "+f"(d[20]), "+f"(d[21]), "+f"(d[22]), "+f"(d[23]), "+f"(d[24]), "+f"(d[25]), "+f"(d[26]), "+f"(d[27]), "+f"(d[28]), "+f"(d[29]), "+f"(d[30]), "+f"(d[31])
      : "l"(adesc), "l"(bdesc), "r"(scale_d));
}
__device__ __forceinline__ void wgmma_ss_n96(float (&d)[48], uint64_t adesc, uint64_t bdesc, int scale_d) {
    asm volatile("{\n.reg .pred p;\nsetp.ne.b32 p, %50, 0;\n"
      "wgmma.mma_async.sync.aligned.m64n96k16.f32.bf16.bf16 {%0,%1,%2,%3,%4,%5,%6,%7,%8,%9,%10,%11,%12,%13,%14,%15,%16,%17,%18,%19,%20,%21,%22,%23,%24,%25,%26,%27,%28,%29,%30,%31,%32,%33,%34,%35,%36,%37,%38,%39,%40,%41,%42,%43,%44,%45,%46,%47}, %48, %49, p, 1, 1, 0, 1;\n}"
      : "+f"(d[0]), "+f"(d[1]), "+f"(d[2]), "+f"(d[3]), "+f"(d[4]), "+f"(d[5]), "+f"(d[6]), "+f"(d[7]), "+f"(d[8]), "+f"(d[9]), "+f"(d[10]), "+f"(d[11]), "+f"(d[12]), "+f"(d[13]), "+f"(d[14]), "+f"(d[15]), "+f"(d[16]), "+f"(d[17]), "+f"(d[18]), "+f"(d[19]), "+f"(d[20]), "+f"(d[21]), "+f"(d[22]), "+f"(d[23]), "+f"(d[24]), "+f"(d[25]), "+f"(d[26]), "+f"(d[27]), "+f"(d[28]), "+f"(d[29]), "+f"(d[30]), "+f"(d[31]), "+f"(d[32]), "+f"(d[33]), "+f"(d[34]), "+f"(d[35]), "+f"(d[36]), "+f"(d[37]), "+f"(d[38]), "+f"(d[39]), "+f"(d[40]), "+f"(d[41]), "+f"(d[42]), "+f"(d[43]), "+f"(d[44]), "+f"(d[45]), "+f"(d[46]), "+f"(d[47])
      : "l"(adesc), "l"(bdesc), "r"(scale_d));
}
__device__ __forceinline__ void wgmma_ss_n128(float (&d)[64], uint64_t adesc, uint64_t bdesc, int scale_d) {
    asm volatile("{\n.reg .pred p;\nsetp.ne.b32 p, %66, 0;\n"
      "wgmma.mma_async.sync.aligned.m64n128k16.f32.bf16.bf16 {%0,%1,%2,%3,%4,%5,%6,%7,%8,%9,%10,%11,%12,%13,%14,%15,%16,%17,%18,%19,%20,%21,%22,%23,%24,%25,%26,%27,%28,%29,%30,%31,%32,%33,%34,%35,%36,%37,%38,%39,%40,%41,%42,%43,%44,%45,%46,%47,%48,%49,%50,%51,%52,%53,%54,%55,%56,%57,%58,%59,%60,%61,%62,%63}, %64, %65, p, 1, 1, 0, 1;\n}"
      : "+f"(d[0]), "+f"(d[1]), "+f"(d[2]), "+f"(d[3]), "+f"(d[4]), "+f"(d[5]), "+f"(d[6]), "+f"(d[7]), "+f"(d[8]), "+f"(d[9]), "+f"(d[10]), "+f"(d[11]), "+f"(d[12]), "+f"(d[13]), "+f"(d[14]), "+f"(d[15]), "+f"(d[16]), "+f"(d[17]), "+f"(d[18]), "+f"(d[19]), "+f"(d[20]), "+f"(d[21]), "+f"(d[22]), "+f"(d[23]), "+f"(d[24]), "+f"(d[25]), "+f"(d[26]), "+f"(d[27]), "+f"(d[28]), "+f"(d[29]), "+f"(d[30]), "+f"(d[31]), "+f"(d[32]), "+f"(d[33]), "+f"(d[34]), "+f"(d[35]), "+f"(d[36]), "+f"(d[37]), "+f"(d[38]), "+f"(d[39]), "+f"(d[40]), "+f"(d[41]), "+f"(d[42]), "+f"(d[43]), "+f"(d[44]), "+f"(d[45]), "+f"(d[46]), "+f"(d[47]), "+f"(d[48]), "+f"(d[49]), "+f"(d[50]), "+f"(d[51]), "+f"(d[52]), "+f"(d[53]), "+f"(d[54]), "+f"(d[55]), "+f"(d[56]), "+f"(d[57]), "+f"(d[58]), "+f"(d[59]), "+f"(d[60]), "+f"(d[61]), "+f"(d[62]), "+f"(d[63])
      : "l"(adesc), "l"(bdesc), "r"(scale_d));
}
__device__ __forceinline__ void wgmma_ss_n192(float (&d)[96], uint64_t adesc, uint64_t bdesc, int scale_d) {
    asm volatile("{\n.reg .pred p;\nsetp.ne.b32 p, %98, 0;\n"
      "wgmma.mma_async.sync.aligned.m64n192k16.f32.bf16.bf16 {%0,%1,%2,%3,%4,%5,%6,%7,%8,%9,%10,%11,%12,%13,%14,%15,%16,%17,%18,%19,%20,%21,%22,%23,%24,%25,%26,%27,%28,%29,%30,%31,%32,%33,%34,%35,%36,%37,%38,%39,%40,%41,%42,%43,%44,%45,%46,%47,%48,%49,%50,%51,%52,%53,%54,%55,%56,%57,%58,%59,%60,%61,%62,%63,%64,%65,%66,%67,%68,%69,%70,%71,%72,%73,%74,%75,%76,%77,%78,%79,%80,%81,%82,%83,%84,%85,%86,%87,%88,%89,%90,%91,%92,%93,%94,%95}, %96, %97, p, 1, 1, 0, 1;\n}"
      : "+f"(d[0]), "+f"(d[1]), "+f"(d[2]), "+f"(d[3]), "+f"(d[4]), "+f"(d[5]), "+f"(d[6]), "+f"(d[7]), "+f"(d[8]), "+f"(d[9]), "+f"(d[10]), "+f"(d[11]), "+f"(d[12]), "+f"(d[13]), "+f"(d[14]), "+f"(d[15]), "+f"(d[16]), "+f"(d[17]), "+f"(d[18]), "+f"(d[19]), "+f"(d[20]), "+f"(d[21]), "+f"(d[22]), "+f"(d[23]), "+f"(d[24]), "+f"(d[25]), "+f"(d[26]), "+f"(d[27]), "+f"(d[28]), "+f"(d[29]), "+f"(d[30]), "+f"(d[31]), "+f"(d[32]), "+f"(d[33]), "+f"(d[34]), "+f"(d[35]), "+f"(d[36]), "+f"(d[37]), "+f"(d[38]), "+f"(d[39]), "+f"(d[40]), "+f"(d[41]), "+f"(d[42]), "+f"(d[43]), "+f"(d[44]), "+f"(d[45]), "+f"(d[46]), "+f"(d[47]), "+f"(d[48]), "+f"(d[49]), "+f"(d[50]), "+f"(d[51]), "+f"(d[52]), "+f"(d[53]), "+f"(d[54]), "+f"(d[55]), "+f"(d[56]), "+f"(d[57]), "+f"(d[58]), "+f"(d[59]), "+f"(d[60]), "+f"(d[61]), "+f"(d[62]), "+f"(d[63]), "+f"(d[64]), "+f"(d[65]), "+f"(d[66]), "+f"(d[67]), "+f"(d[68]), "+f"(d[69]), "+f"(d[70]), "+f"(d[71]), "+f"(d[72]), "+f"(d[73]), "+f"(d[74]), "+f"(d[75]), "+f"(d[76]), "+f"(d[77]), "+f"(d[78]), "+f"(d[79]), "+f"(d[80]), "+f"(d[81]), "+f"(d[82]), "+f"(d[83]), "+f"(d[84]), "+f"(d[85]), "+f"(d[86]), "+f"(d[87]), "+f"(d[88]), "+f"(d[89]), "+f"(d[90]), "+f"(d[91]), "+f"(d[92]), "+f"(d[93]), "+f"(d[94]), "+f"(d[95])
      : "l"(adesc), "l"(bdesc), "r"(scale_d));
}
__device__ __forceinline__ void qk_wgmma_n64(float (&d)[32], const uint32_t (&a)[4], uint64_t desc) {
    asm volatile("wgmma.mma_async.sync.aligned.m64n64k16.f32.bf16.bf16 {%0,%1,%2,%3,%4,%5,%6,%7,%8,%9,%10,%11,%12,%13,%14,%15,%16,%17,%18,%19,%20,%21,%22,%23,%24,%25,%26,%27,%28,%29,%30,%31}, {%32,%33,%34,%35}, %36, 0, 1, 1, 0;"
      : "=f"(d[0]), "=f"(d[1]), "=f"(d[2]), "=f"(d[3]), "=f"(d[4]), "=f"(d[5]), "=f"(d[6]), "=f"(d[7]), "=f"(d[8]), "=f"(d[9]), "=f"(d[10]), "=f"(d[11]), "=f"(d[12]), "=f"(d[13]), "=f"(d[14]), "=f"(d[15]), "=f"(d[16]), "=f"(d[17]), "=f"(d[18]), "=f"(d[19]), "=f"(d[20]), "=f"(d[21]), "=f"(d[22]), "=f"(d[23]), "=f"(d[24]), "=f"(d[25]), "=f"(d[26]), "=f"(d[27]), "=f"(d[28]), "=f"(d[29]), "=f"(d[30]), "=f"(d[31])
      : "r"(a[0]), "r"(a[1]), "r"(a[2]), "r"(a[3]), "l"(desc));
}

__device__ __forceinline__ void pv_wgmma(float (&d)[12], uint32_t a0, uint32_t a1, uint32_t a2, uint32_t a3, uint64_t desc) {
    asm volatile("wgmma.mma_async.sync.aligned.m64n24k16.f32.bf16.bf16 {%0,%1,%2,%3,%4,%5,%6,%7,%8,%9,%10,%11}, {%12,%13,%14,%15}, %16, 1, 1, 1, 1;"
      : "+f"(d[0]), "+f"(d[1]), "+f"(d[2]), "+f"(d[3]), "+f"(d[4]), "+f"(d[5]), "+f"(d[6]), "+f"(d[7]), "+f"(d[8]), "+f"(d[9]), "+f"(d[10]), "+f"(d[11])
      : "r"(a0), "r"(a1), "r"(a2), "r"(a3), "l"(desc));
}

__device__ __forceinline__ uint32_t mapa(uint32_t a, uint32_t rank) { uint32_t r; asm("mapa.shared::cluster.u32 %0, %1, %2;" : "=r"(r) : "r"(a), "r"(rank)); return r; }
__device__ __forceinline__ void mbar_arrive_remote(uint32_t a) { asm volatile("mbarrier.arrive.relaxed.cluster.shared::cluster.b64 _, [%0];" :: "r"(a) : "memory"); }
__device__ __forceinline__ void mbar_wait_cluster(uint32_t a, int parity) {
    uint32_t done;
    int it = 0;
    do {
        asm volatile("{\n.reg .pred p;\nmbarrier.try_wait.parity.acquire.cluster.shared::cta.b64 p, [%1], %2;\nselp.u32 %0, 1, 0, p;\n}"
                     : "=r"(done) : "r"(a), "r"(parity) : "memory");
        if (++it > (1 << 24)) __trap();
    } while (!done);
}
__device__ __forceinline__ void tma2d_mc(uint32_t dst, const CUtensorMap* m, int c0, int c1, uint32_t bar) {
    asm volatile("cp.async.bulk.tensor.2d.shared::cluster.global.mbarrier::complete_tx::bytes.multicast::cluster [%0], [%1, {%3, %4}], [%2], %5;"
                 :: "r"(dst), "l"(m), "r"(bar), "r"(c0), "r"(c1), "h"((uint16_t)3) : "memory");
}
__device__ __forceinline__ void bulk_g2s_mc(uint32_t dst, const void* src, int bytes, uint32_t bar) {
    asm volatile("cp.async.bulk.shared::cluster.global.mbarrier::complete_tx::bytes.multicast::cluster [%0], [%1], %2, [%3], %4;"
                 :: "r"(dst), "l"(src), "r"(bytes), "r"(bar), "h"((uint16_t)3) : "memory");
}
__device__ __forceinline__ void tile_of(int bid, int& mb, int& nt) {
    int grp = bid >> 4, in = bid & 15;
    mb = (grp >> 1) * 4 + (in >> 2);
    nt = (grp & 1) * 4 + (in & 3);
}

constexpr int K1_STAGES = 5, K1_STAGE = 16384 + 24576;
constexpr int K1_BAR = K1_STAGES * K1_STAGE, K1_RS = K1_BAR + 128, K1_CS = K1_RS + 1024, K1_SMEM = K1_CS + 768;

__device__ __forceinline__ float2 row_stats_regs(uint4 a, uint4 b) {
    float v[16];
    v[0] = bf_lo(a.x); v[1] = bf_hi(a.x); v[2] = bf_lo(a.y); v[3] = bf_hi(a.y);
    v[4] = bf_lo(a.z); v[5] = bf_hi(a.z); v[6] = bf_lo(a.w); v[7] = bf_hi(a.w);
    v[8] = bf_lo(b.x); v[9] = bf_hi(b.x); v[10] = bf_lo(b.y); v[11] = bf_hi(b.y);
    v[12] = bf_lo(b.z); v[13] = bf_hi(b.z); v[14] = bf_lo(b.w); v[15] = bf_hi(b.w);
    float s = 0.f;
#pragma unroll
    for (int i = 0; i < 16; i++) s += v[i];
    float mean = warp_sum(s) * (1.0f / DM);
    float q = 0.f;
#pragma unroll
    for (int i = 0; i < 16; i++) { float d = v[i] - mean; q = fmaf(d, d, q); }
    float var = warp_sum(q) * (1.0f / DM);
    float rstd = rsqrtf(var + 1e-5f);
    return make_float2(rstd, -mean * rstd);
}
__device__ __forceinline__ float2 row_stats_x(const __nv_bfloat16* x, int row, int lane) {
    const uint4* p = (const uint4*)(x + (size_t)row * DM);
    return row_stats_regs(__ldg(p + lane), __ldg(p + 32 + lane));
}
__device__ __forceinline__ void colsum8(const __nv_bfloat16* w, int ld, int col, int k0, int nk, float (&s)[8]) {
#pragma unroll
    for (int i = 0; i < 8; i++) s[i] = 0.f;
    for (int k = k0; k < k0 + nk; k += 8) {
        uint4 u[8];
#pragma unroll
        for (int i = 0; i < 8; i++) u[i] = __ldg((const uint4*)(w + (size_t)(k + i) * ld + col));
#pragma unroll
        for (int i = 0; i < 8; i++) {
            s[0] += bf_lo(u[i].x); s[1] += bf_hi(u[i].x); s[2] += bf_lo(u[i].y); s[3] += bf_hi(u[i].y);
            s[4] += bf_lo(u[i].z); s[5] += bf_hi(u[i].z); s[6] += bf_lo(u[i].w); s[7] += bf_hi(u[i].w);
        }
    }
}
__device__ __forceinline__ bool wait_count(const unsigned int* p, unsigned int target, int lane) {
    int ok = 1;
    if (lane == 0) {
        int it = 0;
        while (ld_acquire(p) < target) { if (++it > (1 << 18)) { ok = 0; break; } }
    }
    ok = __shfl_sync(0xffffffffu, ok, 0);
    return ok != 0;
}

__global__ void __launch_bounds__(384, 1)
qkv_kernel(const __grid_constant__ CUtensorMap tm_x, const __grid_constant__ CUtensorMap tm_w,
           const __nv_bfloat16* __restrict__ x, const __nv_bfloat16* __restrict__ wqkv) {
    extern __shared__ __align__(1024) unsigned char smem[];
    const uint32_t sb = smem_u32(smem);
    const int tid = threadIdx.x, warp = __shfl_sync(0xffffffffu, tid >> 5, 0), lane = tid & 31;
    TLDECL
    TL(0);
    int mb, nt;
    tile_of(blockIdx.x, mb, nt);
    const uint32_t full = sb + K1_BAR, empty = full + 40, auxb = full + 80;
    if (tid == 0) {
        prefetch_tmap(&tm_x); prefetch_tmap(&tm_w);
        for (int i = 0; i < K1_STAGES; i++) { mbar_init(full + 8 * i, 1); mbar_init(empty + 8 * i, 8); }
        mbar_init(auxb, 3);
        fence_barrier_init();
    }
    __syncthreads();
    pdl_launch();
    if (warp == 0) {
        if (blockIdx.x == 0) for (int i = lane; i < 160; i += 32) g_cnt2[i] = 0;
        if (lane == 0) {
            for (int kb = 0; kb < 8; kb++) {
                int s = kb % K1_STAGES;
                if (kb >= K1_STAGES) mbar_wait(empty + 8 * s, 0);
                mbar_expect(full + 8 * s, K1_STAGE);
                tma2d(sb + s * K1_STAGE, &tm_x, kb * 64, mb * 128, full + 8 * s);
                tma3d(sb + s * K1_STAGE + 16384, &tm_w, 0, kb * 64, nt * 3, full + 8 * s);
            }
        }
    } else if (warp < 4) {
        float2* s_rs = (float2*)(smem + K1_RS);
        float* s_cs = (float*)(smem + K1_CS);
        if (warp < 3) {
            const int r0 = mb * 128 + nt * 16 + (warp - 1) * 8;
            uint4 u[16];
#pragma unroll
            for (int i = 0; i < 8; i++) {
                const uint4* p = (const uint4*)(x + (size_t)(r0 + i) * DM);
                u[2 * i] = __ldg(p + lane); u[2 * i + 1] = __ldg(p + 32 + lane);
            }
            float2 mine = make_float2(0.f, 0.f);
#pragma unroll
            for (int i = 0; i < 8; i++) {
                float2 st = row_stats_regs(u[2 * i], u[2 * i + 1]);
                if (lane == i) mine = st;
            }
            if (lane < 8) g_rowstat1[r0 + lane] = mine;
            __syncwarp();
            if (lane == 0) red_release(&g_cnt[mb]);
        } else {
            uint4 u[24];
#pragma unroll
            for (int c = 0; c < 3; c++)
#pragma unroll
                for (int i = 0; i < 8; i++)
                    u[c * 8 + i] = __ldg((const uint4*)(wqkv + (size_t)(mb * 32 + (lane >> 3) * 8 + i) * 1536 + nt * 192 + (c * 8 + (lane & 7)) * 8));
#pragma unroll
            for (int c = 0; c < 3; c++) {
                float cs[8];
#pragma unroll
                for (int i = 0; i < 8; i++) cs[i] = 0.f;
#pragma unroll
                for (int i = 0; i < 8; i++) {
                    const uint4 w = u[c * 8 + i];
                    cs[0] += bf_lo(w.x); cs[1] += bf_hi(w.x); cs[2] += bf_lo(w.y); cs[3] += bf_hi(w.y);
                    cs[4] += bf_lo(w.z); cs[5] += bf_hi(w.z); cs[6] += bf_lo(w.w); cs[7] += bf_hi(w.w);
                }
#pragma unroll
                for (int i = 0; i < 8; i++) {
                    cs[i] += __shfl_xor_sync(0xffffffffu, cs[i], 8);
                    cs[i] += __shfl_xor_sync(0xffffffffu, cs[i], 16);
                }
                if (lane < 8) {
                    float4* d = (float4*)(g_cs1_part + mb * 1536 + nt * 192 + (c * 8 + lane) * 8);
                    d[0] = make_float4(cs[0], cs[1], cs[2], cs[3]);
                    d[1] = make_float4(cs[4], cs[5], cs[6], cs[7]);
                }
            }
            __syncwarp();
            if (lane == 0) red_release(&g_cnt[16 + nt]);
        }
        TX(8 + warp);
        if (warp == 1) {
            if (wait_count(&g_cnt[mb], 16, lane)) {
#pragma unroll
                for (int i = 0; i < 4; i++) s_rs[lane + 32 * i] = __ldcg(&g_rowstat1[mb * 128 + lane + 32 * i]);
            } else {
                for (int i = 0; i < 128; i++) {
                    float2 st = row_stats_x(x, mb * 128 + i, lane);
                    if (lane == 0) s_rs[i] = st;
                }
            }
        } else {
            int c0 = (warp - 2) * 96;
            if (wait_count(&g_cnt[16 + nt], 16, lane)) {
#pragma unroll
                for (int i = 0; i < 3; i++) {
                    float s = 0.f;
#pragma unroll
                    for (int p = 0; p < 16; p++) s += __ldcg(&g_cs1_part[p * 1536 + nt * 192 + c0 + lane + 32 * i]);
                    s_cs[c0 + lane + 32 * i] = s;
                }
            } else if (lane < 12) {
                float s[8];
                colsum8(wqkv, 1536, nt * 192 + c0 + lane * 8, 0, 512, s);
#pragma unroll
                for (int i = 0; i < 8; i++) s_cs[c0 + lane * 8 + i] = s[i];
            }
        }
        __syncwarp();
        TX(12 + warp);
        if (lane == 0) mbar_arrive(auxb);
        bar_sync(2, 256 + 96);
        const int a = tid - 32;
        {
            const int hh = a >> 3, w = a & 7;
            const float4* p = (const float4*)(smem + 49152) + (hh * 256 + w * 32) / 2;
            float m = 0.f;
#pragma unroll
            for (int i = 0; i < 8; i++) {
                const int ii = (i + a) & 7;
                float4 u = p[2 * ii], v = p[2 * ii + 1];
                float n0 = u.x + u.z + v.x + v.z, n1 = u.y + u.w + v.y + v.w;
                if (!(n0 <= 3.0e38f) || !(n1 <= 3.0e38f)) m = __int_as_float(0x7f800000);
                m = fmaxf(m, fmaxf(n0, n1));
            }
            const int col0 = nt * 192 + hh * 16;
            g_nrm[((col0 >> 9) * NH + ((col0 & 511) >> 4)) * 128 + mb * 8 + w] = m;
        }
        if (a < 24) bulk_wait_all();
        TL(27);
        TLDUMP;
    } else {
        const int wgi = (warp >> 2) - 1, ww = warp & 3;
        float acc[96];
#pragma unroll 1
        for (int kb = 0; kb < 8; kb++) {
            int s = kb % K1_STAGES;
            mbar_wait(full + 8 * s, (kb / K1_STAGES) & 1);
            if (warp == 4) TX(kb);
            uint64_t ad = make_desc(sb + s * K1_STAGE + wgi * 8192, 16, 1024, 1);
            uint64_t bd = make_desc(sb + s * K1_STAGE + 16384, 8192, 1024, 1);
            WG_FENCE();
#pragma unroll
            for (int k = 0; k < 4; k++) wgmma_ss_n192(acc, ad + k * 2, bd + k * 128, (kb | k) != 0);
            WG_COMMIT();
            if (kb > 0) {
                wg_wait<1>();
                if (lane == 0) mbar_arrive(empty + 8 * ((kb - 1) % K1_STAGES));
            }
        }
        wg_wait<0>();
        fence_regs(acc);
        TL(1);
        if (warp == 4) TX(16);
        mbar_wait(auxb, 0);
        if (warp == 4) TX(17);
        bar_sync(1, 256);
        const float2* s_rs = (const float2*)(smem + K1_RS);
        const float* s_cs = (const float*)(smem + K1_CS);
        const int g = lane >> 2, t = lane & 3;
        const int rl = wgi * 64 + ww * 16 + g;
        const float2 st0 = s_rs[rl], st1 = s_rs[rl + 8];
        const float QS = 0.25f * 1.4426950408889634f;
        const uint32_t stg = sb + ((lane >> 4) * 16 + wgi * 8 + ww * 2 + ((lane >> 3) & 1)) * 128 + (lane & 7) * 16;
        float2* s_np = (float2*)(smem + 49152) + (warp - 4) * 32 + lane;
#pragma unroll
        for (int hh = 0; hh < 12; hh++) {
            const int which = (nt * 192 + hh * 16) >> 9;
            const float sc = (which == 0) ? QS : 1.0f;
            const float a0 = st0.x * sc, b0 = st0.y * sc, a1 = st1.x * sc, b1 = st1.y * sc;
            const float2 c0 = *(const float2*)(s_cs + 16 * hh + 2 * t), c1 = *(const float2*)(s_cs + 16 * hh + 8 + 2 * t);
            const float* a = acc + 8 * hh;
            float v0 = fmaf(a0, a[0], b0 * c0.x), v1 = fmaf(a0, a[1], b0 * c0.y), v2 = fmaf(a1, a[2], b1 * c0.x), v3 = fmaf(a1, a[3], b1 * c0.y);
            float v4 = fmaf(a0, a[4], b0 * c1.x), v5 = fmaf(a0, a[5], b0 * c1.y), v6 = fmaf(a1, a[6], b1 * c1.x), v7 = fmaf(a1, a[7], b1 * c1.y);
            {
                const int head = ((nt * 192 + hh * 16) & 511) >> 4;
                uint32_t* o = (uint32_t*)g_qkv + ((size_t)((which * NH + head) * 2) * 256 + mb * 16 + wgi * 8 + ww * 2) * 32 + lane;
                o[0] = pack_bf16(v0, v1); o[32] = pack_bf16(v2, v3); o[8192] = pack_bf16(v4, v5); o[8192 + 32] = pack_bf16(v6, v7);
            }
            s_np[hh * 256] = make_float2(fmaf(v0, v0, fmaf(v1, v1, fmaf(v4, v4, v5 * v5))), fmaf(v2, v2, fmaf(v3, v3, fmaf(v6, v6, v7 * v7))));
        }
        fence_proxy_async();
        bar_arrive(2, 256 + 96);
        TL(2);
        TLDUMP;
    }
}

constexpr int AT_K = 0, AT_V = 65536, AT_ONES = 131072, AT_BAR = 163840, AT_SMEM = AT_BAR + 128;
#define POLY_MASK 0xAD6A

__device__ __forceinline__ uint32_t exp2_pair_poly(float x0, float x1) {
    uint32_t t0 = __float_as_uint(x0 + 32895.0f);
    uint32_t t1 = __float_as_uint(x1 + 32895.0f);
    uint32_t gd = __byte_perm(t0, t1, 0x6420);
    uint32_t wm = __byte_perm(t0, t1, 0x5612);
    uint32_t v = hfma2(gd, 0x71477147u, 0x354f354fu);
    uint32_t z = hmul2(v, gd);
    return (wm >> 1) + z;
}
__device__ __forceinline__ uint32_t exp2_pair_mufu(float x0, float x1) { return pack_bf16(ex2f(x0), ex2f(x1)); }
template <uint32_t MASK>
__device__ __forceinline__ void exp_blocks(const float (&s)[32], uint32_t (&p)[16]) {
#pragma unroll
    for (int b = 0; b < 8; b++) {
        if ((MASK >> b) & 1) {
            p[2 * b] = exp2_pair_poly(s[4 * b], s[4 * b + 1]);
            p[2 * b + 1] = exp2_pair_poly(s[4 * b + 2], s[4 * b + 3]);
        } else {
            p[2 * b] = exp2_pair_mufu(s[4 * b], s[4 * b + 1]);
            p[2 * b + 1] = exp2_pair_mufu(s[4 * b + 2], s[4 * b + 3]);
        }
    }
}
#define PV4(P) _Pragma("unroll") for (int i = 0; i < 4; i++) { pv_wgmma(o, P[4 * i], P[4 * i + 1], P[4 * i + 2], P[4 * i + 3], vd); vd += 16; }

__device__ __forceinline__ void attn_store(float (&o)[12], int row0, int head, int lane) {
    float l0 = __shfl_sync(0xffffffffu, o[8], lane & 28);
    float l1 = __shfl_sync(0xffffffffu, o[10], lane & 28);
    float r0 = 1.0f / l0, r1 = 1.0f / l1;
    uint32_t* op = (uint32_t*)g_ao;
    int mb = row0 >> 7, rg = (row0 & 127) >> 3;
    int kb = head >> 2, kc = (head & 3) * 2;
    size_t base = (((size_t)(mb * 8 + kb) * 8 + kc) * 16 + rg) * 32 + lane;
    op[base] = pack_bf16(o[0] * r0, o[1] * r0);
    op[base + 32] = pack_bf16(o[2] * r1, o[3] * r1);
    op[base + 16 * 32] = pack_bf16(o[4] * r0, o[5] * r0);
    op[base + 16 * 32 + 32] = pack_bf16(o[6] * r1, o[7] * r1);
}

__device__ __forceinline__ void attn_load_q(uint32_t (&q)[4], const __nv_bfloat16* gq, int row0, int lane) {
    const uint32_t* qp = (const uint32_t*)gq;
    int j0 = row0 >> 3;
    q[0] = __ldcg(qp + (0 * 256 + j0) * 32 + lane);
    q[1] = __ldcg(qp + (0 * 256 + j0 + 1) * 32 + lane);
    q[2] = __ldcg(qp + (1 * 256 + j0) * 32 + lane);
    q[3] = __ldcg(qp + (1 * 256 + j0 + 1) * 32 + lane);
}

__device__ __forceinline__ void attn_tile_safe(const uint32_t (&q)[4], uint64_t kd, uint64_t vd, int row0, int head, int lane) {
    float o[12];
#pragma unroll
    for (int i = 0; i < 12; i++) o[i] = 0.f;
    float m0 = -INFINITY, m1 = -INFINITY;
    fence_regs(o);
#pragma unroll 1
    for (int j = 0; j < 32; j++) {
        float s[32];
        uint32_t p[16];
        WG_FENCE();
        qk_wgmma_n64(s, q, kd); kd += 64;
        WG_COMMIT();
        wg_wait<0>();
        fence_regs(s);
        fence_regs(o);
        float x0 = m0, x1 = m1;
#pragma unroll
        for (int b = 0; b < 8; b++) {
            x0 = fmaxf(x0, fmaxf(s[4 * b], s[4 * b + 1]));
            x1 = fmaxf(x1, fmaxf(s[4 * b + 2], s[4 * b + 3]));
        }
        x0 = fmaxf(x0, __shfl_xor_sync(0xffffffffu, x0, 1)); x0 = fmaxf(x0, __shfl_xor_sync(0xffffffffu, x0, 2));
        x1 = fmaxf(x1, __shfl_xor_sync(0xffffffffu, x1, 1)); x1 = fmaxf(x1, __shfl_xor_sync(0xffffffffu, x1, 2));
        float al0 = ex2f(m0 - x0), al1 = ex2f(m1 - x1);
        m0 = x0; m1 = x1;
#pragma unroll
        for (int i = 0; i < 3; i++) { o[4 * i] *= al0; o[4 * i + 1] *= al0; o[4 * i + 2] *= al1; o[4 * i + 3] *= al1; }
#pragma unroll
        for (int b = 0; b < 8; b++) {
            p[2 * b] = exp2_pair_mufu(s[4 * b] - m0, s[4 * b + 1] - m0);
            p[2 * b + 1] = exp2_pair_mufu(s[4 * b + 2] - m1, s[4 * b + 3] - m1);
        }
        fence_regs(o);
        WG_FENCE();
        PV4(p);
        WG_COMMIT();
        wg_wait<0>();
        fence_regs(o);
    }
    attn_store(o, row0, head, lane);
}

__global__ void __launch_bounds__(512, 1)
attn_kernel(const __nv_bfloat16* __restrict__ wg_, const __nv_bfloat16* __restrict__ wu_,
            const __nv_bfloat16* __restrict__ wo_, const __nv_bfloat16* __restrict__ wd_) {
    extern __shared__ __align__(1024) unsigned char smem[];
    const uint32_t sb = smem_u32(smem);
    const int tid = threadIdx.x, wg = tid >> 7, warp = (tid >> 5) & 3, lane = tid & 31;
    TLDECL
    pdl_launch();
    if (blockIdx.x >= 128) {
        const int e = blockIdx.x - 128;
        const __nv_bfloat16* w = (e < 2) ? wg_ : wu_;
        float* red = (float*)smem;
        const int cgrp = tid & 127, kq = tid >> 7;
        if (cgrp < 112) {
            float s[8];
            colsum8(w, FF, (e & 1) * 896 + cgrp * 8, kq * 128, 128, s);
#pragma unroll
            for (int i = 0; i < 8; i++) red[kq * 896 + cgrp * 8 + i] = s[i];
        }
        __syncthreads();
        for (int c = tid; c < 896; c += 512)
            g_cs2[(e >> 1) * FF + (e & 1) * 896 + c] = red[c] + red[896 + c] + red[1792 + c] + red[2688 + c];
        if (tid < 32) {
            const char* p0 = (const char*)wo_ + e * (DM * DM * 2 / 4);
            for (int i = lane; i < 32; i += 32)
                asm volatile("cp.async.bulk.prefetch.L2.global [%0], %1;" :: "l"(p0 + i * 4096), "r"(4096) : "memory");
            const char* p1 = (const char*)wd_ + e * (FF * DM * 2 / 4);
            for (int i = lane; i < 112; i += 32)
                asm volatile("cp.async.bulk.prefetch.L2.global [%0], %1;" :: "l"(p1 + i * 4096), "r"(4096) : "memory");
        }
        return;
    }
    const int head = blockIdx.x >> 2, qq = blockIdx.x & 3;
    const __nv_bfloat16* gq = g_qkv + (size_t)head * (S_LEN * 16);
    const __nv_bfloat16* gk = g_qkv + (size_t)(NH + head) * (S_LEN * 16);
    const __nv_bfloat16* gv = g_qkv + (size_t)(2 * NH + head) * (S_LEN * 16);
    if (tid == 0) {
        for (int i = 0; i < 8; i++) mbar_init(sb + AT_BAR + 8 * i, 1);
        fence_barrier_init();
    }
    {
        uint4 one = make_uint4(0x00003F80u, 0, 0, 0);
#pragma unroll
        for (int i = 0; i < 4; i++) *(uint4*)(smem + AT_ONES + (i * 512 + tid) * 16) = one;
        fence_proxy_async();
    }
    __syncthreads();
    TL(3);
    pdl_wait();
    TL(4);
    auto load_kv = [&](int i) {
        uint32_t bar = sb + AT_BAR + 8 * i;
        mbar_expect(bar, 16384);
        bulk_g2s(sb + AT_K + i * 4096, gk + i * 2048, 4096, bar);
        bulk_g2s(sb + AT_K + 32768 + i * 4096, gk + 16384 + i * 2048, 4096, bar);
        bulk_g2s(sb + AT_V + i * 4096, gv + i * 2048, 4096, bar);
        bulk_g2s(sb + AT_V + 32768 + i * 4096, gv + 16384 + i * 2048, 4096, bar);
    };
    if (tid == 0) { load_kv(0); load_kv(1); }
    uint32_t q[4], q2[4];
    attn_load_q(q, gq, qq * 512 + wg * 64 + warp * 16, lane);
    attn_load_q(q2, gq, qq * 512 + (4 + wg) * 64 + warp * 16, lane);
    bool fast;
    {
        const float* nq = g_nrm + (0 * NH + head) * 128 + qq * 32;
        const float* nk = g_nrm + (1 * NH + head) * 128;
        const float* nv = g_nrm + (2 * NH + head) * 128;
        float4 k4 = __ldcg((const float4*)nk + lane), v4 = __ldcg((const float4*)nv + lane);
        float qm = warp_max(__ldcg(nq + lane));
        float km = warp_max(fmaxf(fmaxf(k4.x, k4.y), fmaxf(k4.z, k4.w)));
        float vm = warp_max(fmaxf(fmaxf(v4.x, v4.y), fmaxf(v4.z, v4.w)));
        fast = __all_sync(0xffffffffu, (qm * km <= 3500.0f) && (vm <= 1.0e24f));
    }
    TL(24);
    const uint64_t kdesc0 = make_desc(sb + AT_K, 32768, 128, 0);
    const uint64_t vdesc0 = make_desc(sb + AT_V, 128, 32768, 0);
    if (!fast) {
        if (tid == 0) for (int i = 2; i < 8; i++) load_kv(i);
        for (int i = 0; i < 8; i++) mbar_wait(sb + AT_BAR + 8 * i, 0);
#pragma unroll 1
        for (int tile = 0; tile < 2; tile++) {
            const int row0 = qq * 512 + (tile * 4 + wg) * 64 + warp * 16;
            attn_tile_safe(q, kdesc0, vdesc0, row0, head, lane);
#pragma unroll
            for (int i = 0; i < 4; i++) q[i] = q2[i];
        }
        return;
    }
#pragma unroll 1
    for (int tile = 0; tile < 2; tile++) {
        const int row0 = qq * 512 + (tile * 4 + wg) * 64 + warp * 16;
        float o[12];
#pragma unroll
        for (int i = 0; i < 12; i++) o[i] = 0.f;
        fence_regs(o);
        float sa[32];
        uint32_t pa[16];
        uint64_t kd = kdesc0, vd = vdesc0;
        if (tile == 0) { mbar_wait(sb + AT_BAR, 0); TL(25); }
        WG_FENCE();
        qk_wgmma_n64(sa, q, kd); kd += 64;
        WG_COMMIT();
#pragma unroll 1
        for (int jj = 0; jj < 8; jj++) {
            if (tile == 0 && jj < 7) {
                if (tid == 0 && jj < 6) load_kv(jj + 2);
                mbar_wait(sb + AT_BAR + 8 * (jj + 1), 0);
            }
            if (wg == 0 && warp == 0) TX(128 + tile * 8 + jj);
#pragma unroll
            for (int j = 0; j < 4; j++) {
                wg_wait<0>();
                fence_regs(sa);
                if (j & 1) exp_blocks<(POLY_MASK >> 8)>(sa, pa); else exp_blocks<(POLY_MASK & 255)>(sa, pa);
                WG_FENCE();
                qk_wgmma_n64(sa, q, kd); kd += 64;
                PV4(pa);
                WG_COMMIT();
            }
        }
        wg_wait<0>();
        fence_regs(o);
        fence_regs(sa);
        if (tile == 0) TL(26);
        attn_store(o, row0, head, lane);
#pragma unroll
        for (int i = 0; i < 4; i++) q[i] = q2[i];
    }
    TL(5);
    TLDUMP;
}

#define DELAYC 9
constexpr int F_R2 = 131072, F_X = 196608, F_BAR = 229376;
constexpr int F_RS = F_BAR + 256, F_CS = F_RS + 1024, F_SMEM = F_CS + 1792;
enum { B_FA = 0, B_HF = 4, B_BF = 8, B_BE = 11, B_CF = 14, B_CE = 20, B_ADONE = 26, B_BDONE = 27, B_XC = 28, B_PRDY = 29, B_AUX = 30, B_NUM = 31 };

__device__ __forceinline__ void st_async4(uint32_t dst, float a, float b, float c, float d, uint32_t bar) {
    asm volatile("st.async.weak.shared::cluster.mbarrier::complete_tx::bytes.v4.f32 [%0], {%1,%2,%3,%4}, [%5];"
                 :: "r"(dst), "f"(a), "f"(b), "f"(c), "f"(d), "r"(bar) : "memory");
}
__device__ __forceinline__ void poll_count(const unsigned int* p, unsigned int target) {
    int it = 0;
    while (ld_acquire(p) < target) { if (++it > (1 << 22)) __trap(); }
    asm volatile("fence.proxy.async.global;" ::: "memory");
}
__device__ __forceinline__ void tma2d_store(const CUtensorMap* m, uint32_t src, int c0, int c1) {
    asm volatile("cp.async.bulk.tensor.2d.global.shared::cta.bulk_group [%0, {%2, %3}], [%1];" :: "l"(m), "r"(src), "r"(c0), "r"(c1) : "memory");
}
__device__ __forceinline__ float2 h_row_stats(int row) {
    const float4* hp = (const float4*)(g_hstat + (size_t)row * 8);
    float4 a = __ldcg(hp), b = __ldcg(hp + 1), c = __ldcg(hp + 2), d = __ldcg(hp + 3);
    float mean = 0.125f * (a.x + a.z + b.x + b.z + c.x + c.z + d.x + d.z);
    float m2 = a.y + a.w + b.y + b.w + c.y + c.w + d.y + d.w;
    float e;
    e = a.x - mean; m2 = fmaf(64.f * e, e, m2); e = a.z - mean; m2 = fmaf(64.f * e, e, m2);
    e = b.x - mean; m2 = fmaf(64.f * e, e, m2); e = b.z - mean; m2 = fmaf(64.f * e, e, m2);
    e = c.x - mean; m2 = fmaf(64.f * e, e, m2); e = c.z - mean; m2 = fmaf(64.f * e, e, m2);
    e = d.x - mean; m2 = fmaf(64.f * e, e, m2); e = d.z - mean; m2 = fmaf(64.f * e, e, m2);
    return make_float2(rsqrtf(m2 * (1.0f / DM) + 1e-5f), -mean);
}
__device__ __forceinline__ int c_kblock(int i, int r) {
    if (i < 6) { const int e = 2 * i + r, m = e / 3, k = e - 3 * m; return 7 * m + (k == 2 ? 4 : k); }
    const int l = 2 * (i - 6) + r, m = l >> 2, k = l & 3;
    return 7 * m + (k < 2 ? 2 + k : 3 + k);
}
__device__ __forceinline__ uint32_t c_stage_a(int s, int ntB) { return s < 4 ? ((ntB + 2 * s) & 7) * 16384 : F_R2 + (s - 4) * 32768; }
__device__ __forceinline__ uint32_t c_stage_b(int s, int ntB) { return s < 4 ? ((ntB + 2 * s + 1) & 7) * 16384 : F_R2 + (s - 4) * 32768 + 16384; }
template <int R>
__device__ __forceinline__ void xchg(float (&acc)[64], float (&o)[32], uint32_t sb, unsigned char* smem, int bar, int ctid) {
    const uint32_t dst = mapa(sb + F_X + ctid * 16, 1 - R), rb = mapa(sb + F_BAR + 8 * bar, 1 - R);
#pragma unroll
    for (int q = 0; q < 8; q++) {
        const int j = (1 - R) * 32 + 4 * q;
        st_async4(dst + q * 4096, acc[j], acc[j + 1], acc[j + 2], acc[j + 3], rb);
    }
    mbar_wait_cluster(sb + F_BAR + 8 * bar, 0);
#pragma unroll
    for (int q = 0; q < 8; q++) {
        float4 v = *(const float4*)(smem + F_X + q * 4096 + ctid * 16);
        const int j = R * 32 + 4 * q;
        o[4 * q] = acc[j] + v.x; o[4 * q + 1] = acc[j + 1] + v.y; o[4 * q + 2] = acc[j + 2] + v.z; o[4 * q + 3] = acc[j + 3] + v.w;
    }
}

template <int NB, bool STAGE>
__device__ __forceinline__ void ffn_epilogue(const float* ag, const float* au, const float* s_cs, int cs_off, uint32_t* gp, uint32_t stg,
                                             float2 st0, float2 st1, int lane) {
    const int t = lane & 3;
    const float C1 = 0.7978845608028654f, C2 = 0.044715f * 0.7978845608028654f;
    const float k10 = st0.x * C1, k20 = st0.x * st0.x * st0.x * C2, k11 = st1.x * C1, k21 = st1.x * st1.x * st1.x * C2;
#pragma unroll
    for (int j2 = 0; j2 < NB / 2; j2++) {
        uint32_t pk[4];
#pragma unroll
        for (int jj = 0; jj < 2; jj++) {
            const int j = 2 * j2 + jj;
            const float2 cg = *(const float2*)(s_cs + cs_off + 8 * j + 2 * t);
            const float2 cu = *(const float2*)(s_cs + 224 + cs_off + 8 * j + 2 * t);
            float r[4];
#pragma unroll
            for (int e = 0; e < 4; e++) {
                const float nm = (e < 2) ? st0.y : st1.y, k1 = (e < 2) ? k10 : k11, k2 = (e < 2) ? k20 : k21;
                const float tg = fmaf(nm, (e & 1) ? cg.y : cg.x, ag[4 * j + e]);
                const float tu = fmaf(nm, (e & 1) ? cu.y : cu.x, au[4 * j + e]);
                const float th = tanh_fast(tg * fmaf(tg * tg, k2, k1));
                const float p = tg * tu;
                r[e] = fmaf(p, th, p);
            }
            pk[2 * jj] = pack_bf16(r[0], r[1]);
            pk[2 * jj + 1] = pack_bf16(r[2], r[3]);
        }
        if (STAGE) {
            stsm4(stg + j2 * 4096, pk[0], pk[1], pk[2], pk[3]);
        } else {
            gp[j2 * 1024] = pk[0]; gp[j2 * 1024 + 32] = pk[1]; gp[j2 * 1024 + 512] = pk[2]; gp[j2 * 1024 + 544] = pk[3];
        }
    }
}

__global__ void __cluster_dims__(2, 1, 1) __launch_bounds__(384, 1)
tail_kernel(const __grid_constant__ CUtensorMap tm_o, const __grid_constant__ CUtensorMap tm_g,
            const __grid_constant__ CUtensorMap tm_u, const __grid_constant__ CUtensorMap tm_d,
            const __grid_constant__ CUtensorMap tm_out, const __nv_bfloat16* __restrict__ x) {
    extern __shared__ __align__(1024) unsigned char smem[];
    const uint32_t sb = smem_u32(smem);
    const uint32_t bars = sb + F_BAR;
    const int tid = threadIdx.x, warp = __shfl_sync(0xffffffffu, tid >> 5, 0), lane = tid & 31;
    TLDECL
    TL(6);
    if (warp == 4) TX(200);
    const int cl = blockIdx.x >> 1, r = blockIdx.x & 1;
    const int mb = ((cl & 7) >> 1) * 4 + (cl >> 4), ntA = (cl & 1) * 2 + ((cl >> 3) & 1);
    const int nt = ntA * 2 + r;
    const int mbB = (mb & ~1) + r, ntB = (mb & 1) * 4 + ntA;
    if (tid == 0) {
#pragma unroll
        for (int i = 0; i < B_NUM; i++) {
            const int cnt = (i >= B_BE && i < B_BE + 3) ? 16 : (i == B_BDONE) ? DELAYC : ((i >= B_CE && i < B_CE + 6) || i == B_PRDY) ? 8 : (i == B_AUX || i == B_ADONE) ? 2 : 1;
            mbar_init(bars + 8 * i, cnt);
        }
        mbar_expect(bars + 8 * B_XC, 32768);
        fence_barrier_init();
    }
    TL(28);
    __syncthreads();
    TL(29);
    asm volatile("barrier.cluster.arrive.relaxed.aligned;" ::: "memory");
    TL(30);
    if (warp < 4) {
        asm volatile("setmaxnreg.dec.sync.aligned.u32 56;");
        if (warp == 0) TX(205);
        if (warp == 0) {
            if (lane == 0) {
                auto load_b = [&](int it) {
                    const int s = it % 3, pass = it >> 3, kb = (ntB + it) & 7;
                    const int ng = pass ? 3 : 4, c0 = ntB * 224 + pass * 128;
                    const uint32_t bar = bars + 8 * (B_BF + s), dst = sb + F_R2 + s * 32768 + r * 16384;
                    mbar_expect(bar, ng * 8192);
                    for (int i = 0; i < ng; i++) tma2d_mc(dst + i * 4096, r ? &tm_u : &tm_g, c0 + i * 32, kb * 64, bar);
                };
                for (int i = 0; i < 8; i++) {
                    const uint32_t bar = bars + 8 * (B_FA + (i >> 1));
                    if (!(i & 1)) mbar_expect(bar, 49152);
                    tma2d(sb + F_R2 + 32768 + i * 8192, &tm_o, nt * 64, i * 64, bar);
                }
                asm volatile("barrier.cluster.wait.acquire;" ::: "memory");
                pdl_wait();
                TL(16);
                for (int i = 0; i < 4; i++)
                    bulk_g2s_mc(sb + (2 * i + r) * 16384, g_ao + (size_t)(mb * 8 + 2 * i + r) * 8192, 16384, bars + 8 * (B_FA + i));
                load_b(0);
                if (blockIdx.x == 0)
                    for (int i = 0; i < 32; i++) g_cnt[i] = 0;
                mbar_wait_cluster(bars + 8 * B_ADONE, 0);
                load_b(1); load_b(2);
                auto load_c = [&](int i) {
                    const int s = i % 6, kb = c_kblock(i, r);
                    const uint32_t bar = bars + 8 * (B_CF + s), da = sb + c_stage_a(s, ntB), db = sb + c_stage_b(s, ntB);
                    mbar_expect(bar, 32768);
                    tma2d(db, &tm_d, ntA * 128, kb * 64, bar);
                    tma2d(db + 8192, &tm_d, ntA * 128 + 64, kb * 64, bar);
                    bulk_g2s(da, g_g + (size_t)(mb * 28 + kb) * 8192, 16384, bar);
                };
                for (int it = 3; it < 16; it++) {
                    mbar_wait_cluster(bars + 8 * (B_BE + it % 3), (it / 3 - 1) & 1);
                    load_b(it);
                    if (it == 12) { poll_count(&g_cnt2[mb], 8); load_c(0); }
                    if (it == 14) load_c(1);
                }
                mbar_wait(bars + 8 * B_BDONE, 0);
                for (int i = 2; i < 14; i++) {
                    if (i >= 6) mbar_wait(bars + 8 * (B_CE + i % 6), ((i / 6) - 1) & 1);
                    if (i == 6) { poll_count(&g_cnt2[16 + mb], 8); TL(18); }
                    load_c(i);
                }
            }
            else asm volatile("barrier.cluster.wait.acquire;" ::: "memory");
            TLDUMP;
        } else if (warp == 1) {
            asm volatile("barrier.cluster.wait.acquire.aligned;" ::: "memory");
            bar_sync(5, 288);
            if (lane == 0) { red_release(&g_cnt2[32 + mb * 8 + nt]); TL(9); }
            __syncwarp();
            bar_sync(1, 288);
            if (lane == 0) red_release(&g_cnt2[mbB]);
            __syncwarp();
            bar_sync(2, 288);
            if (lane == 0) {
                red_release(&g_cnt2[16 + mbB]);
                if (DELAYC == 9) mbar_arrive(bars + 8 * B_BDONE);
                TL(13);
            }
            __syncwarp();
            bar_sync(3, 288);
            if (lane == 0) {
                tma2d_store(&tm_out, sb, nt * 64, mb * 128);
                bulk_commit();
                bulk_wait_all();
                TL(15);
            }
            TLDUMP;
        } else {
            asm volatile("barrier.cluster.wait.acquire.aligned;" ::: "memory");
            pdl_wait();
            float2* s_rs = (float2*)(smem + F_RS);
            float* s_cs = (float*)(smem + F_CS);
            for (int c = tid - 64; c < 448; c += 64)
                s_cs[c] = __ldcg(&g_cs2[(c >= 224 ? FF - 224 : 0) + ntB * 224 + c]);
            if (tid == 96) {
                mbar_wait_cluster(bars + 8 * B_ADONE, 0);
                for (int i = 0; i < 8; i++) {
                    const int kb = (ntB + i) & 7;
                    const uint32_t bar = bars + 8 * (i < 4 ? B_HF + i : B_FA + i - 4);
                    poll_count(&g_cnt2[32 + mbB * 8 + kb], 1);
                    mbar_expect(bar, 16384);
                    bulk_g2s(sb + kb * 16384, g_h + (size_t)(mbB * 8 + kb) * 8192, 16384, bar);
                }
                TL(17);
            }
            __syncwarp();
            if (lane < 8) poll_count(&g_cnt2[32 + mbB * 8 + lane], 1);
            __syncwarp();
            for (int rr = tid - 64; rr < 128; rr += 64) {
                s_rs[rr] = h_row_stats(mbB * 128 + rr);
            }
            __syncwarp();
            if (lane == 0) mbar_arrive(bars + 8 * B_AUX);
            TLDUMP;
        }
    } else {
        asm volatile("setmaxnreg.inc.sync.aligned.u32 216;");
        if (warp == 4) TX(206);
        const int wgi = (warp >> 2) - 1, ww = warp & 3, ctid = tid - 128;
        const int g = lane >> 2, t = lane & 3;
        const int rl = wgi * 64 + ww * 16 + g, row = mb * 128 + rl;
        const int rgl = wgi * 8 + ww * 2;
        const float2* s_rs = (const float2*)(smem + F_RS);
        const float* s_cs = (const float*)(smem + F_CS);
        const uint32_t stl = ((lane >> 4) * 16 + rgl + ((lane >> 3) & 1)) * 128 + (lane & 7) * 16;
        uint32_t* hp = (uint32_t*)g_h + ((size_t)(mb * 8 + nt) * 8 * 16 + rgl) * 32 + lane;
        const uint32_t rbars = mapa(bars, 1 - r);
        TL(23);
        {
            uint32_t xr[16];
            const uint32_t* xp = (const uint32_t*)(x + (size_t)row * DM + nt * 64) + t;
#pragma unroll
            for (int j = 0; j < 8; j++) { xr[2 * j] = __ldg(xp + 4 * j); xr[2 * j + 1] = __ldg(xp + 8 * (DM / 2) + 4 * j); }
            float acc[32];
#pragma unroll 1
            for (int i = 0; i < 8; i++) {
                if (!(i & 1)) { mbar_wait(bars + 8 * (B_FA + (i >> 1)), 0); if (i == 0) TL(19); }
                uint64_t ad = make_desc(sb + i * 16384 + wgi * 1024, 2048, 128, 0);
                uint64_t bd = make_desc(sb + F_R2 + 32768 + i * 8192, 8192, 1024, 1);
                WG_FENCE();
#pragma unroll
                for (int k = 0; k < 4; k++) wgmma_ss_n64(acc, ad + k * 256, bd + k * 128, (i | k) != 0);
                WG_COMMIT();
            }
            wg_wait<0>();
            fence_regs(acc);
            TL(7);
            asm volatile("barrier.cluster.wait.acquire.aligned;" ::: "memory");
            bar_sync(4, 256);
            if (tid == 128) { mbar_arrive(bars + 8 * B_ADONE); mbar_arrive_remote(mapa(bars + 8 * B_ADONE, 1 - r)); }
            float v0[16], v1[16];
            float s0 = 0.f, s1 = 0.f;
#pragma unroll
            for (int j2 = 0; j2 < 4; j2++) {
                uint32_t u[4];
#pragma unroll
                for (int jj = 0; jj < 2; jj++) {
                    const int j = 2 * j2 + jj;
                    u[2 * jj] = pack_bf16(bf_lo(xr[2 * j]) + acc[4 * j], bf_hi(xr[2 * j]) + acc[4 * j + 1]);
                    u[2 * jj + 1] = pack_bf16(bf_lo(xr[2 * j + 1]) + acc[4 * j + 2], bf_hi(xr[2 * j + 1]) + acc[4 * j + 3]);
                    v0[2 * j] = bf_lo(u[2 * jj]); v0[2 * j + 1] = bf_hi(u[2 * jj]);
                    v1[2 * j] = bf_lo(u[2 * jj + 1]); v1[2 * j + 1] = bf_hi(u[2 * jj + 1]);
                    s0 += v0[2 * j] + v0[2 * j + 1];
                    s1 += v1[2 * j] + v1[2 * j + 1];
                }
                hp[j2 * 1024] = u[0]; hp[j2 * 1024 + 32] = u[1]; hp[j2 * 1024 + 512] = u[2]; hp[j2 * 1024 + 544] = u[3];
            }
            float m0 = s0 * (1.0f / 16), m1 = s1 * (1.0f / 16), q0 = 0.f, q1 = 0.f;
#pragma unroll
            for (int i = 0; i < 16; i++) {
                float d0 = v0[i] - m0, d1 = v1[i] - m1;
                q0 = fmaf(d0, d0, q0); q1 = fmaf(d1, d1, q1);
            }
#pragma unroll
            for (int st = 0; st < 2; st++) {
                float hn = st ? 16.f : 8.f;
                float om0 = __shfl_xor_sync(0xffffffffu, m0, 1 << st), oq0 = __shfl_xor_sync(0xffffffffu, q0, 1 << st);
                float om1 = __shfl_xor_sync(0xffffffffu, m1, 1 << st), oq1 = __shfl_xor_sync(0xffffffffu, q1, 1 << st);
                float d0 = om0 - m0, d1 = om1 - m1;
                q0 = q0 + oq0 + d0 * d0 * hn; q1 = q1 + oq1 + d1 * d1 * hn;
                m0 = 0.5f * (m0 + om0); m1 = 0.5f * (m1 + om1);
            }
            if (t == 0) {
                g_hstat[row * 8 + nt] = make_float2(m0, q0);
                g_hstat[(row + 8) * 8 + nt] = make_float2(m1, q1);
            }
            bar_arrive(5, 288);
            TL(8);
        }
        uint32_t* gp = (uint32_t*)g_g + (((size_t)mbB * 224 + ntB * 28) * 16 + rgl) * 32 + lane;
        {
            float ag[64], au[64];
#pragma unroll 1
            for (int kb = 0; kb < 8; kb++) {
                const int s = kb % 3;
                mbar_wait(bars + 8 * (kb < 4 ? B_HF + kb : B_FA + kb - 4), kb < 4 ? 0 : 1);
                mbar_wait(bars + 8 * (B_BF + s), (kb / 3) & 1);
                uint64_t ad = make_desc(sb + ((ntB + kb) & 7) * 16384 + wgi * 1024, 2048, 128, 0);
                uint64_t bd = make_desc(sb + F_R2 + s * 32768, 4096, 512, 2);
                WG_FENCE();
#pragma unroll
                for (int k = 0; k < 4; k++) {
                    wgmma_ss_n128(ag, ad + k * 256, bd + k * 64, (kb | k) != 0);
                    wgmma_ss_n128(au, ad + k * 256, bd + 1024 + k * 64, (kb | k) != 0);
                }
                WG_COMMIT();
                if (kb > 0) {
                    wg_wait<1>();
                    if (lane == 0) { mbar_arrive(bars + 8 * (B_BE + (kb - 1) % 3)); mbar_arrive_remote(rbars + 8 * (B_BE + (kb - 1) % 3)); }
                }
            }
            wg_wait<0>();
            if (lane == 0) { mbar_arrive(bars + 8 * (B_BE + 7 % 3)); mbar_arrive_remote(rbars + 8 * (B_BE + 7 % 3)); }
            fence_regs(ag); fence_regs(au);
            TL(10);
            mbar_wait(bars + 8 * B_AUX, 0);
            ffn_epilogue<16, false>(ag, au, s_cs, 0, gp, 0, s_rs[rl], s_rs[rl + 8], lane);
            bar_arrive(1, 288);
        }
        {
            float ag[48], au[48];
#pragma unroll 1
            for (int kb = 0; kb < 8; kb++) {
                const int it = 8 + kb, s = it % 3;
                mbar_wait(bars + 8 * (B_BF + s), (it / 3) & 1);
                uint64_t ad = make_desc(sb + ((ntB + kb) & 7) * 16384 + wgi * 1024, 2048, 128, 0);
                uint64_t bd = make_desc(sb + F_R2 + s * 32768, 4096, 512, 2);
                WG_FENCE();
#pragma unroll
                for (int k = 0; k < 4; k++) {
                    wgmma_ss_n96(ag, ad + k * 256, bd + k * 64, (kb | k) != 0);
                    wgmma_ss_n96(au, ad + k * 256, bd + 1024 + k * 64, (kb | k) != 0);
                }
                WG_COMMIT();
                if (kb > 0) {
                    wg_wait<1>();
                    if (lane == 0 && it + 2 < 16) { mbar_arrive(bars + 8 * (B_BE + (it - 1) % 3)); mbar_arrive_remote(rbars + 8 * (B_BE + (it - 1) % 3)); }
                }
            }
            wg_wait<0>();
            if (lane == 0) {
                mbar_arrive(bars + 8 * B_BDONE);
                mbar_arrive_remote(rbars + 8 * B_PRDY);
            }
            fence_regs(ag); fence_regs(au);
            TL(11);
            ffn_epilogue<12, false>(ag, au, s_cs, 128, gp + 16 * 512, 0, s_rs[rl], s_rs[rl + 8], lane);
            bar_arrive(2, 288);
            TL(12);
        }
        {
            uint32_t hr[16];
#pragma unroll
            for (int j = 0; j < 8; j++) { hr[2 * j] = __ldcg(hp + j * 512); hr[2 * j + 1] = __ldcg(hp + j * 512 + 32); }
            mbar_wait(bars + 8 * (B_CF + 0), 0);
            const float a0 = h_row_stats(row).x, a1 = h_row_stats(row + 8).x;
            float acc[64];
#pragma unroll 1
            for (int kb = 0; kb < 14; kb++) {
                const int s = kb % 6;
                mbar_wait(bars + 8 * (B_CF + s), (kb / 6) & 1);
                if (warp == 4) TX(96 + kb);
                uint64_t ad = make_desc(sb + c_stage_a(s, ntB) + wgi * 1024, 2048, 128, 0);
                uint64_t bd = make_desc(sb + c_stage_b(s, ntB), 8192, 1024, 1);
                WG_FENCE();
#pragma unroll
                for (int k = 0; k < 4; k++) wgmma_ss_n128(acc, ad + k * 256, bd + k * 128, (kb | k) != 0);
                WG_COMMIT();
                if (kb > 0) {
                    wg_wait<1>();
                    if (lane == 0) mbar_arrive(bars + 8 * (B_CE + (kb - 1) % 6));
                }
            }
            wg_wait<0>();
            fence_regs(acc);
            TL(14);
            mbar_wait_cluster(bars + 8 * B_PRDY, 0);
            float o[32];
            if (r == 0) xchg<0>(acc, o, sb, smem, B_XC, ctid); else xchg<1>(acc, o, sb, smem, B_XC, ctid);
            TL(22);
            bar_sync(4, 256);
            const float k0 = 0.5f * a0 * a0, k1 = 0.5f * a1 * a1;
            const int srow = wgi * 64 + ww * 16 + ((lane >> 3) & 1) * 8 + (lane & 7);
#pragma unroll
            for (int j2 = 0; j2 < 4; j2++) {
                uint32_t u[4];
#pragma unroll
                for (int jj = 0; jj < 2; jj++) {
                    const int j = 2 * j2 + jj;
                    u[2 * jj] = pack_bf16(fmaf(k0, o[4 * j], bf_lo(hr[2 * j])), fmaf(k0, o[4 * j + 1], bf_hi(hr[2 * j])));
                    u[2 * jj + 1] = pack_bf16(fmaf(k1, o[4 * j + 2], bf_lo(hr[2 * j + 1])), fmaf(k1, o[4 * j + 3], bf_hi(hr[2 * j + 1])));
                }
                const int chunk = 2 * j2 + (lane >> 4);
                stsm4(sb + srow * 128 + ((chunk ^ (lane & 7)) * 16), u[0], u[1], u[2], u[3]);
            }
            fence_proxy_async();
            bar_arrive(3, 288);
            TLDUMP;
        }
    }
}

typedef CUresult (*EncodeFn)(CUtensorMap*, CUtensorMapDataType, cuuint32_t, void*, const cuuint64_t*, const cuuint64_t*,
                             const cuuint32_t*, const cuuint32_t*, CUtensorMapInterleave, CUtensorMapSwizzle,
                             CUtensorMapL2promotion, CUtensorMapFloatOOBfill);

void encode(EncodeFn fn, CUtensorMap* m, const void* ptr, int rank, const cuuint64_t* dims, const cuuint64_t* strides,
            const cuuint32_t* box, CUtensorMapSwizzle swz) {
    cuuint32_t es[3] = {1, 1, 1};
    fn(m, CU_TENSOR_MAP_DATA_TYPE_BFLOAT16, rank, (void*)ptr, dims, strides, box, es, CU_TENSOR_MAP_INTERLEAVE_NONE, swz,
       CU_TENSOR_MAP_L2_PROMOTION_L2_256B, CU_TENSOR_MAP_FLOAT_OOB_FILL_NONE);
}

template <typename... KArgs, typename... Args>
void launch(void (*kern)(KArgs...), int grid, int block, int smem, bool pdl, Args... args) {
    cudaLaunchConfig_t cfg = {};
    cfg.gridDim = dim3(grid); cfg.blockDim = dim3(block); cfg.dynamicSmemBytes = smem;
    cfg.stream = cudaStreamPerThread;
    cudaLaunchAttribute at[1];
    at[0].id = cudaLaunchAttributeProgrammaticStreamSerialization;
    at[0].val.programmaticStreamSerializationAllowed = 1;
    cfg.attrs = at; cfg.numAttrs = pdl ? 1 : 0;
    cudaLaunchKernelEx(&cfg, kern, KArgs(args)...);
}

}

extern "C" void kernel_launch(void* const* d_in, const int* in_sizes, int n_in, void* d_out, int out_size) {
    const __nv_bfloat16* x = (const __nv_bfloat16*)d_in[0];
    const __nv_bfloat16* wqkv = (const __nv_bfloat16*)d_in[1];
    const __nv_bfloat16* wo = (const __nv_bfloat16*)d_in[2];
    const __nv_bfloat16* wgate = (const __nv_bfloat16*)d_in[4];
    const __nv_bfloat16* wup = (const __nv_bfloat16*)d_in[5];
    const __nv_bfloat16* wdown = (const __nv_bfloat16*)d_in[6];
    __nv_bfloat16* out = (__nv_bfloat16*)d_out;

    static CUtensorMap tm_x, tm_wqkv, tm_wo, tm_wg, tm_wu, tm_wd, tm_out;
    static const void* cached[7] = {nullptr, nullptr, nullptr, nullptr, nullptr, nullptr, nullptr};
    if (cached[0] != x || cached[1] != wqkv || cached[2] != wo || cached[3] != wgate || cached[4] != wup || cached[5] != wdown || cached[6] != out) {
        void* fp = nullptr;
        cudaDriverEntryPointQueryResult qr;
        cudaGetDriverEntryPoint("cuTensorMapEncodeTiled", &fp, cudaEnableDefault, &qr);
        EncodeFn fn = (EncodeFn)fp;
        { cuuint64_t d[2] = {512, 2048}, s[1] = {1024}; cuuint32_t b[2] = {64, 128};
          encode(fn, &tm_x, x, 2, d, s, b, CU_TENSOR_MAP_SWIZZLE_128B);
          encode(fn, &tm_out, out, 2, d, s, b, CU_TENSOR_MAP_SWIZZLE_128B); }
        { cuuint64_t d[3] = {64, 512, 24}, s[2] = {3072, 128}; cuuint32_t b[3] = {64, 64, 3};
          encode(fn, &tm_wqkv, wqkv, 3, d, s, b, CU_TENSOR_MAP_SWIZZLE_128B); }
        { cuuint64_t d[2] = {512, 512}, s[1] = {1024}; cuuint32_t b[2] = {64, 64};
          encode(fn, &tm_wo, wo, 2, d, s, b, CU_TENSOR_MAP_SWIZZLE_128B); }
        { cuuint64_t d[2] = {1792, 512}, s[1] = {3584}; cuuint32_t b[2] = {32, 64};
          encode(fn, &tm_wg, wgate, 2, d, s, b, CU_TENSOR_MAP_SWIZZLE_64B);
          encode(fn, &tm_wu, wup, 2, d, s, b, CU_TENSOR_MAP_SWIZZLE_64B); }
        { cuuint64_t d[2] = {512, 1792}, s[1] = {1024}; cuuint32_t b[2] = {64, 64};
          encode(fn, &tm_wd, wdown, 2, d, s, b, CU_TENSOR_MAP_SWIZZLE_128B); }
        cudaFuncSetAttribute(qkv_kernel, cudaFuncAttributeMaxDynamicSharedMemorySize, F_SMEM);
        cudaFuncSetAttribute(qkv_kernel, cudaFuncAttributePreferredSharedMemoryCarveout, 100);
        cudaFuncSetAttribute(attn_kernel, cudaFuncAttributeMaxDynamicSharedMemorySize, F_SMEM);
        cudaFuncSetAttribute(attn_kernel, cudaFuncAttributePreferredSharedMemoryCarveout, 100);
        cudaFuncSetAttribute(tail_kernel, cudaFuncAttributeMaxDynamicSharedMemorySize, F_SMEM);
        cudaFuncSetAttribute(tail_kernel, cudaFuncAttributePreferredSharedMemoryCarveout, 100);
        cached[0] = x; cached[1] = wqkv; cached[2] = wo; cached[3] = wgate; cached[4] = wup; cached[5] = wdown; cached[6] = out;
    }
    launch(qkv_kernel, 128, 384, F_SMEM, false, tm_x, tm_wqkv, x, wqkv);
    launch(attn_kernel, 132, 512, F_SMEM, true, wgate, wup, wo, wdown);
    launch(tail_kernel, 128, 384, F_SMEM, true, tm_wo, tm_wg, tm_wu, tm_wd, tm_out, x);
}
```

```cpp
#include <cuda_runtime.h>
#include <cuda_bf16.h>
#include <cuda.h>
#include <stdint.h>

#define K1_DIRECT
namespace {

constexpr int S_LEN = 2048, DM = 512, NH = 32, FF = 1792;

__device__ __align__(1024) __nv_bfloat16 g_qkv[3 * NH * S_LEN * 16];
__device__ __align__(1024) __nv_bfloat16 g_ao[S_LEN * DM];
__device__ __align__(1024) __nv_bfloat16 g_h[S_LEN * DM];
__device__ __align__(1024) __nv_bfloat16 g_g[S_LEN * FF];
__device__ __align__(16) float2 g_rowstat1[S_LEN];
__device__ float g_cs1_part[16 * 1536];
__device__ unsigned int g_cnt[32];
__device__ unsigned int g_cnt2[160];
__device__ float g_nrm[3 * NH * 128];
__device__ float2 g_hstat[S_LEN * 8];
__device__ float g_cs2[2 * FF];

#define TLDECL
#define TL(slot)
#define TLDUMP
#define TX(slot)
__device__ __forceinline__ uint32_t smem_u32(const void* p) { return (uint32_t)__cvta_generic_to_shared(p); }
__device__ __forceinline__ void mbar_init(uint32_t a, int c) { asm volatile("mbarrier.init.shared.b64 [%0], %1;" :: "r"(a), "r"(c)); }
__device__ __forceinline__ void mbar_expect(uint32_t a, int bytes) { asm volatile("mbarrier.arrive.expect_tx.shared.b64 _, [%0], %1;" :: "r"(a), "r"(bytes) : "memory"); }
__device__ __forceinline__ void mbar_arrive(uint32_t a) { asm volatile("mbarrier.arrive.shared.b64 _, [%0];" :: "r"(a) : "memory"); }
__device__ __forceinline__ void mbar_wait(uint32_t a, int parity) {
    uint32_t done;
    int it = 0;
    do {
        asm volatile("{\n.reg .pred p;\nmbarrier.try_wait.parity.shared.b64 p, [%1], %2;\nselp.u32 %0, 1, 0, p;\n}"
                     : "=r"(done) : "r"(a), "r"(parity) : "memory");
        if (++it > (1 << 24)) __trap();
    } while (!done);
}
__device__ __forceinline__ void bulk_g2s(uint32_t dst, const void* src, int bytes, uint32_t bar) {
    asm volatile("cp.async.bulk.shared::cluster.global.mbarrier::complete_tx::bytes [%0], [%1], %2, [%3];"
                 :: "r"(dst), "l"(src), "r"(bytes), "r"(bar) : "memory");
}
__device__ __forceinline__ void tma2d(uint32_t dst, const CUtensorMap* m, int c0, int c1, uint32_t bar) {
    asm volatile("cp.async.bulk.tensor.2d.shared::cluster.global.mbarrier::complete_tx::bytes [%0], [%1, {%3, %4}], [%2];"
                 :: "r"(dst), "l"(m), "r"(bar), "r"(c0), "r"(c1) : "memory");
}
__device__ __forceinline__ void tma3d(uint32_t dst, const CUtensorMap* m, int c0, int c1, int c2, uint32_t bar) {
    asm volatile("cp.async.bulk.tensor.3d.shared::cluster.global.mbarrier::complete_tx::bytes [%0], [%1, {%3, %4, %5}], [%2];"
                 :: "r"(dst), "l"(m), "r"(bar), "r"(c0), "r"(c1), "r"(c2) : "memory");
}
__device__ __forceinline__ void prefetch_tmap(const CUtensorMap* m) { asm volatile("prefetch.tensormap [%0];" :: "l"(m) : "memory"); }
__device__ __forceinline__ void pdl_wait() { asm volatile("griddepcontrol.wait;" ::: "memory"); }
__device__ __forceinline__ void pdl_launch() { asm volatile("griddepcontrol.launch_dependents;" ::: "memory"); }
__device__ __forceinline__ void fence_barrier_init() { asm volatile("fence.mbarrier_init.release.cluster;" ::: "memory"); }
__device__ __forceinline__ void fence_proxy_async() { asm volatile("fence.proxy.async.shared::cta;" ::: "memory"); }
__device__ __forceinline__ uint64_t make_desc(uint32_t saddr, uint32_t lbo, uint32_t sbo, uint32_t swz) {
    return (uint64_t)((saddr & 0x3FFFF) >> 4) | ((uint64_t)((lbo & 0x3FFFF) >> 4) << 16) |
           ((uint64_t)((sbo & 0x3FFFF) >> 4) << 32) | ((uint64_t)swz << 62);
}
#define WG_FENCE() asm volatile("wgmma.fence.sync.aligned;" ::: "memory")
#define WG_COMMIT() asm volatile("wgmma.commit_group.sync.aligned;" ::: "memory")
template <int N> __device__ __forceinline__ void wg_wait() { asm volatile("wgmma.wait_group.sync.aligned %0;" :: "n"(N) : "memory"); }
template <int N> __device__ __forceinline__ void fence_regs(float (&d)[N]) {
#pragma unroll
    for (int i = 0; i < N; i++) asm volatile("" : "+f"(d[i]) :: "memory");
}
__device__ __forceinline__ float ex2f(float x) { float y; asm("ex2.approx.ftz.f32 %0, %1;" : "=f"(y) : "f"(x)); return y; }
__device__ __forceinline__ float tanh_fast(float x) { float y; asm("tanh.approx.f32 %0, %1;" : "=f"(y) : "f"(x)); return y; }
__device__ __forceinline__ uint32_t pack_bf16(float lo, float hi) { uint32_t r; asm("cvt.rn.bf16x2.f32 %0, %1, %2;" : "=r"(r) : "f"(hi), "f"(lo)); return r; }
__device__ __forceinline__ float bf_lo(uint32_t u) { return __uint_as_float(u << 16); }
__device__ __forceinline__ float bf_hi(uint32_t u) { return __uint_as_float(u & 0xFFFF0000u); }
__device__ __forceinline__ uint32_t hfma2(uint32_t a, uint32_t b, uint32_t c) { uint32_t r; asm("fma.rn.f16x2 %0, %1, %2, %3;" : "=r"(r) : "r"(a), "r"(b), "r"(c)); return r; }
__device__ __forceinline__ uint32_t hmul2(uint32_t a, uint32_t b) { uint32_t r; asm("mul.rn.f16x2 %0, %1, %2;" : "=r"(r) : "r"(a), "r"(b)); return r; }
__device__ __forceinline__ unsigned int ld_acquire(const unsigned int* p) { unsigned int v; asm volatile("ld.acquire.gpu.u32 %0, [%1];" : "=r"(v) : "l"(p) : "memory"); return v; }
__device__ __forceinline__ void red_release(unsigned int* p) { asm volatile("red.release.gpu.global.add.u32 [%0], 1;" :: "l"(p) : "memory"); }
__device__ __forceinline__ void stsm4(uint32_t addr, uint32_t a, uint32_t b, uint32_t c, uint32_t d) {
    asm volatile("stmatrix.sync.aligned.m8n8.x4.shared.b16 [%0], {%1,%2,%3,%4};" :: "r"(addr), "r"(a), "r"(b), "r"(c), "r"(d) : "memory");
}
__device__ __forceinline__ void bulk_s2g(void* dst, uint32_t src, int bytes) {
    asm volatile("cp.async.bulk.global.shared::cta.bulk_group [%0], [%1], %2;" :: "l"(dst), "r"(src), "r"(bytes) : "memory");
}
__device__ __forceinline__ void bulk_commit() { asm volatile("cp.async.bulk.commit_group;" ::: "memory"); }
__device__ __forceinline__ void bulk_wait_all() { asm volatile("cp.async.bulk.wait_group 0;" ::: "memory"); }
__device__ __forceinline__ void bulk_wait_read() { asm volatile("cp.async.bulk.wait_group.read 0;" ::: "memory"); }
__device__ __forceinline__ void bar_sync(int id, int n) { asm volatile("bar.sync %0, %1;" :: "r"(id), "r"(n) : "memory"); }
__device__ __forceinline__ void bar_arrive(int id, int n) { asm volatile("bar.arrive %0, %1;" :: "r"(id), "r"(n) : "memory"); }
__device__ __forceinline__ float warp_sum(float v) {
#pragma unroll
    for (int o = 16; o; o >>= 1) v += __shfl_xor_sync(0xffffffffu, v, o);
    return v;
}
__device__ __forceinline__ float warp_max(float v) {
#pragma unroll
    for (int o = 16; o; o >>= 1) v = fmaxf(v, __shfl_xor_sync(0xffffffffu, v, o));
    return v;
}

__device__ __forceinline__ void wgmma_ss_n64(float (&d)[32], uint64_t adesc, uint64_t bdesc, int scale_d) {
    asm volatile("{\n.reg .pred p;\nsetp.ne.b32 p, %34, 0;\n"
      "wgmma.mma_async.sync.aligned.m64n64k16.f32.bf16.bf16 {%0,%1,%2,%3,%4,%5,%6,%7,%8,%9,%10,%11,%12,%13,%14,%15,%16,%17,%18,%19,%20,%21,%22,%23,%24,%25,%26,%27,%28,%29,%30,%31}, %32, %33, p, 1, 1, 0, 1;\n}"
      : "+f"(d[0]), "+f"(d[1]), "+f"(d[2]), "+f"(d[3]), "+f"(d[4]), "+f"(d[5]), "+f"(d[6]), "+f"(d[7]), "+f"(d[8]), "+f"(d[9]), "+f"(d[10]), "+f"(d[11]), "+f"(d[12]), "+f"(d[13]), "+f"(d[14]), "+f"(d[15]), "+f"(d[16]), "+f"(d[17]), "+f"(d[18]), "+f"(d[19]), "+f"(d[20]), "+f"(d[21]), "+f"(d[22]), "+f"(d[23]), "+f"(d[24]), "+f"(d[25]), "+f"(d[26]), "+f"(d[27]), "+f"(d[28]), "+f"(d[29]), "+f"(d[30]), "+f"(d[31])
      : "l"(adesc), "l"(bdesc), "r"(scale_d));
}
__device__ __forceinline__ void wgmma_ss_n128(float (&d)[64], uint64_t adesc, uint64_t bdesc, int scale_d) {
    asm volatile("{\n.reg .pred p;\nsetp.ne.b32 p, %66, 0;\n"
      "wgmma.mma_async.sync.aligned.m64n128k16.f32.bf16.bf16 {%0,%1,%2,%3,%4,%5,%6,%7,%8,%9,%10,%11,%12,%13,%14,%15,%16,%17,%18,%19,%20,%21,%22,%23,%24,%25,%26,%27,%28,%29,%30,%31,%32,%33,%34,%35,%36,%37,%38,%39,%40,%41,%42,%43,%44,%45,%46,%47,%48,%49,%50,%51,%52,%53,%54,%55,%56,%57,%58,%59,%60,%61,%62,%63}, %64, %65, p, 1, 1, 0, 1;\n}"
      : "+f"(d[0]), "+f"(d[1]), "+f"(d[2]), "+f"(d[3]), "+f"(d[4]), "+f"(d[5]), "+f"(d[6]), "+f"(d[7]), "+f"(d[8]), "+f"(d[9]), "+f"(d[10]), "+f"(d[11]), "+f"(d[12]), "+f"(d[13]), "+f"(d[14]), "+f"(d[15]), "+f"(d[16]), "+f"(d[17]), "+f"(d[18]), "+f"(d[19]), "+f"(d[20]), "+f"(d[21]), "+f"(d[22]), "+f"(d[23]), "+f"(d[24]), "+f"(d[25]), "+f"(d[26]), "+f"(d[27]), "+f"(d[28]), "+f"(d[29]), "+f"(d[30]), "+f"(d[31]), "+f"(d[32]), "+f"(d[33]), "+f"(d[34]), "+f"(d[35]), "+f"(d[36]), "+f"(d[37]), "+f"(d[38]), "+f"(d[39]), "+f"(d[40]), "+f"(d[41]), "+f"(d[42]), "+f"(d[43]), "+f"(d[44]), "+f"(d[45]), "+f"(d[46]), "+f"(d[47]), "+f"(d[48]), "+f"(d[49]), "+f"(d[50]), "+f"(d[51]), "+f"(d[52]), "+f"(d[53]), "+f"(d[54]), "+f"(d[55]), "+f"(d[56]), "+f"(d[57]), "+f"(d[58]), "+f"(d[59]), "+f"(d[60]), "+f"(d[61]), "+f"(d[62]), "+f"(d[63])
      : "l"(adesc), "l"(bdesc), "r"(scale_d));
}
__device__ __forceinline__ void wgmma_ss_n192(float (&d)[96], uint64_t adesc, uint64_t bdesc, int scale_d) {
    asm volatile("{\n.reg .pred p;\nsetp.ne.b32 p, %98, 0;\n"
      "wgmma.mma_async.sync.aligned.m64n192k16.f32.bf16.bf16 {%0,%1,%2,%3,%4,%5,%6,%7,%8,%9,%10,%11,%12,%13,%14,%15,%16,%17,%18,%19,%20,%21,%22,%23,%24,%25,%26,%27,%28,%29,%30,%31,%32,%33,%34,%35,%36,%37,%38,%39,%40,%41,%42,%43,%44,%45,%46,%47,%48,%49,%50,%51,%52,%53,%54,%55,%56,%57,%58,%59,%60,%61,%62,%63,%64,%65,%66,%67,%68,%69,%70,%71,%72,%73,%74,%75,%76,%77,%78,%79,%80,%81,%82,%83,%84,%85,%86,%87,%88,%89,%90,%91,%92,%93,%94,%95}, %96, %97, p, 1, 1, 0, 1;\n}"
      : "+f"(d[0]), "+f"(d[1]), "+f"(d[2]), "+f"(d[3]), "+f"(d[4]), "+f"(d[5]), "+f"(d[6]), "+f"(d[7]), "+f"(d[8]), "+f"(d[9]), "+f"(d[10]), "+f"(d[11]), "+f"(d[12]), "+f"(d[13]), "+f"(d[14]), "+f"(d[15]), "+f"(d[16]), "+f"(d[17]), "+f"(d[18]), "+f"(d[19]), "+f"(d[20]), "+f"(d[21]), "+f"(d[22]), "+f"(d[23]), "+f"(d[24]), "+f"(d[25]), "+f"(d[26]), "+f"(d[27]), "+f"(d[28]), "+f"(d[29]), "+f"(d[30]), "+f"(d[31]), "+f"(d[32]), "+f"(d[33]), "+f"(d[34]), "+f"(d[35]), "+f"(d[36]), "+f"(d[37]), "+f"(d[38]), "+f"(d[39]), "+f"(d[40]), "+f"(d[41]), "+f"(d[42]), "+f"(d[43]), "+f"(d[44]), "+f"(d[45]), "+f"(d[46]), "+f"(d[47]), "+f"(d[48]), "+f"(d[49]), "+f"(d[50]), "+f"(d[51]), "+f"(d[52]), "+f"(d[53]), "+f"(d[54]), "+f"(d[55]), "+f"(d[56]), "+f"(d[57]), "+f"(d[58]), "+f"(d[59]), "+f"(d[60]), "+f"(d[61]), "+f"(d[62]), "+f"(d[63]), "+f"(d[64]), "+f"(d[65]), "+f"(d[66]), "+f"(d[67]), "+f"(d[68]), "+f"(d[69]), "+f"(d[70]), "+f"(d[71]), "+f"(d[72]), "+f"(d[73]), "+f"(d[74]), "+f"(d[75]), "+f"(d[76]), "+f"(d[77]), "+f"(d[78]), "+f"(d[79]), "+f"(d[80]), "+f"(d[81]), "+f"(d[82]), "+f"(d[83]), "+f"(d[84]), "+f"(d[85]), "+f"(d[86]), "+f"(d[87]), "+f"(d[88]), "+f"(d[89]), "+f"(d[90]), "+f"(d[91]), "+f"(d[92]), "+f"(d[93]), "+f"(d[94]), "+f"(d[95])
      : "l"(adesc), "l"(bdesc), "r"(scale_d));
}
__device__ __forceinline__ void wgmma_ss_n256(float (&d)[128], uint64_t adesc, uint64_t bdesc, int scale_d) {
    asm volatile("{\n.reg .pred p;\nsetp.ne.b32 p, %130, 0;\n"
      "wgmma.mma_async.sync.aligned.m64n256k16.f32.bf16.bf16 {%0,%1,%2,%3,%4,%5,%6,%7,%8,%9,%10,%11,%12,%13,%14,%15,%16,%17,%18,%19,%20,%21,%22,%23,%24,%25,%26,%27,%28,%29,%30,%31,%32,%33,%34,%35,%36,%37,%38,%39,%40,%41,%42,%43,%44,%45,%46,%47,%48,%49,%50,%51,%52,%53,%54,%55,%56,%57,%58,%59,%60,%61,%62,%63,%64,%65,%66,%67,%68,%69,%70,%71,%72,%73,%74,%75,%76,%77,%78,%79,%80,%81,%82,%83,%84,%85,%86,%87,%88,%89,%90,%91,%92,%93,%94,%95,%96,%97,%98,%99,%100,%101,%102,%103,%104,%105,%106,%107,%108,%109,%110,%111,%112,%113,%114,%115,%116,%117,%118,%119,%120,%121,%122,%123,%124,%125,%126,%127}, %128, %129, p, 1, 1, 0, 1;\n}"
      : "+f"(d[0]), "+f"(d[1]), "+f"(d[2]), "+f"(d[3]), "+f"(d[4]), "+f"(d[5]), "+f"(d[6]), "+f"(d[7]), "+f"(d[8]), "+f"(d[9]), "+f"(d[10]), "+f"(d[11]), "+f"(d[12]), "+f"(d[13]), "+f"(d[14]), "+f"(d[15]), "+f"(d[16]), "+f"(d[17]), "+f"(d[18]), "+f"(d[19]), "+f"(d[20]), "+f"(d[21]), "+f"(d[22]), "+f"(d[23]), "+f"(d[24]), "+f"(d[25]), "+f"(d[26]), "+f"(d[27]), "+f"(d[28]), "+f"(d[29]), "+f"(d[30]), "+f"(d[31]), "+f"(d[32]), "+f"(d[33]), "+f"(d[34]), "+f"(d[35]), "+f"(d[36]), "+f"(d[37]), "+f"(d[38]), "+f"(d[39]), "+f"(d[40]), "+f"(d[41]), "+f"(d[42]), "+f"(d[43]), "+f"(d[44]), "+f"(d[45]), "+f"(d[46]), "+f"(d[47]), "+f"(d[48]), "+f"(d[49]), "+f"(d[50]), "+f"(d[51]), "+f"(d[52]), "+f"(d[53]), "+f"(d[54]), "+f"(d[55]), "+f"(d[56]), "+f"(d[57]), "+f"(d[58]), "+f"(d[59]), "+f"(d[60]), "+f"(d[61]), "+f"(d[62]), "+f"(d[63]), "+f"(d[64]), "+f"(d[65]), "+f"(d[66]), "+f"(d[67]), "+f"(d[68]), "+f"(d[69]), "+f"(d[70]), "+f"(d[71]), "+f"(d[72]), "+f"(d[73]), "+f"(d[74]), "+f"(d[75]), "+f"(d[76]), "+f"(d[77]), "+f"(d[78]), "+f"(d[79]), "+f"(d[80]), "+f"(d[81]), "+f"(d[82]), "+f"(d[83]), "+f"(d[84]), "+f"(d[85]), "+f"(d[86]), "+f"(d[87]), "+f"(d[88]), "+f"(d[89]), "+f"(d[90]), "+f"(d[91]), "+f"(d[92]), "+f"(d[93]), "+f"(d[94]), "+f"(d[95]), "+f"(d[96]), "+f"(d[97]), "+f"(d[98]), "+f"(d[99]), "+f"(d[100]), "+f"(d[101]), "+f"(d[102]), "+f"(d[103]), "+f"(d[104]), "+f"(d[105]), "+f"(d[106]), "+f"(d[107]), "+f"(d[108]), "+f"(d[109]), "+f"(d[110]), "+f"(d[111]), "+f"(d[112]), "+f"(d[113]), "+f"(d[114]), "+f"(d[115]), "+f"(d[116]), "+f"(d[117]), "+f"(d[118]), "+f"(d[119]), "+f"(d[120]), "+f"(d[121]), "+f"(d[122]), "+f"(d[123]), "+f"(d[124]), "+f"(d[125]), "+f"(d[126]), "+f"(d[127])
      : "l"(adesc), "l"(bdesc), "r"(scale_d));
}
__device__ __forceinline__ void qk_wgmma_n64(float (&d)[32], const uint32_t (&a)[4], uint64_t desc) {
    asm volatile("wgmma.mma_async.sync.aligned.m64n64k16.f32.bf16.bf16 {%0,%1,%2,%3,%4,%5,%6,%7,%8,%9,%10,%11,%12,%13,%14,%15,%16,%17,%18,%19,%20,%21,%22,%23,%24,%25,%26,%27,%28,%29,%30,%31}, {%32,%33,%34,%35}, %36, 0, 1, 1, 0;"
      : "=f"(d[0]), "=f"(d[1]), "=f"(d[2]), "=f"(d[3]), "=f"(d[4]), "=f"(d[5]), "=f"(d[6]), "=f"(d[7]), "=f"(d[8]), "=f"(d[9]), "=f"(d[10]), "=f"(d[11]), "=f"(d[12]), "=f"(d[13]), "=f"(d[14]), "=f"(d[15]), "=f"(d[16]), "=f"(d[17]), "=f"(d[18]), "=f"(d[19]), "=f"(d[20]), "=f"(d[21]), "=f"(d[22]), "=f"(d[23]), "=f"(d[24]), "=f"(d[25]), "=f"(d[26]), "=f"(d[27]), "=f"(d[28]), "=f"(d[29]), "=f"(d[30]), "=f"(d[31])
      : "r"(a[0]), "r"(a[1]), "r"(a[2]), "r"(a[3]), "l"(desc));
}

__device__ __forceinline__ void pv_wgmma(float (&d)[12], uint32_t a0, uint32_t a1, uint32_t a2, uint32_t a3, uint64_t desc) {
    asm volatile("wgmma.mma_async.sync.aligned.m64n24k16.f32.bf16.bf16 {%0,%1,%2,%3,%4,%5,%6,%7,%8,%9,%10,%11}, {%12,%13,%14,%15}, %16, 1, 1, 1, 1;"
      : "+f"(d[0]), "+f"(d[1]), "+f"(d[2]), "+f"(d[3]), "+f"(d[4]), "+f"(d[5]), "+f"(d[6]), "+f"(d[7]), "+f"(d[8]), "+f"(d[9]), "+f"(d[10]), "+f"(d[11])
      : "r"(a0), "r"(a1), "r"(a2), "r"(a3), "l"(desc));
}

__device__ __forceinline__ uint32_t mapa(uint32_t a, uint32_t rank) { uint32_t r; asm("mapa.shared::cluster.u32 %0, %1, %2;" : "=r"(r) : "r"(a), "r"(rank)); return r; }
__device__ __forceinline__ void mbar_arrive_remote(uint32_t a) { asm volatile("mbarrier.arrive.relaxed.cluster.shared::cluster.b64 _, [%0];" :: "r"(a) : "memory"); }
__device__ __forceinline__ void mbar_wait_cluster(uint32_t a, int parity) {
    uint32_t done;
    int it = 0;
    do {
        asm volatile("{\n.reg .pred p;\nmbarrier.try_wait.parity.acquire.cluster.shared::cta.b64 p, [%1], %2;\nselp.u32 %0, 1, 0, p;\n}"
                     : "=r"(done) : "r"(a), "r"(parity) : "memory");
        if (++it > (1 << 24)) __trap();
    } while (!done);
}
__device__ __forceinline__ void tma2d_mc(uint32_t dst, const CUtensorMap* m, int c0, int c1, uint32_t bar) {
    asm volatile("cp.async.bulk.tensor.2d.shared::cluster.global.mbarrier::complete_tx::bytes.multicast::cluster [%0], [%1, {%3, %4}], [%2], %5;"
                 :: "r"(dst), "l"(m), "r"(bar), "r"(c0), "r"(c1), "h"((uint16_t)3) : "memory");
}
__device__ __forceinline__ void bulk_g2s_mc(uint32_t dst, const void* src, int bytes, uint32_t bar) {
    asm volatile("cp.async.bulk.shared::cluster.global.mbarrier::complete_tx::bytes.multicast::cluster [%0], [%1], %2, [%3], %4;"
                 :: "r"(dst), "l"(src), "r"(bytes), "r"(bar), "h"((uint16_t)3) : "memory");
}
__device__ __forceinline__ void tile_of(int bid, int& mb, int& nt) {
    int grp = bid >> 4, in = bid & 15;
    mb = (grp >> 1) * 4 + (in >> 2);
    nt = (grp & 1) * 4 + (in & 3);
}

constexpr int K1_STAGES = 5, K1_STAGE = 16384 + 24576;
constexpr int K1_BAR = K1_STAGES * K1_STAGE, K1_RS = K1_BAR + 128, K1_CS = K1_RS + 1024, K1_SMEM = K1_CS + 768;

__device__ __forceinline__ float2 row_stats_regs(uint4 a, uint4 b) {
    float v[16];
    v[0] = bf_lo(a.x); v[1] = bf_hi(a.x); v[2] = bf_lo(a.y); v[3] = bf_hi(a.y);
    v[4] = bf_lo(a.z); v[5] = bf_hi(a.z); v[6] = bf_lo(a.w); v[7] = bf_hi(a.w);
    v[8] = bf_lo(b.x); v[9] = bf_hi(b.x); v[10] = bf_lo(b.y); v[11] = bf_hi(b.y);
    v[12] = bf_lo(b.z); v[13] = bf_hi(b.z); v[14] = bf_lo(b.w); v[15] = bf_hi(b.w);
    float s = 0.f;
#pragma unroll
    for (int i = 0; i < 16; i++) s += v[i];
    float mean = warp_sum(s) * (1.0f / DM);
    float q = 0.f;
#pragma unroll
    for (int i = 0; i < 16; i++) { float d = v[i] - mean; q = fmaf(d, d, q); }
    float var = warp_sum(q) * (1.0f / DM);
    float rstd = rsqrtf(var + 1e-5f);
    return make_float2(rstd, -mean * rstd);
}
__device__ __forceinline__ float2 row_stats_x(const __nv_bfloat16* x, int row, int lane) {
    const uint4* p = (const uint4*)(x + (size_t)row * DM);
    return row_stats_regs(__ldg(p + lane), __ldg(p + 32 + lane));
}
__device__ __forceinline__ void colsum8(const __nv_bfloat16* w, int ld, int col, int k0, int nk, float (&s)[8]) {
#pragma unroll
    for (int i = 0; i < 8; i++) s[i] = 0.f;
    for (int k = k0; k < k0 + nk; k += 8) {
        uint4 u[8];
#pragma unroll
        for (int i = 0; i < 8; i++) u[i] = __ldg((const uint4*)(w + (size_t)(k + i) * ld + col));
#pragma unroll
        for (int i = 0; i < 8; i++) {
            s[0] += bf_lo(u[i].x); s[1] += bf_hi(u[i].x); s[2] += bf_lo(u[i].y); s[3] += bf_hi(u[i].y);
            s[4] += bf_lo(u[i].z); s[5] += bf_hi(u[i].z); s[6] += bf_lo(u[i].w); s[7] += bf_hi(u[i].w);
        }
    }
}
__device__ __forceinline__ bool wait_count(const unsigned int* p, unsigned int target, int lane) {
    int ok = 1;
    if (lane == 0) {
        int it = 0;
        while (ld_acquire(p) < target) { if (++it > (1 << 18)) { ok = 0; break; } }
    }
    ok = __shfl_sync(0xffffffffu, ok, 0);
    return ok != 0;
}

__global__ void __launch_bounds__(384, 1)
qkv_kernel(const __grid_constant__ CUtensorMap tm_x, const __grid_constant__ CUtensorMap tm_w,
           const __nv_bfloat16* __restrict__ x, const __nv_bfloat16* __restrict__ wqkv) {
    extern __shared__ __align__(1024) unsigned char smem[];
    const uint32_t sb = smem_u32(smem);
    const int tid = threadIdx.x, warp = __shfl_sync(0xffffffffu, tid >> 5, 0), lane = tid & 31;
    TLDECL
    TL(0);
    int mb, nt;
    tile_of(blockIdx.x, mb, nt);
    const uint32_t full = sb + K1_BAR, empty = full + 40, auxb = full + 80;
    if (tid == 0) {
        prefetch_tmap(&tm_x); prefetch_tmap(&tm_w);
        for (int i = 0; i < K1_STAGES; i++) { mbar_init(full + 8 * i, 1); mbar_init(empty + 8 * i, 8); }
        mbar_init(auxb, 3);
        fence_barrier_init();
    }
    __syncthreads();
    pdl_launch();
    if (warp == 0) {
        if (blockIdx.x == 0) for (int i = lane; i < 160; i += 32) g_cnt2[i] = 0;
        if (lane == 0) {
            for (int kb = 0; kb < 8; kb++) {
                int s = kb % K1_STAGES;
                if (kb >= K1_STAGES) mbar_wait(empty + 8 * s, 0);
                mbar_expect(full + 8 * s, K1_STAGE);
                tma2d(sb + s * K1_STAGE, &tm_x, kb * 64, mb * 128, full + 8 * s);
                tma3d(sb + s * K1_STAGE + 16384, &tm_w, 0, kb * 64, nt * 3, full + 8 * s);
            }
        }
    } else if (warp < 4) {
        float2* s_rs = (float2*)(smem + K1_RS);
        float* s_cs = (float*)(smem + K1_CS);
        if (warp < 3) {
            const int r0 = mb * 128 + nt * 16 + (warp - 1) * 8;
            uint4 u[16];
#pragma unroll
            for (int i = 0; i < 8; i++) {
                const uint4* p = (const uint4*)(x + (size_t)(r0 + i) * DM);
                u[2 * i] = __ldg(p + lane); u[2 * i + 1] = __ldg(p + 32 + lane);
            }
            float2 mine = make_float2(0.f, 0.f);
#pragma unroll
            for (int i = 0; i < 8; i++) {
                float2 st = row_stats_regs(u[2 * i], u[2 * i + 1]);
                if (lane == i) mine = st;
            }
            if (lane < 8) g_rowstat1[r0 + lane] = mine;
            __syncwarp();
            if (lane == 0) red_release(&g_cnt[mb]);
        } else {
            uint4 u[24];
#pragma unroll
            for (int c = 0; c < 3; c++)
#pragma unroll
                for (int i = 0; i < 8; i++)
                    u[c * 8 + i] = __ldg((const uint4*)(wqkv + (size_t)(mb * 32 + (lane >> 3) * 8 + i) * 1536 + nt * 192 + (c * 8 + (lane & 7)) * 8));
#pragma unroll
            for (int c = 0; c < 3; c++) {
                float cs[8];
#pragma unroll
                for (int i = 0; i < 8; i++) cs[i] = 0.f;
#pragma unroll
                for (int i = 0; i < 8; i++) {
                    const uint4 w = u[c * 8 + i];
                    cs[0] += bf_lo(w.x); cs[1] += bf_hi(w.x); cs[2] += bf_lo(w.y); cs[3] += bf_hi(w.y);
                    cs[4] += bf_lo(w.z); cs[5] += bf_hi(w.z); cs[6] += bf_lo(w.w); cs[7] += bf_hi(w.w);
                }
#pragma unroll
                for (int i = 0; i < 8; i++) {
                    cs[i] += __shfl_xor_sync(0xffffffffu, cs[i], 8);
                    cs[i] += __shfl_xor_sync(0xffffffffu, cs[i], 16);
                }
                if (lane < 8) {
                    float4* d = (float4*)(g_cs1_part + mb * 1536 + nt * 192 + (c * 8 + lane) * 8);
                    d[0] = make_float4(cs[0], cs[1], cs[2], cs[3]);
                    d[1] = make_float4(cs[4], cs[5], cs[6], cs[7]);
                }
            }
            __syncwarp();
            if (lane == 0) red_release(&g_cnt[16 + nt]);
        }
        TX(8 + warp);
        if (warp == 1) {
            if (wait_count(&g_cnt[mb], 16, lane)) {
#pragma unroll
                for (int i = 0; i < 4; i++) s_rs[lane + 32 * i] = __ldcg(&g_rowstat1[mb * 128 + lane + 32 * i]);
            } else {
                for (int i = 0; i < 128; i++) {
                    float2 st = row_stats_x(x, mb * 128 + i, lane);
                    if (lane == 0) s_rs[i] = st;
                }
            }
        } else {
            int c0 = (warp - 2) * 96;
            if (wait_count(&g_cnt[16 + nt], 16, lane)) {
#pragma unroll
                for (int i = 0; i < 3; i++) {
                    float s = 0.f;
#pragma unroll
                    for (int p = 0; p < 16; p++) s += __ldcg(&g_cs1_part[p * 1536 + nt * 192 + c0 + lane + 32 * i]);
                    s_cs[c0 + lane + 32 * i] = s;
                }
            } else if (lane < 12) {
                float s[8];
                colsum8(wqkv, 1536, nt * 192 + c0 + lane * 8, 0, 512, s);
#pragma unroll
                for (int i = 0; i < 8; i++) s_cs[c0 + lane * 8 + i] = s[i];
            }
        }
        __syncwarp();
        TX(12 + warp);
        if (lane == 0) mbar_arrive(auxb);
        bar_sync(2, 256 + 96);
        const int a = tid - 32;
        {
            const int hh = a >> 3, w = a & 7;
            const float4* p = (const float4*)(smem + 49152) + (hh * 256 + w * 32) / 2;
            float m = 0.f;
#pragma unroll
            for (int i = 0; i < 8; i++) {
                const int ii = (i + a) & 7;
                float4 u = p[2 * ii], v = p[2 * ii + 1];
                float n0 = u.x + u.z + v.x + v.z, n1 = u.y + u.w + v.y + v.w;
                if (!(n0 <= 3.0e38f) || !(n1 <= 3.0e38f)) m = __int_as_float(0x7f800000);
                m = fmaxf(m, fmaxf(n0, n1));
            }
            const int col0 = nt * 192 + hh * 16;
            g_nrm[((col0 >> 9) * NH + ((col0 & 511) >> 4)) * 128 + mb * 8 + w] = m;
        }
        if (a < 24) bulk_wait_all();
        TL(27);
        TLDUMP;
    } else {
        const int wgi = (warp >> 2) - 1, ww = warp & 3;
        float acc[96];
#pragma unroll 1
        for (int kb = 0; kb < 8; kb++) {
            int s = kb % K1_STAGES;
            mbar_wait(full + 8 * s, (kb / K1_STAGES) & 1);
            if (warp == 4) TX(kb);
            uint64_t ad = make_desc(sb + s * K1_STAGE + wgi * 8192, 16, 1024, 1);
            uint64_t bd = make_desc(sb + s * K1_STAGE + 16384, 8192, 1024, 1);
            WG_FENCE();
#pragma unroll
            for (int k = 0; k < 4; k++) wgmma_ss_n192(acc, ad + k * 2, bd + k * 128, (kb | k) != 0);
            WG_COMMIT();
            if (kb > 0) {
                wg_wait<1>();
                if (lane == 0) mbar_arrive(empty + 8 * ((kb - 1) % K1_STAGES));
            }
        }
        wg_wait<0>();
        fence_regs(acc);
        TL(1);
        if (warp == 4) TX(16);
        mbar_wait(auxb, 0);
        if (warp == 4) TX(17);
        bar_sync(1, 256);
        const float2* s_rs = (const float2*)(smem + K1_RS);
        const float* s_cs = (const float*)(smem + K1_CS);
        const int g = lane >> 2, t = lane & 3;
        const int rl = wgi * 64 + ww * 16 + g;
        const float2 st0 = s_rs[rl], st1 = s_rs[rl + 8];
        const float QS = 0.25f * 1.4426950408889634f;
        const uint32_t stg = sb + ((lane >> 4) * 16 + wgi * 8 + ww * 2 + ((lane >> 3) & 1)) * 128 + (lane & 7) * 16;
        float2* s_np = (float2*)(smem + 49152) + (warp - 4) * 32 + lane;
#pragma unroll
        for (int hh = 0; hh < 12; hh++) {
            const int which = (nt * 192 + hh * 16) >> 9;
            const float sc = (which == 0) ? QS : 1.0f;
            const float a0 = st0.x * sc, b0 = st0.y * sc, a1 = st1.x * sc, b1 = st1.y * sc;
            const float2 c0 = *(const float2*)(s_cs + 16 * hh + 2 * t), c1 = *(const float2*)(s_cs + 16 * hh + 8 + 2 * t);
            const float* a = acc + 8 * hh;
            float v0 = fmaf(a0, a[0], b0 * c0.x), v1 = fmaf(a0, a[1], b0 * c0.y), v2 = fmaf(a1, a[2], b1 * c0.x), v3 = fmaf(a1, a[3], b1 * c0.y);
            float v4 = fmaf(a0, a[4], b0 * c1.x), v5 = fmaf(a0, a[5], b0 * c1.y), v6 = fmaf(a1, a[6], b1 * c1.x), v7 = fmaf(a1, a[7], b1 * c1.y);
            {
                const int head = ((nt * 192 + hh * 16) & 511) >> 4;
                uint32_t* o = (uint32_t*)g_qkv + ((size_t)((which * NH + head) * 2) * 256 + mb * 16 + wgi * 8 + ww * 2) * 32 + lane;
                o[0] = pack_bf16(v0, v1); o[32] = pack_bf16(v2, v3); o[8192] = pack_bf16(v4, v5); o[8192 + 32] = pack_bf16(v6, v7);
            }
            s_np[hh * 256] = make_float2(fmaf(v0, v0, fmaf(v1, v1, fmaf(v4, v4, v5 * v5))), fmaf(v2, v2, fmaf(v3, v3, fmaf(v6, v6, v7 * v7))));
        }
        fence_proxy_async();
        bar_arrive(2, 256 + 96);
        TL(2);
        TLDUMP;
    }
}

constexpr int AT_K = 0, AT_V = 65536, AT_ONES = 131072, AT_BAR = 163840, AT_SMEM = AT_BAR + 128;
#define POLY_MASK 0xAD6A

__device__ __forceinline__ uint32_t exp2_pair_poly(float x0, float x1) {
    uint32_t t0 = __float_as_uint(x0 + 32895.0f);
    uint32_t t1 = __float_as_uint(x1 + 32895.0f);
    uint32_t gd = __byte_perm(t0, t1, 0x6420);
    uint32_t wm = __byte_perm(t0, t1, 0x5612);
    uint32_t v = hfma2(gd, 0x71477147u, 0x354f354fu);
    uint32_t z = hmul2(v, gd);
    return (wm >> 1) + z;
}
__device__ __forceinline__ uint32_t exp2_pair_mufu(float x0, float x1) { return pack_bf16(ex2f(x0), ex2f(x1)); }
template <uint32_t MASK>
__device__ __forceinline__ void exp_blocks(const float (&s)[32], uint32_t (&p)[16]) {
#pragma unroll
    for (int b = 0; b < 8; b++) {
        if ((MASK >> b) & 1) {
            p[2 * b] = exp2_pair_poly(s[4 * b], s[4 * b + 1]);
            p[2 * b + 1] = exp2_pair_poly(s[4 * b + 2], s[4 * b + 3]);
        } else {
            p[2 * b] = exp2_pair_mufu(s[4 * b], s[4 * b + 1]);
            p[2 * b + 1] = exp2_pair_mufu(s[4 * b + 2], s[4 * b + 3]);
        }
    }
}
#define PV4(P) _Pragma("unroll") for (int i = 0; i < 4; i++) { pv_wgmma(o, P[4 * i], P[4 * i + 1], P[4 * i + 2], P[4 * i + 3], vd); vd += 16; }

__device__ __forceinline__ void attn_store(float (&o)[12], int row0, int head, int lane) {
    float l0 = __shfl_sync(0xffffffffu, o[8], lane & 28);
    float l1 = __shfl_sync(0xffffffffu, o[10], lane & 28);
    float r0 = 1.0f / l0, r1 = 1.0f / l1;
    uint32_t* op = (uint32_t*)g_ao;
    int mb = row0 >> 7, rg = (row0 & 127) >> 3;
    int kb = head >> 2, kc = (head & 3) * 2;
    size_t base = (((size_t)(mb * 8 + kb) * 8 + kc) * 16 + rg) * 32 + lane;
    op[base] = pack_bf16(o[0] * r0, o[1] * r0);
    op[base + 32] = pack_bf16(o[2] * r1, o[3] * r1);
    op[base + 16 * 32] = pack_bf16(o[4] * r0, o[5] * r0);
    op[base + 16 * 32 + 32] = pack_bf16(o[6] * r1, o[7] * r1);
}

__device__ __forceinline__ void attn_load_q(uint32_t (&q)[4], const __nv_bfloat16* gq, int row0, int lane) {
    const uint32_t* qp = (const uint32_t*)gq;
    int j0 = row0 >> 3;
    q[0] = __ldcg(qp + (0 * 256 + j0) * 32 + lane);
    q[1] = __ldcg(qp + (0 * 256 + j0 + 1) * 32 + lane);
    q[2] = __ldcg(qp + (1 * 256 + j0) * 32 + lane);
    q[3] = __ldcg(qp + (1 * 256 + j0 + 1) * 32 + lane);
}

__device__ __forceinline__ void attn_tile_safe(const uint32_t (&q)[4], uint64_t kd, uint64_t vd, int row0, int head, int lane) {
    float o[12];
#pragma unroll
    for (int i = 0; i < 12; i++) o[i] = 0.f;
    float m0 = -INFINITY, m1 = -INFINITY;
    fence_regs(o);
#pragma unroll 1
    for (int j = 0; j < 32; j++) {
        float s[32];
        uint32_t p[16];
        WG_FENCE();
        qk_wgmma_n64(s, q, kd); kd += 64;
        WG_COMMIT();
        wg_wait<0>();
        fence_regs(s);
        fence_regs(o);
        float x0 = m0, x1 = m1;
#pragma unroll
        for (int b = 0; b < 8; b++) {
            x0 = fmaxf(x0, fmaxf(s[4 * b], s[4 * b + 1]));
            x1 = fmaxf(x1, fmaxf(s[4 * b + 2], s[4 * b + 3]));
        }
        x0 = fmaxf(x0, __shfl_xor_sync(0xffffffffu, x0, 1)); x0 = fmaxf(x0, __shfl_xor_sync(0xffffffffu, x0, 2));
        x1 = fmaxf(x1, __shfl_xor_sync(0xffffffffu, x1, 1)); x1 = fmaxf(x1, __shfl_xor_sync(0xffffffffu, x1, 2));
        float al0 = ex2f(m0 - x0), al1 = ex2f(m1 - x1);
        m0 = x0; m1 = x1;
#pragma unroll
        for (int i = 0; i < 3; i++) { o[4 * i] *= al0; o[4 * i + 1] *= al0; o[4 * i + 2] *= al1; o[4 * i + 3] *= al1; }
#pragma unroll
        for (int b = 0; b < 8; b++) {
            p[2 * b] = exp2_pair_mufu(s[4 * b] - m0, s[4 * b + 1] - m0);
            p[2 * b + 1] = exp2_pair_mufu(s[4 * b + 2] - m1, s[4 * b + 3] - m1);
        }
        fence_regs(o);
        WG_FENCE();
        PV4(p);
        WG_COMMIT();
        wg_wait<0>();
        fence_regs(o);
    }
    attn_store(o, row0, head, lane);
}

__global__ void __launch_bounds__(512, 1)
attn_kernel(const __nv_bfloat16* __restrict__ wg_, const __nv_bfloat16* __restrict__ wu_,
            const __nv_bfloat16* __restrict__ wo_, const __nv_bfloat16* __restrict__ wd_) {
    extern __shared__ __align__(1024) unsigned char smem[];
    const uint32_t sb = smem_u32(smem);
    const int tid = threadIdx.x, wg = tid >> 7, warp = (tid >> 5) & 3, lane = tid & 31;
    TLDECL
    pdl_launch();
    if (blockIdx.x >= 128) {
        const int e = blockIdx.x - 128;
        const __nv_bfloat16* w = (e < 2) ? wg_ : wu_;
        float* red = (float*)smem;
        const int cgrp = tid & 127, kq = tid >> 7;
        if (cgrp < 112) {
            float s[8];
            colsum8(w, FF, (e & 1) * 896 + cgrp * 8, kq * 128, 128, s);
#pragma unroll
            for (int i = 0; i < 8; i++) red[kq * 896 + cgrp * 8 + i] = s[i];
        }
        __syncthreads();
        for (int c = tid; c < 896; c += 512)
            g_cs2[(e >> 1) * FF + (e & 1) * 896 + c] = red[c] + red[896 + c] + red[1792 + c] + red[2688 + c];
        if (tid < 32) {
            const char* p0 = (const char*)wo_ + e * (DM * DM * 2 / 4);
            for (int i = lane; i < 32; i += 32)
                asm volatile("cp.async.bulk.prefetch.L2.global [%0], %1;" :: "l"(p0 + i * 4096), "r"(4096) : "memory");
            const char* p1 = (const char*)wd_ + e * (FF * DM * 2 / 4);
            for (int i = lane; i < 112; i += 32)
                asm volatile("cp.async.bulk.prefetch.L2.global [%0], %1;" :: "l"(p1 + i * 4096), "r"(4096) : "memory");
        }
        return;
    }
    const int head = blockIdx.x >> 2, qq = blockIdx.x & 3;
    const __nv_bfloat16* gq = g_qkv + (size_t)head * (S_LEN * 16);
    const __nv_bfloat16* gk = g_qkv + (size_t)(NH + head) * (S_LEN * 16);
    const __nv_bfloat16* gv = g_qkv + (size_t)(2 * NH + head) * (S_LEN * 16);
    if (tid == 0) {
        for (int i = 0; i < 8; i++) mbar_init(sb + AT_BAR + 8 * i, 1);
        fence_barrier_init();
    }
    {
        uint4 one = make_uint4(0x00003F80u, 0, 0, 0);
#pragma unroll
        for (int i = 0; i < 4; i++) *(uint4*)(smem + AT_ONES + (i * 512 + tid) * 16) = one;
        fence_proxy_async();
    }
    __syncthreads();
    TL(3);
    pdl_wait();
    TL(4);
    auto load_kv = [&](int i) {
        uint32_t bar = sb + AT_BAR + 8 * i;
        mbar_expect(bar, 16384);
        bulk_g2s(sb + AT_K + i * 4096, gk + i * 2048, 4096, bar);
        bulk_g2s(sb + AT_K + 32768 + i * 4096, gk + 16384 + i * 2048, 4096, bar);
        bulk_g2s(sb + AT_V + i * 4096, gv + i * 2048, 4096, bar);
        bulk_g2s(sb + AT_V + 32768 + i * 4096, gv + 16384 + i * 2048, 4096, bar);
    };
    if (tid == 0) { load_kv(0); load_kv(1); }
    uint32_t q[4], q2[4];
    attn_load_q(q, gq, qq * 512 + wg * 64 + warp * 16, lane);
    attn_load_q(q2, gq, qq * 512 + (4 + wg) * 64 + warp * 16, lane);
    bool fast;
    {
        const float* nq = g_nrm + (0 * NH + head) * 128 + qq * 32;
        const float* nk = g_nrm + (1 * NH + head) * 128;
        const float* nv = g_nrm + (2 * NH + head) * 128;
        float4 k4 = __ldcg((const float4*)nk + lane), v4 = __ldcg((const float4*)nv + lane);
        float qm = warp_max(__ldcg(nq + lane));
        float km = warp_max(fmaxf(fmaxf(k4.x, k4.y), fmaxf(k4.z, k4.w)));
        float vm = warp_max(fmaxf(fmaxf(v4.x, v4.y), fmaxf(v4.z, v4.w)));
        fast = __all_sync(0xffffffffu, (qm * km <= 3500.0f) && (vm <= 1.0e24f));
    }
    TL(24);
    const uint64_t kdesc0 = make_desc(sb + AT_K, 32768, 128, 0);
    const uint64_t vdesc0 = make_desc(sb + AT_V, 128, 32768, 0);
    if (!fast) {
        if (tid == 0) for (int i = 2; i < 8; i++) load_kv(i);
        for (int i = 0; i < 8; i++) mbar_wait(sb + AT_BAR + 8 * i, 0);
#pragma unroll 1
        for (int tile = 0; tile < 2; tile++) {
            const int row0 = qq * 512 + (tile * 4 + wg) * 64 + warp * 16;
            attn_tile_safe(q, kdesc0, vdesc0, row0, head, lane);
#pragma unroll
            for (int i = 0; i < 4; i++) q[i] = q2[i];
        }
        return;
    }
#pragma unroll 1
    for (int tile = 0; tile < 2; tile++) {
        const int row0 = qq * 512 + (tile * 4 + wg) * 64 + warp * 16;
        float o[12];
#pragma unroll
        for (int i = 0; i < 12; i++) o[i] = 0.f;
        fence_regs(o);
        float sa[32];
        uint32_t pa[16];
        uint64_t kd = kdesc0, vd = vdesc0;
        if (tile == 0) { mbar_wait(sb + AT_BAR, 0); TL(25); }
        WG_FENCE();
        qk_wgmma_n64(sa, q, kd); kd += 64;
        WG_COMMIT();
#pragma unroll 1
        for (int jj = 0; jj < 8; jj++) {
            if (tile == 0 && jj < 7) {
                if (tid == 0 && jj < 6) load_kv(jj + 2);
                mbar_wait(sb + AT_BAR + 8 * (jj + 1), 0);
            }
            if (wg == 0 && warp == 0) TX(128 + tile * 8 + jj);
#pragma unroll
            for (int j = 0; j < 4; j++) {
                wg_wait<0>();
                fence_regs(sa);
                if (j & 1) exp_blocks<(POLY_MASK >> 8)>(sa, pa); else exp_blocks<(POLY_MASK & 255)>(sa, pa);
                WG_FENCE();
                qk_wgmma_n64(sa, q, kd); kd += 64;
                PV4(pa);
                WG_COMMIT();
            }
        }
        wg_wait<0>();
        fence_regs(o);
        fence_regs(sa);
        if (tile == 0) TL(26);
        attn_store(o, row0, head, lane);
#pragma unroll
        for (int i = 0; i < 4; i++) q[i] = q2[i];
    }
    TL(5);
    TLDUMP;
}

#define DELAYC 9
constexpr int F_R2 = 131072, F_X = 196608, F_BAR = 229376;
constexpr int F_RS = F_BAR + 256, F_CS = F_RS + 1024, F_SMEM = F_CS + 1792;
enum { B_FA = 0, B_HF = 4, B_BF = 8, B_BE = 11, B_CF = 14, B_CE = 20, B_ADONE = 26, B_BDONE = 27, B_XC = 28, B_PRDY = 29, B_AUX = 30, B_NUM = 31 };

__device__ __forceinline__ void st_async4(uint32_t dst, float a, float b, float c, float d, uint32_t bar) {
    asm volatile("st.async.weak.shared::cluster.mbarrier::complete_tx::bytes.v4.f32 [%0], {%1,%2,%3,%4}, [%5];"
                 :: "r"(dst), "f"(a), "f"(b), "f"(c), "f"(d), "r"(bar) : "memory");
}
__device__ __forceinline__ void poll_count(const unsigned int* p, unsigned int target) {
    int it = 0;
    while (ld_acquire(p) < target) { if (++it > (1 << 22)) __trap(); }
    asm volatile("fence.proxy.async.global;" ::: "memory");
}
__device__ __forceinline__ void tma2d_store(const CUtensorMap* m, uint32_t src, int c0, int c1) {
    asm volatile("cp.async.bulk.tensor.2d.global.shared::cta.bulk_group [%0, {%2, %3}], [%1];" :: "l"(m), "r"(src), "r"(c0), "r"(c1) : "memory");
}
__device__ __forceinline__ float2 h_row_stats(int row) {
    const float4* hp = (const float4*)(g_hstat + (size_t)row * 8);
    float4 a = __ldcg(hp), b = __ldcg(hp + 1), c = __ldcg(hp + 2), d = __ldcg(hp + 3);
    float mean = 0.125f * (a.x + a.z + b.x + b.z + c.x + c.z + d.x + d.z);
    float m2 = a.y + a.w + b.y + b.w + c.y + c.w + d.y + d.w;
    float e;
    e = a.x - mean; m2 = fmaf(64.f * e, e, m2); e = a.z - mean; m2 = fmaf(64.f * e, e, m2);
    e = b.x - mean; m2 = fmaf(64.f * e, e, m2); e = b.z - mean; m2 = fmaf(64.f * e, e, m2);
    e = c.x - mean; m2 = fmaf(64.f * e, e, m2); e = c.z - mean; m2 = fmaf(64.f * e, e, m2);
    e = d.x - mean; m2 = fmaf(64.f * e, e, m2); e = d.z - mean; m2 = fmaf(64.f * e, e, m2);
    return make_float2(rsqrtf(m2 * (1.0f / DM) + 1e-5f), -mean);
}
__device__ __forceinline__ int c_kblock(int i, int r) {
    if (i < 6) { const int e = 2 * i + r, m = e / 3, k = e - 3 * m; return 7 * m + (k == 2 ? 4 : k); }
    const int l = 2 * (i - 6) + r, m = l >> 2, k = l & 3;
    return 7 * m + (k < 2 ? 2 + k : 3 + k);
}
__device__ __forceinline__ uint32_t c_stage_a(int s, int ntB) { return s < 4 ? ((ntB + 2 * s) & 7) * 16384 : F_R2 + (s - 4) * 32768; }
__device__ __forceinline__ uint32_t c_stage_b(int s, int ntB) { return s < 4 ? ((ntB + 2 * s + 1) & 7) * 16384 : F_R2 + (s - 4) * 32768 + 16384; }
template <int R>
__device__ __forceinline__ void xchg(float (&acc)[64], float (&o)[32], uint32_t sb, unsigned char* smem, int bar, int ctid) {
    const uint32_t dst = mapa(sb + F_X + ctid * 16, 1 - R), rb = mapa(sb + F_BAR + 8 * bar, 1 - R);
#pragma unroll
    for (int q = 0; q < 8; q++) {
        const int j = (1 - R) * 32 + 4 * q;
        st_async4(dst + q * 4096, acc[j], acc[j + 1], acc[j + 2], acc[j + 3], rb);
    }
    mbar_wait_cluster(sb + F_BAR + 8 * bar, 0);
#pragma unroll
    for (int q = 0; q < 8; q++) {
        float4 v = *(const float4*)(smem + F_X + q * 4096 + ctid * 16);
        const int j = R * 32 + 4 * q;
        o[4 * q] = acc[j] + v.x; o[4 * q + 1] = acc[j + 1] + v.y; o[4 * q + 2] = acc[j + 2] + v.z; o[4 * q + 3] = acc[j + 3] + v.w;
    }
}

template <int NB, bool STAGE>
__device__ __forceinline__ void ffn_epilogue(const float* ag, const float* au, const float* s_cs, int cs_off, uint32_t* gp, uint32_t stg,
                                             float2 st0, float2 st1, int lane) {
    const int t = lane & 3;
    const float C1 = 0.7978845608028654f, C2 = 0.044715f * 0.7978845608028654f;
    const float k10 = st0.x * C1, k20 = st0.x * st0.x * st0.x * C2, k11 = st1.x * C1, k21 = st1.x * st1.x * st1.x * C2;
#pragma unroll
    for (int j2 = 0; j2 < NB / 2; j2++) {
        uint32_t pk[4];
#pragma unroll
        for (int jj = 0; jj < 2; jj++) {
            const int j = 2 * j2 + jj;
            const float2 cg = *(const float2*)(s_cs + cs_off + 8 * j + 2 * t);
            const float2 cu = *(const float2*)(s_cs + 224 + cs_off + 8 * j + 2 * t);
            float r[4];
#pragma unroll
            for (int e = 0; e < 4; e++) {
                const float nm = (e < 2) ? st0.y : st1.y, k1 = (e < 2) ? k10 : k11, k2 = (e < 2) ? k20 : k21;
                const float tg = fmaf(nm, (e & 1) ? cg.y : cg.x, ag[4 * j + e]);
                const float tu = fmaf(nm, (e & 1) ? cu.y : cu.x, au[4 * j + e]);
                const float th = tanh_fast(tg * fmaf(tg * tg, k2, k1));
                const float p = tg * tu;
                r[e] = fmaf(p, th, p);
            }
            pk[2 * jj] = pack_bf16(r[0], r[1]);
            pk[2 * jj + 1] = pack_bf16(r[2], r[3]);
        }
        if (STAGE) {
            stsm4(stg + j2 * 4096, pk[0], pk[1], pk[2], pk[3]);
        } else {
            gp[j2 * 1024] = pk[0]; gp[j2 * 1024 + 32] = pk[1]; gp[j2 * 1024 + 512] = pk[2]; gp[j2 * 1024 + 544] = pk[3];
        }
    }
}

__global__ void __cluster_dims__(2, 1, 1) __launch_bounds__(384, 1)
tail_kernel(const __grid_constant__ CUtensorMap tm_o, const __grid_constant__ CUtensorMap tm_g,
            const __grid_constant__ CUtensorMap tm_u, const __grid_constant__ CUtensorMap tm_d,
            const __grid_constant__ CUtensorMap tm_out, const __nv_bfloat16* __restrict__ x) {
    extern __shared__ __align__(1024) unsigned char smem[];
    const uint32_t sb = smem_u32(smem);
    const uint32_t bars = sb + F_BAR;
    const int tid = threadIdx.x, warp = __shfl_sync(0xffffffffu, tid >> 5, 0), lane = tid & 31;
    TLDECL
    TL(6);
    if (warp == 4) TX(200);
    const int cl = blockIdx.x >> 1, r = blockIdx.x & 1;
    const int mb = ((cl & 7) >> 1) * 4 + (cl >> 4), ntA = (cl & 1) * 2 + ((cl >> 3) & 1);
    const int nt = ntA * 2 + r;
    const int mbB = (mb & ~1) + r, ntB = (mb & 1) * 4 + ntA;
    if (tid == 0) {
#pragma unroll
        for (int i = 0; i < B_NUM; i++) {
            const int cnt = (i >= B_BE && i < B_BE + 3) ? 16 : (i == B_BDONE) ? DELAYC : ((i >= B_CE && i < B_CE + 6) || i == B_PRDY) ? 8 : (i == B_AUX || i == B_ADONE) ? 2 : 1;
            mbar_init(bars + 8 * i, cnt);
        }
        mbar_expect(bars + 8 * B_XC, 32768);
        fence_barrier_init();
    }
    TL(28);
    __syncthreads();
    TL(29);
    asm volatile("barrier.cluster.arrive.relaxed.aligned;" ::: "memory");
    TL(30);
    if (warp < 4) {
        asm volatile("setmaxnreg.dec.sync.aligned.u32 56;");
        if (warp == 0) TX(205);
        if (warp == 0) {
            if (lane == 0) {
                auto load_b = [&](int it) {
                    const int s = it % 3, pass = it >> 3, kb = (ntB + it) & 7;
                    const int ng = pass ? 3 : 4, c0 = ntB * 224 + pass * 128;
                    const uint32_t bar = bars + 8 * (B_BF + s), dst = sb + F_R2 + s * 32768 + r * ng * 4096;
                    mbar_expect(bar, ng * 8192);
                    for (int i = 0; i < ng; i++) tma2d_mc(dst + i * 4096, r ? &tm_u : &tm_g, c0 + i * 32, kb * 64, bar);
                };
                for (int i = 0; i < 8; i++) {
                    const uint32_t bar = bars + 8 * (B_FA + (i >> 1));
                    if (!(i & 1)) mbar_expect(bar, 49152);
                    tma2d(sb + F_R2 + 32768 + i * 8192, &tm_o, nt * 64, i * 64, bar);
                }
                asm volatile("barrier.cluster.wait.acquire;" ::: "memory");
                pdl_wait();
                TL(16);
                for (int i = 0; i < 4; i++)
                    bulk_g2s_mc(sb + (2 * i + r) * 16384, g_ao + (size_t)(mb * 8 + 2 * i + r) * 8192, 16384, bars + 8 * (B_FA + i));
                load_b(0);
                if (blockIdx.x == 0)
                    for (int i = 0; i < 32; i++) g_cnt[i] = 0;
                mbar_wait_cluster(bars + 8 * B_ADONE, 0);
                load_b(1); load_b(2);
                auto load_c = [&](int i) {
                    const int s = i % 6, kb = c_kblock(i, r);
                    const uint32_t bar = bars + 8 * (B_CF + s), da = sb + c_stage_a(s, ntB), db = sb + c_stage_b(s, ntB);
                    mbar_expect(bar, 32768);
                    tma2d(db, &tm_d, ntA * 128, kb * 64, bar);
                    tma2d(db + 8192, &tm_d, ntA * 128 + 64, kb * 64, bar);
                    bulk_g2s(da, g_g + (size_t)(mb * 28 + kb) * 8192, 16384, bar);
                };
                for (int it = 3; it < 16; it++) {
                    mbar_wait_cluster(bars + 8 * (B_BE + it % 3), (it / 3 - 1) & 1);
                    load_b(it);
                    if (it == 12) { poll_count(&g_cnt2[mb], 8); load_c(0); }
                    if (it == 14) load_c(1);
                }
                mbar_wait(bars + 8 * B_BDONE, 0);
                for (int i = 2; i < 14; i++) {
                    if (i >= 6) mbar_wait(bars + 8 * (B_CE + i % 6), ((i / 6) - 1) & 1);
                    if (i == 6) { poll_count(&g_cnt2[16 + mb], 8); TL(18); }
                    load_c(i);
                }
            }
            else asm volatile("barrier.cluster.wait.acquire;" ::: "memory");
            TLDUMP;
        } else if (warp == 1) {
            asm volatile("barrier.cluster.wait.acquire.aligned;" ::: "memory");
            bar_sync(5, 288);
            if (lane == 0) { red_release(&g_cnt2[32 + mb * 8 + nt]); TL(9); }
            __syncwarp();
            bar_sync(1, 288);
            if (lane == 0) red_release(&g_cnt2[mbB]);
            __syncwarp();
            bar_sync(2, 288);
            if (lane == 0) {
                red_release(&g_cnt2[16 + mbB]);
                if (DELAYC == 9) mbar_arrive(bars + 8 * B_BDONE);
                TL(13);
            }
            __syncwarp();
            bar_sync(3, 288);
            if (lane == 0) {
                tma2d_store(&tm_out, sb, nt * 64, mb * 128);
                bulk_commit();
                bulk_wait_all();
                TL(15);
            }
            TLDUMP;
        } else {
            asm volatile("barrier.cluster.wait.acquire.aligned;" ::: "memory");
            pdl_wait();
            float2* s_rs = (float2*)(smem + F_RS);
            float* s_cs = (float*)(smem + F_CS);
            for (int c = tid - 64; c < 448; c += 64)
                s_cs[c] = __ldcg(&g_cs2[(c >= 224 ? FF - 224 : 0) + ntB * 224 + c]);
            if (tid == 96) {
                mbar_wait_cluster(bars + 8 * B_ADONE, 0);
                for (int i = 0; i < 8; i++) {
                    const int kb = (ntB + i) & 7;
                    const uint32_t bar = bars + 8 * (i < 4 ? B_HF + i : B_FA + i - 4);
                    poll_count(&g_cnt2[32 + mbB * 8 + kb], 1);
                    mbar_expect(bar, 16384);
                    bulk_g2s(sb + kb * 16384, g_h + (size_t)(mbB * 8 + kb) * 8192, 16384, bar);
                }
                TL(17);
            }
            __syncwarp();
            if (lane < 8) poll_count(&g_cnt2[32 + mbB * 8 + lane], 1);
            __syncwarp();
            for (int rr = tid - 64; rr < 128; rr += 64) {
                s_rs[rr] = h_row_stats(mbB * 128 + rr);
            }
            __syncwarp();
            if (lane == 0) mbar_arrive(bars + 8 * B_AUX);
            TLDUMP;
        }
    } else {
        asm volatile("setmaxnreg.inc.sync.aligned.u32 216;");
        if (warp == 4) TX(206);
        const int wgi = (warp >> 2) - 1, ww = warp & 3, ctid = tid - 128;
        const int g = lane >> 2, t = lane & 3;
        const int rl = wgi * 64 + ww * 16 + g, row = mb * 128 + rl;
        const int rgl = wgi * 8 + ww * 2;
        const float2* s_rs = (const float2*)(smem + F_RS);
        const float* s_cs = (const float*)(smem + F_CS);
        const uint32_t stl = ((lane >> 4) * 16 + rgl + ((lane >> 3) & 1)) * 128 + (lane & 7) * 16;
        uint32_t* hp = (uint32_t*)g_h + ((size_t)(mb * 8 + nt) * 8 * 16 + rgl) * 32 + lane;
        const uint32_t rbars = mapa(bars, 1 - r);
        TL(23);
        {
            uint32_t xr[16];
            const uint32_t* xp = (const uint32_t*)(x + (size_t)row * DM + nt * 64) + t;
#pragma unroll
            for (int j = 0; j < 8; j++) { xr[2 * j] = __ldg(xp + 4 * j); xr[2 * j + 1] = __ldg(xp + 8 * (DM / 2) + 4 * j); }
            float acc[32];
#pragma unroll 1
            for (int i = 0; i < 8; i++) {
                if (!(i & 1)) { mbar_wait(bars + 8 * (B_FA + (i >> 1)), 0); if (i == 0) TL(19); }
                uint64_t ad = make_desc(sb + i * 16384 + wgi * 1024, 2048, 128, 0);
                uint64_t bd = make_desc(sb + F_R2 + 32768 + i * 8192, 8192, 1024, 1);
                WG_FENCE();
#pragma unroll
                for (int k = 0; k < 4; k++) wgmma_ss_n64(acc, ad + k * 256, bd + k * 128, (i | k) != 0);
                WG_COMMIT();
            }
            wg_wait<0>();
            fence_regs(acc);
            TL(7);
            asm volatile("barrier.cluster.wait.acquire.aligned;" ::: "memory");
            bar_sync(4, 256);
            if (tid == 128) { mbar_arrive(bars + 8 * B_ADONE); mbar_arrive_remote(mapa(bars + 8 * B_ADONE, 1 - r)); }
            float v0[16], v1[16];
            float s0 = 0.f, s1 = 0.f;
#pragma unroll
            for (int j2 = 0; j2 < 4; j2++) {
                uint32_t u[4];
#pragma unroll
                for (int jj = 0; jj < 2; jj++) {
                    const int j = 2 * j2 + jj;
                    u[2 * jj] = pack_bf16(bf_lo(xr[2 * j]) + acc[4 * j], bf_hi(xr[2 * j]) + acc[4 * j + 1]);
                    u[2 * jj + 1] = pack_bf16(bf_lo(xr[2 * j + 1]) + acc[4 * j + 2], bf_hi(xr[2 * j + 1]) + acc[4 * j + 3]);
                    v0[2 * j] = bf_lo(u[2 * jj]); v0[2 * j + 1] = bf_hi(u[2 * jj]);
                    v1[2 * j] = bf_lo(u[2 * jj + 1]); v1[2 * j + 1] = bf_hi(u[2 * jj + 1]);
                    s0 += v0[2 * j] + v0[2 * j + 1];
                    s1 += v1[2 * j] + v1[2 * j + 1];
                }
                hp[j2 * 1024] = u[0]; hp[j2 * 1024 + 32] = u[1]; hp[j2 * 1024 + 512] = u[2]; hp[j2 * 1024 + 544] = u[3];
            }
            float m0 = s0 * (1.0f / 16), m1 = s1 * (1.0f / 16), q0 = 0.f, q1 = 0.f;
#pragma unroll
            for (int i = 0; i < 16; i++) {
                float d0 = v0[i] - m0, d1 = v1[i] - m1;
                q0 = fmaf(d0, d0, q0); q1 = fmaf(d1, d1, q1);
            }
#pragma unroll
            for (int st = 0; st < 2; st++) {
                float hn = st ? 16.f : 8.f;
                float om0 = __shfl_xor_sync(0xffffffffu, m0, 1 << st), oq0 = __shfl_xor_sync(0xffffffffu, q0, 1 << st);
                float om1 = __shfl_xor_sync(0xffffffffu, m1, 1 << st), oq1 = __shfl_xor_sync(0xffffffffu, q1, 1 << st);
                float d0 = om0 - m0, d1 = om1 - m1;
                q0 = q0 + oq0 + d0 * d0 * hn; q1 = q1 + oq1 + d1 * d1 * hn;
                m0 = 0.5f * (m0 + om0); m1 = 0.5f * (m1 + om1);
            }
            if (t == 0) {
                g_hstat[row * 8 + nt] = make_float2(m0, q0);
                g_hstat[(row + 8) * 8 + nt] = make_float2(m1, q1);
            }
            bar_arrive(5, 288);
            TL(8);
        }
        uint32_t* gp = (uint32_t*)g_g + (((size_t)mbB * 224 + ntB * 28) * 16 + rgl) * 32 + lane;
        {
            float ag[128];
#pragma unroll 1
            for (int kb = 0; kb < 8; kb++) {
                const int s = kb % 3;
                mbar_wait(bars + 8 * (kb < 4 ? B_HF + kb : B_FA + kb - 4), kb < 4 ? 0 : 1);
                mbar_wait(bars + 8 * (B_BF + s), (kb / 3) & 1);
                uint64_t ad = make_desc(sb + ((ntB + kb) & 7) * 16384 + wgi * 1024, 2048, 128, 0);
                uint64_t bd = make_desc(sb + F_R2 + s * 32768, 4096, 512, 2);
                WG_FENCE();
#pragma unroll
                for (int k = 0; k < 4; k++) wgmma_ss_n256(ag, ad + k * 256, bd + k * 64, (kb | k) != 0);
                WG_COMMIT();
                if (kb > 0) {
                    wg_wait<1>();
                    if (lane == 0) { mbar_arrive(bars + 8 * (B_BE + (kb - 1) % 3)); mbar_arrive_remote(rbars + 8 * (B_BE + (kb - 1) % 3)); }
                }
            }
            wg_wait<0>();
            if (lane == 0) { mbar_arrive(bars + 8 * (B_BE + 7 % 3)); mbar_arrive_remote(rbars + 8 * (B_BE + 7 % 3)); }
            fence_regs(ag);
            TL(10);
            mbar_wait(bars + 8 * B_AUX, 0);
            ffn_epilogue<16, false>(ag, ag + 64, s_cs, 0, gp, 0, s_rs[rl], s_rs[rl + 8], lane);
            bar_arrive(1, 288);
        }
        {
            float ag[96];
#pragma unroll 1
            for (int kb = 0; kb < 8; kb++) {
                const int it = 8 + kb, s = it % 3;
                mbar_wait(bars + 8 * (B_BF + s), (it / 3) & 1);
                uint64_t ad = make_desc(sb + ((ntB + kb) & 7) * 16384 + wgi * 1024, 2048, 128, 0);
                uint64_t bd = make_desc(sb + F_R2 + s * 32768, 4096, 512, 2);
                WG_FENCE();
#pragma unroll
                for (int k = 0; k < 4; k++) wgmma_ss_n192(ag, ad + k * 256, bd + k * 64, (kb | k) != 0);
                WG_COMMIT();
                if (kb > 0) {
                    wg_wait<1>();
                    if (lane == 0 && it + 2 < 16) { mbar_arrive(bars + 8 * (B_BE + (it - 1) % 3)); mbar_arrive_remote(rbars + 8 * (B_BE + (it - 1) % 3)); }
                }
            }
            wg_wait<0>();
            if (lane == 0) {
                mbar_arrive(bars + 8 * B_BDONE);
                mbar_arrive_remote(rbars + 8 * B_PRDY);
            }
            fence_regs(ag);
            TL(11);
            ffn_epilogue<12, false>(ag, ag + 48, s_cs, 128, gp + 16 * 512, 0, s_rs[rl], s_rs[rl + 8], lane);
            bar_arrive(2, 288);
            TL(12);
        }
        {
            uint32_t hr[16];
#pragma unroll
            for (int j = 0; j < 8; j++) { hr[2 * j] = __ldcg(hp + j * 512); hr[2 * j + 1] = __ldcg(hp + j * 512 + 32); }
            mbar_wait(bars + 8 * (B_CF + 0), 0);
            const float a0 = h_row_stats(row).x, a1 = h_row_stats(row + 8).x;
            float acc[64];
#pragma unroll 1
            for (int kb = 0; kb < 14; kb++) {
                const int s = kb % 6;
                mbar_wait(bars + 8 * (B_CF + s), (kb / 6) & 1);
                if (warp == 4) TX(96 + kb);
                uint64_t ad = make_desc(sb + c_stage_a(s, ntB) + wgi * 1024, 2048, 128, 0);
                uint64_t bd = make_desc(sb + c_stage_b(s, ntB), 8192, 1024, 1);
                WG_FENCE();
#pragma unroll
                for (int k = 0; k < 4; k++) wgmma_ss_n128(acc, ad + k * 256, bd + k * 128, (kb | k) != 0);
                WG_COMMIT();
                if (kb > 0) {
                    wg_wait<1>();
                    if (lane == 0) mbar_arrive(bars + 8 * (B_CE + (kb - 1) % 6));
                }
            }
            wg_wait<0>();
            fence_regs(acc);
            TL(14);
            mbar_wait_cluster(bars + 8 * B_PRDY, 0);
            float o[32];
            if (r == 0) xchg<0>(acc, o, sb, smem, B_XC, ctid); else xchg<1>(acc, o, sb, smem, B_XC, ctid);
            TL(22);
            bar_sync(4, 256);
            const float k0 = 0.5f * a0 * a0, k1 = 0.5f * a1 * a1;
            const int srow = wgi * 64 + ww * 16 + ((lane >> 3) & 1) * 8 + (lane & 7);
#pragma unroll
            for (int j2 = 0; j2 < 4; j2++) {
                uint32_t u[4];
#pragma unroll
                for (int jj = 0; jj < 2; jj++) {
                    const int j = 2 * j2 + jj;
                    u[2 * jj] = pack_bf16(fmaf(k0, o[4 * j], bf_lo(hr[2 * j])), fmaf(k0, o[4 * j + 1], bf_hi(hr[2 * j])));
                    u[2 * jj + 1] = pack_bf16(fmaf(k1, o[4 * j + 2], bf_lo(hr[2 * j + 1])), fmaf(k1, o[4 * j + 3], bf_hi(hr[2 * j + 1])));
                }
                const int chunk = 2 * j2 + (lane >> 4);
                stsm4(sb + srow * 128 + ((chunk ^ (lane & 7)) * 16), u[0], u[1], u[2], u[3]);
            }
            fence_proxy_async();
            bar_arrive(3, 288);
            TLDUMP;
        }
    }
}

typedef CUresult (*EncodeFn)(CUtensorMap*, CUtensorMapDataType, cuuint32_t, void*, const cuuint64_t*, const cuuint64_t*,
                             const cuuint32_t*, const cuuint32_t*, CUtensorMapInterleave, CUtensorMapSwizzle,
                             CUtensorMapL2promotion, CUtensorMapFloatOOBfill);

void encode(EncodeFn fn, CUtensorMap* m, const void* ptr, int rank, const cuuint64_t* dims, const cuuint64_t* strides,
            const cuuint32_t* box, CUtensorMapSwizzle swz) {
    cuuint32_t es[3] = {1, 1, 1};
    fn(m, CU_TENSOR_MAP_DATA_TYPE_BFLOAT16, rank, (void*)ptr, dims, strides, box, es, CU_TENSOR_MAP_INTERLEAVE_NONE, swz,
       CU_TENSOR_MAP_L2_PROMOTION_L2_256B, CU_TENSOR_MAP_FLOAT_OOB_FILL_NONE);
}

template <typename... KArgs, typename... Args>
void launch(void (*kern)(KArgs...), int grid, int block, int smem, bool pdl, Args... args) {
    cudaLaunchConfig_t cfg = {};
    cfg.gridDim = dim3(grid); cfg.blockDim = dim3(block); cfg.dynamicSmemBytes = smem;
    cfg.stream = cudaStreamPerThread;
    cudaLaunchAttribute at[1];
    at[0].id = cudaLaunchAttributeProgrammaticStreamSerialization;
    at[0].val.programmaticStreamSerializationAllowed = 1;
    cfg.attrs = at; cfg.numAttrs = pdl ? 1 : 0;
    cudaLaunchKernelEx(&cfg, kern, KArgs(args)...);
}

}

extern "C" void kernel_launch(void* const* d_in, const int* in_sizes, int n_in, void* d_out, int out_size) {
    const __nv_bfloat16* x = (const __nv_bfloat16*)d_in[0];
    const __nv_bfloat16* wqkv = (const __nv_bfloat16*)d_in[1];
    const __nv_bfloat16* wo = (const __nv_bfloat16*)d_in[2];
    const __nv_bfloat16* wgate = (const __nv_bfloat16*)d_in[4];
    const __nv_bfloat16* wup = (const __nv_bfloat16*)d_in[5];
    const __nv_bfloat16* wdown = (const __nv_bfloat16*)d_in[6];
    __nv_bfloat16* out = (__nv_bfloat16*)d_out;

    static CUtensorMap tm_x, tm_wqkv, tm_wo, tm_wg, tm_wu, tm_wd, tm_out;
    static const void* cached[7] = {nullptr, nullptr, nullptr, nullptr, nullptr, nullptr, nullptr};
    if (cached[0] != x || cached[1] != wqkv || cached[2] != wo || cached[3] != wgate || cached[4] != wup || cached[5] != wdown || cached[6] != out) {
        void* fp = nullptr;
        cudaDriverEntryPointQueryResult qr;
        cudaGetDriverEntryPoint("cuTensorMapEncodeTiled", &fp, cudaEnableDefault, &qr);
        EncodeFn fn = (EncodeFn)fp;
        { cuuint64_t d[2] = {512, 2048}, s[1] = {1024}; cuuint32_t b[2] = {64, 128};
          encode(fn, &tm_x, x, 2, d, s, b, CU_TENSOR_MAP_SWIZZLE_128B);
          encode(fn, &tm_out, out, 2, d, s, b, CU_TENSOR_MAP_SWIZZLE_128B); }
        { cuuint64_t d[3] = {64, 512, 24}, s[2] = {3072, 128}; cuuint32_t b[3] = {64, 64, 3};
          encode(fn, &tm_wqkv, wqkv, 3, d, s, b, CU_TENSOR_MAP_SWIZZLE_128B); }
        { cuuint64_t d[2] = {512, 512}, s[1] = {1024}; cuuint32_t b[2] = {64, 64};
          encode(fn, &tm_wo, wo, 2, d, s, b, CU_TENSOR_MAP_SWIZZLE_128B); }
        { cuuint64_t d[2] = {1792, 512}, s[1] = {3584}; cuuint32_t b[2] = {32, 64};
          encode(fn, &tm_wg, wgate, 2, d, s, b, CU_TENSOR_MAP_SWIZZLE_64B);
          encode(fn, &tm_wu, wup, 2, d, s, b, CU_TENSOR_MAP_SWIZZLE_64B); }
        { cuuint64_t d[2] = {512, 1792}, s[1] = {1024}; cuuint32_t b[2] = {64, 64};
          encode(fn, &tm_wd, wdown, 2, d, s, b, CU_TENSOR_MAP_SWIZZLE_128B); }
        cudaFuncSetAttribute(qkv_kernel, cudaFuncAttributeMaxDynamicSharedMemorySize, F_SMEM);
        cudaFuncSetAttribute(qkv_kernel, cudaFuncAttributePreferredSharedMemoryCarveout, 100);
        cudaFuncSetAttribute(attn_kernel, cudaFuncAttributeMaxDynamicSharedMemorySize, F_SMEM);
        cudaFuncSetAttribute(attn_kernel, cudaFuncAttributePreferredSharedMemoryCarveout, 100);
        cudaFuncSetAttribute(tail_kernel, cudaFuncAttributeMaxDynamicSharedMemorySize, F_SMEM);
        cudaFuncSetAttribute(tail_kernel, cudaFuncAttributePreferredSharedMemoryCarveout, 100);
        cached[0] = x; cached[1] = wqkv; cached[2] = wo; cached[3] = wgate; cached[4] = wup; cached[5] = wdown; cached[6] = out;
    }
    launch(qkv_kernel, 128, 384, F_SMEM, false, tm_x, tm_wqkv, x, wqkv);
    launch(attn_kernel, 132, 512, F_SMEM, true, wgate, wup, wo, wdown);
    launch(tail_kernel, 128, 384, F_SMEM, true, tm_wo, tm_wg, tm_wu, tm_wd, tm_out, x);
}
```

```cpp
#include <cuda_runtime.h>
#include <cuda_bf16.h>
#include <cuda.h>
#include <stdint.h>

#define K1_DIRECT
namespace {

constexpr int S_LEN = 2048, DM = 512, NH = 32, FF = 1792;

__device__ __align__(1024) __nv_bfloat16 g_qkv[3 * NH * S_LEN * 16];
__device__ __align__(1024) __nv_bfloat16 g_ao[S_LEN * DM];
__device__ __align__(1024) __nv_bfloat16 g_h[S_LEN * DM];
__device__ __align__(1024) __nv_bfloat16 g_g[S_LEN * FF];
__device__ __align__(16) float2 g_rowstat1[S_LEN];
__device__ float g_cs1_part[16 * 1536];
__device__ unsigned int g_cnt[32];
__device__ unsigned int g_cnt2[160];
__device__ float g_nrm[3 * NH * 128];
__device__ float2 g_hstat[S_LEN * 8];
__device__ float g_cs2[2 * FF];

#define TLDECL
#define TL(slot)
#define TLDUMP
#define TX(slot)
__device__ __forceinline__ uint32_t smem_u32(const void* p) { return (uint32_t)__cvta_generic_to_shared(p); }
__device__ __forceinline__ void mbar_init(uint32_t a, int c) { asm volatile("mbarrier.init.shared.b64 [%0], %1;" :: "r"(a), "r"(c)); }
__device__ __forceinline__ void mbar_expect(uint32_t a, int bytes) { asm volatile("mbarrier.arrive.expect_tx.shared.b64 _, [%0], %1;" :: "r"(a), "r"(bytes) : "memory"); }
__device__ __forceinline__ void mbar_arrive(uint32_t a) { asm volatile("mbarrier.arrive.shared.b64 _, [%0];" :: "r"(a) : "memory"); }
__device__ __forceinline__ void mbar_wait(uint32_t a, int parity) {
    uint32_t done;
    int it = 0;
    do {
        asm volatile("{\n.reg .pred p;\nmbarrier.try_wait.parity.shared.b64 p, [%1], %2;\nselp.u32 %0, 1, 0, p;\n}"
                     : "=r"(done) : "r"(a), "r"(parity) : "memory");
        if (++it > (1 << 24)) __trap();
    } while (!done);
}
__device__ __forceinline__ void bulk_g2s(uint32_t dst, const void* src, int bytes, uint32_t bar) {
    asm volatile("cp.async.bulk.shared::cluster.global.mbarrier::complete_tx::bytes [%0], [%1], %2, [%3];"
                 :: "r"(dst), "l"(src), "r"(bytes), "r"(bar) : "memory");
}
__device__ __forceinline__ void tma2d(uint32_t dst, const CUtensorMap* m, int c0, int c1, uint32_t bar) {
    asm volatile("cp.async.bulk.tensor.2d.shared::cluster.global.mbarrier::complete_tx::bytes [%0], [%1, {%3, %4}], [%2];"
                 :: "r"(dst), "l"(m), "r"(bar), "r"(c0), "r"(c1) : "memory");
}
__device__ __forceinline__ void tma3d(uint32_t dst, const CUtensorMap* m, int c0, int c1, int c2, uint32_t bar) {
    asm volatile("cp.async.bulk.tensor.3d.shared::cluster.global.mbarrier::complete_tx::bytes [%0], [%1, {%3, %4, %5}], [%2];"
                 :: "r"(dst), "l"(m), "r"(bar), "r"(c0), "r"(c1), "r"(c2) : "memory");
}
__device__ __forceinline__ void prefetch_tmap(const CUtensorMap* m) { asm volatile("prefetch.tensormap [%0];" :: "l"(m) : "memory"); }
__device__ __forceinline__ void pdl_wait() { asm volatile("griddepcontrol.wait;" ::: "memory"); }
__device__ __forceinline__ void pdl_launch() { asm volatile("griddepcontrol.launch_dependents;" ::: "memory"); }
__device__ __forceinline__ void fence_barrier_init() { asm volatile("fence.mbarrier_init.release.cluster;" ::: "memory"); }
__device__ __forceinline__ void fence_proxy_async() { asm volatile("fence.proxy.async.shared::cta;" ::: "memory"); }
__device__ __forceinline__ uint64_t make_desc(uint32_t saddr, uint32_t lbo, uint32_t sbo, uint32_t swz) {
    return (uint64_t)((saddr & 0x3FFFF) >> 4) | ((uint64_t)((lbo & 0x3FFFF) >> 4) << 16) |
           ((uint64_t)((sbo & 0x3FFFF) >> 4) << 32) | ((uint64_t)swz << 62);
}
#define WG_FENCE() asm volatile("wgmma.fence.sync.aligned;" ::: "memory")
#define WG_COMMIT() asm volatile("wgmma.commit_group.sync.aligned;" ::: "memory")
template <int N> __device__ __forceinline__ void wg_wait() { asm volatile("wgmma.wait_group.sync.aligned %0;" :: "n"(N) : "memory"); }
template <int N> __device__ __forceinline__ void fence_regs(float (&d)[N]) {
#pragma unroll
    for (int i = 0; i < N; i++) asm volatile("" : "+f"(d[i]) :: "memory");
}
__device__ __forceinline__ float ex2f(float x) { float y; asm("ex2.approx.ftz.f32 %0, %1;" : "=f"(y) : "f"(x)); return y; }
__device__ __forceinline__ float tanh_fast(float x) { float y; asm("tanh.approx.f32 %0, %1;" : "=f"(y) : "f"(x)); return y; }
__device__ __forceinline__ uint32_t pack_bf16(float lo, float hi) { uint32_t r; asm("cvt.rn.bf16x2.f32 %0, %1, %2;" : "=r"(r) : "f"(hi), "f"(lo)); return r; }
__device__ __forceinline__ float bf_lo(uint32_t u) { return __uint_as_float(u << 16); }
__device__ __forceinline__ float bf_hi(uint32_t u) { return __uint_as_float(u & 0xFFFF0000u); }
__device__ __forceinline__ uint32_t hfma2(uint32_t a, uint32_t b, uint32_t c) { uint32_t r; asm("fma.rn.f16x2 %0, %1, %2, %3;" : "=r"(r) : "r"(a), "r"(b), "r"(c)); return r; }
__device__ __forceinline__ uint32_t hmul2(uint32_t a, uint32_t b) { uint32_t r; asm("mul.rn.f16x2 %0, %1, %2;" : "=r"(r) : "r"(a), "r"(b)); return r; }
__device__ __forceinline__ unsigned int ld_acquire(const unsigned int* p) { unsigned int v; asm volatile("ld.acquire.gpu.u32 %0, [%1];" : "=r"(v) : "l"(p) : "memory"); return v; }
__device__ __forceinline__ void red_release(unsigned int* p) { asm volatile("red.release.gpu.global.add.u32 [%0], 1;" :: "l"(p) : "memory"); }
__device__ __forceinline__ void stsm4(uint32_t addr, uint32_t a, uint32_t b, uint32_t c, uint32_t d) {
    asm volatile("stmatrix.sync.aligned.m8n8.x4.shared.b16 [%0], {%1,%2,%3,%4};" :: "r"(addr), "r"(a), "r"(b), "r"(c), "r"(d) : "memory");
}
__device__ __forceinline__ void bulk_s2g(void* dst, uint32_t src, int bytes) {
    asm volatile("cp.async.bulk.global.shared::cta.bulk_group [%0], [%1], %2;" :: "l"(dst), "r"(src), "r"(bytes) : "memory");
}
__device__ __forceinline__ void bulk_commit() { asm volatile("cp.async.bulk.commit_group;" ::: "memory"); }
__device__ __forceinline__ void bulk_wait_all() { asm volatile("cp.async.bulk.wait_group 0;" ::: "memory"); }
__device__ __forceinline__ void bulk_wait_read() { asm volatile("cp.async.bulk.wait_group.read 0;" ::: "memory"); }
__device__ __forceinline__ void bar_sync(int id, int n) { asm volatile("bar.sync %0, %1;" :: "r"(id), "r"(n) : "memory"); }
__device__ __forceinline__ void bar_arrive(int id, int n) { asm volatile("bar.arrive %0, %1;" :: "r"(id), "r"(n) : "memory"); }
__device__ __forceinline__ float warp_sum(float v) {
#pragma unroll
    for (int o = 16; o; o >>= 1) v += __shfl_xor_sync(0xffffffffu, v, o);
    return v;
}
__device__ __forceinline__ float warp_max(float v) {
#pragma unroll
    for (int o = 16; o; o >>= 1) v = fmaxf(v, __shfl_xor_sync(0xffffffffu, v, o));
    return v;
}

__device__ __forceinline__ void wgmma_ss_n64(float (&d)[32], uint64_t adesc, uint64_t bdesc, int scale_d) {
    asm volatile("{\n.reg .pred p;\nsetp.ne.b32 p, %34, 0;\n"
      "wgmma.mma_async.sync.aligned.m64n64k16.f32.bf16.bf16 {%0,%1,%2,%3,%4,%5,%6,%7,%8,%9,%10,%11,%12,%13,%14,%15,%16,%17,%18,%19,%20,%21,%22,%23,%24,%25,%26,%27,%28,%29,%30,%31}, %32, %33, p, 1, 1, 0, 1;\n}"
      : "+f"(d[0]), "+f"(d[1]), "+f"(d[2]), "+f"(d[3]), "+f"(d[4]), "+f"(d[5]), "+f"(d[6]), "+f"(d[7]), "+f"(d[8]), "+f"(d[9]), "+f"(d[10]), "+f"(d[11]), "+f"(d[12]), "+f"(d[13]), "+f"(d[14]), "+f"(d[15]), "+f"(d[16]), "+f"(d[17]), "+f"(d[18]), "+f"(d[19]), "+f"(d[20]), "+f"(d[21]), "+f"(d[22]), "+f"(d[23]), "+f"(d[24]), "+f"(d[25]), "+f"(d[26]), "+f"(d[27]), "+f"(d[28]), "+f"(d[29]), "+f"(d[30]), "+f"(d[31])
      : "l"(adesc), "l"(bdesc), "r"(scale_d));
}
__device__ __forceinline__ void wgmma_ss_n128(float (&d)[64], uint64_t adesc, uint64_t bdesc, int scale_d) {
    asm volatile("{\n.reg .pred p;\nsetp.ne.b32 p, %66, 0;\n"
      "wgmma.mma_async.sync.aligned.m64n128k16.f32.bf16.bf16 {%0,%1,%2,%3,%4,%5,%6,%7,%8,%9,%10,%11,%12,%13,%14,%15,%16,%17,%18,%19,%20,%21,%22,%23,%24,%25,%26,%27,%28,%29,%30,%31,%32,%33,%34,%35,%36,%37,%38,%39,%40,%41,%42,%43,%44,%45,%46,%47,%48,%49,%50,%51,%52,%53,%54,%55,%56,%57,%58,%59,%60,%61,%62,%63}, %64, %65, p, 1, 1, 0, 1;\n}"
      : "+f"(d[0]), "+f"(d[1]), "+f"(d[2]), "+f"(d[3]), "+f"(d[4]), "+f"(d[5]), "+f"(d[6]), "+f"(d[7]), "+f"(d[8]), "+f"(d[9]), "+f"(d[10]), "+f"(d[11]), "+f"(d[12]), "+f"(d[13]), "+f"(d[14]), "+f"(d[15]), "+f"(d[16]), "+f"(d[17]), "+f"(d[18]), "+f"(d[19]), "+f"(d[20]), "+f"(d[21]), "+f"(d[22]), "+f"(d[23]), "+f"(d[24]), "+f"(d[25]), "+f"(d[26]), "+f"(d[27]), "+f"(d[28]), "+f"(d[29]), "+f"(d[30]), "+f"(d[31]), "+f"(d[32]), "+f"(d[33]), "+f"(d[34]), "+f"(d[35]), "+f"(d[36]), "+f"(d[37]), "+f"(d[38]), "+f"(d[39]), "+f"(d[40]), "+f"(d[41]), "+f"(d[42]), "+f"(d[43]), "+f"(d[44]), "+f"(d[45]), "+f"(d[46]), "+f"(d[47]), "+f"(d[48]), "+f"(d[49]), "+f"(d[50]), "+f"(d[51]), "+f"(d[52]), "+f"(d[53]), "+f"(d[54]), "+f"(d[55]), "+f"(d[56]), "+f"(d[57]), "+f"(d[58]), "+f"(d[59]), "+f"(d[60]), "+f"(d[61]), "+f"(d[62]), "+f"(d[63])
      : "l"(adesc), "l"(bdesc), "r"(scale_d));
}
__device__ __forceinline__ void wgmma_ss_n192(float (&d)[96], uint64_t adesc, uint64_t bdesc, int scale_d) {
    asm volatile("{\n.reg .pred p;\nsetp.ne.b32 p, %98, 0;\n"
      "wgmma.mma_async.sync.aligned.m64n192k16.f32.bf16.bf16 {%0,%1,%2,%3,%4,%5,%6,%7,%8,%9,%10,%11,%12,%13,%14,%15,%16,%17,%18,%19,%20,%21,%22,%23,%24,%25,%26,%27,%28,%29,%30,%31,%32,%33,%34,%35,%36,%37,%38,%39,%40,%41,%42,%43,%44,%45,%46,%47,%48,%49,%50,%51,%52,%53,%54,%55,%56,%57,%58,%59,%60,%61,%62,%63,%64,%65,%66,%67,%68,%69,%70,%71,%72,%73,%74,%75,%76,%77,%78,%79,%80,%81,%82,%83,%84,%85,%86,%87,%88,%89,%90,%91,%92,%93,%94,%95}, %96, %97, p, 1, 1, 0, 1;\n}"
      : "+f"(d[0]), "+f"(d[1]), "+f"(d[2]), "+f"(d[3]), "+f"(d[4]), "+f"(d[5]), "+f"(d[6]), "+f"(d[7]), "+f"(d[8]), "+f"(d[9]), "+f"(d[10]), "+f"(d[11]), "+f"(d[12]), "+f"(d[13]), "+f"(d[14]), "+f"(d[15]), "+f"(d[16]), "+f"(d[17]), "+f"(d[18]), "+f"(d[19]), "+f"(d[20]), "+f"(d[21]), "+f"(d[22]), "+f"(d[23]), "+f"(d[24]), "+f"(d[25]), "+f"(d[26]), "+f"(d[27]), "+f"(d[28]), "+f"(d[29]), "+f"(d[30]), "+f"(d[31]), "+f"(d[32]), "+f"(d[33]), "+f"(d[34]), "+f"(d[35]), "+f"(d[36]), "+f"(d[37]), "+f"(d[38]), "+f"(d[39]), "+f"(d[40]), "+f"(d[41]), "+f"(d[42]), "+f"(d[43]), "+f"(d[44]), "+f"(d[45]), "+f"(d[46]), "+f"(d[47]), "+f"(d[48]), "+f"(d[49]), "+f"(d[50]), "+f"(d[51]), "+f"(d[52]), "+f"(d[53]), "+f"(d[54]), "+f"(d[55]), "+f"(d[56]), "+f"(d[57]), "+f"(d[58]), "+f"(d[59]), "+f"(d[60]), "+f"(d[61]), "+f"(d[62]), "+f"(d[63]), "+f"(d[64]), "+f"(d[65]), "+f"(d[66]), "+f"(d[67]), "+f"(d[68]), "+f"(d[69]), "+f"(d[70]), "+f"(d[71]), "+f"(d[72]), "+f"(d[73]), "+f"(d[74]), "+f"(d[75]), "+f"(d[76]), "+f"(d[77]), "+f"(d[78]), "+f"(d[79]), "+f"(d[80]), "+f"(d[81]), "+f"(d[82]), "+f"(d[83]), "+f"(d[84]), "+f"(d[85]), "+f"(d[86]), "+f"(d[87]), "+f"(d[88]), "+f"(d[89]), "+f"(d[90]), "+f"(d[91]), "+f"(d[92]), "+f"(d[93]), "+f"(d[94]), "+f"(d[95])
      : "l"(adesc), "l"(bdesc), "r"(scale_d));
}
__device__ __forceinline__ void wgmma_ss_n256(float (&d)[128], uint64_t adesc, uint64_t bdesc, int scale_d) {
    asm volatile("{\n.reg .pred p;\nsetp.ne.b32 p, %130, 0;\n"
      "wgmma.mma_async.sync.aligned.m64n256k16.f32.bf16.bf16 {%0,%1,%2,%3,%4,%5,%6,%7,%8,%9,%10,%11,%12,%13,%14,%15,%16,%17,%18,%19,%20,%21,%22,%23,%24,%25,%26,%27,%28,%29,%30,%31,%32,%33,%34,%35,%36,%37,%38,%39,%40,%41,%42,%43,%44,%45,%46,%47,%48,%49,%50,%51,%52,%53,%54,%55,%56,%57,%58,%59,%60,%61,%62,%63,%64,%65,%66,%67,%68,%69,%70,%71,%72,%73,%74,%75,%76,%77,%78,%79,%80,%81,%82,%83,%84,%85,%86,%87,%88,%89,%90,%91,%92,%93,%94,%95,%96,%97,%98,%99,%100,%101,%102,%103,%104,%105,%106,%107,%108,%109,%110,%111,%112,%113,%114,%115,%116,%117,%118,%119,%120,%121,%122,%123,%124,%125,%126,%127}, %128, %129, p, 1, 1, 0, 1;\n}"
      : "+f"(d[0]), "+f"(d[1]), "+f"(d[2]), "+f"(d[3]), "+f"(d[4]), "+f"(d[5]), "+f"(d[6]), "+f"(d[7]), "+f"(d[8]), "+f"(d[9]), "+f"(d[10]), "+f"(d[11]), "+f"(d[12]), "+f"(d[13]), "+f"(d[14]), "+f"(d[15]), "+f"(d[16]), "+f"(d[17]), "+f"(d[18]), "+f"(d[19]), "+f"(d[20]), "+f"(d[21]), "+f"(d[22]), "+f"(d[23]), "+f"(d[24]), "+f"(d[25]), "+f"(d[26]), "+f"(d[27]), "+f"(d[28]), "+f"(d[29]), "+f"(d[30]), "+f"(d[31]), "+f"(d[32]), "+f"(d[33]), "+f"(d[34]), "+f"(d[35]), "+f"(d[36]), "+f"(d[37]), "+f"(d[38]), "+f"(d[39]), "+f"(d[40]), "+f"(d[41]), "+f"(d[42]), "+f"(d[43]), "+f"(d[44]), "+f"(d[45]), "+f"(d[46]), "+f"(d[47]), "+f"(d[48]), "+f"(d[49]), "+f"(d[50]), "+f"(d[51]), "+f"(d[52]), "+f"(d[53]), "+f"(d[54]), "+f"(d[55]), "+f"(d[56]), "+f"(d[57]), "+f"(d[58]), "+f"(d[59]), "+f"(d[60]), "+f"(d[61]), "+f"(d[62]), "+f"(d[63]), "+f"(d[64]), "+f"(d[65]), "+f"(d[66]), "+f"(d[67]), "+f"(d[68]), "+f"(d[69]), "+f"(d[70]), "+f"(d[71]), "+f"(d[72]), "+f"(d[73]), "+f"(d[74]), "+f"(d[75]), "+f"(d[76]), "+f"(d[77]), "+f"(d[78]), "+f"(d[79]), "+f"(d[80]), "+f"(d[81]), "+f"(d[82]), "+f"(d[83]), "+f"(d[84]), "+f"(d[85]), "+f"(d[86]), "+f"(d[87]), "+f"(d[88]), "+f"(d[89]), "+f"(d[90]), "+f"(d[91]), "+f"(d[92]), "+f"(d[93]), "+f"(d[94]), "+f"(d[95]), "+f"(d[96]), "+f"(d[97]), "+f"(d[98]), "+f"(d[99]), "+f"(d[100]), "+f"(d[101]), "+f"(d[102]), "+f"(d[103]), "+f"(d[104]), "+f"(d[105]), "+f"(d[106]), "+f"(d[107]), "+f"(d[108]), "+f"(d[109]), "+f"(d[110]), "+f"(d[111]), "+f"(d[112]), "+f"(d[113]), "+f"(d[114]), "+f"(d[115]), "+f"(d[116]), "+f"(d[117]), "+f"(d[118]), "+f"(d[119]), "+f"(d[120]), "+f"(d[121]), "+f"(d[122]), "+f"(d[123]), "+f"(d[124]), "+f"(d[125]), "+f"(d[126]), "+f"(d[127])
      : "l"(adesc), "l"(bdesc), "r"(scale_d));
}
__device__ __forceinline__ void qk_wgmma_n64(float (&d)[32], const uint32_t (&a)[4], uint64_t desc) {
    asm volatile("wgmma.mma_async.sync.aligned.m64n64k16.f32.bf16.bf16 {%0,%1,%2,%3,%4,%5,%6,%7,%8,%9,%10,%11,%12,%13,%14,%15,%16,%17,%18,%19,%20,%21,%22,%23,%24,%25,%26,%27,%28,%29,%30,%31}, {%32,%33,%34,%35}, %36, 0, 1, 1, 0;"
      : "=f"(d[0]), "=f"(d[1]), "=f"(d[2]), "=f"(d[3]), "=f"(d[4]), "=f"(d[5]), "=f"(d[6]), "=f"(d[7]), "=f"(d[8]), "=f"(d[9]), "=f"(d[10]), "=f"(d[11]), "=f"(d[12]), "=f"(d[13]), "=f"(d[14]), "=f"(d[15]), "=f"(d[16]), "=f"(d[17]), "=f"(d[18]), "=f"(d[19]), "=f"(d[20]), "=f"(d[21]), "=f"(d[22]), "=f"(d[23]), "=f"(d[24]), "=f"(d[25]), "=f"(d[26]), "=f"(d[27]), "=f"(d[28]), "=f"(d[29]), "=f"(d[30]), "=f"(d[31])
      : "r"(a[0]), "r"(a[1]), "r"(a[2]), "r"(a[3]), "l"(desc));
}

__device__ __forceinline__ void pv_wgmma(float (&d)[12], uint32_t a0, uint32_t a1, uint32_t a2, uint32_t a3, uint64_t desc) {
    asm volatile("wgmma.mma_async.sync.aligned.m64n24k16.f32.bf16.bf16 {%0,%1,%2,%3,%4,%5,%6,%7,%8,%9,%10,%11}, {%12,%13,%14,%15}, %16, 1, 1, 1, 1;"
      : "+f"(d[0]), "+f"(d[1]), "+f"(d[2]), "+f"(d[3]), "+f"(d[4]), "+f"(d[5]), "+f"(d[6]), "+f"(d[7]), "+f"(d[8]), "+f"(d[9]), "+f"(d[10]), "+f"(d[11])
      : "r"(a0), "r"(a1), "r"(a2), "r"(a3), "l"(desc));
}

__device__ __forceinline__ uint32_t mapa(uint32_t a, uint32_t rank) { uint32_t r; asm("mapa.shared::cluster.u32 %0, %1, %2;" : "=r"(r) : "r"(a), "r"(rank)); return r; }
__device__ __forceinline__ void mbar_arrive_remote(uint32_t a) { asm volatile("mbarrier.arrive.relaxed.cluster.shared::cluster.b64 _, [%0];" :: "r"(a) : "memory"); }
__device__ __forceinline__ void mbar_wait_cluster(uint32_t a, int parity) {
    uint32_t done;
    int it = 0;
    do {
        asm volatile("{\n.reg .pred p;\nmbarrier.try_wait.parity.acquire.cluster.shared::cta.b64 p, [%1], %2;\nselp.u32 %0, 1, 0, p;\n}"
                     : "=r"(done) : "r"(a), "r"(parity) : "memory");
        if (++it > (1 << 24)) __trap();
    } while (!done);
}
__device__ __forceinline__ void tma2d_mc(uint32_t dst, const CUtensorMap* m, int c0, int c1, uint32_t bar) {
    asm volatile("cp.async.bulk.tensor.2d.shared::cluster.global.mbarrier::complete_tx::bytes.multicast::cluster [%0], [%1, {%3, %4}], [%2], %5;"
                 :: "r"(dst), "l"(m), "r"(bar), "r"(c0), "r"(c1), "h"((uint16_t)3) : "memory");
}
__device__ __forceinline__ void bulk_g2s_mc(uint32_t dst, const void* src, int bytes, uint32_t bar) {
    asm volatile("cp.async.bulk.shared::cluster.global.mbarrier::complete_tx::bytes.multicast::cluster [%0], [%1], %2, [%3], %4;"
                 :: "r"(dst), "l"(src), "r"(bytes), "r"(bar), "h"((uint16_t)3) : "memory");
}
__device__ __forceinline__ void tile_of(int bid, int& mb, int& nt) {
    int grp = bid >> 4, in = bid & 15;
    mb = (grp >> 1) * 4 + (in >> 2);
    nt = (grp & 1) * 4 + (in & 3);
}

constexpr int K1_STAGES = 5, K1_STAGE = 16384 + 24576;
constexpr int K1_BAR = K1_STAGES * K1_STAGE, K1_RS = K1_BAR + 128, K1_CS = K1_RS + 1024, K1_SMEM = K1_CS + 768;

__device__ __forceinline__ float2 row_stats_regs(uint4 a, uint4 b) {
    float v[16];
    v[0] = bf_lo(a.x); v[1] = bf_hi(a.x); v[2] = bf_lo(a.y); v[3] = bf_hi(a.y);
    v[4] = bf_lo(a.z); v[5] = bf_hi(a.z); v[6] = bf_lo(a.w); v[7] = bf_hi(a.w);
    v[8] = bf_lo(b.x); v[9] = bf_hi(b.x); v[10] = bf_lo(b.y); v[11] = bf_hi(b.y);
    v[12] = bf_lo(b.z); v[13] = bf_hi(b.z); v[14] = bf_lo(b.w); v[15] = bf_hi(b.w);
    float s = 0.f;
#pragma unroll
    for (int i = 0; i < 16; i++) s += v[i];
    float mean = warp_sum(s) * (1.0f / DM);
    float q = 0.f;
#pragma unroll
    for (int i = 0; i < 16; i++) { float d = v[i] - mean; q = fmaf(d, d, q); }
    float var = warp_sum(q) * (1.0f / DM);
    float rstd = rsqrtf(var + 1e-5f);
    return make_float2(rstd, -mean * rstd);
}
__device__ __forceinline__ float2 row_stats_x(const __nv_bfloat16* x, int row, int lane) {
    const uint4* p = (const uint4*)(x + (size_t)row * DM);
    return row_stats_regs(__ldg(p + lane), __ldg(p + 32 + lane));
}
__device__ __forceinline__ void colsum8(const __nv_bfloat16* w, int ld, int col, int k0, int nk, float (&s)[8]) {
#pragma unroll
    for (int i = 0; i < 8; i++) s[i] = 0.f;
    for (int k = k0; k < k0 + nk; k += 8) {
        uint4 u[8];
#pragma unroll
        for (int i = 0; i < 8; i++) u[i] = __ldg((const uint4*)(w + (size_t)(k + i) * ld + col));
#pragma unroll
        for (int i = 0; i < 8; i++) {
            s[0] += bf_lo(u[i].x); s[1] += bf_hi(u[i].x); s[2] += bf_lo(u[i].y); s[3] += bf_hi(u[i].y);
            s[4] += bf_lo(u[i].z); s[5] += bf_hi(u[i].z); s[6] += bf_lo(u[i].w); s[7] += bf_hi(u[i].w);
        }
    }
}
__device__ __forceinline__ bool wait_count(const unsigned int* p, unsigned int target, int lane) {
    int ok = 1;
    if (lane == 0) {
        int it = 0;
        while (ld_acquire(p) < target) { if (++it > (1 << 18)) { ok = 0; break; } }
    }
    ok = __shfl_sync(0xffffffffu, ok, 0);
    return ok != 0;
}

__global__ void __launch_bounds__(384, 1)
qkv_kernel(const __grid_constant__ CUtensorMap tm_x, const __grid_constant__ CUtensorMap tm_w,
           const __nv_bfloat16* __restrict__ x, const __nv_bfloat16* __restrict__ wqkv) {
    extern __shared__ __align__(1024) unsigned char smem[];
    const uint32_t sb = smem_u32(smem);
    const int tid = threadIdx.x, warp = __shfl_sync(0xffffffffu, tid >> 5, 0), lane = tid & 31;
    TLDECL
    TL(0);
    int mb, nt;
    tile_of(blockIdx.x, mb, nt);
    const uint32_t full = sb + K1_BAR, empty = full + 40, auxb = full + 80;
    if (tid == 0) {
        prefetch_tmap(&tm_x); prefetch_tmap(&tm_w);
        for (int i = 0; i < K1_STAGES; i++) { mbar_init(full + 8 * i, 1); mbar_init(empty + 8 * i, 8); }
        mbar_init(auxb, 3);
        fence_barrier_init();
    }
    __syncthreads();
    pdl_launch();
    if (warp == 0) {
        if (blockIdx.x == 0) for (int i = lane; i < 160; i += 32) g_cnt2[i] = 0;
        if (lane == 0) {
            for (int kb = 0; kb < 8; kb++) {
                int s = kb % K1_STAGES;
                if (kb >= K1_STAGES) mbar_wait(empty + 8 * s, 0);
                mbar_expect(full + 8 * s, K1_STAGE);
                tma2d(sb + s * K1_STAGE, &tm_x, kb * 64, mb * 128, full + 8 * s);
                tma3d(sb + s * K1_STAGE + 16384, &tm_w, 0, kb * 64, nt * 3, full + 8 * s);
            }
        }
    } else if (warp < 4) {
        float2* s_rs = (float2*)(smem + K1_RS);
        float* s_cs = (float*)(smem + K1_CS);
        if (warp < 3) {
            const int r0 = mb * 128 + nt * 16 + (warp - 1) * 8;
            uint4 u[16];
#pragma unroll
            for (int i = 0; i < 8; i++) {
                const uint4* p = (const uint4*)(x + (size_t)(r0 + i) * DM);
                u[2 * i] = __ldg(p + lane); u[2 * i + 1] = __ldg(p + 32 + lane);
            }
            float2 mine = make_float2(0.f, 0.f);
#pragma unroll
            for (int i = 0; i < 8; i++) {
                float2 st = row_stats_regs(u[2 * i], u[2 * i + 1]);
                if (lane == i) mine = st;
            }
            if (lane < 8) g_rowstat1[r0 + lane] = mine;
            __syncwarp();
            if (lane == 0) red_release(&g_cnt[mb]);
        } else {
            uint4 u[24];
#pragma unroll
            for (int c = 0; c < 3; c++)
#pragma unroll
                for (int i = 0; i < 8; i++)
                    u[c * 8 + i] = __ldg((const uint4*)(wqkv + (size_t)(mb * 32 + (lane >> 3) * 8 + i) * 1536 + nt * 192 + (c * 8 + (lane & 7)) * 8));
#pragma unroll
            for (int c = 0; c < 3; c++) {
                float cs[8];
#pragma unroll
                for (int i = 0; i < 8; i++) cs[i] = 0.f;
#pragma unroll
                for (int i = 0; i < 8; i++) {
                    const uint4 w = u[c * 8 + i];
                    cs[0] += bf_lo(w.x); cs[1] += bf_hi(w.x); cs[2] += bf_lo(w.y); cs[3] += bf_hi(w.y);
                    cs[4] += bf_lo(w.z); cs[5] += bf_hi(w.z); cs[6] += bf_lo(w.w); cs[7] += bf_hi(w.w);
                }
#pragma unroll
                for (int i = 0; i < 8; i++) {
                    cs[i] += __shfl_xor_sync(0xffffffffu, cs[i], 8);
                    cs[i] += __shfl_xor_sync(0xffffffffu, cs[i], 16);
                }
                if (lane < 8) {
                    float4* d = (float4*)(g_cs1_part + mb * 1536 + nt * 192 + (c * 8 + lane) * 8);
                    d[0] = make_float4(cs[0], cs[1], cs[2], cs[3]);
                    d[1] = make_float4(cs[4], cs[5], cs[6], cs[7]);
                }
            }
            __syncwarp();
            if (lane == 0) red_release(&g_cnt[16 + nt]);
        }
        TX(8 + warp);
        if (warp == 1) {
            if (wait_count(&g_cnt[mb], 16, lane)) {
#pragma unroll
                for (int i = 0; i < 4; i++) s_rs[lane + 32 * i] = __ldcg(&g_rowstat1[mb * 128 + lane + 32 * i]);
            } else {
                for (int i = 0; i < 128; i++) {
                    float2 st = row_stats_x(x, mb * 128 + i, lane);
                    if (lane == 0) s_rs[i] = st;
                }
            }
        } else {
            int c0 = (warp - 2) * 96;
            if (wait_count(&g_cnt[16 + nt], 16, lane)) {
#pragma unroll
                for (int i = 0; i < 3; i++) {
                    float s = 0.f;
#pragma unroll
                    for (int p = 0; p < 16; p++) s += __ldcg(&g_cs1_part[p * 1536 + nt * 192 + c0 + lane + 32 * i]);
                    s_cs[c0 + lane + 32 * i] = s;
                }
            } else if (lane < 12) {
                float s[8];
                colsum8(wqkv, 1536, nt * 192 + c0 + lane * 8, 0, 512, s);
#pragma unroll
                for (int i = 0; i < 8; i++) s_cs[c0 + lane * 8 + i] = s[i];
            }
        }
        __syncwarp();
        TX(12 + warp);
        if (lane == 0) mbar_arrive(auxb);
        bar_sync(2, 256 + 96);
        const int a = tid - 32;
        {
            const int hh = a >> 3, w = a & 7;
            const float4* p = (const float4*)(smem + 49152) + (hh * 256 + w * 32) / 2;
            float m = 0.f;
#pragma unroll
            for (int i = 0; i < 8; i++) {
                const int ii = (i + a) & 7;
                float4 u = p[2 * ii], v = p[2 * ii + 1];
                float n0 = u.x + u.z + v.x + v.z, n1 = u.y + u.w + v.y + v.w;
                if (!(n0 <= 3.0e38f) || !(n1 <= 3.0e38f)) m = __int_as_float(0x7f800000);
                m = fmaxf(m, fmaxf(n0, n1));
            }
            const int col0 = nt * 192 + hh * 16;
            g_nrm[((col0 >> 9) * NH + ((col0 & 511) >> 4)) * 128 + mb * 8 + w] = m;
        }
        if (a < 24) bulk_wait_all();
        TL(27);
        TLDUMP;
    } else {
        const int wgi = (warp >> 2) - 1, ww = warp & 3;
        float acc[96];
#pragma unroll 1
        for (int kb = 0; kb < 8; kb++) {
            int s = kb % K1_STAGES;
            mbar_wait(full + 8 * s, (kb / K1_STAGES) & 1);
            if (warp == 4) TX(kb);
            uint64_t ad = make_desc(sb + s * K1_STAGE + wgi * 8192, 16, 1024, 1);
            uint64_t bd = make_desc(sb + s * K1_STAGE + 16384, 8192, 1024, 1);
            WG_FENCE();
#pragma unroll
            for (int k = 0; k < 4; k++) wgmma_ss_n192(acc, ad + k * 2, bd + k * 128, (kb | k) != 0);
            WG_COMMIT();
            if (kb > 0) {
                wg_wait<1>();
                if (lane == 0) mbar_arrive(empty + 8 * ((kb - 1) % K1_STAGES));
            }
        }
        wg_wait<0>();
        fence_regs(acc);
        TL(1);
        if (warp == 4) TX(16);
        mbar_wait(auxb, 0);
        if (warp == 4) TX(17);
        bar_sync(1, 256);
        const float2* s_rs = (const float2*)(smem + K1_RS);
        const float* s_cs = (const float*)(smem + K1_CS);
        const int g = lane >> 2, t = lane & 3;
        const int rl = wgi * 64 + ww * 16 + g;
        const float2 st0 = s_rs[rl], st1 = s_rs[rl + 8];
        const float QS = 0.25f * 1.4426950408889634f;
        const uint32_t stg = sb + ((lane >> 4) * 16 + wgi * 8 + ww * 2 + ((lane >> 3) & 1)) * 128 + (lane & 7) * 16;
        float2* s_np = (float2*)(smem + 49152) + (warp - 4) * 32 + lane;
#pragma unroll
        for (int hh = 0; hh < 12; hh++) {
            const int which = (nt * 192 + hh * 16) >> 9;
            const float sc = (which == 0) ? QS : 1.0f;
            const float a0 = st0.x * sc, b0 = st0.y * sc, a1 = st1.x * sc, b1 = st1.y * sc;
            const float2 c0 = *(const float2*)(s_cs + 16 * hh + 2 * t), c1 = *(const float2*)(s_cs + 16 * hh + 8 + 2 * t);
            const float* a = acc + 8 * hh;
            float v0 = fmaf(a0, a[0], b0 * c0.x), v1 = fmaf(a0, a[1], b0 * c0.y), v2 = fmaf(a1, a[2], b1 * c0.x), v3 = fmaf(a1, a[3], b1 * c0.y);
            float v4 = fmaf(a0, a[4], b0 * c1.x), v5 = fmaf(a0, a[5], b0 * c1.y), v6 = fmaf(a1, a[6], b1 * c1.x), v7 = fmaf(a1, a[7], b1 * c1.y);
            {
                const int head = ((nt * 192 + hh * 16) & 511) >> 4;
                uint32_t* o = (uint32_t*)g_qkv + ((size_t)((which * NH + head) * 2) * 256 + mb * 16 + wgi * 8 + ww * 2) * 32 + lane;
                o[0] = pack_bf16(v0, v1); o[32] = pack_bf16(v2, v3); o[8192] = pack_bf16(v4, v5); o[8192 + 32] = pack_bf16(v6, v7);
            }
            s_np[hh * 256] = make_float2(fmaf(v0, v0, fmaf(v1, v1, fmaf(v4, v4, v5 * v5))), fmaf(v2, v2, fmaf(v3, v3, fmaf(v6, v6, v7 * v7))));
        }
        fence_proxy_async();
        bar_arrive(2, 256 + 96);
        TL(2);
        TLDUMP;
    }
}

constexpr int AT_K = 0, AT_V = 65536, AT_ONES = 131072, AT_BAR = 163840, AT_SMEM = AT_BAR + 128;
#define POLY_MASK 0xAD6A

__device__ __forceinline__ uint32_t exp2_pair_poly(float x0, float x1) {
    uint32_t t0 = __float_as_uint(x0 + 32895.0f);
    uint32_t t1 = __float_as_uint(x1 + 32895.0f);
    uint32_t gd = __byte_perm(t0, t1, 0x6420);
    uint32_t wm = __byte_perm(t0, t1, 0x5612);
    uint32_t v = hfma2(gd, 0x71477147u, 0x354f354fu);
    uint32_t z = hmul2(v, gd);
    return (wm >> 1) + z;
}
__device__ __forceinline__ uint32_t exp2_pair_mufu(float x0, float x1) { return pack_bf16(ex2f(x0), ex2f(x1)); }
template <uint32_t MASK>
__device__ __forceinline__ void exp_blocks(const float (&s)[32], uint32_t (&p)[16]) {
#pragma unroll
    for (int b = 0; b < 8; b++) {
        if ((MASK >> b) & 1) {
            p[2 * b] = exp2_pair_poly(s[4 * b], s[4 * b + 1]);
            p[2 * b + 1] = exp2_pair_poly(s[4 * b + 2], s[4 * b + 3]);
        } else {
            p[2 * b] = exp2_pair_mufu(s[4 * b], s[4 * b + 1]);
            p[2 * b + 1] = exp2_pair_mufu(s[4 * b + 2], s[4 * b + 3]);
        }
    }
}
#define PV4(P) _Pragma("unroll") for (int i = 0; i < 4; i++) { pv_wgmma(o, P[4 * i], P[4 * i + 1], P[4 * i + 2], P[4 * i + 3], vd); vd += 16; }

__device__ __forceinline__ void attn_store(float (&o)[12], int row0, int head, int lane) {
    float l0 = __shfl_sync(0xffffffffu, o[8], lane & 28);
    float l1 = __shfl_sync(0xffffffffu, o[10], lane & 28);
    float r0 = 1.0f / l0, r1 = 1.0f / l1;
    uint32_t* op = (uint32_t*)g_ao;
    int mb = row0 >> 7, rg = (row0 & 127) >> 3;
    int kb = head >> 2, kc = (head & 3) * 2;
    size_t base = (((size_t)(mb * 8 + kb) * 8 + kc) * 16 + rg) * 32 + lane;
    op[base] = pack_bf16(o[0] * r0, o[1] * r0);
    op[base + 32] = pack_bf16(o[2] * r1, o[3] * r1);
    op[base + 16 * 32] = pack_bf16(o[4] * r0, o[5] * r0);
    op[base + 16 * 32 + 32] = pack_bf16(o[6] * r1, o[7] * r1);
}

__device__ __forceinline__ void attn_load_q(uint32_t (&q)[4], const __nv_bfloat16* gq, int row0, int lane) {
    const uint32_t* qp = (const uint32_t*)gq;
    int j0 = row0 >> 3;
    q[0] = __ldcg(qp + (0 * 256 + j0) * 32 + lane);
    q[1] = __ldcg(qp + (0 * 256 + j0 + 1) * 32 + lane);
    q[2] = __ldcg(qp + (1 * 256 + j0) * 32 + lane);
    q[3] = __ldcg(qp + (1 * 256 + j0 + 1) * 32 + lane);
}

__device__ __forceinline__ void attn_tile_safe(const uint32_t (&q)[4], uint64_t kd, uint64_t vd, int row0, int head, int lane) {
    float o[12];
#pragma unroll
    for (int i = 0; i < 12; i++) o[i] = 0.f;
    float m0 = -INFINITY, m1 = -INFINITY;
    fence_regs(o);
#pragma unroll 1
    for (int j = 0; j < 32; j++) {
        float s[32];
        uint32_t p[16];
        WG_FENCE();
        qk_wgmma_n64(s, q, kd); kd += 64;
        WG_COMMIT();
        wg_wait<0>();
        fence_regs(s);
        fence_regs(o);
        float x0 = m0, x1 = m1;
#pragma unroll
        for (int b = 0; b < 8; b++) {
            x0 = fmaxf(x0, fmaxf(s[4 * b], s[4 * b + 1]));
            x1 = fmaxf(x1, fmaxf(s[4 * b + 2], s[4 * b + 3]));
        }
        x0 = fmaxf(x0, __shfl_xor_sync(0xffffffffu, x0, 1)); x0 = fmaxf(x0, __shfl_xor_sync(0xffffffffu, x0, 2));
        x1 = fmaxf(x1, __shfl_xor_sync(0xffffffffu, x1, 1)); x1 = fmaxf(x1, __shfl_xor_sync(0xffffffffu, x1, 2));
        float al0 = ex2f(m0 - x0), al1 = ex2f(m1 - x1);
        m0 = x0; m1 = x1;
#pragma unroll
        for (int i = 0; i < 3; i++) { o[4 * i] *= al0; o[4 * i + 1] *= al0; o[4 * i + 2] *= al1; o[4 * i + 3] *= al1; }
#pragma unroll
        for (int b = 0; b < 8; b++) {
            p[2 * b] = exp2_pair_mufu(s[4 * b] - m0, s[4 * b + 1] - m0);
            p[2 * b + 1] = exp2_pair_mufu(s[4 * b + 2] - m1, s[4 * b + 3] - m1);
        }
        fence_regs(o);
        WG_FENCE();
        PV4(p);
        WG_COMMIT();
        wg_wait<0>();
        fence_regs(o);
    }
    attn_store(o, row0, head, lane);
}

__global__ void __launch_bounds__(512, 1)
attn_kernel(const __nv_bfloat16* __restrict__ wg_, const __nv_bfloat16* __restrict__ wu_,
            const __nv_bfloat16* __restrict__ wo_, const __nv_bfloat16* __restrict__ wd_) {
    extern __shared__ __align__(1024) unsigned char smem[];
    const uint32_t sb = smem_u32(smem);
    const int tid = threadIdx.x, wg = tid >> 7, warp = (tid >> 5) & 3, lane = tid & 31;
    TLDECL
    pdl_launch();
    if (blockIdx.x >= 128) {
        const int e = blockIdx.x - 128;
        const __nv_bfloat16* w = (e < 2) ? wg_ : wu_;
        float* red = (float*)smem;
        const int cgrp = tid & 127, kq = tid >> 7;
        if (cgrp < 112) {
            float s[8];
            colsum8(w, FF, (e & 1) * 896 + cgrp * 8, kq * 128, 128, s);
#pragma unroll
            for (int i = 0; i < 8; i++) red[kq * 896 + cgrp * 8 + i] = s[i];
        }
        __syncthreads();
        for (int c = tid; c < 896; c += 512)
            g_cs2[(e >> 1) * FF + (e & 1) * 896 + c] = red[c] + red[896 + c] + red[1792 + c] + red[2688 + c];
        if (tid < 32) {
            const char* p0 = (const char*)wo_ + e * (DM * DM * 2 / 4);
            for (int i = lane; i < 32; i += 32)
                asm volatile("cp.async.bulk.prefetch.L2.global [%0], %1;" :: "l"(p0 + i * 4096), "r"(4096) : "memory");
            const char* p1 = (const char*)wd_ + e * (FF * DM * 2 / 4);
            for (int i = lane; i < 112; i += 32)
                asm volatile("cp.async.bulk.prefetch.L2.global [%0], %1;" :: "l"(p1 + i * 4096), "r"(4096) : "memory");
        }
        return;
    }
    const int head = blockIdx.x >> 2, qq = blockIdx.x & 3;
    const __nv_bfloat16* gq = g_qkv + (size_t)head * (S_LEN * 16);
    const __nv_bfloat16* gk = g_qkv + (size_t)(NH + head) * (S_LEN * 16);
    const __nv_bfloat16* gv = g_qkv + (size_t)(2 * NH + head) * (S_LEN * 16);
    if (tid == 0) {
        for (int i = 0; i < 8; i++) mbar_init(sb + AT_BAR + 8 * i, 1);
        fence_barrier_init();
    }
    {
        uint4 one = make_uint4(0x00003F80u, 0, 0, 0);
#pragma unroll
        for (int i = 0; i < 4; i++) *(uint4*)(smem + AT_ONES + (i * 512 + tid) * 16) = one;
        fence_proxy_async();
    }
    __syncthreads();
    TL(3);
    pdl_wait();
    TL(4);
    auto load_kv = [&](int i) {
        uint32_t bar = sb + AT_BAR + 8 * i;
        mbar_expect(bar, 16384);
        bulk_g2s(sb + AT_K + i * 4096, gk + i * 2048, 4096, bar);
        bulk_g2s(sb + AT_K + 32768 + i * 4096, gk + 16384 + i * 2048, 4096, bar);
        bulk_g2s(sb + AT_V + i * 4096, gv + i * 2048, 4096, bar);
        bulk_g2s(sb + AT_V + 32768 + i * 4096, gv + 16384 + i * 2048, 4096, bar);
    };
    if (tid == 0) { load_kv(0); load_kv(1); }
    uint32_t q[4], q2[4];
    attn_load_q(q, gq, qq * 512 + wg * 64 + warp * 16, lane);
    attn_load_q(q2, gq, qq * 512 + (4 + wg) * 64 + warp * 16, lane);
    bool fast;
    {
        const float* nq = g_nrm + (0 * NH + head) * 128 + qq * 32;
        const float* nk = g_nrm + (1 * NH + head) * 128;
        const float* nv = g_nrm + (2 * NH + head) * 128;
        float4 k4 = __ldcg((const float4*)nk + lane), v4 = __ldcg((const float4*)nv + lane);
        float qm = warp_max(__ldcg(nq + lane));
        float km = warp_max(fmaxf(fmaxf(k4.x, k4.y), fmaxf(k4.z, k4.w)));
        float vm = warp_max(fmaxf(fmaxf(v4.x, v4.y), fmaxf(v4.z, v4.w)));
        fast = __all_sync(0xffffffffu, (qm * km <= 3500.0f) && (vm <= 1.0e24f));
    }
    TL(24);
    const uint64_t kdesc0 = make_desc(sb + AT_K, 32768, 128, 0);
    const uint64_t vdesc0 = make_desc(sb + AT_V, 128, 32768, 0);
    if (!fast) {
        if (tid == 0) for (int i = 2; i < 8; i++) load_kv(i);
        for (int i = 0; i < 8; i++) mbar_wait(sb + AT_BAR + 8 * i, 0);
#pragma unroll 1
        for (int tile = 0; tile < 2; tile++) {
            const int row0 = qq * 512 + (tile * 4 + wg) * 64 + warp * 16;
            attn_tile_safe(q, kdesc0, vdesc0, row0, head, lane);
#pragma unroll
            for (int i = 0; i < 4; i++) q[i] = q2[i];
        }
        return;
    }
#pragma unroll 1
    for (int tile = 0; tile < 2; tile++) {
        const int row0 = qq * 512 + (tile * 4 + wg) * 64 + warp * 16;
        float o[12];
#pragma unroll
        for (int i = 0; i < 12; i++) o[i] = 0.f;
        fence_regs(o);
        float sa[32];
        uint32_t pa[16];
        uint64_t kd = kdesc0, vd = vdesc0;
        if (tile == 0) { mbar_wait(sb + AT_BAR, 0); TL(25); }
        WG_FENCE();
        qk_wgmma_n64(sa, q, kd); kd += 64;
        WG_COMMIT();
#pragma unroll 1
        for (int jj = 0; jj < 8; jj++) {
            if (tile == 0 && jj < 7) {
                if (tid == 0 && jj < 6) load_kv(jj + 2);
                mbar_wait(sb + AT_BAR + 8 * (jj + 1), 0);
            }
            if (wg == 0 && warp == 0) TX(128 + tile * 8 + jj);
#pragma unroll
            for (int j = 0; j < 4; j++) {
                wg_wait<0>();
                fence_regs(sa);
                if (j & 1) exp_blocks<(POLY_MASK >> 8)>(sa, pa); else exp_blocks<(POLY_MASK & 255)>(sa, pa);
                WG_FENCE();
                qk_wgmma_n64(sa, q, kd); kd += 64;
                PV4(pa);
                WG_COMMIT();
            }
        }
        wg_wait<0>();
        fence_regs(o);
        fence_regs(sa);
        if (tile == 0) TL(26);
        attn_store(o, row0, head, lane);
#pragma unroll
        for (int i = 0; i < 4; i++) q[i] = q2[i];
    }
    TL(5);
    TLDUMP;
}

#define DELAYC 9
constexpr int F_R2 = 131072, F_X = 196608, F_BAR = 229376;
constexpr int F_RS = F_BAR + 256, F_CS = F_RS + 1024, F_SMEM = F_CS + 1792;
enum { B_FA = 0, B_HF = 4, B_BF = 8, B_BE = 11, B_CF = 14, B_CE = 20, B_ADONE = 26, B_BDONE = 27, B_XC = 28, B_PRDY = 29, B_AUX = 30, B_NUM = 31 };

__device__ __forceinline__ void st_async4(uint32_t dst, float a, float b, float c, float d, uint32_t bar) {
    asm volatile("st.async.weak.shared::cluster.mbarrier::complete_tx::bytes.v4.f32 [%0], {%1,%2,%3,%4}, [%5];"
                 :: "r"(dst), "f"(a), "f"(b), "f"(c), "f"(d), "r"(bar) : "memory");
}
__device__ __forceinline__ void poll_count(const unsigned int* p, unsigned int target) {
    int it = 0;
    while (ld_acquire(p) < target) { if (++it > (1 << 22)) __trap(); }
    asm volatile("fence.proxy.async.global;" ::: "memory");
}
__device__ __forceinline__ void tma2d_store(const CUtensorMap* m, uint32_t src, int c0, int c1) {
    asm volatile("cp.async.bulk.tensor.2d.global.shared::cta.bulk_group [%0, {%2, %3}], [%1];" :: "l"(m), "r"(src), "r"(c0), "r"(c1) : "memory");
}
__device__ __forceinline__ float2 h_row_stats(int row) {
    const float4* hp = (const float4*)(g_hstat + (size_t)row * 8);
    float4 a = __ldcg(hp), b = __ldcg(hp + 1), c = __ldcg(hp + 2), d = __ldcg(hp + 3);
    float mean = 0.125f * (a.x + a.z + b.x + b.z + c.x + c.z + d.x + d.z);
    float m2 = a.y + a.w + b.y + b.w + c.y + c.w + d.y + d.w;
    float e;
    e = a.x - mean; m2 = fmaf(64.f * e, e, m2); e = a.z - mean; m2 = fmaf(64.f * e, e, m2);
    e = b.x - mean; m2 = fmaf(64.f * e, e, m2); e = b.z - mean; m2 = fmaf(64.f * e, e, m2);
    e = c.x - mean; m2 = fmaf(64.f * e, e, m2); e = c.z - mean; m2 = fmaf(64.f * e, e, m2);
    e = d.x - mean; m2 = fmaf(64.f * e, e, m2); e = d.z - mean; m2 = fmaf(64.f * e, e, m2);
    return make_float2(rsqrtf(m2 * (1.0f / DM) + 1e-5f), -mean);
}
__device__ __forceinline__ int c_kblock(int i, int r) {
    if (i < 6) { const int e = 2 * i + r, m = e / 3, k = e - 3 * m; return 7 * m + (k == 2 ? 4 : k); }
    const int l = 2 * (i - 6) + r, m = l >> 2, k = l & 3;
    return 7 * m + (k < 2 ? 2 + k : 3 + k);
}
__device__ __forceinline__ uint32_t c_stage_a(int s, int ntB) { return s < 4 ? ((ntB + 2 * s) & 7) * 16384 : F_R2 + (s - 4) * 32768; }
__device__ __forceinline__ uint32_t c_stage_b(int s, int ntB) { return s < 4 ? ((ntB + 2 * s + 1) & 7) * 16384 : F_R2 + (s - 4) * 32768 + 16384; }
template <int R>
__device__ __forceinline__ void xchg(float (&acc)[64], float (&o)[32], uint32_t sb, unsigned char* smem, int bar, int ctid) {
    const uint32_t dst = mapa(sb + F_X + ctid * 16, 1 - R), rb = mapa(sb + F_BAR + 8 * bar, 1 - R);
#pragma unroll
    for (int q = 0; q < 8; q++) {
        const int j = (1 - R) * 32 + 4 * q;
        st_async4(dst + q * 4096, acc[j], acc[j + 1], acc[j + 2], acc[j + 3], rb);
    }
    mbar_wait_cluster(sb + F_BAR + 8 * bar, 0);
#pragma unroll
    for (int q = 0; q < 8; q++) {
        float4 v = *(const float4*)(smem + F_X + q * 4096 + ctid * 16);
        const int j = R * 32 + 4 * q;
        o[4 * q] = acc[j] + v.x; o[4 * q + 1] = acc[j + 1] + v.y; o[4 * q + 2] = acc[j + 2] + v.z; o[4 * q + 3] = acc[j + 3] + v.w;
    }
}

template <int NB, bool STAGE>
__device__ __forceinline__ void ffn_epilogue(const float* ag, const float* au, const float* s_cs, int cs_off, uint32_t* gp, uint32_t stg,
                                             float2 st0, float2 st1, int lane) {
    const int t = lane & 3;
    const float C1 = 0.7978845608028654f, C2 = 0.044715f * 0.7978845608028654f;
    const float k10 = st0.x * C1, k20 = st0.x * st0.x * st0.x * C2, k11 = st1.x * C1, k21 = st1.x * st1.x * st1.x * C2;
#pragma unroll
    for (int j2 = 0; j2 < NB / 2; j2++) {
        uint32_t pk[4];
#pragma unroll
        for (int jj = 0; jj < 2; jj++) {
            const int j = 2 * j2 + jj;
            const float2 cg = *(const float2*)(s_cs + cs_off + 8 * j + 2 * t);
            const float2 cu = *(const float2*)(s_cs + 224 + cs_off + 8 * j + 2 * t);
            float r[4];
#pragma unroll
            for (int e = 0; e < 4; e++) {
                const float nm = (e < 2) ? st0.y : st1.y, k1 = (e < 2) ? k10 : k11, k2 = (e < 2) ? k20 : k21;
                const float tg = fmaf(nm, (e & 1) ? cg.y : cg.x, ag[4 * j + e]);
                const float tu = fmaf(nm, (e & 1) ? cu.y : cu.x, au[4 * j + e]);
                const float th = tanh_fast(tg * fmaf(tg * tg, k2, k1));
                const float p = tg * tu;
                r[e] = fmaf(p, th, p);
            }
            pk[2 * jj] = pack_bf16(r[0], r[1]);
            pk[2 * jj + 1] = pack_bf16(r[2], r[3]);
        }
        if (STAGE) {
            stsm4(stg + j2 * 4096, pk[0], pk[1], pk[2], pk[3]);
        } else {
            gp[j2 * 1024] = pk[0]; gp[j2 * 1024 + 32] = pk[1]; gp[j2 * 1024 + 512] = pk[2]; gp[j2 * 1024 + 544] = pk[3];
        }
    }
}

__global__ void __cluster_dims__(2, 1, 1) __launch_bounds__(384, 1)
tail_kernel(const __grid_constant__ CUtensorMap tm_o, const __grid_constant__ CUtensorMap tm_g,
            const __grid_constant__ CUtensorMap tm_u, const __grid_constant__ CUtensorMap tm_d,
            const __grid_constant__ CUtensorMap tm_out, const __nv_bfloat16* __restrict__ x) {
    extern __shared__ __align__(1024) unsigned char smem[];
    const uint32_t sb = smem_u32(smem);
    const uint32_t bars = sb + F_BAR;
    const int tid = threadIdx.x, warp = __shfl_sync(0xffffffffu, tid >> 5, 0), lane = tid & 31;
    TLDECL
    TL(6);
    if (warp == 4) TX(200);
    const int cl = blockIdx.x >> 1, r = blockIdx.x & 1;
    const int mb = ((cl & 7) >> 1) * 4 + (cl >> 4), ntA = (cl & 1) * 2 + ((cl >> 3) & 1);
    const int nt = ntA * 2 + r;
    const int mbB = (mb & ~1) + r, ntB = (mb & 1) * 4 + ntA;
    if (tid == 0) {
#pragma unroll
        for (int i = 0; i < B_NUM; i++) {
            const int cnt = (i >= B_BE && i < B_BE + 3) ? 16 : (i == B_BDONE) ? DELAYC : ((i >= B_CE && i < B_CE + 6) || i == B_PRDY) ? 8 : (i == B_AUX || i == B_ADONE) ? 2 : 1;
            mbar_init(bars + 8 * i, cnt);
        }
        mbar_expect(bars + 8 * B_XC, 32768);
        fence_barrier_init();
    }
    TL(28);
    __syncthreads();
    TL(29);
    asm volatile("barrier.cluster.arrive.relaxed.aligned;" ::: "memory");
    TL(30);
    if (warp < 4) {
        asm volatile("setmaxnreg.dec.sync.aligned.u32 56;");
        if (warp == 0) TX(205);
        if (warp == 0) {
            if (lane == 0) {
                auto load_b = [&](int it) {
                    const int s = it % 3, pass = it >> 3, kb = (ntB + it) & 7;
                    const int ng = pass ? 3 : 4, c0 = ntB * 224 + pass * 128;
                    const uint32_t bar = bars + 8 * (B_BF + s), dst = sb + F_R2 + s * 32768 + r * ng * 4096;
                    mbar_expect(bar, ng * 8192);
                    for (int i = 0; i < ng; i++) tma2d_mc(dst + i * 4096, r ? &tm_u : &tm_g, c0 + i * 32, kb * 64, bar);
                };
                for (int i = 0; i < 8; i++) {
                    const uint32_t bar = bars + 8 * (B_FA + (i >> 1));
                    if (!(i & 1)) mbar_expect(bar, 49152);
                    tma2d(sb + F_R2 + 32768 + i * 8192, &tm_o, nt * 64, i * 64, bar);
                }
                asm volatile("barrier.cluster.wait.acquire;" ::: "memory");
                pdl_wait();
                TL(16);
                for (int i = 0; i < 4; i++)
                    bulk_g2s_mc(sb + (2 * i + r) * 16384, g_ao + (size_t)(mb * 8 + 2 * i + r) * 8192, 16384, bars + 8 * (B_FA + i));
                load_b(0);
                if (blockIdx.x == 0)
                    for (int i = 0; i < 32; i++) g_cnt[i] = 0;
                mbar_wait_cluster(bars + 8 * B_ADONE, 0);
                load_b(1); load_b(2);
                auto load_c = [&](int i) {
                    const int s = i % 6, kb = c_kblock(i, r);
                    const uint32_t bar = bars + 8 * (B_CF + s), da = sb + c_stage_a(s, ntB), db = sb + c_stage_b(s, ntB);
                    mbar_expect(bar, 32768);
                    tma2d(db, &tm_d, ntA * 128, kb * 64, bar);
                    tma2d(db + 8192, &tm_d, ntA * 128 + 64, kb * 64, bar);
                    bulk_g2s(da, g_g + (size_t)(mb * 28 + kb) * 8192, 16384, bar);
                };
                for (int it = 3; it < 16; it++) {
                    mbar_wait_cluster(bars + 8 * (B_BE + it % 3), (it / 3 - 1) & 1);
                    load_b(it);
                    if (it == 12) { poll_count(&g_cnt2[mb], 8); load_c(0); }
                    if (it == 14) load_c(1);
                }
                mbar_wait(bars + 8 * B_BDONE, 0);
                for (int i = 2; i < 14; i++) {
                    if (i >= 6) mbar_wait(bars + 8 * (B_CE + i % 6), ((i / 6) - 1) & 1);
                    if (i == 6) { poll_count(&g_cnt2[16 + mb], 8); TL(18); }
                    load_c(i);
                }
            }
            else asm volatile("barrier.cluster.wait.acquire;" ::: "memory");
            TLDUMP;
        } else if (warp == 1) {
            asm volatile("barrier.cluster.wait.acquire.aligned;" ::: "memory");
            bar_sync(5, 288);
            if (lane == 0) { red_release(&g_cnt2[32 + mb * 8 + nt]); TL(9); }
            __syncwarp();
            bar_sync(1, 288);
            if (lane == 0) red_release(&g_cnt2[mbB]);
            __syncwarp();
            bar_sync(2, 288);
            if (lane == 0) {
                red_release(&g_cnt2[16 + mbB]);
                if (DELAYC == 9) mbar_arrive(bars + 8 * B_BDONE);
                TL(13);
            }
            __syncwarp();
            bar_sync(3, 288);
            if (lane == 0) {
                tma2d_store(&tm_out, sb, nt * 64, mb * 128);
                bulk_commit();
                bulk_wait_all();
                TL(15);
            }
            TLDUMP;
        } else {
            asm volatile("barrier.cluster.wait.acquire.aligned;" ::: "memory");
            pdl_wait();
            float2* s_rs = (float2*)(smem + F_RS);
            float* s_cs = (float*)(smem + F_CS);
            for (int c = tid - 64; c < 448; c += 64)
                s_cs[c] = __ldcg(&g_cs2[(c >= 224 ? FF - 224 : 0) + ntB * 224 + c]);
            if (warp == 3 && lane < 8) {
                const int kb = (ntB + lane) & 7;
                const uint32_t bar = bars + 8 * (lane < 4 ? B_HF + lane : B_FA + lane - 4);
                mbar_wait_cluster(bars + 8 * B_ADONE, 0);
                poll_count(&g_cnt2[32 + mbB * 8 + kb], 1);
                mbar_expect(bar, 16384);
                bulk_g2s(sb + kb * 16384, g_h + (size_t)(mbB * 8 + kb) * 8192, 16384, bar);
            }
            TL(17);
            __syncwarp();
            if (lane < 8) poll_count(&g_cnt2[32 + mbB * 8 + lane], 1);
            __syncwarp();
            for (int rr = tid - 64; rr < 128; rr += 64) {
                s_rs[rr] = h_row_stats(mbB * 128 + rr);
            }
            __syncwarp();
            if (lane == 0) mbar_arrive(bars + 8 * B_AUX);
            TLDUMP;
        }
    } else {
        asm volatile("setmaxnreg.inc.sync.aligned.u32 216;");
        if (warp == 4) TX(206);
        const int wgi = (warp >> 2) - 1, ww = warp & 3, ctid = tid - 128;
        const int g = lane >> 2, t = lane & 3;
        const int rl = wgi * 64 + ww * 16 + g, row = mb * 128 + rl;
        const int rgl = wgi * 8 + ww * 2;
        const float2* s_rs = (const float2*)(smem + F_RS);
        const float* s_cs = (const float*)(smem + F_CS);
        const uint32_t stl = ((lane >> 4) * 16 + rgl + ((lane >> 3) & 1)) * 128 + (lane & 7) * 16;
        uint32_t* hp = (uint32_t*)g_h + ((size_t)(mb * 8 + nt) * 8 * 16 + rgl) * 32 + lane;
        const uint32_t rbars = mapa(bars, 1 - r);
        TL(23);
        {
            uint32_t xr[16];
            const uint32_t* xp = (const uint32_t*)(x + (size_t)row * DM + nt * 64) + t;
#pragma unroll
            for (int j = 0; j < 8; j++) { xr[2 * j] = __ldg(xp + 4 * j); xr[2 * j + 1] = __ldg(xp + 8 * (DM / 2) + 4 * j); }
            float acc[32];
#pragma unroll 1
            for (int i = 0; i < 8; i++) {
                if (!(i & 1)) { mbar_wait(bars + 8 * (B_FA + (i >> 1)), 0); if (i == 0) TL(19); }
                uint64_t ad = make_desc(sb + i * 16384 + wgi * 1024, 2048, 128, 0);
                uint64_t bd = make_desc(sb + F_R2 + 32768 + i * 8192, 8192, 1024, 1);
                WG_FENCE();
#pragma unroll
                for (int k = 0; k < 4; k++) wgmma_ss_n64(acc, ad + k * 256, bd + k * 128, (i | k) != 0);
                WG_COMMIT();
            }
            wg_wait<0>();
            fence_regs(acc);
            TL(7);
            asm volatile("barrier.cluster.wait.acquire.aligned;" ::: "memory");
            bar_sync(4, 256);
            if (tid == 128) { mbar_arrive(bars + 8 * B_ADONE); mbar_arrive_remote(mapa(bars + 8 * B_ADONE, 1 - r)); }
            float v0[16], v1[16];
            float s0 = 0.f, s1 = 0.f;
#pragma unroll
            for (int j2 = 0; j2 < 4; j2++) {
                uint32_t u[4];
#pragma unroll
                for (int jj = 0; jj < 2; jj++) {
                    const int j = 2 * j2 + jj;
                    u[2 * jj] = pack_bf16(bf_lo(xr[2 * j]) + acc[4 * j], bf_hi(xr[2 * j]) + acc[4 * j + 1]);
                    u[2 * jj + 1] = pack_bf16(bf_lo(xr[2 * j + 1]) + acc[4 * j + 2], bf_hi(xr[2 * j + 1]) + acc[4 * j + 3]);
                    v0[2 * j] = bf_lo(u[2 * jj]); v0[2 * j + 1] = bf_hi(u[2 * jj]);
                    v1[2 * j] = bf_lo(u[2 * jj + 1]); v1[2 * j + 1] = bf_hi(u[2 * jj + 1]);
                    s0 += v0[2 * j] + v0[2 * j + 1];
                    s1 += v1[2 * j] + v1[2 * j + 1];
                }
                hp[j2 * 1024] = u[0]; hp[j2 * 1024 + 32] = u[1]; hp[j2 * 1024 + 512] = u[2]; hp[j2 * 1024 + 544] = u[3];
            }
            float m0 = s0 * (1.0f / 16), m1 = s1 * (1.0f / 16), q0 = 0.f, q1 = 0.f;
#pragma unroll
            for (int i = 0; i < 16; i++) {
                float d0 = v0[i] - m0, d1 = v1[i] - m1;
                q0 = fmaf(d0, d0, q0); q1 = fmaf(d1, d1, q1);
            }
#pragma unroll
            for (int st = 0; st < 2; st++) {
                float hn = st ? 16.f : 8.f;
                float om0 = __shfl_xor_sync(0xffffffffu, m0, 1 << st), oq0 = __shfl_xor_sync(0xffffffffu, q0, 1 << st);
                float om1 = __shfl_xor_sync(0xffffffffu, m1, 1 << st), oq1 = __shfl_xor_sync(0xffffffffu, q1, 1 << st);
                float d0 = om0 - m0, d1 = om1 - m1;
                q0 = q0 + oq0 + d0 * d0 * hn; q1 = q1 + oq1 + d1 * d1 * hn;
                m0 = 0.5f * (m0 + om0); m1 = 0.5f * (m1 + om1);
            }
            if (t == 0) {
                g_hstat[row * 8 + nt] = make_float2(m0, q0);
                g_hstat[(row + 8) * 8 + nt] = make_float2(m1, q1);
            }
            bar_arrive(5, 288);
            TL(8);
        }
        uint32_t* gp = (uint32_t*)g_g + (((size_t)mbB * 224 + ntB * 28) * 16 + rgl) * 32 + lane;
        {
            float ag[128];
#pragma unroll 1
            for (int kb = 0; kb < 8; kb++) {
                const int s = kb % 3;
                mbar_wait(bars + 8 * (kb < 4 ? B_HF + kb : B_FA + kb - 4), kb < 4 ? 0 : 1);
                mbar_wait(bars + 8 * (B_BF + s), (kb / 3) & 1);
                uint64_t ad = make_desc(sb + ((ntB + kb) & 7) * 16384 + wgi * 1024, 2048, 128, 0);
                uint64_t bd = make_desc(sb + F_R2 + s * 32768, 4096, 512, 2);
                WG_FENCE();
#pragma unroll
                for (int k = 0; k < 4; k++) wgmma_ss_n256(ag, ad + k * 256, bd + k * 64, (kb | k) != 0);
                WG_COMMIT();
                if (kb > 0) {
                    wg_wait<1>();
                    if (lane == 0) { mbar_arrive(bars + 8 * (B_BE + (kb - 1) % 3)); mbar_arrive_remote(rbars + 8 * (B_BE + (kb - 1) % 3)); }
                }
            }
            wg_wait<0>();
            if (lane == 0) { mbar_arrive(bars + 8 * (B_BE + 7 % 3)); mbar_arrive_remote(rbars + 8 * (B_BE + 7 % 3)); }
            fence_regs(ag);
            TL(10);
            mbar_wait(bars + 8 * B_AUX, 0);
            ffn_epilogue<16, false>(ag, ag + 64, s_cs, 0, gp, 0, s_rs[rl], s_rs[rl + 8], lane);
            bar_arrive(1, 288);
        }
        {
            float ag[96];
#pragma unroll 1
            for (int kb = 0; kb < 8; kb++) {
                const int it = 8 + kb, s = it % 3;
                mbar_wait(bars + 8 * (B_BF + s), (it / 3) & 1);
                uint64_t ad = make_desc(sb + ((ntB + kb) & 7) * 16384 + wgi * 1024, 2048, 128, 0);
                uint64_t bd = make_desc(sb + F_R2 + s * 32768, 4096, 512, 2);
                WG_FENCE();
#pragma unroll
                for (int k = 0; k < 4; k++) wgmma_ss_n192(ag, ad + k * 256, bd + k * 64, (kb | k) != 0);
                WG_COMMIT();
                if (kb > 0) {
                    wg_wait<1>();
                    if (lane == 0 && it + 2 < 16) { mbar_arrive(bars + 8 * (B_BE + (it - 1) % 3)); mbar_arrive_remote(rbars + 8 * (B_BE + (it - 1) % 3)); }
                }
            }
            wg_wait<0>();
            if (lane == 0) {
                mbar_arrive(bars + 8 * B_BDONE);
                mbar_arrive_remote(rbars + 8 * B_PRDY);
            }
            fence_regs(ag);
            TL(11);
            ffn_epilogue<12, false>(ag, ag + 48, s_cs, 128, gp + 16 * 512, 0, s_rs[rl], s_rs[rl + 8], lane);
            bar_arrive(2, 288);
            TL(12);
        }
        {
            uint32_t hr[16];
#pragma unroll
            for (int j = 0; j < 8; j++) { hr[2 * j] = __ldcg(hp + j * 512); hr[2 * j + 1] = __ldcg(hp + j * 512 + 32); }
            mbar_wait(bars + 8 * (B_CF + 0), 0);
            const float a0 = h_row_stats(row).x, a1 = h_row_stats(row + 8).x;
            float acc[64];
#pragma unroll 1
            for (int kb = 0; kb < 14; kb++) {
                const int s = kb % 6;
                mbar_wait(bars + 8 * (B_CF + s), (kb / 6) & 1);
                if (warp == 4) TX(96 + kb);
                uint64_t ad = make_desc(sb + c_stage_a(s, ntB) + wgi * 1024, 2048, 128, 0);
                uint64_t bd = make_desc(sb + c_stage_b(s, ntB), 8192, 1024, 1);
                WG_FENCE();
#pragma unroll
                for (int k = 0; k < 4; k++) wgmma_ss_n128(acc, ad + k * 256, bd + k * 128, (kb | k) != 0);
                WG_COMMIT();
                if (kb > 0) {
                    wg_wait<1>();
                    if (lane == 0) mbar_arrive(bars + 8 * (B_CE + (kb - 1) % 6));
                }
            }
            wg_wait<0>();
            fence_regs(acc);
            TL(14);
            mbar_wait_cluster(bars + 8 * B_PRDY, 0);
            float o[32];
            if (r == 0) xchg<0>(acc, o, sb, smem, B_XC, ctid); else xchg<1>(acc, o, sb, smem, B_XC, ctid);
            TL(22);
            bar_sync(4, 256);
            const float k0 = 0.5f * a0 * a0, k1 = 0.5f * a1 * a1;
            const int srow = wgi * 64 + ww * 16 + ((lane >> 3) & 1) * 8 + (lane & 7);
#pragma unroll
            for (int j2 = 0; j2 < 4; j2++) {
                uint32_t u[4];
#pragma unroll
                for (int jj = 0; jj < 2; jj++) {
                    const int j = 2 * j2 + jj;
                    u[2 * jj] = pack_bf16(fmaf(k0, o[4 * j], bf_lo(hr[2 * j])), fmaf(k0, o[4 * j + 1], bf_hi(hr[2 * j])));
                    u[2 * jj + 1] = pack_bf16(fmaf(k1, o[4 * j + 2], bf_lo(hr[2 * j + 1])), fmaf(k1, o[4 * j + 3], bf_hi(hr[2 * j + 1])));
                }
                const int chunk = 2 * j2 + (lane >> 4);
                stsm4(sb + srow * 128 + ((chunk ^ (lane & 7)) * 16), u[0], u[1], u[2], u[3]);
            }
            fence_proxy_async();
            bar_arrive(3, 288);
            TLDUMP;
        }
    }
}

typedef CUresult (*EncodeFn)(CUtensorMap*, CUtensorMapDataType, cuuint32_t, void*, const cuuint64_t*, const cuuint64_t*,
                             const cuuint32_t*, const cuuint32_t*, CUtensorMapInterleave, CUtensorMapSwizzle,
                             CUtensorMapL2promotion, CUtensorMapFloatOOBfill);

void encode(EncodeFn fn, CUtensorMap* m, const void* ptr, int rank, const cuuint64_t* dims, const cuuint64_t* strides,
            const cuuint32_t* box, CUtensorMapSwizzle swz) {
    cuuint32_t es[3] = {1, 1, 1};
    fn(m, CU_TENSOR_MAP_DATA_TYPE_BFLOAT16, rank, (void*)ptr, dims, strides, box, es, CU_TENSOR_MAP_INTERLEAVE_NONE, swz,
       CU_TENSOR_MAP_L2_PROMOTION_L2_256B, CU_TENSOR_MAP_FLOAT_OOB_FILL_NONE);
}

template <typename... KArgs, typename... Args>
void launch(void (*kern)(KArgs...), int grid, int block, int smem, bool pdl, Args... args) {
    cudaLaunchConfig_t cfg = {};
    cfg.gridDim = dim3(grid); cfg.blockDim = dim3(block); cfg.dynamicSmemBytes = smem;
    cfg.stream = cudaStreamPerThread;
    cudaLaunchAttribute at[1];
    at[0].id = cudaLaunchAttributeProgrammaticStreamSerialization;
    at[0].val.programmaticStreamSerializationAllowed = 1;
    cfg.attrs = at; cfg.numAttrs = pdl ? 1 : 0;
    cudaLaunchKernelEx(&cfg, kern, KArgs(args)...);
}

}

extern "C" void kernel_launch(void* const* d_in, const int* in_sizes, int n_in, void* d_out, int out_size) {
    const __nv_bfloat16* x = (const __nv_bfloat16*)d_in[0];
    const __nv_bfloat16* wqkv = (const __nv_bfloat16*)d_in[1];
    const __nv_bfloat16* wo = (const __nv_bfloat16*)d_in[2];
    const __nv_bfloat16* wgate = (const __nv_bfloat16*)d_in[4];
    const __nv_bfloat16* wup = (const __nv_bfloat16*)d_in[5];
    const __nv_bfloat16* wdown = (const __nv_bfloat16*)d_in[6];
    __nv_bfloat16* out = (__nv_bfloat16*)d_out;

    static CUtensorMap tm_x, tm_wqkv, tm_wo, tm_wg, tm_wu, tm_wd, tm_out;
    static const void* cached[7] = {nullptr, nullptr, nullptr, nullptr, nullptr, nullptr, nullptr};
    if (cached[0] != x || cached[1] != wqkv || cached[2] != wo || cached[3] != wgate || cached[4] != wup || cached[5] != wdown || cached[6] != out) {
        void* fp = nullptr;
        cudaDriverEntryPointQueryResult qr;
        cudaGetDriverEntryPoint("cuTensorMapEncodeTiled", &fp, cudaEnableDefault, &qr);
        EncodeFn fn = (EncodeFn)fp;
        { cuuint64_t d[2] = {512, 2048}, s[1] = {1024}; cuuint32_t b[2] = {64, 128};
          encode(fn, &tm_x, x, 2, d, s, b, CU_TENSOR_MAP_SWIZZLE_128B);
          encode(fn, &tm_out, out, 2, d, s, b, CU_TENSOR_MAP_SWIZZLE_128B); }
        { cuuint64_t d[3] = {64, 512, 24}, s[2] = {3072, 128}; cuuint32_t b[3] = {64, 64, 3};
          encode(fn, &tm_wqkv, wqkv, 3, d, s, b, CU_TENSOR_MAP_SWIZZLE_128B); }
        { cuuint64_t d[2] = {512, 512}, s[1] = {1024}; cuuint32_t b[2] = {64, 64};
          encode(fn, &tm_wo, wo, 2, d, s, b, CU_TENSOR_MAP_SWIZZLE_128B); }
        { cuuint64_t d[2] = {1792, 512}, s[1] = {3584}; cuuint32_t b[2] = {32, 64};
          encode(fn, &tm_wg, wgate, 2, d, s, b, CU_TENSOR_MAP_SWIZZLE_64B);
          encode(fn, &tm_wu, wup, 2, d, s, b, CU_TENSOR_MAP_SWIZZLE_64B); }
        { cuuint64_t d[2] = {512, 1792}, s[1] = {1024}; cuuint32_t b[2] = {64, 64};
          encode(fn, &tm_wd, wdown, 2, d, s, b, CU_TENSOR_MAP_SWIZZLE_128B); }
        cudaFuncSetAttribute(qkv_kernel, cudaFuncAttributeMaxDynamicSharedMemorySize, F_SMEM);
        cudaFuncSetAttribute(qkv_kernel, cudaFuncAttributePreferredSharedMemoryCarveout, 100);
        cudaFuncSetAttribute(attn_kernel, cudaFuncAttributeMaxDynamicSharedMemorySize, F_SMEM);
        cudaFuncSetAttribute(attn_kernel, cudaFuncAttributePreferredSharedMemoryCarveout, 100);
        cudaFuncSetAttribute(tail_kernel, cudaFuncAttributeMaxDynamicSharedMemorySize, F_SMEM);
        cudaFuncSetAttribute(tail_kernel, cudaFuncAttributePreferredSharedMemoryCarveout, 100);
        cached[0] = x; cached[1] = wqkv; cached[2] = wo; cached[3] = wgate; cached[4] = wup; cached[5] = wdown; cached[6] = out;
    }
    launch(qkv_kernel, 128, 384, F_SMEM, false, tm_x, tm_wqkv, x, wqkv);
    launch(attn_kernel, 132, 512, F_SMEM, true, wgate, wup, wo, wdown);
    launch(tail_kernel, 128, 384, F_SMEM, true, tm_wo, tm_wg, tm_wu, tm_wd, tm_out, x);
}
```

```cpp
#include <cuda_runtime.h>
#include <cuda_bf16.h>
#include <cuda.h>
#include <stdint.h>

#define K1_DIRECT
namespace {

constexpr int S_LEN = 2048, DM = 512, NH = 32, FF = 1792;

__device__ __align__(1024) __nv_bfloat16 g_qkv[3 * NH * S_LEN * 16];
__device__ __align__(1024) __nv_bfloat16 g_ao[S_LEN * DM];
__device__ __align__(1024) __nv_bfloat16 g_h[S_LEN * DM];
__device__ __align__(1024) __nv_bfloat16 g_g[S_LEN * FF];
__device__ __align__(16) float2 g_rowstat1[S_LEN];
__device__ float g_cs1_part[16 * 1536];
__device__ unsigned int g_cnt[32];
__device__ unsigned int g_cnt2[160];
__device__ float g_nrm[3 * NH * 128];
__device__ float2 g_hstat[S_LEN * 8];
__device__ float g_cs2[2 * FF];

#define TLDECL
#define TL(slot)
#define TLDUMP
#define TX(slot)
__device__ __forceinline__ uint32_t smem_u32(const void* p) { return (uint32_t)__cvta_generic_to_shared(p); }
__device__ __forceinline__ void mbar_init(uint32_t a, int c) { asm volatile("mbarrier.init.shared.b64 [%0], %1;" :: "r"(a), "r"(c)); }
__device__ __forceinline__ void mbar_expect(uint32_t a, int bytes) { asm volatile("mbarrier.arrive.expect_tx.shared.b64 _, [%0], %1;" :: "r"(a), "r"(bytes) : "memory"); }
__device__ __forceinline__ void mbar_arrive(uint32_t a) { asm volatile("mbarrier.arrive.shared.b64 _, [%0];" :: "r"(a) : "memory"); }
__device__ __forceinline__ void mbar_wait(uint32_t a, int parity) {
    uint32_t done;
    int it = 0;
    do {
        asm volatile("{\n.reg .pred p;\nmbarrier.try_wait.parity.shared.b64 p, [%1], %2;\nselp.u32 %0, 1, 0, p;\n}"
                     : "=r"(done) : "r"(a), "r"(parity) : "memory");
        if (++it > (1 << 24)) __trap();
    } while (!done);
}
__device__ __forceinline__ void bulk_g2s(uint32_t dst, const void* src, int bytes, uint32_t bar) {
    asm volatile("cp.async.bulk.shared::cluster.global.mbarrier::complete_tx::bytes [%0], [%1], %2, [%3];"
                 :: "r"(dst), "l"(src), "r"(bytes), "r"(bar) : "memory");
}
__device__ __forceinline__ void tma2d(uint32_t dst, const CUtensorMap* m, int c0, int c1, uint32_t bar) {
    asm volatile("cp.async.bulk.tensor.2d.shared::cluster.global.mbarrier::complete_tx::bytes [%0], [%1, {%3, %4}], [%2];"
                 :: "r"(dst), "l"(m), "r"(bar), "r"(c0), "r"(c1) : "memory");
}
__device__ __forceinline__ void tma3d(uint32_t dst, const CUtensorMap* m, int c0, int c1, int c2, uint32_t bar) {
    asm volatile("cp.async.bulk.tensor.3d.shared::cluster.global.mbarrier::complete_tx::bytes [%0], [%1, {%3, %4, %5}], [%2];"
                 :: "r"(dst), "l"(m), "r"(bar), "r"(c0), "r"(c1), "r"(c2) : "memory");
}
__device__ __forceinline__ void prefetch_tmap(const CUtensorMap* m) { asm volatile("prefetch.tensormap [%0];" :: "l"(m) : "memory"); }
__device__ __forceinline__ void pdl_wait() { asm volatile("griddepcontrol.wait;" ::: "memory"); }
__device__ __forceinline__ void pdl_launch() { asm volatile("griddepcontrol.launch_dependents;" ::: "memory"); }
__device__ __forceinline__ void fence_barrier_init() { asm volatile("fence.mbarrier_init.release.cluster;" ::: "memory"); }
__device__ __forceinline__ void fence_proxy_async() { asm volatile("fence.proxy.async.shared::cta;" ::: "memory"); }
__device__ __forceinline__ uint64_t make_desc(uint32_t saddr, uint32_t lbo, uint32_t sbo, uint32_t swz) {
    return (uint64_t)((saddr & 0x3FFFF) >> 4) | ((uint64_t)((lbo & 0x3FFFF) >> 4) << 16) |
           ((uint64_t)((sbo & 0x3FFFF) >> 4) << 32) | ((uint64_t)swz << 62);
}
#define WG_FENCE() asm volatile("wgmma.fence.sync.aligned;" ::: "memory")
#define WG_COMMIT() asm volatile("wgmma.commit_group.sync.aligned;" ::: "memory")
template <int N> __device__ __forceinline__ void wg_wait() { asm volatile("wgmma.wait_group.sync.aligned %0;" :: "n"(N) : "memory"); }
template <int N> __device__ __forceinline__ void fence_regs(float (&d)[N]) {
#pragma unroll
    for (int i = 0; i < N; i++) asm volatile("" : "+f"(d[i]) :: "memory");
}
__device__ __forceinline__ float ex2f(float x) { float y; asm("ex2.approx.ftz.f32 %0, %1;" : "=f"(y) : "f"(x)); return y; }
__device__ __forceinline__ float tanh_fast(float x) { float y; asm("tanh.approx.f32 %0, %1;" : "=f"(y) : "f"(x)); return y; }
__device__ __forceinline__ uint32_t pack_bf16(float lo, float hi) { uint32_t r; asm("cvt.rn.bf16x2.f32 %0, %1, %2;" : "=r"(r) : "f"(hi), "f"(lo)); return r; }
__device__ __forceinline__ float bf_lo(uint32_t u) { return __uint_as_float(u << 16); }
__device__ __forceinline__ float bf_hi(uint32_t u) { return __uint_as_float(u & 0xFFFF0000u); }
__device__ __forceinline__ uint32_t hfma2(uint32_t a, uint32_t b, uint32_t c) { uint32_t r; asm("fma.rn.f16x2 %0, %1, %2, %3;" : "=r"(r) : "r"(a), "r"(b), "r"(c)); return r; }
__device__ __forceinline__ uint32_t hmul2(uint32_t a, uint32_t b) { uint32_t r; asm("mul.rn.f16x2 %0, %1, %2;" : "=r"(r) : "r"(a), "r"(b)); return r; }
__device__ __forceinline__ unsigned int ld_acquire(const unsigned int* p) { unsigned int v; asm volatile("ld.acquire.gpu.u32 %0, [%1];" : "=r"(v) : "l"(p) : "memory"); return v; }
__device__ __forceinline__ void red_release(unsigned int* p) { asm volatile("red.release.gpu.global.add.u32 [%0], 1;" :: "l"(p) : "memory"); }
__device__ __forceinline__ void stsm4(uint32_t addr, uint32_t a, uint32_t b, uint32_t c, uint32_t d) {
    asm volatile("stmatrix.sync.aligned.m8n8.x4.shared.b16 [%0], {%1,%2,%3,%4};" :: "r"(addr), "r"(a), "r"(b), "r"(c), "r"(d) : "memory");
}
__device__ __forceinline__ void bulk_s2g(void* dst, uint32_t src, int bytes) {
    asm volatile("cp.async.bulk.global.shared::cta.bulk_group [%0], [%1], %2;" :: "l"(dst), "r"(src), "r"(bytes) : "memory");
}
__device__ __forceinline__ void bulk_commit() { asm volatile("cp.async.bulk.commit_group;" ::: "memory"); }
__device__ __forceinline__ void bulk_wait_all() { asm volatile("cp.async.bulk.wait_group 0;" ::: "memory"); }
__device__ __forceinline__ void bulk_wait_read() { asm volatile("cp.async.bulk.wait_group.read 0;" ::: "memory"); }
__device__ __forceinline__ void bar_sync(int id, int n) { asm volatile("bar.sync %0, %1;" :: "r"(id), "r"(n) : "memory"); }
__device__ __forceinline__ void bar_arrive(int id, int n) { asm volatile("bar.arrive %0, %1;" :: "r"(id), "r"(n) : "memory"); }
__device__ __forceinline__ float warp_sum(float v) {
#pragma unroll
    for (int o = 16; o; o >>= 1) v += __shfl_xor_sync(0xffffffffu, v, o);
    return v;
}
__device__ __forceinline__ float warp_max(float v) {
#pragma unroll
    for (int o = 16; o; o >>= 1) v = fmaxf(v, __shfl_xor_sync(0xffffffffu, v, o));
    return v;
}

__device__ __forceinline__ void wgmma_ss_n64(float (&d)[32], uint64_t adesc, uint64_t bdesc, int scale_d) {
    asm volatile("{\n.reg .pred p;\nsetp.ne.b32 p, %34, 0;\n"
      "wgmma.mma_async.sync.aligned.m64n64k16.f32.bf16.bf16 {%0,%1,%2,%3,%4,%5,%6,%7,%8,%9,%10,%11,%12,%13,%14,%15,%16,%17,%18,%19,%20,%21,%22,%23,%24,%25,%26,%27,%28,%29,%30,%31}, %32, %33, p, 1, 1, 0, 1;\n}"
      : "+f"(d[0]), "+f"(d[1]), "+f"(d[2]), "+f"(d[3]), "+f"(d[4]), "+f"(d[5]), "+f"(d[6]), "+f"(d[7]), "+f"(d[8]), "+f"(d[9]), "+f"(d[10]), "+f"(d[11]), "+f"(d[12]), "+f"(d[13]), "+f"(d[14]), "+f"(d[15]), "+f"(d[16]), "+f"(d[17]), "+f"(d[18]), "+f"(d[19]), "+f"(d[20]), "+f"(d[21]), "+f"(d[22]), "+f"(d[23]), "+f"(d[24]), "+f"(d[25]), "+f"(d[26]), "+f"(d[27]), "+f"(d[28]), "+f"(d[29]), "+f"(d[30]), "+f"(d[31])
      : "l"(adesc), "l"(bdesc), "r"(scale_d));
}
__device__ __forceinline__ void wgmma_ss_n128(float (&d)[64], uint64_t adesc, uint64_t bdesc, int scale_d) {
    asm volatile("{\n.reg .pred p;\nsetp.ne.b32 p, %66, 0;\n"
      "wgmma.mma_async.sync.aligned.m64n128k16.f32.bf16.bf16 {%0,%1,%2,%3,%4,%5,%6,%7,%8,%9,%10,%11,%12,%13,%14,%15,%16,%17,%18,%19,%20,%21,%22,%23,%24,%25,%26,%27,%28,%29,%30,%31,%32,%33,%34,%35,%36,%37,%38,%39,%40,%41,%42,%43,%44,%45,%46,%47,%48,%49,%50,%51,%52,%53,%54,%55,%56,%57,%58,%59,%60,%61,%62,%63}, %64, %65, p, 1, 1, 0, 1;\n}"
      : "+f"(d[0]), "+f"(d[1]), "+f"(d[2]), "+f"(d[3]), "+f"(d[4]), "+f"(d[5]), "+f"(d[6]), "+f"(d[7]), "+f"(d[8]), "+f"(d[9]), "+f"(d[10]), "+f"(d[11]), "+f"(d[12]), "+f"(d[13]), "+f"(d[14]), "+f"(d[15]), "+f"(d[16]), "+f"(d[17]), "+f"(d[18]), "+f"(d[19]), "+f"(d[20]), "+f"(d[21]), "+f"(d[22]), "+f"(d[23]), "+f"(d[24]), "+f"(d[25]), "+f"(d[26]), "+f"(d[27]), "+f"(d[28]), "+f"(d[29]), "+f"(d[30]), "+f"(d[31]), "+f"(d[32]), "+f"(d[33]), "+f"(d[34]), "+f"(d[35]), "+f"(d[36]), "+f"(d[37]), "+f"(d[38]), "+f"(d[39]), "+f"(d[40]), "+f"(d[41]), "+f"(d[42]), "+f"(d[43]), "+f"(d[44]), "+f"(d[45]), "+f"(d[46]), "+f"(d[47]), "+f"(d[48]), "+f"(d[49]), "+f"(d[50]), "+f"(d[51]), "+f"(d[52]), "+f"(d[53]), "+f"(d[54]), "+f"(d[55]), "+f"(d[56]), "+f"(d[57]), "+f"(d[58]), "+f"(d[59]), "+f"(d[60]), "+f"(d[61]), "+f"(d[62]), "+f"(d[63])
      : "l"(adesc), "l"(bdesc), "r"(scale_d));
}
__device__ __forceinline__ void wgmma_ss_n192(float (&d)[96], uint64_t adesc, uint64_t bdesc, int scale_d) {
    asm volatile("{\n.reg .pred p;\nsetp.ne.b32 p, %98, 0;\n"
      "wgmma.mma_async.sync.aligned.m64n192k16.f32.bf16.bf16 {%0,%1,%2,%3,%4,%5,%6,%7,%8,%9,%10,%11,%12,%13,%14,%15,%16,%17,%18,%19,%20,%21,%22,%23,%24,%25,%26,%27,%28,%29,%30,%31,%32,%33,%34,%35,%36,%37,%38,%39,%40,%41,%42,%43,%44,%45,%46,%47,%48,%49,%50,%51,%52,%53,%54,%55,%56,%57,%58,%59,%60,%61,%62,%63,%64,%65,%66,%67,%68,%69,%70,%71,%72,%73,%74,%75,%76,%77,%78,%79,%80,%81,%82,%83,%84,%85,%86,%87,%88,%89,%90,%91,%92,%93,%94,%95}, %96, %97, p, 1, 1, 0, 1;\n}"
      : "+f"(d[0]), "+f"(d[1]), "+f"(d[2]), "+f"(d[3]), "+f"(d[4]), "+f"(d[5]), "+f"(d[6]), "+f"(d[7]), "+f"(d[8]), "+f"(d[9]), "+f"(d[10]), "+f"(d[11]), "+f"(d[12]), "+f"(d[13]), "+f"(d[14]), "+f"(d[15]), "+f"(d[16]), "+f"(d[17]), "+f"(d[18]), "+f"(d[19]), "+f"(d[20]), "+f"(d[21]), "+f"(d[22]), "+f"(d[23]), "+f"(d[24]), "+f"(d[25]), "+f"(d[26]), "+f"(d[27]), "+f"(d[28]), "+f"(d[29]), "+f"(d[30]), "+f"(d[31]), "+f"(d[32]), "+f"(d[33]), "+f"(d[34]), "+f"(d[35]), "+f"(d[36]), "+f"(d[37]), "+f"(d[38]), "+f"(d[39]), "+f"(d[40]), "+f"(d[41]), "+f"(d[42]), "+f"(d[43]), "+f"(d[44]), "+f"(d[45]), "+f"(d[46]), "+f"(d[47]), "+f"(d[48]), "+f"(d[49]), "+f"(d[50]), "+f"(d[51]), "+f"(d[52]), "+f"(d[53]), "+f"(d[54]), "+f"(d[55]), "+f"(d[56]), "+f"(d[57]), "+f"(d[58]), "+f"(d[59]), "+f"(d[60]), "+f"(d[61]), "+f"(d[62]), "+f"(d[63]), "+f"(d[64]), "+f"(d[65]), "+f"(d[66]), "+f"(d[67]), "+f"(d[68]), "+f"(d[69]), "+f"(d[70]), "+f"(d[71]), "+f"(d[72]), "+f"(d[73]), "+f"(d[74]), "+f"(d[75]), "+f"(d[76]), "+f"(d[77]), "+f"(d[78]), "+f"(d[79]), "+f"(d[80]), "+f"(d[81]), "+f"(d[82]), "+f"(d[83]), "+f"(d[84]), "+f"(d[85]), "+f"(d[86]), "+f"(d[87]), "+f"(d[88]), "+f"(d[89]), "+f"(d[90]), "+f"(d[91]), "+f"(d[92]), "+f"(d[93]), "+f"(d[94]), "+f"(d[95])
      : "l"(adesc), "l"(bdesc), "r"(scale_d));
}
__device__ __forceinline__ void wgmma_ss_n256(float (&d)[128], uint64_t adesc, uint64_t bdesc, int scale_d) {
    asm volatile("{\n.reg .pred p;\nsetp.ne.b32 p, %130, 0;\n"
      "wgmma.mma_async.sync.aligned.m64n256k16.f32.bf16.bf16 {%0,%1,%2,%3,%4,%5,%6,%7,%8,%9,%10,%11,%12,%13,%14,%15,%16,%17,%18,%19,%20,%21,%22,%23,%24,%25,%26,%27,%28,%29,%30,%31,%32,%33,%34,%35,%36,%37,%38,%39,%40,%41,%42,%43,%44,%45,%46,%47,%48,%49,%50,%51,%52,%53,%54,%55,%56,%57,%58,%59,%60,%61,%62,%63,%64,%65,%66,%67,%68,%69,%70,%71,%72,%73,%74,%75,%76,%77,%78,%79,%80,%81,%82,%83,%84,%85,%86,%87,%88,%89,%90,%91,%92,%93,%94,%95,%96,%97,%98,%99,%100,%101,%102,%103,%104,%105,%106,%107,%108,%109,%110,%111,%112,%113,%114,%115,%116,%117,%118,%119,%120,%121,%122,%123,%124,%125,%126,%127}, %128, %129, p, 1, 1, 0, 1;\n}"
      : "+f"(d[0]), "+f"(d[1]), "+f"(d[2]), "+f"(d[3]), "+f"(d[4]), "+f"(d[5]), "+f"(d[6]), "+f"(d[7]), "+f"(d[8]), "+f"(d[9]), "+f"(d[10]), "+f"(d[11]), "+f"(d[12]), "+f"(d[13]), "+f"(d[14]), "+f"(d[15]), "+f"(d[16]), "+f"(d[17]), "+f"(d[18]), "+f"(d[19]), "+f"(d[20]), "+f"(d[21]), "+f"(d[22]), "+f"(d[23]), "+f"(d[24]), "+f"(d[25]), "+f"(d[26]), "+f"(d[27]), "+f"(d[28]), "+f"(d[29]), "+f"(d[30]), "+f"(d[31]), "+f"(d[32]), "+f"(d[33]), "+f"(d[34]), "+f"(d[35]), "+f"(d[36]), "+f"(d[37]), "+f"(d[38]), "+f"(d[39]), "+f"(d[40]), "+f"(d[41]), "+f"(d[42]), "+f"(d[43]), "+f"(d[44]), "+f"(d[45]), "+f"(d[46]), "+f"(d[47]), "+f"(d[48]), "+f"(d[49]), "+f"(d[50]), "+f"(d[51]), "+f"(d[52]), "+f"(d[53]), "+f"(d[54]), "+f"(d[55]), "+f"(d[56]), "+f"(d[57]), "+f"(d[58]), "+f"(d[59]), "+f"(d[60]), "+f"(d[61]), "+f"(d[62]), "+f"(d[63]), "+f"(d[64]), "+f"(d[65]), "+f"(d[66]), "+f"(d[67]), "+f"(d[68]), "+f"(d[69]), "+f"(d[70]), "+f"(d[71]), "+f"(d[72]), "+f"(d[73]), "+f"(d[74]), "+f"(d[75]), "+f"(d[76]), "+f"(d[77]), "+f"(d[78]), "+f"(d[79]), "+f"(d[80]), "+f"(d[81]), "+f"(d[82]), "+f"(d[83]), "+f"(d[84]), "+f"(d[85]), "+f"(d[86]), "+f"(d[87]), "+f"(d[88]), "+f"(d[89]), "+f"(d[90]), "+f"(d[91]), "+f"(d[92]), "+f"(d[93]), "+f"(d[94]), "+f"(d[95]), "+f"(d[96]), "+f"(d[97]), "+f"(d[98]), "+f"(d[99]), "+f"(d[100]), "+f"(d[101]), "+f"(d[102]), "+f"(d[103]), "+f"(d[104]), "+f"(d[105]), "+f"(d[106]), "+f"(d[107]), "+f"(d[108]), "+f"(d[109]), "+f"(d[110]), "+f"(d[111]), "+f"(d[112]), "+f"(d[113]), "+f"(d[114]), "+f"(d[115]), "+f"(d[116]), "+f"(d[117]), "+f"(d[118]), "+f"(d[119]), "+f"(d[120]), "+f"(d[121]), "+f"(d[122]), "+f"(d[123]), "+f"(d[124]), "+f"(d[125]), "+f"(d[126]), "+f"(d[127])
      : "l"(adesc), "l"(bdesc), "r"(scale_d));
}
__device__ __forceinline__ void qk_wgmma_n64(float (&d)[32], const uint32_t (&a)[4], uint64_t desc) {
    asm volatile("wgmma.mma_async.sync.aligned.m64n64k16.f32.bf16.bf16 {%0,%1,%2,%3,%4,%5,%6,%7,%8,%9,%10,%11,%12,%13,%14,%15,%16,%17,%18,%19,%20,%21,%22,%23,%24,%25,%26,%27,%28,%29,%30,%31}, {%32,%33,%34,%35}, %36, 0, 1, 1, 0;"
      : "=f"(d[0]), "=f"(d[1]), "=f"(d[2]), "=f"(d[3]), "=f"(d[4]), "=f"(d[5]), "=f"(d[6]), "=f"(d[7]), "=f"(d[8]), "=f"(d[9]), "=f"(d[10]), "=f"(d[11]), "=f"(d[12]), "=f"(d[13]), "=f"(d[14]), "=f"(d[15]), "=f"(d[16]), "=f"(d[17]), "=f"(d[18]), "=f"(d[19]), "=f"(d[20]), "=f"(d[21]), "=f"(d[22]), "=f"(d[23]), "=f"(d[24]), "=f"(d[25]), "=f"(d[26]), "=f"(d[27]), "=f"(d[28]), "=f"(d[29]), "=f"(d[30]), "=f"(d[31])
      : "r"(a[0]), "r"(a[1]), "r"(a[2]), "r"(a[3]), "l"(desc));
}

__device__ __forceinline__ void pv_wgmma(float (&d)[12], uint32_t a0, uint32_t a1, uint32_t a2, uint32_t a3, uint64_t desc) {
    asm volatile("wgmma.mma_async.sync.aligned.m64n24k16.f32.bf16.bf16 {%0,%1,%2,%3,%4,%5,%6,%7,%8,%9,%10,%11}, {%12,%13,%14,%15}, %16, 1, 1, 1, 1;"
      : "+f"(d[0]), "+f"(d[1]), "+f"(d[2]), "+f"(d[3]), "+f"(d[4]), "+f"(d[5]), "+f"(d[6]), "+f"(d[7]), "+f"(d[8]), "+f"(d[9]), "+f"(d[10]), "+f"(d[11])
      : "r"(a0), "r"(a1), "r"(a2), "r"(a3), "l"(desc));
}

__device__ __forceinline__ uint32_t mapa(uint32_t a, uint32_t rank) { uint32_t r; asm("mapa.shared::cluster.u32 %0, %1, %2;" : "=r"(r) : "r"(a), "r"(rank)); return r; }
__device__ __forceinline__ void mbar_arrive_remote(uint32_t a) { asm volatile("mbarrier.arrive.relaxed.cluster.shared::cluster.b64 _, [%0];" :: "r"(a) : "memory"); }
__device__ __forceinline__ void mbar_wait_cluster(uint32_t a, int parity) {
    uint32_t done;
    int it = 0;
    do {
        asm volatile("{\n.reg .pred p;\nmbarrier.try_wait.parity.acquire.cluster.shared::cta.b64 p, [%1], %2;\nselp.u32 %0, 1, 0, p;\n}"
                     : "=r"(done) : "r"(a), "r"(parity) : "memory");
        if (++it > (1 << 24)) __trap();
    } while (!done);
}
__device__ __forceinline__ void tma2d_mc(uint32_t dst, const CUtensorMap* m, int c0, int c1, uint32_t bar) {
    asm volatile("cp.async.bulk.tensor.2d.shared::cluster.global.mbarrier::complete_tx::bytes.multicast::cluster [%0], [%1, {%3, %4}], [%2], %5;"
                 :: "r"(dst), "l"(m), "r"(bar), "r"(c0), "r"(c1), "h"((uint16_t)3) : "memory");
}
__device__ __forceinline__ void bulk_g2s_mc(uint32_t dst, const void* src, int bytes, uint32_t bar) {
    asm volatile("cp.async.bulk.shared::cluster.global.mbarrier::complete_tx::bytes.multicast::cluster [%0], [%1], %2, [%3], %4;"
                 :: "r"(dst), "l"(src), "r"(bytes), "r"(bar), "h"((uint16_t)3) : "memory");
}
__device__ __forceinline__ void tile_of(int bid, int& mb, int& nt) {
    int grp = bid >> 4, in = bid & 15;
    mb = (grp >> 1) * 4 + (in >> 2);
    nt = (grp & 1) * 4 + (in & 3);
}

constexpr int K1_STAGES = 5, K1_STAGE = 16384 + 24576;
constexpr int K1_BAR = K1_STAGES * K1_STAGE, K1_RS = K1_BAR + 128, K1_CS = K1_RS + 1024, K1_SMEM = K1_CS + 768;

__device__ __forceinline__ float2 row_stats_regs(uint4 a, uint4 b) {
    float v[16];
    v[0] = bf_lo(a.x); v[1] = bf_hi(a.x); v[2] = bf_lo(a.y); v[3] = bf_hi(a.y);
    v[4] = bf_lo(a.z); v[5] = bf_hi(a.z); v[6] = bf_lo(a.w); v[7] = bf_hi(a.w);
    v[8] = bf_lo(b.x); v[9] = bf_hi(b.x); v[10] = bf_lo(b.y); v[11] = bf_hi(b.y);
    v[12] = bf_lo(b.z); v[13] = bf_hi(b.z); v[14] = bf_lo(b.w); v[15] = bf_hi(b.w);
    float s = 0.f;
#pragma unroll
    for (int i = 0; i < 16; i++) s += v[i];
    float mean = warp_sum(s) * (1.0f / DM);
    float q = 0.f;
#pragma unroll
    for (int i = 0; i < 16; i++) { float d = v[i] - mean; q = fmaf(d, d, q); }
    float var = warp_sum(q) * (1.0f / DM);
    float rstd = rsqrtf(var + 1e-5f);
    return make_float2(rstd, -mean * rstd);
}
__device__ __forceinline__ float2 row_stats_x(const __nv_bfloat16* x, int row, int lane) {
    const uint4* p = (const uint4*)(x + (size_t)row * DM);
    return row_stats_regs(__ldg(p + lane), __ldg(p + 32 + lane));
}
__device__ __forceinline__ void colsum8(const __nv_bfloat16* w, int ld, int col, int k0, int nk, float (&s)[8]) {
#pragma unroll
    for (int i = 0; i < 8; i++) s[i] = 0.f;
    for (int k = k0; k < k0 + nk; k += 8) {
        uint4 u[8];
#pragma unroll
        for (int i = 0; i < 8; i++) u[i] = __ldg((const uint4*)(w + (size_t)(k + i) * ld + col));
#pragma unroll
        for (int i = 0; i < 8; i++) {
            s[0] += bf_lo(u[i].x); s[1] += bf_hi(u[i].x); s[2] += bf_lo(u[i].y); s[3] += bf_hi(u[i].y);
            s[4] += bf_lo(u[i].z); s[5] += bf_hi(u[i].z); s[6] += bf_lo(u[i].w); s[7] += bf_hi(u[i].w);
        }
    }
}
__device__ __forceinline__ bool wait_count(const unsigned int* p, unsigned int target, int lane) {
    int ok = 1;
    if (lane == 0) {
        int it = 0;
        while (ld_acquire(p) < target) { if (++it > (1 << 18)) { ok = 0; break; } }
    }
    ok = __shfl_sync(0xffffffffu, ok, 0);
    return ok != 0;
}

__global__ void __launch_bounds__(384, 1)
qkv_kernel(const __grid_constant__ CUtensorMap tm_x, const __grid_constant__ CUtensorMap tm_w,
           const __nv_bfloat16* __restrict__ x, const __nv_bfloat16* __restrict__ wqkv) {
    extern __shared__ __align__(1024) unsigned char smem[];
    const uint32_t sb = smem_u32(smem);
    const int tid = threadIdx.x, warp = __shfl_sync(0xffffffffu, tid >> 5, 0), lane = tid & 31;
    TLDECL
    TL(0);
    int mb, nt;
    tile_of(blockIdx.x, mb, nt);
    const uint32_t full = sb + K1_BAR, empty = full + 40, auxb = full + 80;
    if (tid == 0) {
        prefetch_tmap(&tm_x); prefetch_tmap(&tm_w);
        for (int i = 0; i < K1_STAGES; i++) { mbar_init(full + 8 * i, 1); mbar_init(empty + 8 * i, 8); }
        mbar_init(auxb, 3);
        fence_barrier_init();
    }
    __syncthreads();
    pdl_launch();
    if (warp == 0) {
        if (blockIdx.x == 0) for (int i = lane; i < 160; i += 32) g_cnt2[i] = 0;
        if (lane == 0) {
            for (int kb = 0; kb < 8; kb++) {
                int s = kb % K1_STAGES;
                if (kb >= K1_STAGES) mbar_wait(empty + 8 * s, 0);
                mbar_expect(full + 8 * s, K1_STAGE);
                tma2d(sb + s * K1_STAGE, &tm_x, kb * 64, mb * 128, full + 8 * s);
                tma3d(sb + s * K1_STAGE + 16384, &tm_w, 0, kb * 64, nt * 3, full + 8 * s);
            }
        }
    } else if (warp < 4) {
        float2* s_rs = (float2*)(smem + K1_RS);
        float* s_cs = (float*)(smem + K1_CS);
        if (warp < 3) {
            const int r0 = mb * 128 + nt * 16 + (warp - 1) * 8;
            uint4 u[16];
#pragma unroll
            for (int i = 0; i < 8; i++) {
                const uint4* p = (const uint4*)(x + (size_t)(r0 + i) * DM);
                u[2 * i] = __ldg(p + lane); u[2 * i + 1] = __ldg(p + 32 + lane);
            }
            float2 mine = make_float2(0.f, 0.f);
#pragma unroll
            for (int i = 0; i < 8; i++) {
                float2 st = row_stats_regs(u[2 * i], u[2 * i + 1]);
                if (lane == i) mine = st;
            }
            if (lane < 8) g_rowstat1[r0 + lane] = mine;
            __syncwarp();
            if (lane == 0) red_release(&g_cnt[mb]);
        } else {
            uint4 u[24];
#pragma unroll
            for (int c = 0; c < 3; c++)
#pragma unroll
                for (int i = 0; i < 8; i++)
                    u[c * 8 + i] = __ldg((const uint4*)(wqkv + (size_t)(mb * 32 + (lane >> 3) * 8 + i) * 1536 + nt * 192 + (c * 8 + (lane & 7)) * 8));
#pragma unroll
            for (int c = 0; c < 3; c++) {
                float cs[8];
#pragma unroll
                for (int i = 0; i < 8; i++) cs[i] = 0.f;
#pragma unroll
                for (int i = 0; i < 8; i++) {
                    const uint4 w = u[c * 8 + i];
                    cs[0] += bf_lo(w.x); cs[1] += bf_hi(w.x); cs[2] += bf_lo(w.y); cs[3] += bf_hi(w.y);
                    cs[4] += bf_lo(w.z); cs[5] += bf_hi(w.z); cs[6] += bf_lo(w.w); cs[7] += bf_hi(w.w);
                }
#pragma unroll
                for (int i = 0; i < 8; i++) {
                    cs[i] += __shfl_xor_sync(0xffffffffu, cs[i], 8);
                    cs[i] += __shfl_xor_sync(0xffffffffu, cs[i], 16);
                }
                if (lane < 8) {
                    float4* d = (float4*)(g_cs1_part + mb * 1536 + nt * 192 + (c * 8 + lane) * 8);
                    d[0] = make_float4(cs[0], cs[1], cs[2], cs[3]);
                    d[1] = make_float4(cs[4], cs[5], cs[6], cs[7]);
                }
            }
            __syncwarp();
            if (lane == 0) red_release(&g_cnt[16 + nt]);
        }
        TX(8 + warp);
        if (warp == 1) {
            if (wait_count(&g_cnt[mb], 16, lane)) {
#pragma unroll
                for (int i = 0; i < 4; i++) s_rs[lane + 32 * i] = __ldcg(&g_rowstat1[mb * 128 + lane + 32 * i]);
            } else {
                for (int i = 0; i < 128; i++) {
                    float2 st = row_stats_x(x, mb * 128 + i, lane);
                    if (lane == 0) s_rs[i] = st;
                }
            }
        } else {
            int c0 = (warp - 2) * 96;
            if (wait_count(&g_cnt[16 + nt], 16, lane)) {
#pragma unroll
                for (int i = 0; i < 3; i++) {
                    float s = 0.f;
#pragma unroll
                    for (int p = 0; p < 16; p++) s += __ldcg(&g_cs1_part[p * 1536 + nt * 192 + c0 + lane + 32 * i]);
                    s_cs[c0 + lane + 32 * i] = s;
                }
            } else if (lane < 12) {
                float s[8];
                colsum8(wqkv, 1536, nt * 192 + c0 + lane * 8, 0, 512, s);
#pragma unroll
                for (int i = 0; i < 8; i++) s_cs[c0 + lane * 8 + i] = s[i];
            }
        }
        __syncwarp();
        TX(12 + warp);
        if (lane == 0) mbar_arrive(auxb);
        bar_sync(2, 256 + 96);
        const int a = tid - 32;
        {
            const int hh = a >> 3, w = a & 7;
            const float4* p = (const float4*)(smem + 49152) + (hh * 256 + w * 32) / 2;
            float m = 0.f;
#pragma unroll
            for (int i = 0; i < 8; i++) {
                const int ii = (i + a) & 7;
                float4 u = p[2 * ii], v = p[2 * ii + 1];
                float n0 = u.x + u.z + v.x + v.z, n1 = u.y + u.w + v.y + v.w;
                if (!(n0 <= 3.0e38f) || !(n1 <= 3.0e38f)) m = __int_as_float(0x7f800000);
                m = fmaxf(m, fmaxf(n0, n1));
            }
            const int col0 = nt * 192 + hh * 16;
            g_nrm[((col0 >> 9) * NH + ((col0 & 511) >> 4)) * 128 + mb * 8 + w] = m;
        }
        if (a < 24) bulk_wait_all();
        TL(27);
        TLDUMP;
    } else {
        const int wgi = (warp >> 2) - 1, ww = warp & 3;
        float acc[96];
#pragma unroll 1
        for (int kb = 0; kb < 8; kb++) {
            int s = kb % K1_STAGES;
            mbar_wait(full + 8 * s, (kb / K1_STAGES) & 1);
            if (warp == 4) TX(kb);
            uint64_t ad = make_desc(sb + s * K1_STAGE + wgi * 8192, 16, 1024, 1);
            uint64_t bd = make_desc(sb + s * K1_STAGE + 16384, 8192, 1024, 1);
            WG_FENCE();
#pragma unroll
            for (int k = 0; k < 4; k++) wgmma_ss_n192(acc, ad + k * 2, bd + k * 128, (kb | k) != 0);
            WG_COMMIT();
            if (kb > 0) {
                wg_wait<1>();
                if (lane == 0) mbar_arrive(empty + 8 * ((kb - 1) % K1_STAGES));
            }
        }
        wg_wait<0>();
        fence_regs(acc);
        TL(1);
        if (warp == 4) TX(16);
        mbar_wait(auxb, 0);
        if (warp == 4) TX(17);
        bar_sync(1, 256);
        const float2* s_rs = (const float2*)(smem + K1_RS);
        const float* s_cs = (const float*)(smem + K1_CS);
        const int g = lane >> 2, t = lane & 3;
        const int rl = wgi * 64 + ww * 16 + g;
        const float2 st0 = s_rs[rl], st1 = s_rs[rl + 8];
        const float QS = 0.25f * 1.4426950408889634f;
        const uint32_t stg = sb + ((lane >> 4) * 16 + wgi * 8 + ww * 2 + ((lane >> 3) & 1)) * 128 + (lane & 7) * 16;
        float2* s_np = (float2*)(smem + 49152) + (warp - 4) * 32 + lane;
#pragma unroll
        for (int hh = 0; hh < 12; hh++) {
            const int which = (nt * 192 + hh * 16) >> 9;
            const float sc = (which == 0) ? QS : 1.0f;
            const float a0 = st0.x * sc, b0 = st0.y * sc, a1 = st1.x * sc, b1 = st1.y * sc;
            const float2 c0 = *(const float2*)(s_cs + 16 * hh + 2 * t), c1 = *(const float2*)(s_cs + 16 * hh + 8 + 2 * t);
            const float* a = acc + 8 * hh;
            float v0 = fmaf(a0, a[0], b0 * c0.x), v1 = fmaf(a0, a[1], b0 * c0.y), v2 = fmaf(a1, a[2], b1 * c0.x), v3 = fmaf(a1, a[3], b1 * c0.y);
            float v4 = fmaf(a0, a[4], b0 * c1.x), v5 = fmaf(a0, a[5], b0 * c1.y), v6 = fmaf(a1, a[6], b1 * c1.x), v7 = fmaf(a1, a[7], b1 * c1.y);
            {
                const int head = ((nt * 192 + hh * 16) & 511) >> 4;
                uint32_t* o = (uint32_t*)g_qkv + ((size_t)((which * NH + head) * 2) * 256 + mb * 16 + wgi * 8 + ww * 2) * 32 + lane;
                o[0] = pack_bf16(v0, v1); o[32] = pack_bf16(v2, v3); o[8192] = pack_bf16(v4, v5); o[8192 + 32] = pack_bf16(v6, v7);
            }
            s_np[hh * 256] = make_float2(fmaf(v0, v0, fmaf(v1, v1, fmaf(v4, v4, v5 * v5))), fmaf(v2, v2, fmaf(v3, v3, fmaf(v6, v6, v7 * v7))));
        }
        fence_proxy_async();
        bar_arrive(2, 256 + 96);
        TL(2);
        TLDUMP;
    }
}

constexpr int AT_K = 0, AT_V = 65536, AT_ONES = 131072, AT_BAR = 163840, AT_SMEM = AT_BAR + 128;
#define POLY_MASK 0xAD6A

__device__ __forceinline__ uint32_t exp2_pair_poly(float x0, float x1) {
    uint32_t t0 = __float_as_uint(x0 + 32895.0f);
    uint32_t t1 = __float_as_uint(x1 + 32895.0f);
    uint32_t gd = __byte_perm(t0, t1, 0x6420);
    uint32_t wm = __byte_perm(t0, t1, 0x5612);
    uint32_t v = hfma2(gd, 0x71477147u, 0x354f354fu);
    uint32_t z = hmul2(v, gd);
    return (wm >> 1) + z;
}
__device__ __forceinline__ uint32_t exp2_pair_mufu(float x0, float x1) { return pack_bf16(ex2f(x0), ex2f(x1)); }
template <uint32_t MASK>
__device__ __forceinline__ void exp_blocks(const float (&s)[32], uint32_t (&p)[16]) {
#pragma unroll
    for (int b = 0; b < 8; b++) {
        if ((MASK >> b) & 1) {
            p[2 * b] = exp2_pair_poly(s[4 * b], s[4 * b + 1]);
            p[2 * b + 1] = exp2_pair_poly(s[4 * b + 2], s[4 * b + 3]);
        } else {
            p[2 * b] = exp2_pair_mufu(s[4 * b], s[4 * b + 1]);
            p[2 * b + 1] = exp2_pair_mufu(s[4 * b + 2], s[4 * b + 3]);
        }
    }
}
#define PV4(P) _Pragma("unroll") for (int i = 0; i < 4; i++) { pv_wgmma(o, P[4 * i], P[4 * i + 1], P[4 * i + 2], P[4 * i + 3], vd); vd += 16; }

__device__ __forceinline__ void attn_store(float (&o)[12], int row0, int head, int lane) {
    float l0 = __shfl_sync(0xffffffffu, o[8], lane & 28);
    float l1 = __shfl_sync(0xffffffffu, o[10], lane & 28);
    float r0 = 1.0f / l0, r1 = 1.0f / l1;
    uint32_t* op = (uint32_t*)g_ao;
    int mb = row0 >> 7, rg = (row0 & 127) >> 3;
    int kb = head >> 2, kc = (head & 3) * 2;
    size_t base = (((size_t)(mb * 8 + kb) * 8 + kc) * 16 + rg) * 32 + lane;
    op[base] = pack_bf16(o[0] * r0, o[1] * r0);
    op[base + 32] = pack_bf16(o[2] * r1, o[3] * r1);
    op[base + 16 * 32] = pack_bf16(o[4] * r0, o[5] * r0);
    op[base + 16 * 32 + 32] = pack_bf16(o[6] * r1, o[7] * r1);
}

__device__ __forceinline__ void attn_load_q(uint32_t (&q)[4], const __nv_bfloat16* gq, int row0, int lane) {
    const uint32_t* qp = (const uint32_t*)gq;
    int j0 = row0 >> 3;
    q[0] = __ldcg(qp + (0 * 256 + j0) * 32 + lane);
    q[1] = __ldcg(qp + (0 * 256 + j0 + 1) * 32 + lane);
    q[2] = __ldcg(qp + (1 * 256 + j0) * 32 + lane);
    q[3] = __ldcg(qp + (1 * 256 + j0 + 1) * 32 + lane);
}

__device__ __forceinline__ void attn_tile_safe(const uint32_t (&q)[4], uint64_t kd, uint64_t vd, int row0, int head, int lane) {
    float o[12];
#pragma unroll
    for (int i = 0; i < 12; i++) o[i] = 0.f;
    float m0 = -INFINITY, m1 = -INFINITY;
    fence_regs(o);
#pragma unroll 1
    for (int j = 0; j < 32; j++) {
        float s[32];
        uint32_t p[16];
        WG_FENCE();
        qk_wgmma_n64(s, q, kd); kd += 64;
        WG_COMMIT();
        wg_wait<0>();
        fence_regs(s);
        fence_regs(o);
        float x0 = m0, x1 = m1;
#pragma unroll
        for (int b = 0; b < 8; b++) {
            x0 = fmaxf(x0, fmaxf(s[4 * b], s[4 * b + 1]));
            x1 = fmaxf(x1, fmaxf(s[4 * b + 2], s[4 * b + 3]));
        }
        x0 = fmaxf(x0, __shfl_xor_sync(0xffffffffu, x0, 1)); x0 = fmaxf(x0, __shfl_xor_sync(0xffffffffu, x0, 2));
        x1 = fmaxf(x1, __shfl_xor_sync(0xffffffffu, x1, 1)); x1 = fmaxf(x1, __shfl_xor_sync(0xffffffffu, x1, 2));
        float al0 = ex2f(m0 - x0), al1 = ex2f(m1 - x1);
        m0 = x0; m1 = x1;
#pragma unroll
        for (int i = 0; i < 3; i++) { o[4 * i] *= al0; o[4 * i + 1] *= al0; o[4 * i + 2] *= al1; o[4 * i + 3] *= al1; }
#pragma unroll
        for (int b = 0; b < 8; b++) {
            p[2 * b] = exp2_pair_mufu(s[4 * b] - m0, s[4 * b + 1] - m0);
            p[2 * b + 1] = exp2_pair_mufu(s[4 * b + 2] - m1, s[4 * b + 3] - m1);
        }
        fence_regs(o);
        WG_FENCE();
        PV4(p);
        WG_COMMIT();
        wg_wait<0>();
        fence_regs(o);
    }
    attn_store(o, row0, head, lane);
}

__global__ void __launch_bounds__(512, 1)
attn_kernel(const __nv_bfloat16* __restrict__ wg_, const __nv_bfloat16* __restrict__ wu_,
            const __nv_bfloat16* __restrict__ wo_, const __nv_bfloat16* __restrict__ wd_) {
    extern __shared__ __align__(1024) unsigned char smem[];
    const uint32_t sb = smem_u32(smem);
    const int tid = threadIdx.x, wg = tid >> 7, warp = (tid >> 5) & 3, lane = tid & 31;
    TLDECL
    pdl_launch();
    if (blockIdx.x >= 128) {
        const int e = blockIdx.x - 128;
        const __nv_bfloat16* w = (e < 2) ? wg_ : wu_;
        float* red = (float*)smem;
        const int cgrp = tid & 127, kq = tid >> 7;
        if (cgrp < 112) {
            float s[8];
            colsum8(w, FF, (e & 1) * 896 + cgrp * 8, kq * 128, 128, s);
#pragma unroll
            for (int i = 0; i < 8; i++) red[kq * 896 + cgrp * 8 + i] = s[i];
        }
        __syncthreads();
        for (int c = tid; c < 896; c += 512)
            g_cs2[(e >> 1) * FF + (e & 1) * 896 + c] = red[c] + red[896 + c] + red[1792 + c] + red[2688 + c];
        if (tid < 32) {
            const char* p0 = (const char*)wo_ + e * (DM * DM * 2 / 4);
            for (int i = lane; i < 32; i += 32)
                asm volatile("cp.async.bulk.prefetch.L2.global [%0], %1;" :: "l"(p0 + i * 4096), "r"(4096) : "memory");
            const char* p1 = (const char*)wd_ + e * (FF * DM * 2 / 4);
            for (int i = lane; i < 112; i += 32)
                asm volatile("cp.async.bulk.prefetch.L2.global [%0], %1;" :: "l"(p1 + i * 4096), "r"(4096) : "memory");
        }
        return;
    }
    const int head = blockIdx.x >> 2, qq = blockIdx.x & 3;
    const __nv_bfloat16* gq = g_qkv + (size_t)head * (S_LEN * 16);
    const __nv_bfloat16* gk = g_qkv + (size_t)(NH + head) * (S_LEN * 16);
    const __nv_bfloat16* gv = g_qkv + (size_t)(2 * NH + head) * (S_LEN * 16);
    if (tid == 0) {
        for (int i = 0; i < 8; i++) mbar_init(sb + AT_BAR + 8 * i, 1);
        fence_barrier_init();
    }
    {
        uint4 one = make_uint4(0x00003F80u, 0, 0, 0);
#pragma unroll
        for (int i = 0; i < 4; i++) *(uint4*)(smem + AT_ONES + (i * 512 + tid) * 16) = one;
        fence_proxy_async();
    }
    __syncthreads();
    TL(3);
    pdl_wait();
    TL(4);
    auto load_kv = [&](int i) {
        uint32_t bar = sb + AT_BAR + 8 * i;
        mbar_expect(bar, 16384);
        bulk_g2s(sb + AT_K + i * 4096, gk + i * 2048, 4096, bar);
        bulk_g2s(sb + AT_K + 32768 + i * 4096, gk + 16384 + i * 2048, 4096, bar);
        bulk_g2s(sb + AT_V + i * 4096, gv + i * 2048, 4096, bar);
        bulk_g2s(sb + AT_V + 32768 + i * 4096, gv + 16384 + i * 2048, 4096, bar);
    };
    if (tid == 0) { load_kv(0); load_kv(1); }
    uint32_t q[4], q2[4];
    attn_load_q(q, gq, qq * 512 + wg * 64 + warp * 16, lane);
    attn_load_q(q2, gq, qq * 512 + (4 + wg) * 64 + warp * 16, lane);
    bool fast;
    {
        const float* nq = g_nrm + (0 * NH + head) * 128 + qq * 32;
        const float* nk = g_nrm + (1 * NH + head) * 128;
        const float* nv = g_nrm + (2 * NH + head) * 128;
        float4 k4 = __ldcg((const float4*)nk + lane), v4 = __ldcg((const float4*)nv + lane);
        float qm = warp_max(__ldcg(nq + lane));
        float km = warp_max(fmaxf(fmaxf(k4.x, k4.y), fmaxf(k4.z, k4.w)));
        float vm = warp_max(fmaxf(fmaxf(v4.x, v4.y), fmaxf(v4.z, v4.w)));
        fast = __all_sync(0xffffffffu, (qm * km <= 3500.0f) && (vm <= 1.0e24f));
    }
    TL(24);
    const uint64_t kdesc0 = make_desc(sb + AT_K, 32768, 128, 0);
    const uint64_t vdesc0 = make_desc(sb + AT_V, 128, 32768, 0);
    if (!fast) {
        if (tid == 0) for (int i = 2; i < 8; i++) load_kv(i);
        for (int i = 0; i < 8; i++) mbar_wait(sb + AT_BAR + 8 * i, 0);
#pragma unroll 1
        for (int tile = 0; tile < 2; tile++) {
            const int row0 = qq * 512 + (tile * 4 + wg) * 64 + warp * 16;
            attn_tile_safe(q, kdesc0, vdesc0, row0, head, lane);
#pragma unroll
            for (int i = 0; i < 4; i++) q[i] = q2[i];
        }
        return;
    }
#pragma unroll 1
    for (int tile = 0; tile < 2; tile++) {
        const int row0 = qq * 512 + (tile * 4 + wg) * 64 + warp * 16;
        float o[12];
#pragma unroll
        for (int i = 0; i < 12; i++) o[i] = 0.f;
        fence_regs(o);
        float sa[32];
        uint32_t pa[16];
        uint64_t kd = kdesc0, vd = vdesc0;
        if (tile == 0) { mbar_wait(sb + AT_BAR, 0); TL(25); }
        WG_FENCE();
        qk_wgmma_n64(sa, q, kd); kd += 64;
        WG_COMMIT();
#pragma unroll 1
        for (int jj = 0; jj < 8; jj++) {
            if (tile == 0 && jj < 7) {
                if (tid == 0 && jj < 6) load_kv(jj + 2);
                mbar_wait(sb + AT_BAR + 8 * (jj + 1), 0);
            }
            if (wg == 0 && warp == 0) TX(128 + tile * 8 + jj);
#pragma unroll
            for (int j = 0; j < 4; j++) {
                wg_wait<0>();
                fence_regs(sa);
                if (j & 1) exp_blocks<(POLY_MASK >> 8)>(sa, pa); else exp_blocks<(POLY_MASK & 255)>(sa, pa);
                WG_FENCE();
                qk_wgmma_n64(sa, q, kd); kd += 64;
                PV4(pa);
                WG_COMMIT();
            }
        }
        wg_wait<0>();
        fence_regs(o);
        fence_regs(sa);
        if (tile == 0) TL(26);
        attn_store(o, row0, head, lane);
#pragma unroll
        for (int i = 0; i < 4; i++) q[i] = q2[i];
    }
    TL(5);
    TLDUMP;
}

#define DELAYC 9
constexpr int F_R2 = 131072, F_X = 196608, F_BAR = 229376;
constexpr int F_RS = F_BAR + 256, F_CS = F_RS + 1024, F_SMEM = F_CS + 1792;
enum { B_FA = 0, B_HF = 4, B_BF = 8, B_BE = 11, B_CF = 14, B_CE = 20, B_ADONE = 26, B_BDONE = 27, B_XC = 28, B_PRDY = 29, B_AUX = 30, B_NUM = 31 };

__device__ __forceinline__ void st_async4(uint32_t dst, float a, float b, float c, float d, uint32_t bar) {
    asm volatile("st.async.weak.shared::cluster.mbarrier::complete_tx::bytes.v4.f32 [%0], {%1,%2,%3,%4}, [%5];"
                 :: "r"(dst), "f"(a), "f"(b), "f"(c), "f"(d), "r"(bar) : "memory");
}
__device__ __forceinline__ void poll_count(const unsigned int* p, unsigned int target) {
    int it = 0;
    while (ld_acquire(p) < target) { if (++it > (1 << 22)) __trap(); }
    asm volatile("fence.proxy.async.global;" ::: "memory");
}
__device__ __forceinline__ void tma2d_store(const CUtensorMap* m, uint32_t src, int c0, int c1) {
    asm volatile("cp.async.bulk.tensor.2d.global.shared::cta.bulk_group [%0, {%2, %3}], [%1];" :: "l"(m), "r"(src), "r"(c0), "r"(c1) : "memory");
}
__device__ __forceinline__ float2 h_row_stats(int row) {
    const float4* hp = (const float4*)(g_hstat + (size_t)row * 8);
    float4 a = __ldcg(hp), b = __ldcg(hp + 1), c = __ldcg(hp + 2), d = __ldcg(hp + 3);
    float mean = 0.125f * (a.x + a.z + b.x + b.z + c.x + c.z + d.x + d.z);
    float m2 = a.y + a.w + b.y + b.w + c.y + c.w + d.y + d.w;
    float e;
    e = a.x - mean; m2 = fmaf(64.f * e, e, m2); e = a.z - mean; m2 = fmaf(64.f * e, e, m2);
    e = b.x - mean; m2 = fmaf(64.f * e, e, m2); e = b.z - mean; m2 = fmaf(64.f * e, e, m2);
    e = c.x - mean; m2 = fmaf(64.f * e, e, m2); e = c.z - mean; m2 = fmaf(64.f * e, e, m2);
    e = d.x - mean; m2 = fmaf(64.f * e, e, m2); e = d.z - mean; m2 = fmaf(64.f * e, e, m2);
    return make_float2(rsqrtf(m2 * (1.0f / DM) + 1e-5f), -mean);
}
__device__ __forceinline__ int c_kblock(int i, int r) {
    if (i < 6) { const int e = 2 * i + r, m = e / 3, k = e - 3 * m; return 7 * m + (k == 2 ? 4 : k); }
    const int l = 2 * (i - 6) + r, m = l >> 2, k = l & 3;
    return 7 * m + (k < 2 ? 2 + k : 3 + k);
}
__device__ __forceinline__ uint32_t c_stage_a(int s, int ntB) { return s < 4 ? ((ntB + 2 * s) & 7) * 16384 : F_R2 + (s - 4) * 32768; }
__device__ __forceinline__ uint32_t c_stage_b(int s, int ntB) { return s < 4 ? ((ntB + 2 * s + 1) & 7) * 16384 : F_R2 + (s - 4) * 32768 + 16384; }
template <int R>
__device__ __forceinline__ void xchg(float (&acc)[64], float (&o)[32], uint32_t sb, unsigned char* smem, int bar, int ctid) {
    const uint32_t dst = mapa(sb + F_X + ctid * 16, 1 - R), rb = mapa(sb + F_BAR + 8 * bar, 1 - R);
#pragma unroll
    for (int q = 0; q < 8; q++) {
        const int j = (1 - R) * 32 + 4 * q;
        st_async4(dst + q * 4096, acc[j], acc[j + 1], acc[j + 2], acc[j + 3], rb);
    }
    mbar_wait_cluster(sb + F_BAR + 8 * bar, 0);
#pragma unroll
    for (int q = 0; q < 8; q++) {
        float4 v = *(const float4*)(smem + F_X + q * 4096 + ctid * 16);
        const int j = R * 32 + 4 * q;
        o[4 * q] = acc[j] + v.x; o[4 * q + 1] = acc[j + 1] + v.y; o[4 * q + 2] = acc[j + 2] + v.z; o[4 * q + 3] = acc[j + 3] + v.w;
    }
}

template <int NB, bool STAGE>
__device__ __forceinline__ void ffn_epilogue(const float* ag, const float* au, const float* s_cs, int cs_off, uint32_t* gp, uint32_t stg,
                                             float2 st0, float2 st1, int lane) {
    const int t = lane & 3;
    const float C1 = 0.7978845608028654f, C2 = 0.044715f * 0.7978845608028654f;
    const float k10 = st0.x * C1, k20 = st0.x * st0.x * st0.x * C2, k11 = st1.x * C1, k21 = st1.x * st1.x * st1.x * C2;
#pragma unroll
    for (int j2 = 0; j2 < NB / 2; j2++) {
        uint32_t pk[4];
#pragma unroll
        for (int jj = 0; jj < 2; jj++) {
            const int j = 2 * j2 + jj;
            const float2 cg = *(const float2*)(s_cs + cs_off + 8 * j + 2 * t);
            const float2 cu = *(const float2*)(s_cs + 224 + cs_off + 8 * j + 2 * t);
            float r[4];
#pragma unroll
            for (int e = 0; e < 4; e++) {
                const float nm = (e < 2) ? st0.y : st1.y, k1 = (e < 2) ? k10 : k11, k2 = (e < 2) ? k20 : k21;
                const float tg = fmaf(nm, (e & 1) ? cg.y : cg.x, ag[4 * j + e]);
                const float tu = fmaf(nm, (e & 1) ? cu.y : cu.x, au[4 * j + e]);
                const float th = tanh_fast(tg * fmaf(tg * tg, k2, k1));
                const float p = tg * tu;
                r[e] = fmaf(p, th, p);
            }
            pk[2 * jj] = pack_bf16(r[0], r[1]);
            pk[2 * jj + 1] = pack_bf16(r[2], r[3]);
        }
        if (STAGE) {
            stsm4(stg + j2 * 4096, pk[0], pk[1], pk[2], pk[3]);
        } else {
            gp[j2 * 1024] = pk[0]; gp[j2 * 1024 + 32] = pk[1]; gp[j2 * 1024 + 512] = pk[2]; gp[j2 * 1024 + 544] = pk[3];
        }
    }
}

__global__ void __cluster_dims__(2, 1, 1) __launch_bounds__(384, 1)
tail_kernel(const __grid_constant__ CUtensorMap tm_o, const __grid_constant__ CUtensorMap tm_g,
            const __grid_constant__ CUtensorMap tm_u, const __grid_constant__ CUtensorMap tm_d,
            const __grid_constant__ CUtensorMap tm_out, const __nv_bfloat16* __restrict__ x) {
    extern __shared__ __align__(1024) unsigned char smem[];
    const uint32_t sb = smem_u32(smem);
    const uint32_t bars = sb + F_BAR;
    const int tid = threadIdx.x, warp = __shfl_sync(0xffffffffu, tid >> 5, 0), lane = tid & 31;
    TLDECL
    TL(6);
    if (warp == 4) TX(200);
    const int cl = blockIdx.x >> 1, r = blockIdx.x & 1;
    const int mb = ((cl & 7) >> 1) * 4 + (cl >> 4), ntA = (cl & 1) * 2 + ((cl >> 3) & 1);
    const int nt = ntA * 2 + r;
    const int mbB = (mb & ~1) + r, ntB = (mb & 1) * 4 + ntA;
    if (tid == 0) {
#pragma unroll
        for (int i = 0; i < B_NUM; i++) {
            const int cnt = (i >= B_BE && i < B_BE + 3) ? 16 : (i == B_BDONE) ? DELAYC : ((i >= B_CE && i < B_CE + 6) || i == B_PRDY) ? 8 : (i == B_AUX || i == B_ADONE) ? 2 : 1;
            mbar_init(bars + 8 * i, cnt);
        }
        mbar_expect(bars + 8 * B_XC, 32768);
        fence_barrier_init();
    }
    TL(28);
    __syncthreads();
    TL(29);
    asm volatile("barrier.cluster.arrive.relaxed.aligned;" ::: "memory");
    TL(30);
    if (warp < 4) {
        asm volatile("setmaxnreg.dec.sync.aligned.u32 56;");
        if (warp == 0) TX(205);
        if (warp == 0) {
            if (lane == 0) {
                auto load_b = [&](int it) {
                    const int s = it % 3, pass = it >> 3, kb = (ntB + it) & 7;
                    const int ng = pass ? 3 : 4, c0 = ntB * 224 + pass * 128;
                    const uint32_t bar = bars + 8 * (B_BF + s), dst = sb + F_R2 + s * 32768 + r * ng * 4096;
                    mbar_expect(bar, ng * 8192);
                    for (int i = 0; i < ng; i++) tma2d_mc(dst + i * 4096, r ? &tm_u : &tm_g, c0 + i * 32, kb * 64, bar);
                };
                for (int i = 0; i < 8; i++) {
                    const uint32_t bar = bars + 8 * (B_FA + (i >> 1));
                    if (!(i & 1)) mbar_expect(bar, 49152);
                    tma2d(sb + F_R2 + 32768 + i * 8192, &tm_o, nt * 64, i * 64, bar);
                }
                asm volatile("barrier.cluster.wait.acquire;" ::: "memory");
                pdl_wait();
                TL(16);
                for (int i = 0; i < 4; i++)
                    bulk_g2s_mc(sb + (2 * i + r) * 16384, g_ao + (size_t)(mb * 8 + 2 * i + r) * 8192, 16384, bars + 8 * (B_FA + i));
                load_b(0);
                if (blockIdx.x == 0)
                    for (int i = 0; i < 32; i++) g_cnt[i] = 0;
                mbar_wait_cluster(bars + 8 * B_ADONE, 0);
                load_b(1); load_b(2);
                auto load_c = [&](int i) {
                    const int s = i % 6, kb = c_kblock(i, r);
                    const uint32_t bar = bars + 8 * (B_CF + s), da = sb + c_stage_a(s, ntB), db = sb + c_stage_b(s, ntB);
                    mbar_expect(bar, 32768);
                    tma2d(db, &tm_d, ntA * 128, kb * 64, bar);
                    tma2d(db + 8192, &tm_d, ntA * 128 + 64, kb * 64, bar);
                    bulk_g2s(da, g_g + (size_t)(mb * 28 + kb) * 8192, 16384, bar);
                };
                for (int it = 3; it < 16; it++) {
                    mbar_wait_cluster(bars + 8 * (B_BE + it % 3), (it / 3 - 1) & 1);
                    load_b(it);
                    if (it == 12) { poll_count(&g_cnt2[mb], 8); load_c(0); }
                    if (it == 14) load_c(1);
                }
                mbar_wait(bars + 8 * B_BDONE, 0);
                for (int i = 2; i < 14; i++) {
                    if (i >= 6) mbar_wait(bars + 8 * (B_CE + i % 6), ((i / 6) - 1) & 1);
                    if (i == 6) { poll_count(&g_cnt2[16 + mb], 8); TL(18); }
                    load_c(i);
                }
            }
            else asm volatile("barrier.cluster.wait.acquire;" ::: "memory");
            TLDUMP;
        } else if (warp == 1) {
            asm volatile("barrier.cluster.wait.acquire.aligned;" ::: "memory");
            bar_sync(5, 288);
            if (lane == 0) { red_release(&g_cnt2[32 + mb * 8 + nt]); TL(9); }
            __syncwarp();
            bar_sync(1, 288);
            if (lane == 0) red_release(&g_cnt2[mbB]);
            __syncwarp();
            bar_sync(2, 288);
            if (lane == 0) {
                red_release(&g_cnt2[16 + mbB]);
                if (DELAYC == 9) mbar_arrive(bars + 8 * B_BDONE);
                TL(13);
            }
            __syncwarp();
            bar_sync(3, 288);
            if (lane == 0) {
                tma2d_store(&tm_out, sb, nt * 64, mb * 128);
                bulk_commit();
                bulk_wait_all();
                TL(15);
            }
            TLDUMP;
        } else {
            asm volatile("barrier.cluster.wait.acquire.aligned;" ::: "memory");
            pdl_wait();
            float2* s_rs = (float2*)(smem + F_RS);
            float* s_cs = (float*)(smem + F_CS);
            for (int c = tid - 64; c < 448; c += 64)
                s_cs[c] = __ldcg(&g_cs2[(c >= 224 ? FF - 224 : 0) + ntB * 224 + c]);
            if (warp == 3) {
                const int kb = (ntB + lane) & 7;
                const uint32_t bar = bars + 8 * ((lane & 7) < 4 ? B_HF + (lane & 7) : B_FA + (lane & 7) - 4);
                mbar_wait_cluster(bars + 8 * B_ADONE, 0);
                bool pending = lane < 8;
                int spin = 0;
                while (__any_sync(0xffffffffu, pending)) {
                    if (pending && ld_acquire(&g_cnt2[32 + mbB * 8 + kb]) != 0) {
                        asm volatile("fence.proxy.async.global;" ::: "memory");
                        mbar_expect(bar, 16384);
                        bulk_g2s(sb + kb * 16384, g_h + (size_t)(mbB * 8 + kb) * 8192, 16384, bar);
                        pending = false;
                    }
                    if (++spin > (1 << 22)) __trap();
                }
            }
            TL(17);
            __syncwarp();
            if (lane < 8) poll_count(&g_cnt2[32 + mbB * 8 + lane], 1);
            __syncwarp();
            for (int rr = tid - 64; rr < 128; rr += 64) {
                s_rs[rr] = h_row_stats(mbB * 128 + rr);
            }
            __syncwarp();
            if (lane == 0) mbar_arrive(bars + 8 * B_AUX);
            TLDUMP;
        }
    } else {
        asm volatile("setmaxnreg.inc.sync.aligned.u32 216;");
        if (warp == 4) TX(206);
        const int wgi = (warp >> 2) - 1, ww = warp & 3, ctid = tid - 128;
        const int g = lane >> 2, t = lane & 3;
        const int rl = wgi * 64 + ww * 16 + g, row = mb * 128 + rl;
        const int rgl = wgi * 8 + ww * 2;
        const float2* s_rs = (const float2*)(smem + F_RS);
        const float* s_cs = (const float*)(smem + F_CS);
        const uint32_t stl = ((lane >> 4) * 16 + rgl + ((lane >> 3) & 1)) * 128 + (lane & 7) * 16;
        uint32_t* hp = (uint32_t*)g_h + ((size_t)(mb * 8 + nt) * 8 * 16 + rgl) * 32 + lane;
        const uint32_t rbars = mapa(bars, 1 - r);
        TL(23);
        {
            uint32_t xr[16];
            const uint32_t* xp = (const uint32_t*)(x + (size_t)row * DM + nt * 64) + t;
#pragma unroll
            for (int j = 0; j < 8; j++) { xr[2 * j] = __ldg(xp + 4 * j); xr[2 * j + 1] = __ldg(xp + 8 * (DM / 2) + 4 * j); }
            float acc[32];
#pragma unroll 1
            for (int i = 0; i < 8; i++) {
                if (!(i & 1)) { mbar_wait(bars + 8 * (B_FA + (i >> 1)), 0); if (i == 0) TL(19); }
                uint64_t ad = make_desc(sb + i * 16384 + wgi * 1024, 2048, 128, 0);
                uint64_t bd = make_desc(sb + F_R2 + 32768 + i * 8192, 8192, 1024, 1);
                WG_FENCE();
#pragma unroll
                for (int k = 0; k < 4; k++) wgmma_ss_n64(acc, ad + k * 256, bd + k * 128, (i | k) != 0);
                WG_COMMIT();
            }
            wg_wait<0>();
            fence_regs(acc);
            TL(7);
            asm volatile("barrier.cluster.wait.acquire.aligned;" ::: "memory");
            bar_sync(4, 256);
            if (tid == 128) { mbar_arrive(bars + 8 * B_ADONE); mbar_arrive_remote(mapa(bars + 8 * B_ADONE, 1 - r)); }
            float v0[16], v1[16];
            float s0 = 0.f, s1 = 0.f;
#pragma unroll
            for (int j2 = 0; j2 < 4; j2++) {
                uint32_t u[4];
#pragma unroll
                for (int jj = 0; jj < 2; jj++) {
                    const int j = 2 * j2 + jj;
                    u[2 * jj] = pack_bf16(bf_lo(xr[2 * j]) + acc[4 * j], bf_hi(xr[2 * j]) + acc[4 * j + 1]);
                    u[2 * jj + 1] = pack_bf16(bf_lo(xr[2 * j + 1]) + acc[4 * j + 2], bf_hi(xr[2 * j + 1]) + acc[4 * j + 3]);
                    v0[2 * j] = bf_lo(u[2 * jj]); v0[2 * j + 1] = bf_hi(u[2 * jj]);
                    v1[2 * j] = bf_lo(u[2 * jj + 1]); v1[2 * j + 1] = bf_hi(u[2 * jj + 1]);
                    s0 += v0[2 * j] + v0[2 * j + 1];
                    s1 += v1[2 * j] + v1[2 * j + 1];
                }
                hp[j2 * 1024] = u[0]; hp[j2 * 1024 + 32] = u[1]; hp[j2 * 1024 + 512] = u[2]; hp[j2 * 1024 + 544] = u[3];
            }
            float m0 = s0 * (1.0f / 16), m1 = s1 * (1.0f / 16), q0 = 0.f, q1 = 0.f;
#pragma unroll
            for (int i = 0; i < 16; i++) {
                float d0 = v0[i] - m0, d1 = v1[i] - m1;
                q0 = fmaf(d0, d0, q0); q1 = fmaf(d1, d1, q1);
            }
#pragma unroll
            for (int st = 0; st < 2; st++) {
                float hn = st ? 16.f : 8.f;
                float om0 = __shfl_xor_sync(0xffffffffu, m0, 1 << st), oq0 = __shfl_xor_sync(0xffffffffu, q0, 1 << st);
                float om1 = __shfl_xor_sync(0xffffffffu, m1, 1 << st), oq1 = __shfl_xor_sync(0xffffffffu, q1, 1 << st);
                float d0 = om0 - m0, d1 = om1 - m1;
                q0 = q0 + oq0 + d0 * d0 * hn; q1 = q1 + oq1 + d1 * d1 * hn;
                m0 = 0.5f * (m0 + om0); m1 = 0.5f * (m1 + om1);
            }
            if (t == 0) {
                g_hstat[row * 8 + nt] = make_float2(m0, q0);
                g_hstat[(row + 8) * 8 + nt] = make_float2(m1, q1);
            }
            bar_arrive(5, 288);
            TL(8);
        }
        uint32_t* gp = (uint32_t*)g_g + (((size_t)mbB * 224 + ntB * 28) * 16 + rgl) * 32 + lane;
        {
            float ag[128];
#pragma unroll 1
            for (int kb = 0; kb < 8; kb++) {
                const int s = kb % 3;
                mbar_wait(bars + 8 * (kb < 4 ? B_HF + kb : B_FA + kb - 4), kb < 4 ? 0 : 1);
                mbar_wait(bars + 8 * (B_BF + s), (kb / 3) & 1);
                uint64_t ad = make_desc(sb + ((ntB + kb) & 7) * 16384 + wgi * 1024, 2048, 128, 0);
                uint64_t bd = make_desc(sb + F_R2 + s * 32768, 4096, 512, 2);
                WG_FENCE();
#pragma unroll
                for (int k = 0; k < 4; k++) wgmma_ss_n256(ag, ad + k * 256, bd + k * 64, (kb | k) != 0);
                WG_COMMIT();
                if (kb > 0) {
                    wg_wait<1>();
                    if (lane == 0) { mbar_arrive(bars + 8 * (B_BE + (kb - 1) % 3)); mbar_arrive_remote(rbars + 8 * (B_BE + (kb - 1) % 3)); }
                }
            }
            wg_wait<0>();
            if (lane == 0) { mbar_arrive(bars + 8 * (B_BE + 7 % 3)); mbar_arrive_remote(rbars + 8 * (B_BE + 7 % 3)); }
            fence_regs(ag);
            TL(10);
            mbar_wait(bars + 8 * B_AUX, 0);
            ffn_epilogue<16, false>(ag, ag + 64, s_cs, 0, gp, 0, s_rs[rl], s_rs[rl + 8], lane);
            bar_arrive(1, 288);
        }
        {
            float ag[96];
#pragma unroll 1
            for (int kb = 0; kb < 8; kb++) {
                const int it = 8 + kb, s = it % 3;
                mbar_wait(bars + 8 * (B_BF + s), (it / 3) & 1);
                uint64_t ad = make_desc(sb + ((ntB + kb) & 7) * 16384 + wgi * 1024, 2048, 128, 0);
                uint64_t bd = make_desc(sb + F_R2 + s * 32768, 4096, 512, 2);
                WG_FENCE();
#pragma unroll
                for (int k = 0; k < 4; k++) wgmma_ss_n192(ag, ad + k * 256, bd + k * 64, (kb | k) != 0);
                WG_COMMIT();
                if (kb > 0) {
                    wg_wait<1>();
                    if (lane == 0 && it + 2 < 16) { mbar_arrive(bars + 8 * (B_BE + (it - 1) % 3)); mbar_arrive_remote(rbars + 8 * (B_BE + (it - 1) % 3)); }
                }
            }
            wg_wait<0>();
            if (lane == 0) {
                mbar_arrive(bars + 8 * B_BDONE);
                mbar_arrive_remote(rbars + 8 * B_PRDY);
            }
            fence_regs(ag);
            TL(11);
            ffn_epilogue<12, false>(ag, ag + 48, s_cs, 128, gp + 16 * 512, 0, s_rs[rl], s_rs[rl + 8], lane);
            bar_arrive(2, 288);
            TL(12);
        }
        {
            uint32_t hr[16];
#pragma unroll
            for (int j = 0; j < 8; j++) { hr[2 * j] = __ldcg(hp + j * 512); hr[2 * j + 1] = __ldcg(hp + j * 512 + 32); }
            mbar_wait(bars + 8 * (B_CF + 0), 0);
            const float a0 = h_row_stats(row).x, a1 = h_row_stats(row + 8).x;
            float acc[64];
#pragma unroll 1
            for (int kb = 0; kb < 14; kb++) {
                const int s = kb % 6;
                mbar_wait(bars + 8 * (B_CF + s), (kb / 6) & 1);
                if (warp == 4) TX(96 + kb);
                uint64_t ad = make_desc(sb + c_stage_a(s, ntB) + wgi * 1024, 2048, 128, 0);
                uint64_t bd = make_desc(sb + c_stage_b(s, ntB), 8192, 1024, 1);
                WG_FENCE();
#pragma unroll
                for (int k = 0; k < 4; k++) wgmma_ss_n128(acc, ad + k * 256, bd + k * 128, (kb | k) != 0);
                WG_COMMIT();
                if (kb > 0) {
                    wg_wait<1>();
                    if (lane == 0) mbar_arrive(bars + 8 * (B_CE + (kb - 1) % 6));
                }
            }
            wg_wait<0>();
            fence_regs(acc);
            TL(14);
            mbar_wait_cluster(bars + 8 * B_PRDY, 0);
            float o[32];
            if (r == 0) xchg<0>(acc, o, sb, smem, B_XC, ctid); else xchg<1>(acc, o, sb, smem, B_XC, ctid);
            TL(22);
            bar_sync(4, 256);
            const float k0 = 0.5f * a0 * a0, k1 = 0.5f * a1 * a1;
            const int srow = wgi * 64 + ww * 16 + ((lane >> 3) & 1) * 8 + (lane & 7);
#pragma unroll
            for (int j2 = 0; j2 < 4; j2++) {
                uint32_t u[4];
#pragma unroll
                for (int jj = 0; jj < 2; jj++) {
                    const int j = 2 * j2 + jj;
                    u[2 * jj] = pack_bf16(fmaf(k0, o[4 * j], bf_lo(hr[2 * j])), fmaf(k0, o[4 * j + 1], bf_hi(hr[2 * j])));
                    u[2 * jj + 1] = pack_bf16(fmaf(k1, o[4 * j + 2], bf_lo(hr[2 * j + 1])), fmaf(k1, o[4 * j + 3], bf_hi(hr[2 * j + 1])));
                }
                const int chunk = 2 * j2 + (lane >> 4);
                stsm4(sb + srow * 128 + ((chunk ^ (lane & 7)) * 16), u[0], u[1], u[2], u[3]);
            }
            fence_proxy_async();
            bar_arrive(3, 288);
            TLDUMP;
        }
    }
}

typedef CUresult (*EncodeFn)(CUtensorMap*, CUtensorMapDataType, cuuint32_t, void*, const cuuint64_t*, const cuuint64_t*,
                             const cuuint32_t*, const cuuint32_t*, CUtensorMapInterleave, CUtensorMapSwizzle,
                             CUtensorMapL2promotion, CUtensorMapFloatOOBfill);

void encode(EncodeFn fn, CUtensorMap* m, const void* ptr, int rank, const cuuint64_t* dims, const cuuint64_t* strides,
            const cuuint32_t* box, CUtensorMapSwizzle swz) {
    cuuint32_t es[3] = {1, 1, 1};
    fn(m, CU_TENSOR_MAP_DATA_TYPE_BFLOAT16, rank, (void*)ptr, dims, strides, box, es, CU_TENSOR_MAP_INTERLEAVE_NONE, swz,
       CU_TENSOR_MAP_L2_PROMOTION_L2_256B, CU_TENSOR_MAP_FLOAT_OOB_FILL_NONE);
}

template <typename... KArgs, typename... Args>
void launch(void (*kern)(KArgs...), int grid, int block, int smem, bool pdl, Args... args) {
    cudaLaunchConfig_t cfg = {};
    cfg.gridDim = dim3(grid); cfg.blockDim = dim3(block); cfg.dynamicSmemBytes = smem;
    cfg.stream = cudaStreamPerThread;
    cudaLaunchAttribute at[1];
    at[0].id = cudaLaunchAttributeProgrammaticStreamSerialization;
    at[0].val.programmaticStreamSerializationAllowed = 1;
    cfg.attrs = at; cfg.numAttrs = pdl ? 1 : 0;
    cudaLaunchKernelEx(&cfg, kern, KArgs(args)...);
}

}

extern "C" void kernel_launch(void* const* d_in, const int* in_sizes, int n_in, void* d_out, int out_size) {
    const __nv_bfloat16* x = (const __nv_bfloat16*)d_in[0];
    const __nv_bfloat16* wqkv = (const __nv_bfloat16*)d_in[1];
    const __nv_bfloat16* wo = (const __nv_bfloat16*)d_in[2];
    const __nv_bfloat16* wgate = (const __nv_bfloat16*)d_in[4];
    const __nv_bfloat16* wup = (const __nv_bfloat16*)d_in[5];
    const __nv_bfloat16* wdown = (const __nv_bfloat16*)d_in[6];
    __nv_bfloat16* out = (__nv_bfloat16*)d_out;

    static CUtensorMap tm_x, tm_wqkv, tm_wo, tm_wg, tm_wu, tm_wd, tm_out;
    static const void* cached[7] = {nullptr, nullptr, nullptr, nullptr, nullptr, nullptr, nullptr};
    if (cached[0] != x || cached[1] != wqkv || cached[2] != wo || cached[3] != wgate || cached[4] != wup || cached[5] != wdown || cached[6] != out) {
        void* fp = nullptr;
        cudaDriverEntryPointQueryResult qr;
        cudaGetDriverEntryPoint("cuTensorMapEncodeTiled", &fp, cudaEnableDefault, &qr);
        EncodeFn fn = (EncodeFn)fp;
        { cuuint64_t d[2] = {512, 2048}, s[1] = {1024}; cuuint32_t b[2] = {64, 128};
          encode(fn, &tm_x, x, 2, d, s, b, CU_TENSOR_MAP_SWIZZLE_128B);
          encode(fn, &tm_out, out, 2, d, s, b, CU_TENSOR_MAP_SWIZZLE_128B); }
        { cuuint64_t d[3] = {64, 512, 24}, s[2] = {3072, 128}; cuuint32_t b[3] = {64, 64, 3};
          encode(fn, &tm_wqkv, wqkv, 3, d, s, b, CU_TENSOR_MAP_SWIZZLE_128B); }
        { cuuint64_t d[2] = {512, 512}, s[1] = {1024}; cuuint32_t b[2] = {64, 64};
          encode(fn, &tm_wo, wo, 2, d, s, b, CU_TENSOR_MAP_SWIZZLE_128B); }
        { cuuint64_t d[2] = {1792, 512}, s[1] = {3584}; cuuint32_t b[2] = {32, 64};
          encode(fn, &tm_wg, wgate, 2, d, s, b, CU_TENSOR_MAP_SWIZZLE_64B);
          encode(fn, &tm_wu, wup, 2, d, s, b, CU_TENSOR_MAP_SWIZZLE_64B); }
        { cuuint64_t d[2] = {512, 1792}, s[1] = {1024}; cuuint32_t b[2] = {64, 64};
          encode(fn, &tm_wd, wdown, 2, d, s, b, CU_TENSOR_MAP_SWIZZLE_128B); }
        cudaFuncSetAttribute(qkv_kernel, cudaFuncAttributeMaxDynamicSharedMemorySize, F_SMEM);
        cudaFuncSetAttribute(qkv_kernel, cudaFuncAttributePreferredSharedMemoryCarveout, 100);
        cudaFuncSetAttribute(attn_kernel, cudaFuncAttributeMaxDynamicSharedMemorySize, F_SMEM);
        cudaFuncSetAttribute(attn_kernel, cudaFuncAttributePreferredSharedMemoryCarveout, 100);
        cudaFuncSetAttribute(tail_kernel, cudaFuncAttributeMaxDynamicSharedMemorySize, F_SMEM);
        cudaFuncSetAttribute(tail_kernel, cudaFuncAttributePreferredSharedMemoryCarveout, 100);
        cached[0] = x; cached[1] = wqkv; cached[2] = wo; cached[3] = wgate; cached[4] = wup; cached[5] = wdown; cached[6] = out;
    }
    launch(qkv_kernel, 128, 384, F_SMEM, false, tm_x, tm_wqkv, x, wqkv);
    launch(attn_kernel, 132, 512, F_SMEM, true, wgate, wup, wo, wdown);
    launch(tail_kernel, 128, 384, F_SMEM, true, tm_wo, tm_wg, tm_wu, tm_wd, tm_out, x);
}
```

```cpp
#include <cuda_runtime.h>
#include <cuda_bf16.h>
#include <cuda.h>
#include <stdint.h>

#define K1_DIRECT
namespace {

constexpr int S_LEN = 2048, DM = 512, NH = 32, FF = 1792;

__device__ __align__(1024) __nv_bfloat16 g_qkv[3 * NH * S_LEN * 16];
__device__ __align__(1024) __nv_bfloat16 g_ao[S_LEN * DM];
__device__ __align__(1024) __nv_bfloat16 g_h[S_LEN * DM];
__device__ __align__(1024) __nv_bfloat16 g_g[S_LEN * FF];
__device__ __align__(16) float2 g_rowstat1[S_LEN];
__device__ float g_cs1_part[16 * 1536];
__device__ unsigned int g_cnt[32];
__device__ unsigned int g_cnt2[32 + 128 * 32];
__device__ float g_nrm[3 * NH * 128];
__device__ float2 g_hstat[S_LEN * 8];
__device__ float g_cs2[2 * FF];

#define TLDECL
#define TL(slot)
#define TLDUMP
#define TX(slot)
__device__ __forceinline__ uint32_t smem_u32(const void* p) { return (uint32_t)__cvta_generic_to_shared(p); }
__device__ __forceinline__ void mbar_init(uint32_t a, int c) { asm volatile("mbarrier.init.shared.b64 [%0], %1;" :: "r"(a), "r"(c)); }
__device__ __forceinline__ void mbar_expect(uint32_t a, int bytes) { asm volatile("mbarrier.arrive.expect_tx.shared.b64 _, [%0], %1;" :: "r"(a), "r"(bytes) : "memory"); }
__device__ __forceinline__ void mbar_arrive(uint32_t a) { asm volatile("mbarrier.arrive.shared.b64 _, [%0];" :: "r"(a) : "memory"); }
__device__ __forceinline__ void mbar_wait(uint32_t a, int parity) {
    uint32_t done;
    int it = 0;
    do {
        asm volatile("{\n.reg .pred p;\nmbarrier.try_wait.parity.shared.b64 p, [%1], %2;\nselp.u32 %0, 1, 0, p;\n}"
                     : "=r"(done) : "r"(a), "r"(parity) : "memory");
        if (++it > (1 << 24)) __trap();
    } while (!done);
}
__device__ __forceinline__ void bulk_g2s(uint32_t dst, const void* src, int bytes, uint32_t bar) {
    asm volatile("cp.async.bulk.shared::cluster.global.mbarrier::complete_tx::bytes [%0], [%1], %2, [%3];"
                 :: "r"(dst), "l"(src), "r"(bytes), "r"(bar) : "memory");
}
__device__ __forceinline__ void tma2d(uint32_t dst, const CUtensorMap* m, int c0, int c1, uint32_t bar) {
    asm volatile("cp.async.bulk.tensor.2d.shared::cluster.global.mbarrier::complete_tx::bytes [%0], [%1, {%3, %4}], [%2];"
                 :: "r"(dst), "l"(m), "r"(bar), "r"(c0), "r"(c1) : "memory");
}
__device__ __forceinline__ void tma3d(uint32_t dst, const CUtensorMap* m, int c0, int c1, int c2, uint32_t bar) {
    asm volatile("cp.async.bulk.tensor.3d.shared::cluster.global.mbarrier::complete_tx::bytes [%0], [%1, {%3, %4, %5}], [%2];"
                 :: "r"(dst), "l"(m), "r"(bar), "r"(c0), "r"(c1), "r"(c2) : "memory");
}
__device__ __forceinline__ void prefetch_tmap(const CUtensorMap* m) { asm volatile("prefetch.tensormap [%0];" :: "l"(m) : "memory"); }
__device__ __forceinline__ void pdl_wait() { asm volatile("griddepcontrol.wait;" ::: "memory"); }
__device__ __forceinline__ void pdl_launch() { asm volatile("griddepcontrol.launch_dependents;" ::: "memory"); }
__device__ __forceinline__ void fence_barrier_init() { asm volatile("fence.mbarrier_init.release.cluster;" ::: "memory"); }
__device__ __forceinline__ void fence_proxy_async() { asm volatile("fence.proxy.async.shared::cta;" ::: "memory"); }
__device__ __forceinline__ uint64_t make_desc(uint32_t saddr, uint32_t lbo, uint32_t sbo, uint32_t swz) {
    return (uint64_t)((saddr & 0x3FFFF) >> 4) | ((uint64_t)((lbo & 0x3FFFF) >> 4) << 16) |
           ((uint64_t)((sbo & 0x3FFFF) >> 4) << 32) | ((uint64_t)swz << 62);
}
#define WG_FENCE() asm volatile("wgmma.fence.sync.aligned;" ::: "memory")
#define WG_COMMIT() asm volatile("wgmma.commit_group.sync.aligned;" ::: "memory")
template <int N> __device__ __forceinline__ void wg_wait() { asm volatile("wgmma.wait_group.sync.aligned %0;" :: "n"(N) : "memory"); }
template <int N> __device__ __forceinline__ void fence_regs(float (&d)[N]) {
#pragma unroll
    for (int i = 0; i < N; i++) asm volatile("" : "+f"(d[i]) :: "memory");
}
__device__ __forceinline__ float ex2f(float x) { float y; asm("ex2.approx.ftz.f32 %0, %1;" : "=f"(y) : "f"(x)); return y; }
__device__ __forceinline__ float tanh_fast(float x) { float y; asm("tanh.approx.f32 %0, %1;" : "=f"(y) : "f"(x)); return y; }
__device__ __forceinline__ uint32_t pack_bf16(float lo, float hi) { uint32_t r; asm("cvt.rn.bf16x2.f32 %0, %1, %2;" : "=r"(r) : "f"(hi), "f"(lo)); return r; }
__device__ __forceinline__ float bf_lo(uint32_t u) { return __uint_as_float(u << 16); }
__device__ __forceinline__ float bf_hi(uint32_t u) { return __uint_as_float(u & 0xFFFF0000u); }
__device__ __forceinline__ uint32_t hfma2(uint32_t a, uint32_t b, uint32_t c) { uint32_t r; asm("fma.rn.f16x2 %0, %1, %2, %3;" : "=r"(r) : "r"(a), "r"(b), "r"(c)); return r; }
__device__ __forceinline__ uint32_t hmul2(uint32_t a, uint32_t b) { uint32_t r; asm("mul.rn.f16x2 %0, %1, %2;" : "=r"(r) : "r"(a), "r"(b)); return r; }
__device__ __forceinline__ unsigned int ld_acquire(const unsigned int* p) { unsigned int v; asm volatile("ld.acquire.gpu.u32 %0, [%1];" : "=r"(v) : "l"(p) : "memory"); return v; }
__device__ __forceinline__ void red_release(unsigned int* p) { asm volatile("red.release.gpu.global.add.u32 [%0], 1;" :: "l"(p) : "memory"); }
__device__ __forceinline__ void stsm4(uint32_t addr, uint32_t a, uint32_t b, uint32_t c, uint32_t d) {
    asm volatile("stmatrix.sync.aligned.m8n8.x4.shared.b16 [%0], {%1,%2,%3,%4};" :: "r"(addr), "r"(a), "r"(b), "r"(c), "r"(d) : "memory");
}
__device__ __forceinline__ void bulk_s2g(void* dst, uint32_t src, int bytes) {
    asm volatile("cp.async.bulk.global.shared::cta.bulk_group [%0], [%1], %2;" :: "l"(dst), "r"(src), "r"(bytes) : "memory");
}
__device__ __forceinline__ void bulk_commit() { asm volatile("cp.async.bulk.commit_group;" ::: "memory"); }
__device__ __forceinline__ void bulk_wait_all() { asm volatile("cp.async.bulk.wait_group 0;" ::: "memory"); }
__device__ __forceinline__ void bulk_wait_read() { asm volatile("cp.async.bulk.wait_group.read 0;" ::: "memory"); }
__device__ __forceinline__ void bar_sync(int id, int n) { asm volatile("bar.sync %0, %1;" :: "r"(id), "r"(n) : "memory"); }
__device__ __forceinline__ void bar_arrive(int id, int n) { asm volatile("bar.arrive %0, %1;" :: "r"(id), "r"(n) : "memory"); }
__device__ __forceinline__ float warp_sum(float v) {
#pragma unroll
    for (int o = 16; o; o >>= 1) v += __shfl_xor_sync(0xffffffffu, v, o);
    return v;
}
__device__ __forceinline__ float warp_max(float v) {
#pragma unroll
    for (int o = 16; o; o >>= 1) v = fmaxf(v, __shfl_xor_sync(0xffffffffu, v, o));
    return v;
}

__device__ __forceinline__ void wgmma_ss_n64(float (&d)[32], uint64_t adesc, uint64_t bdesc, int scale_d) {
    asm volatile("{\n.reg .pred p;\nsetp.ne.b32 p, %34, 0;\n"
      "wgmma.mma_async.sync.aligned.m64n64k16.f32.bf16.bf16 {%0,%1,%2,%3,%4,%5,%6,%7,%8,%9,%10,%11,%12,%13,%14,%15,%16,%17,%18,%19,%20,%21,%22,%23,%24,%25,%26,%27,%28,%29,%30,%31}, %32, %33, p, 1, 1, 0, 1;\n}"
      : "+f"(d[0]), "+f"(d[1]), "+f"(d[2]), "+f"(d[3]), "+f"(d[4]), "+f"(d[5]), "+f"(d[6]), "+f"(d[7]), "+f"(d[8]), "+f"(d[9]), "+f"(d[10]), "+f"(d[11]), "+f"(d[12]), "+f"(d[13]), "+f"(d[14]), "+f"(d[15]), "+f"(d[16]), "+f"(d[17]), "+f"(d[18]), "+f"(d[19]), "+f"(d[20]), "+f"(d[21]), "+f"(d[22]), "+f"(d[23]), "+f"(d[24]), "+f"(d[25]), "+f"(d[26]), "+f"(d[27]), "+f"(d[28]), "+f"(d[29]), "+f"(d[30]), "+f"(d[31])
      : "l"(adesc), "l"(bdesc), "r"(scale_d));
}
__device__ __forceinline__ void wgmma_ss_n128(float (&d)[64], uint64_t adesc, uint64_t bdesc, int scale_d) {
    asm volatile("{\n.reg .pred p;\nsetp.ne.b32 p, %66, 0;\n"
      "wgmma.mma_async.sync.aligned.m64n128k16.f32.bf16.bf16 {%0,%1,%2,%3,%4,%5,%6,%7,%8,%9,%10,%11,%12,%13,%14,%15,%16,%17,%18,%19,%20,%21,%22,%23,%24,%25,%26,%27,%28,%29,%30,%31,%32,%33,%34,%35,%36,%37,%38,%39,%40,%41,%42,%43,%44,%45,%46,%47,%48,%49,%50,%51,%52,%53,%54,%55,%56,%57,%58,%59,%60,%61,%62,%63}, %64, %65, p, 1, 1, 0, 1;\n}"
      : "+f"(d[0]), "+f"(d[1]), "+f"(d[2]), "+f"(d[3]), "+f"(d[4]), "+f"(d[5]), "+f"(d[6]), "+f"(d[7]), "+f"(d[8]), "+f"(d[9]), "+f"(d[10]), "+f"(d[11]), "+f"(d[12]), "+f"(d[13]), "+f"(d[14]), "+f"(d[15]), "+f"(d[16]), "+f"(d[17]), "+f"(d[18]), "+f"(d[19]), "+f"(d[20]), "+f"(d[21]), "+f"(d[22]), "+f"(d[23]), "+f"(d[24]), "+f"(d[25]), "+f"(d[26]), "+f"(d[27]), "+f"(d[28]), "+f"(d[29]), "+f"(d[30]), "+f"(d[31]), "+f"(d[32]), "+f"(d[33]), "+f"(d[34]), "+f"(d[35]), "+f"(d[36]), "+f"(d[37]), "+f"(d[38]), "+f"(d[39]), "+f"(d[40]), "+f"(d[41]), "+f"(d[42]), "+f"(d[43]), "+f"(d[44]), "+f"(d[45]), "+f"(d[46]), "+f"(d[47]), "+f"(d[48]), "+f"(d[49]), "+f"(d[50]), "+f"(d[51]), "+f"(d[52]), "+f"(d[53]), "+f"(d[54]), "+f"(d[55]), "+f"(d[56]), "+f"(d[57]), "+f"(d[58]), "+f"(d[59]), "+f"(d[60]), "+f"(d[61]), "+f"(d[62]), "+f"(d[63])
      : "l"(adesc), "l"(bdesc), "r"(scale_d));
}
__device__ __forceinline__ void wgmma_ss_n192(float (&d)[96], uint64_t adesc, uint64_t bdesc, int scale_d) {
    asm volatile("{\n.reg .pred p;\nsetp.ne.b32 p, %98, 0;\n"
      "wgmma.mma_async.sync.aligned.m64n192k16.f32.bf16.bf16 {%0,%1,%2,%3,%4,%5,%6,%7,%8,%9,%10,%11,%12,%13,%14,%15,%16,%17,%18,%19,%20,%21,%22,%23,%24,%25,%26,%27,%28,%29,%30,%31,%32,%33,%34,%35,%36,%37,%38,%39,%40,%41,%42,%43,%44,%45,%46,%47,%48,%49,%50,%51,%52,%53,%54,%55,%56,%57,%58,%59,%60,%61,%62,%63,%64,%65,%66,%67,%68,%69,%70,%71,%72,%73,%74,%75,%76,%77,%78,%79,%80,%81,%82,%83,%84,%85,%86,%87,%88,%89,%90,%91,%92,%93,%94,%95}, %96, %97, p, 1, 1, 0, 1;\n}"
      : "+f"(d[0]), "+f"(d[1]), "+f"(d[2]), "+f"(d[3]), "+f"(d[4]), "+f"(d[5]), "+f"(d[6]), "+f"(d[7]), "+f"(d[8]), "+f"(d[9]), "+f"(d[10]), "+f"(d[11]), "+f"(d[12]), "+f"(d[13]), "+f"(d[14]), "+f"(d[15]), "+f"(d[16]), "+f"(d[17]), "+f"(d[18]), "+f"(d[19]), "+f"(d[20]), "+f"(d[21]), "+f"(d[22]), "+f"(d[23]), "+f"(d[24]), "+f"(d[25]), "+f"(d[26]), "+f"(d[27]), "+f"(d[28]), "+f"(d[29]), "+f"(d[30]), "+f"(d[31]), "+f"(d[32]), "+f"(d[33]), "+f"(d[34]), "+f"(d[35]), "+f"(d[36]), "+f"(d[37]), "+f"(d[38]), "+f"(d[39]), "+f"(d[40]), "+f"(d[41]), "+f"(d[42]), "+f"(d[43]), "+f"(d[44]), "+f"(d[45]), "+f"(d[46]), "+f"(d[47]), "+f"(d[48]), "+f"(d[49]), "+f"(d[50]), "+f"(d[51]), "+f"(d[52]), "+f"(d[53]), "+f"(d[54]), "+f"(d[55]), "+f"(d[56]), "+f"(d[57]), "+f"(d[58]), "+f"(d[59]), "+f"(d[60]), "+f"(d[61]), "+f"(d[62]), "+f"(d[63]), "+f"(d[64]), "+f"(d[65]), "+f"(d[66]), "+f"(d[67]), "+f"(d[68]), "+f"(d[69]), "+f"(d[70]), "+f"(d[71]), "+f"(d[72]), "+f"(d[73]), "+f"(d[74]), "+f"(d[75]), "+f"(d[76]), "+f"(d[77]), "+f"(d[78]), "+f"(d[79]), "+f"(d[80]), "+f"(d[81]), "+f"(d[82]), "+f"(d[83]), "+f"(d[84]), "+f"(d[85]), "+f"(d[86]), "+f"(d[87]), "+f"(d[88]), "+f"(d[89]), "+f"(d[90]), "+f"(d[91]), "+f"(d[92]), "+f"(d[93]), "+f"(d[94]), "+f"(d[95])
      : "l"(adesc), "l"(bdesc), "r"(scale_d));
}
__device__ __forceinline__ void wgmma_ss_n256(float (&d)[128], uint64_t adesc, uint64_t bdesc, int scale_d) {
    asm volatile("{\n.reg .pred p;\nsetp.ne.b32 p, %130, 0;\n"
      "wgmma.mma_async.sync.aligned.m64n256k16.f32.bf16.bf16 {%0,%1,%2,%3,%4,%5,%6,%7,%8,%9,%10,%11,%12,%13,%14,%15,%16,%17,%18,%19,%20,%21,%22,%23,%24,%25,%26,%27,%28,%29,%30,%31,%32,%33,%34,%35,%36,%37,%38,%39,%40,%41,%42,%43,%44,%45,%46,%47,%48,%49,%50,%51,%52,%53,%54,%55,%56,%57,%58,%59,%60,%61,%62,%63,%64,%65,%66,%67,%68,%69,%70,%71,%72,%73,%74,%75,%76,%77,%78,%79,%80,%81,%82,%83,%84,%85,%86,%87,%88,%89,%90,%91,%92,%93,%94,%95,%96,%97,%98,%99,%100,%101,%102,%103,%104,%105,%106,%107,%108,%109,%110,%111,%112,%113,%114,%115,%116,%117,%118,%119,%120,%121,%122,%123,%124,%125,%126,%127}, %128, %129, p, 1, 1, 0, 1;\n}"
      : "+f"(d[0]), "+f"(d[1]), "+f"(d[2]), "+f"(d[3]), "+f"(d[4]), "+f"(d[5]), "+f"(d[6]), "+f"(d[7]), "+f"(d[8]), "+f"(d[9]), "+f"(d[10]), "+f"(d[11]), "+f"(d[12]), "+f"(d[13]), "+f"(d[14]), "+f"(d[15]), "+f"(d[16]), "+f"(d[17]), "+f"(d[18]), "+f"(d[19]), "+f"(d[20]), "+f"(d[21]), "+f"(d[22]), "+f"(d[23]), "+f"(d[24]), "+f"(d[25]), "+f"(d[26]), "+f"(d[27]), "+f"(d[28]), "+f"(d[29]), "+f"(d[30]), "+f"(d[31]), "+f"(d[32]), "+f"(d[33]), "+f"(d[34]), "+f"(d[35]), "+f"(d[36]), "+f"(d[37]), "+f"(d[38]), "+f"(d[39]), "+f"(d[40]), "+f"(d[41]), "+f"(d[42]), "+f"(d[43]), "+f"(d[44]), "+f"(d[45]), "+f"(d[46]), "+f"(d[47]), "+f"(d[48]), "+f"(d[49]), "+f"(d[50]), "+f"(d[51]), "+f"(d[52]), "+f"(d[53]), "+f"(d[54]), "+f"(d[55]), "+f"(d[56]), "+f"(d[57]), "+f"(d[58]), "+f"(d[59]), "+f"(d[60]), "+f"(d[61]), "+f"(d[62]), "+f"(d[63]), "+f"(d[64]), "+f"(d[65]), "+f"(d[66]), "+f"(d[67]), "+f"(d[68]), "+f"(d[69]), "+f"(d[70]), "+f"(d[71]), "+f"(d[72]), "+f"(d[73]), "+f"(d[74]), "+f"(d[75]), "+f"(d[76]), "+f"(d[77]), "+f"(d[78]), "+f"(d[79]), "+f"(d[80]), "+f"(d[81]), "+f"(d[82]), "+f"(d[83]), "+f"(d[84]), "+f"(d[85]), "+f"(d[86]), "+f"(d[87]), "+f"(d[88]), "+f"(d[89]), "+f"(d[90]), "+f"(d[91]), "+f"(d[92]), "+f"(d[93]), "+f"(d[94]), "+f"(d[95]), "+f"(d[96]), "+f"(d[97]), "+f"(d[98]), "+f"(d[99]), "+f"(d[100]), "+f"(d[101]), "+f"(d[102]), "+f"(d[103]), "+f"(d[104]), "+f"(d[105]), "+f"(d[106]), "+f"(d[107]), "+f"(d[108]), "+f"(d[109]), "+f"(d[110]), "+f"(d[111]), "+f"(d[112]), "+f"(d[113]), "+f"(d[114]), "+f"(d[115]), "+f"(d[116]), "+f"(d[117]), "+f"(d[118]), "+f"(d[119]), "+f"(d[120]), "+f"(d[121]), "+f"(d[122]), "+f"(d[123]), "+f"(d[124]), "+f"(d[125]), "+f"(d[126]), "+f"(d[127])
      : "l"(adesc), "l"(bdesc), "r"(scale_d));
}
__device__ __forceinline__ void qk_wgmma_n64(float (&d)[32], const uint32_t (&a)[4], uint64_t desc) {
    asm volatile("wgmma.mma_async.sync.aligned.m64n64k16.f32.bf16.bf16 {%0,%1,%2,%3,%4,%5,%6,%7,%8,%9,%10,%11,%12,%13,%14,%15,%16,%17,%18,%19,%20,%21,%22,%23,%24,%25,%26,%27,%28,%29,%30,%31}, {%32,%33,%34,%35}, %36, 0, 1, 1, 0;"
      : "=f"(d[0]), "=f"(d[1]), "=f"(d[2]), "=f"(d[3]), "=f"(d[4]), "=f"(d[5]), "=f"(d[6]), "=f"(d[7]), "=f"(d[8]), "=f"(d[9]), "=f"(d[10]), "=f"(d[11]), "=f"(d[12]), "=f"(d[13]), "=f"(d[14]), "=f"(d[15]), "=f"(d[16]), "=f"(d[17]), "=f"(d[18]), "=f"(d[19]), "=f"(d[20]), "=f"(d[21]), "=f"(d[22]), "=f"(d[23]), "=f"(d[24]), "=f"(d[25]), "=f"(d[26]), "=f"(d[27]), "=f"(d[28]), "=f"(d[29]), "=f"(d[30]), "=f"(d[31])
      : "r"(a[0]), "r"(a[1]), "r"(a[2]), "r"(a[3]), "l"(desc));
}

__device__ __forceinline__ void pv_wgmma(float (&d)[12], uint32_t a0, uint32_t a1, uint32_t a2, uint32_t a3, uint64_t desc) {
    asm volatile("wgmma.mma_async.sync.aligned.m64n24k16.f32.bf16.bf16 {%0,%1,%2,%3,%4,%5,%6,%7,%8,%9,%10,%11}, {%12,%13,%14,%15}, %16, 1, 1, 1, 1;"
      : "+f"(d[0]), "+f"(d[1]), "+f"(d[2]), "+f"(d[3]), "+f"(d[4]), "+f"(d[5]), "+f"(d[6]), "+f"(d[7]), "+f"(d[8]), "+f"(d[9]), "+f"(d[10]), "+f"(d[11])
      : "r"(a0), "r"(a1), "r"(a2), "r"(a3), "l"(desc));
}

__device__ __forceinline__ uint32_t mapa(uint32_t a, uint32_t rank) { uint32_t r; asm("mapa.shared::cluster.u32 %0, %1, %2;" : "=r"(r) : "r"(a), "r"(rank)); return r; }
__device__ __forceinline__ void mbar_arrive_remote(uint32_t a) { asm volatile("mbarrier.arrive.relaxed.cluster.shared::cluster.b64 _, [%0];" :: "r"(a) : "memory"); }
__device__ __forceinline__ void mbar_wait_cluster(uint32_t a, int parity) {
    uint32_t done;
    int it = 0;
    do {
        asm volatile("{\n.reg .pred p;\nmbarrier.try_wait.parity.acquire.cluster.shared::cta.b64 p, [%1], %2;\nselp.u32 %0, 1, 0, p;\n}"
                     : "=r"(done) : "r"(a), "r"(parity) : "memory");
        if (++it > (1 << 24)) __trap();
    } while (!done);
}
__device__ __forceinline__ void tma2d_mc(uint32_t dst, const CUtensorMap* m, int c0, int c1, uint32_t bar) {
    asm volatile("cp.async.bulk.tensor.2d.shared::cluster.global.mbarrier::complete_tx::bytes.multicast::cluster [%0], [%1, {%3, %4}], [%2], %5;"
                 :: "r"(dst), "l"(m), "r"(bar), "r"(c0), "r"(c1), "h"((uint16_t)3) : "memory");
}
__device__ __forceinline__ void bulk_g2s_mc(uint32_t dst, const void* src, int bytes, uint32_t bar) {
    asm volatile("cp.async.bulk.shared::cluster.global.mbarrier::complete_tx::bytes.multicast::cluster [%0], [%1], %2, [%3], %4;"
                 :: "r"(dst), "l"(src), "r"(bytes), "r"(bar), "h"((uint16_t)3) : "memory");
}
__device__ __forceinline__ void tile_of(int bid, int& mb, int& nt) {
    int grp = bid >> 4, in = bid & 15;
    mb = (grp >> 1) * 4 + (in >> 2);
    nt = (grp & 1) * 4 + (in & 3);
}

constexpr int K1_STAGES = 5, K1_STAGE = 16384 + 24576;
constexpr int K1_BAR = K1_STAGES * K1_STAGE, K1_RS = K1_BAR + 128, K1_CS = K1_RS + 1024, K1_SMEM = K1_CS + 768;

__device__ __forceinline__ float2 row_stats_regs(uint4 a, uint4 b) {
    float v[16];
    v[0] = bf_lo(a.x); v[1] = bf_hi(a.x); v[2] = bf_lo(a.y); v[3] = bf_hi(a.y);
    v[4] = bf_lo(a.z); v[5] = bf_hi(a.z); v[6] = bf_lo(a.w); v[7] = bf_hi(a.w);
    v[8] = bf_lo(b.x); v[9] = bf_hi(b.x); v[10] = bf_lo(b.y); v[11] = bf_hi(b.y);
    v[12] = bf_lo(b.z); v[13] = bf_hi(b.z); v[14] = bf_lo(b.w); v[15] = bf_hi(b.w);
    float s = 0.f;
#pragma unroll
    for (int i = 0; i < 16; i++) s += v[i];
    float mean = warp_sum(s) * (1.0f / DM);
    float q = 0.f;
#pragma unroll
    for (int i = 0; i < 16; i++) { float d = v[i] - mean; q = fmaf(d, d, q); }
    float var = warp_sum(q) * (1.0f / DM);
    float rstd = rsqrtf(var + 1e-5f);
    return make_float2(rstd, -mean * rstd);
}
__device__ __forceinline__ float2 row_stats_x(const __nv_bfloat16* x, int row, int lane) {
    const uint4* p = (const uint4*)(x + (size_t)row * DM);
    return row_stats_regs(__ldg(p + lane), __ldg(p + 32 + lane));
}
__device__ __forceinline__ void colsum8(const __nv_bfloat16* w, int ld, int col, int k0, int nk, float (&s)[8]) {
#pragma unroll
    for (int i = 0; i < 8; i++) s[i] = 0.f;
    for (int k = k0; k < k0 + nk; k += 8) {
        uint4 u[8];
#pragma unroll
        for (int i = 0; i < 8; i++) u[i] = __ldg((const uint4*)(w + (size_t)(k + i) * ld + col));
#pragma unroll
        for (int i = 0; i < 8; i++) {
            s[0] += bf_lo(u[i].x); s[1] += bf_hi(u[i].x); s[2] += bf_lo(u[i].y); s[3] += bf_hi(u[i].y);
            s[4] += bf_lo(u[i].z); s[5] += bf_hi(u[i].z); s[6] += bf_lo(u[i].w); s[7] += bf_hi(u[i].w);
        }
    }
}
__device__ __forceinline__ bool wait_count(const unsigned int* p, unsigned int target, int lane) {
    int ok = 1;
    if (lane == 0) {
        int it = 0;
        while (ld_acquire(p) < target) { if (++it > (1 << 18)) { ok = 0; break; } }
    }
    ok = __shfl_sync(0xffffffffu, ok, 0);
    return ok != 0;
}

__global__ void __launch_bounds__(384, 1)
qkv_kernel(const __grid_constant__ CUtensorMap tm_x, const __grid_constant__ CUtensorMap tm_w,
           const __nv_bfloat16* __restrict__ x, const __nv_bfloat16* __restrict__ wqkv) {
    extern __shared__ __align__(1024) unsigned char smem[];
    const uint32_t sb = smem_u32(smem);
    const int tid = threadIdx.x, warp = __shfl_sync(0xffffffffu, tid >> 5, 0), lane = tid & 31;
    TLDECL
    TL(0);
    int mb, nt;
    tile_of(blockIdx.x, mb, nt);
    const uint32_t full = sb + K1_BAR, empty = full + 40, auxb = full + 80;
    if (tid == 0) {
        prefetch_tmap(&tm_x); prefetch_tmap(&tm_w);
        for (int i = 0; i < K1_STAGES; i++) { mbar_init(full + 8 * i, 1); mbar_init(empty + 8 * i, 8); }
        mbar_init(auxb, 3);
        fence_barrier_init();
    }
    __syncthreads();
    pdl_launch();
    if (warp == 0) {
        if (blockIdx.x == 0) g_cnt2[lane] = 0;
        g_cnt2[32 + blockIdx.x * 32 + lane] = 0;
        if (lane == 0) {
            for (int kb = 0; kb < 8; kb++) {
                int s = kb % K1_STAGES;
                if (kb >= K1_STAGES) mbar_wait(empty + 8 * s, 0);
                mbar_expect(full + 8 * s, K1_STAGE);
                tma2d(sb + s * K1_STAGE, &tm_x, kb * 64, mb * 128, full + 8 * s);
                tma3d(sb + s * K1_STAGE + 16384, &tm_w, 0, kb * 64, nt * 3, full + 8 * s);
            }
        }
    } else if (warp < 4) {
        float2* s_rs = (float2*)(smem + K1_RS);
        float* s_cs = (float*)(smem + K1_CS);
        if (warp < 3) {
            const int r0 = mb * 128 + nt * 16 + (warp - 1) * 8;
            uint4 u[16];
#pragma unroll
            for (int i = 0; i < 8; i++) {
                const uint4* p = (const uint4*)(x + (size_t)(r0 + i) * DM);
                u[2 * i] = __ldg(p + lane); u[2 * i + 1] = __ldg(p + 32 + lane);
            }
            float2 mine = make_float2(0.f, 0.f);
#pragma unroll
            for (int i = 0; i < 8; i++) {
                float2 st = row_stats_regs(u[2 * i], u[2 * i + 1]);
                if (lane == i) mine = st;
            }
            if (lane < 8) g_rowstat1[r0 + lane] = mine;
            __syncwarp();
            if (lane == 0) red_release(&g_cnt[mb]);
        } else {
            uint4 u[24];
#pragma unroll
            for (int c = 0; c < 3; c++)
#pragma unroll
                for (int i = 0; i < 8; i++)
                    u[c * 8 + i] = __ldg((const uint4*)(wqkv + (size_t)(mb * 32 + (lane >> 3) * 8 + i) * 1536 + nt * 192 + (c * 8 + (lane & 7)) * 8));
#pragma unroll
            for (int c = 0; c < 3; c++) {
                float cs[8];
#pragma unroll
                for (int i = 0; i < 8; i++) cs[i] = 0.f;
#pragma unroll
                for (int i = 0; i < 8; i++) {
                    const uint4 w = u[c * 8 + i];
                    cs[0] += bf_lo(w.x); cs[1] += bf_hi(w.x); cs[2] += bf_lo(w.y); cs[3] += bf_hi(w.y);
                    cs[4] += bf_lo(w.z); cs[5] += bf_hi(w.z); cs[6] += bf_lo(w.w); cs[7] += bf_hi(w.w);
                }
#pragma unroll
                for (int i = 0; i < 8; i++) {
                    cs[i] += __shfl_xor_sync(0xffffffffu, cs[i], 8);
                    cs[i] += __shfl_xor_sync(0xffffffffu, cs[i], 16);
                }
                if (lane < 8) {
                    float4* d = (float4*)(g_cs1_part + mb * 1536 + nt * 192 + (c * 8 + lane) * 8);
                    d[0] = make_float4(cs[0], cs[1], cs[2], cs[3]);
                    d[1] = make_float4(cs[4], cs[5], cs[6], cs[7]);
                }
            }
            __syncwarp();
            if (lane == 0) red_release(&g_cnt[16 + nt]);
        }
        TX(8 + warp);
        if (warp == 1) {
            if (wait_count(&g_cnt[mb], 16, lane)) {
#pragma unroll
                for (int i = 0; i < 4; i++) s_rs[lane + 32 * i] = __ldcg(&g_rowstat1[mb * 128 + lane + 32 * i]);
            } else {
                for (int i = 0; i < 128; i++) {
                    float2 st = row_stats_x(x, mb * 128 + i, lane);
                    if (lane == 0) s_rs[i] = st;
                }
            }
        } else {
            int c0 = (warp - 2) * 96;
            if (wait_count(&g_cnt[16 + nt], 16, lane)) {
#pragma unroll
                for (int i = 0; i < 3; i++) {
                    float s = 0.f;
#pragma unroll
                    for (int p = 0; p < 16; p++) s += __ldcg(&g_cs1_part[p * 1536 + nt * 192 + c0 + lane + 32 * i]);
                    s_cs[c0 + lane + 32 * i] = s;
                }
            } else if (lane < 12) {
                float s[8];
                colsum8(wqkv, 1536, nt * 192 + c0 + lane * 8, 0, 512, s);
#pragma unroll
                for (int i = 0; i < 8; i++) s_cs[c0 + lane * 8 + i] = s[i];
            }
        }
        __syncwarp();
        TX(12 + warp);
        if (lane == 0) mbar_arrive(auxb);
        bar_sync(2, 256 + 96);
        const int a = tid - 32;
        {
            const int hh = a >> 3, w = a & 7;
            const float4* p = (const float4*)(smem + 49152) + (hh * 256 + w * 32) / 2;
            float m = 0.f;
#pragma unroll
            for (int i = 0; i < 8; i++) {
                const int ii = (i + a) & 7;
                float4 u = p[2 * ii], v = p[2 * ii + 1];
                float n0 = u.x + u.z + v.x + v.z, n1 = u.y + u.w + v.y + v.w;
                if (!(n0 <= 3.0e38f) || !(n1 <= 3.0e38f)) m = __int_as_float(0x7f800000);
                m = fmaxf(m, fmaxf(n0, n1));
            }
            const int col0 = nt * 192 + hh * 16;
            g_nrm[((col0 >> 9) * NH + ((col0 & 511) >> 4)) * 128 + mb * 8 + w] = m;
        }
        if (a < 24) bulk_wait_all();
        TL(27);
        TLDUMP;
    } else {
        const int wgi = (warp >> 2) - 1, ww = warp & 3;
        float acc[96];
#pragma unroll 1
        for (int kb = 0; kb < 8; kb++) {
            int s = kb % K1_STAGES;
            mbar_wait(full + 8 * s, (kb / K1_STAGES) & 1);
            if (warp == 4) TX(kb);
            uint64_t ad = make_desc(sb + s * K1_STAGE + wgi * 8192, 16, 1024, 1);
            uint64_t bd = make_desc(sb + s * K1_STAGE + 16384, 8192, 1024, 1);
            WG_FENCE();
#pragma unroll
            for (int k = 0; k < 4; k++) wgmma_ss_n192(acc, ad + k * 2, bd + k * 128, (kb | k) != 0);
            WG_COMMIT();
            if (kb > 0) {
                wg_wait<1>();
                if (lane == 0) mbar_arrive(empty + 8 * ((kb - 1) % K1_STAGES));
            }
        }
        wg_wait<0>();
        fence_regs(acc);
        TL(1);
        if (warp == 4) TX(16);
        mbar_wait(auxb, 0);
        if (warp == 4) TX(17);
        bar_sync(1, 256);
        const float2* s_rs = (const float2*)(smem + K1_RS);
        const float* s_cs = (const float*)(smem + K1_CS);
        const int g = lane >> 2, t = lane & 3;
        const int rl = wgi * 64 + ww * 16 + g;
        const float2 st0 = s_rs[rl], st1 = s_rs[rl + 8];
        const float QS = 0.25f * 1.4426950408889634f;
        const uint32_t stg = sb + ((lane >> 4) * 16 + wgi * 8 + ww * 2 + ((lane >> 3) & 1)) * 128 + (lane & 7) * 16;
        float2* s_np = (float2*)(smem + 49152) + (warp - 4) * 32 + lane;
#pragma unroll
        for (int hh = 0; hh < 12; hh++) {
            const int which = (nt * 192 + hh * 16) >> 9;
            const float sc = (which == 0) ? QS : 1.0f;
            const float a0 = st0.x * sc, b0 = st0.y * sc, a1 = st1.x * sc, b1 = st1.y * sc;
            const float2 c0 = *(const float2*)(s_cs + 16 * hh + 2 * t), c1 = *(const float2*)(s_cs + 16 * hh + 8 + 2 * t);
            const float* a = acc + 8 * hh;
            float v0 = fmaf(a0, a[0], b0 * c0.x), v1 = fmaf(a0, a[1], b0 * c0.y), v2 = fmaf(a1, a[2], b1 * c0.x), v3 = fmaf(a1, a[3], b1 * c0.y);
            float v4 = fmaf(a0, a[4], b0 * c1.x), v5 = fmaf(a0, a[5], b0 * c1.y), v6 = fmaf(a1, a[6], b1 * c1.x), v7 = fmaf(a1, a[7], b1 * c1.y);
            {
                const int head = ((nt * 192 + hh * 16) & 511) >> 4;
                uint32_t* o = (uint32_t*)g_qkv + ((size_t)((which * NH + head) * 2) * 256 + mb * 16 + wgi * 8 + ww * 2) * 32 + lane;
                o[0] = pack_bf16(v0, v1); o[32] = pack_bf16(v2, v3); o[8192] = pack_bf16(v4, v5); o[8192 + 32] = pack_bf16(v6, v7);
            }
            s_np[hh * 256] = make_float2(fmaf(v0, v0, fmaf(v1, v1, fmaf(v4, v4, v5 * v5))), fmaf(v2, v2, fmaf(v3, v3, fmaf(v6, v6, v7 * v7))));
        }
        fence_proxy_async();
        bar_arrive(2, 256 + 96);
        TL(2);
        TLDUMP;
    }
}

constexpr int AT_K = 0, AT_V = 65536, AT_ONES = 131072, AT_BAR = 163840, AT_SMEM = AT_BAR + 128;
#define POLY_MASK 0x7B5A

__device__ __forceinline__ uint32_t exp2_pair_poly(float x0, float x1) {
    uint32_t t0 = __float_as_uint(x0 + 32895.0f);
    uint32_t t1 = __float_as_uint(x1 + 32895.0f);
    uint32_t gd = __byte_perm(t0, t1, 0x6420);
    uint32_t wm = __byte_perm(t0, t1, 0x5612);
    uint32_t v = hfma2(gd, 0x71477147u, 0x354f354fu);
    uint32_t z = hmul2(v, gd);
    return (wm >> 1) + z;
}
__device__ __forceinline__ uint32_t exp2_pair_mufu(float x0, float x1) { return pack_bf16(ex2f(x0), ex2f(x1)); }
template <uint32_t MASK>
__device__ __forceinline__ void exp_blocks(const float (&s)[32], uint32_t (&p)[16]) {
#pragma unroll
    for (int b = 0; b < 8; b++) {
        if ((MASK >> b) & 1) {
            p[2 * b] = exp2_pair_poly(s[4 * b], s[4 * b + 1]);
            p[2 * b + 1] = exp2_pair_poly(s[4 * b + 2], s[4 * b + 3]);
        } else {
            p[2 * b] = exp2_pair_mufu(s[4 * b], s[4 * b + 1]);
            p[2 * b + 1] = exp2_pair_mufu(s[4 * b + 2], s[4 * b + 3]);
        }
    }
}
#define PV4(P) _Pragma("unroll") for (int i = 0; i < 4; i++) { pv_wgmma(o, P[4 * i], P[4 * i + 1], P[4 * i + 2], P[4 * i + 3], vd); vd += 16; }

__device__ __forceinline__ void attn_store(float (&o)[12], int row0, int head, int lane) {
    float l0 = __shfl_sync(0xffffffffu, o[8], lane & 28);
    float l1 = __shfl_sync(0xffffffffu, o[10], lane & 28);
    float r0 = 1.0f / l0, r1 = 1.0f / l1;
    uint32_t* op = (uint32_t*)g_ao;
    int mb = row0 >> 7, rg = (row0 & 127) >> 3;
    int kb = head >> 2, kc = (head & 3) * 2;
    size_t base = (((size_t)(mb * 8 + kb) * 8 + kc) * 16 + rg) * 32 + lane;
    op[base] = pack_bf16(o[0] * r0, o[1] * r0);
    op[base + 32] = pack_bf16(o[2] * r1, o[3] * r1);
    op[base + 16 * 32] = pack_bf16(o[4] * r0, o[5] * r0);
    op[base + 16 * 32 + 32] = pack_bf16(o[6] * r1, o[7] * r1);
}

__device__ __forceinline__ void attn_load_q(uint32_t (&q)[4], const __nv_bfloat16* gq, int row0, int lane) {
    const uint32_t* qp = (const uint32_t*)gq;
    int j0 = row0 >> 3;
    q[0] = __ldcg(qp + (0 * 256 + j0) * 32 + lane);
    q[1] = __ldcg(qp + (0 * 256 + j0 + 1) * 32 + lane);
    q[2] = __ldcg(qp + (1 * 256 + j0) * 32 + lane);
    q[3] = __ldcg(qp + (1 * 256 + j0 + 1) * 32 + lane);
}

__device__ __forceinline__ void attn_tile_safe(const uint32_t (&q)[4], uint64_t kd, uint64_t vd, int row0, int head, int lane) {
    float o[12];
#pragma unroll
    for (int i = 0; i < 12; i++) o[i] = 0.f;
    float m0 = -INFINITY, m1 = -INFINITY;
    fence_regs(o);
#pragma unroll 1
    for (int j = 0; j < 32; j++) {
        float s[32];
        uint32_t p[16];
        WG_FENCE();
        qk_wgmma_n64(s, q, kd); kd += 64;
        WG_COMMIT();
        wg_wait<0>();
        fence_regs(s);
        fence_regs(o);
        float x0 = m0, x1 = m1;
#pragma unroll
        for (int b = 0; b < 8; b++) {
            x0 = fmaxf(x0, fmaxf(s[4 * b], s[4 * b + 1]));
            x1 = fmaxf(x1, fmaxf(s[4 * b + 2], s[4 * b + 3]));
        }
        x0 = fmaxf(x0, __shfl_xor_sync(0xffffffffu, x0, 1)); x0 = fmaxf(x0, __shfl_xor_sync(0xffffffffu, x0, 2));
        x1 = fmaxf(x1, __shfl_xor_sync(0xffffffffu, x1, 1)); x1 = fmaxf(x1, __shfl_xor_sync(0xffffffffu, x1, 2));
        float al0 = ex2f(m0 - x0), al1 = ex2f(m1 - x1);
        m0 = x0; m1 = x1;
#pragma unroll
        for (int i = 0; i < 3; i++) { o[4 * i] *= al0; o[4 * i + 1] *= al0; o[4 * i + 2] *= al1; o[4 * i + 3] *= al1; }
#pragma unroll
        for (int b = 0; b < 8; b++) {
            p[2 * b] = exp2_pair_mufu(s[4 * b] - m0, s[4 * b + 1] - m0);
            p[2 * b + 1] = exp2_pair_mufu(s[4 * b + 2] - m1, s[4 * b + 3] - m1);
        }
        fence_regs(o);
        WG_FENCE();
        PV4(p);
        WG_COMMIT();
        wg_wait<0>();
        fence_regs(o);
    }
    attn_store(o, row0, head, lane);
}

__global__ void __launch_bounds__(512, 1)
attn_kernel(const __nv_bfloat16* __restrict__ wg_, const __nv_bfloat16* __restrict__ wu_,
            const __nv_bfloat16* __restrict__ wo_, const __nv_bfloat16* __restrict__ wd_) {
    extern __shared__ __align__(1024) unsigned char smem[];
    const uint32_t sb = smem_u32(smem);
    const int tid = threadIdx.x, wg = tid >> 7, warp = (tid >> 5) & 3, lane = tid & 31;
    TLDECL
    pdl_launch();
    if (blockIdx.x >= 128) {
        const int e = blockIdx.x - 128;
        const __nv_bfloat16* w = (e < 2) ? wg_ : wu_;
        float* red = (float*)smem;
        const int cgrp = tid & 127, kq = tid >> 7;
        if (cgrp < 112) {
            float s[8];
            colsum8(w, FF, (e & 1) * 896 + cgrp * 8, kq * 128, 128, s);
#pragma unroll
            for (int i = 0; i < 8; i++) red[kq * 896 + cgrp * 8 + i] = s[i];
        }
        __syncthreads();
        for (int c = tid; c < 896; c += 512)
            g_cs2[(e >> 1) * FF + (e & 1) * 896 + c] = red[c] + red[896 + c] + red[1792 + c] + red[2688 + c];
        if (tid < 32) {
            const char* p0 = (const char*)wo_ + e * (DM * DM * 2 / 4);
            for (int i = lane; i < 32; i += 32)
                asm volatile("cp.async.bulk.prefetch.L2.global [%0], %1;" :: "l"(p0 + i * 4096), "r"(4096) : "memory");
            const char* p1 = (const char*)wd_ + e * (FF * DM * 2 / 4);
            for (int i = lane; i < 112; i += 32)
                asm volatile("cp.async.bulk.prefetch.L2.global [%0], %1;" :: "l"(p1 + i * 4096), "r"(4096) : "memory");
        }
        return;
    }
    const int head = blockIdx.x >> 2, qq = blockIdx.x & 3;
    const __nv_bfloat16* gq = g_qkv + (size_t)head * (S_LEN * 16);
    const __nv_bfloat16* gk = g_qkv + (size_t)(NH + head) * (S_LEN * 16);
    const __nv_bfloat16* gv = g_qkv + (size_t)(2 * NH + head) * (S_LEN * 16);
    if (tid == 0) {
        for (int i = 0; i < 8; i++) mbar_init(sb + AT_BAR + 8 * i, 1);
        fence_barrier_init();
    }
    {
        uint4 one = make_uint4(0x00003F80u, 0, 0, 0);
#pragma unroll
        for (int i = 0; i < 4; i++) *(uint4*)(smem + AT_ONES + (i * 512 + tid) * 16) = one;
        fence_proxy_async();
    }
    __syncthreads();
    TL(3);
    pdl_wait();
    TL(4);
    auto load_kv = [&](int i) {
        uint32_t bar = sb + AT_BAR + 8 * i;
        mbar_expect(bar, 16384);
        bulk_g2s(sb + AT_K + i * 4096, gk + i * 2048, 4096, bar);
        bulk_g2s(sb + AT_K + 32768 + i * 4096, gk + 16384 + i * 2048, 4096, bar);
        bulk_g2s(sb + AT_V + i * 4096, gv + i * 2048, 4096, bar);
        bulk_g2s(sb + AT_V + 32768 + i * 4096, gv + 16384 + i * 2048, 4096, bar);
    };
    if (tid == 0) { load_kv(0); load_kv(1); }
    uint32_t q[4], q2[4];
    attn_load_q(q, gq, qq * 512 + wg * 64 + warp * 16, lane);
    attn_load_q(q2, gq, qq * 512 + (4 + wg) * 64 + warp * 16, lane);
    bool fast;
    {
        const float* nq = g_nrm + (0 * NH + head) * 128 + qq * 32;
        const float* nk = g_nrm + (1 * NH + head) * 128;
        const float* nv = g_nrm + (2 * NH + head) * 128;
        float4 k4 = __ldcg((const float4*)nk + lane), v4 = __ldcg((const float4*)nv + lane);
        float qm = warp_max(__ldcg(nq + lane));
        float km = warp_max(fmaxf(fmaxf(k4.x, k4.y), fmaxf(k4.z, k4.w)));
        float vm = warp_max(fmaxf(fmaxf(v4.x, v4.y), fmaxf(v4.z, v4.w)));
        fast = __all_sync(0xffffffffu, (qm * km <= 3500.0f) && (vm <= 1.0e24f));
    }
    TL(24);
    const uint64_t kdesc0 = make_desc(sb + AT_K, 32768, 128, 0);
    const uint64_t vdesc0 = make_desc(sb + AT_V, 128, 32768, 0);
    if (!fast) {
        if (tid == 0) for (int i = 2; i < 8; i++) load_kv(i);
        for (int i = 0; i < 8; i++) mbar_wait(sb + AT_BAR + 8 * i, 0);
#pragma unroll 1
        for (int tile = 0; tile < 2; tile++) {
            const int row0 = qq * 512 + (tile * 4 + wg) * 64 + warp * 16;
            attn_tile_safe(q, kdesc0, vdesc0, row0, head, lane);
#pragma unroll
            for (int i = 0; i < 4; i++) q[i] = q2[i];
        }
        return;
    }
#pragma unroll 1
    for (int tile = 0; tile < 2; tile++) {
        const int row0 = qq * 512 + (tile * 4 + wg) * 64 + warp * 16;
        float o[12];
#pragma unroll
        for (int i = 0; i < 12; i++) o[i] = 0.f;
        fence_regs(o);
        float sa[32];
        uint32_t pa[16];
        uint64_t kd = kdesc0, vd = vdesc0;
        if (tile == 0) { mbar_wait(sb + AT_BAR, 0); TL(25); }
        WG_FENCE();
        qk_wgmma_n64(sa, q, kd); kd += 64;
        WG_COMMIT();
#pragma unroll 1
        for (int jj = 0; jj < 8; jj++) {
            if (tile == 0 && jj < 7) {
                if (tid == 0 && jj < 6) load_kv(jj + 2);
                mbar_wait(sb + AT_BAR + 8 * (jj + 1), 0);
            }
            if (wg == 0 && warp == 0) TX(128 + tile * 8 + jj);
#pragma unroll
            for (int j = 0; j < 4; j++) {
                wg_wait<0>();
                fence_regs(sa);
                if (j & 1) exp_blocks<(POLY_MASK >> 8)>(sa, pa); else exp_blocks<(POLY_MASK & 255)>(sa, pa);
                WG_FENCE();
                qk_wgmma_n64(sa, q, kd); kd += 64;
                PV4(pa);
                WG_COMMIT();
            }
        }
        wg_wait<0>();
        fence_regs(o);
        fence_regs(sa);
        if (tile == 0) TL(26);
        attn_store(o, row0, head, lane);
#pragma unroll
        for (int i = 0; i < 4; i++) q[i] = q2[i];
    }
    TL(5);
    TLDUMP;
}

#define POLL_NS 40
#define FLAG_STRIDE 1
#define DELAYC 9
constexpr int F_R2 = 131072, F_X = 196608, F_BAR = 229376;
constexpr int F_RS = F_BAR + 256, F_CS = F_RS + 1024, F_SMEM = F_CS + 1792;
enum { B_FA = 0, B_HF = 4, B_BF = 8, B_BE = 11, B_CF = 14, B_CE = 20, B_ADONE = 26, B_BDONE = 27, B_XC = 28, B_PRDY = 29, B_AUX = 30, B_NUM = 31 };

__device__ __forceinline__ void st_async4(uint32_t dst, float a, float b, float c, float d, uint32_t bar) {
    asm volatile("st.async.weak.shared::cluster.mbarrier::complete_tx::bytes.v4.f32 [%0], {%1,%2,%3,%4}, [%5];"
                 :: "r"(dst), "f"(a), "f"(b), "f"(c), "f"(d), "r"(bar) : "memory");
}
__device__ __forceinline__ void poll_count(const unsigned int* p, unsigned int target) {
    int it = 0;
    while (ld_acquire(p) < target) { if (++it > (1 << 22)) __trap(); }
    asm volatile("fence.proxy.async.global;" ::: "memory");
}
__device__ __forceinline__ void tma2d_store(const CUtensorMap* m, uint32_t src, int c0, int c1) {
    asm volatile("cp.async.bulk.tensor.2d.global.shared::cta.bulk_group [%0, {%2, %3}], [%1];" :: "l"(m), "r"(src), "r"(c0), "r"(c1) : "memory");
}
__device__ __forceinline__ float2 h_row_stats(int row) {
    const float4* hp = (const float4*)(g_hstat + (size_t)row * 8);
    float4 a = __ldcg(hp), b = __ldcg(hp + 1), c = __ldcg(hp + 2), d = __ldcg(hp + 3);
    float mean = 0.125f * (a.x + a.z + b.x + b.z + c.x + c.z + d.x + d.z);
    float m2 = a.y + a.w + b.y + b.w + c.y + c.w + d.y + d.w;
    float e;
    e = a.x - mean; m2 = fmaf(64.f * e, e, m2); e = a.z - mean; m2 = fmaf(64.f * e, e, m2);
    e = b.x - mean; m2 = fmaf(64.f * e, e, m2); e = b.z - mean; m2 = fmaf(64.f * e, e, m2);
    e = c.x - mean; m2 = fmaf(64.f * e, e, m2); e = c.z - mean; m2 = fmaf(64.f * e, e, m2);
    e = d.x - mean; m2 = fmaf(64.f * e, e, m2); e = d.z - mean; m2 = fmaf(64.f * e, e, m2);
    return make_float2(rsqrtf(m2 * (1.0f / DM) + 1e-5f), -mean);
}
__device__ __forceinline__ int c_kblock(int i, int r) {
    if (i < 6) { const int e = 2 * i + r, m = e / 3, k = e - 3 * m; return 7 * m + (k == 2 ? 4 : k); }
    const int l = 2 * (i - 6) + r, m = l >> 2, k = l & 3;
    return 7 * m + (k < 2 ? 2 + k : 3 + k);
}
__device__ __forceinline__ uint32_t c_stage_a(int s, int ntB) { return s < 4 ? ((ntB + 2 * s) & 7) * 16384 : F_R2 + (s - 4) * 32768; }
__device__ __forceinline__ uint32_t c_stage_b(int s, int ntB) { return s < 4 ? ((ntB + 2 * s + 1) & 7) * 16384 : F_R2 + (s - 4) * 32768 + 16384; }
template <int R>
__device__ __forceinline__ void xchg(float (&acc)[64], float (&o)[32], uint32_t sb, unsigned char* smem, int bar, int ctid) {
    const uint32_t dst = mapa(sb + F_X + ctid * 16, 1 - R), rb = mapa(sb + F_BAR + 8 * bar, 1 - R);
#pragma unroll
    for (int q = 0; q < 8; q++) {
        const int j = (1 - R) * 32 + 4 * q;
        st_async4(dst + q * 4096, acc[j], acc[j + 1], acc[j + 2], acc[j + 3], rb);
    }
    mbar_wait_cluster(sb + F_BAR + 8 * bar, 0);
#pragma unroll
    for (int q = 0; q < 8; q++) {
        float4 v = *(const float4*)(smem + F_X + q * 4096 + ctid * 16);
        const int j = R * 32 + 4 * q;
        o[4 * q] = acc[j] + v.x; o[4 * q + 1] = acc[j + 1] + v.y; o[4 * q + 2] = acc[j + 2] + v.z; o[4 * q + 3] = acc[j + 3] + v.w;
    }
}

template <int NB, bool STAGE>
__device__ __forceinline__ void ffn_epilogue(const float* ag, const float* au, const float* s_cs, int cs_off, uint32_t* gp, uint32_t stg,
                                             float2 st0, float2 st1, int lane) {
    const int t = lane & 3;
    const float C1 = 0.7978845608028654f, C2 = 0.044715f * 0.7978845608028654f;
    const float k10 = st0.x * C1, k20 = st0.x * st0.x * st0.x * C2, k11 = st1.x * C1, k21 = st1.x * st1.x * st1.x * C2;
#pragma unroll
    for (int j2 = 0; j2 < NB / 2; j2++) {
        uint32_t pk[4];
#pragma unroll
        for (int jj = 0; jj < 2; jj++) {
            const int j = 2 * j2 + jj;
            const float2 cg = *(const float2*)(s_cs + cs_off + 8 * j + 2 * t);
            const float2 cu = *(const float2*)(s_cs + 224 + cs_off + 8 * j + 2 * t);
            float r[4];
#pragma unroll
            for (int e = 0; e < 4; e++) {
                const float nm = (e < 2) ? st0.y : st1.y, k1 = (e < 2) ? k10 : k11, k2 = (e < 2) ? k20 : k21;
                const float tg = fmaf(nm, (e & 1) ? cg.y : cg.x, ag[4 * j + e]);
                const float tu = fmaf(nm, (e & 1) ? cu.y : cu.x, au[4 * j + e]);
                const float th = tanh_fast(tg * fmaf(tg * tg, k2, k1));
                const float p = tg * tu;
                r[e] = fmaf(p, th, p);
            }
            pk[2 * jj] = pack_bf16(r[0], r[1]);
            pk[2 * jj + 1] = pack_bf16(r[2], r[3]);
        }
        if (STAGE) {
            stsm4(stg + j2 * 4096, pk[0], pk[1], pk[2], pk[3]);
        } else {
            gp[j2 * 1024] = pk[0]; gp[j2 * 1024 + 32] = pk[1]; gp[j2 * 1024 + 512] = pk[2]; gp[j2 * 1024 + 544] = pk[3];
        }
    }
}

__global__ void __cluster_dims__(2, 1, 1) __launch_bounds__(384, 1)
tail_kernel(const __grid_constant__ CUtensorMap tm_o, const __grid_constant__ CUtensorMap tm_g,
            const __grid_constant__ CUtensorMap tm_u, const __grid_constant__ CUtensorMap tm_d,
            const __grid_constant__ CUtensorMap tm_out, const __nv_bfloat16* __restrict__ x) {
    extern __shared__ __align__(1024) unsigned char smem[];
    const uint32_t sb = smem_u32(smem);
    const uint32_t bars = sb + F_BAR;
    const int tid = threadIdx.x, warp = __shfl_sync(0xffffffffu, tid >> 5, 0), lane = tid & 31;
    TLDECL
    TL(6);
    if (warp == 4) TX(200);
    const int cl = blockIdx.x >> 1, r = blockIdx.x & 1;
    const int mb = ((cl & 7) >> 1) * 4 + (cl >> 4), ntA = (cl & 1) * 2 + ((cl >> 3) & 1);
    const int nt = ntA * 2 + r;
    const int mbB = (mb & ~1) + r, ntB = (mb & 1) * 4 + ntA;
    if (tid == 0) {
#pragma unroll
        for (int i = 0; i < B_NUM; i++) {
            const int cnt = (i >= B_BE && i < B_BE + 3) ? 16 : (i == B_BDONE) ? DELAYC : ((i >= B_CE && i < B_CE + 6) || i == B_PRDY) ? 8 : (i == B_AUX || i == B_ADONE) ? 2 : 1;
            mbar_init(bars + 8 * i, cnt);
        }
        mbar_expect(bars + 8 * B_XC, 32768);
        fence_barrier_init();
    }
    TL(28);
    __syncthreads();
    TL(29);
    asm volatile("barrier.cluster.arrive.relaxed.aligned;" ::: "memory");
    TL(30);
    if (warp < 4) {
        asm volatile("setmaxnreg.dec.sync.aligned.u32 56;");
        if (warp == 0) TX(205);
        if (warp == 0) {
            if (lane == 0) {
                auto load_b = [&](int it) {
                    const int s = it % 3, pass = it >> 3, kb = (ntB + it) & 7;
                    const int ng = pass ? 3 : 4, c0 = ntB * 224 + pass * 128;
                    const uint32_t bar = bars + 8 * (B_BF + s), dst = sb + F_R2 + s * 32768 + r * ng * 4096;
                    mbar_expect(bar, ng * 8192);
                    for (int i = 0; i < ng; i++) tma2d_mc(dst + i * 4096, r ? &tm_u : &tm_g, c0 + i * 32, kb * 64, bar);
                };
                for (int i = 0; i < 8; i++) {
                    const uint32_t bar = bars + 8 * (B_FA + (i >> 1));
                    if (!(i & 1)) mbar_expect(bar, 49152);
                    tma2d(sb + F_R2 + 32768 + i * 8192, &tm_o, nt * 64, i * 64, bar);
                }
                asm volatile("barrier.cluster.wait.acquire;" ::: "memory");
                pdl_wait();
                TL(16);
                for (int i = 0; i < 4; i++)
                    bulk_g2s_mc(sb + (2 * i + r) * 16384, g_ao + (size_t)(mb * 8 + 2 * i + r) * 8192, 16384, bars + 8 * (B_FA + i));
                load_b(0);
                if (blockIdx.x == 0)
                    for (int i = 0; i < 32; i++) g_cnt[i] = 0;
                mbar_wait_cluster(bars + 8 * B_ADONE, 0);
                load_b(1); load_b(2);
                auto load_c = [&](int i) {
                    const int s = i % 6, kb = c_kblock(i, r);
                    const uint32_t bar = bars + 8 * (B_CF + s), da = sb + c_stage_a(s, ntB), db = sb + c_stage_b(s, ntB);
                    mbar_expect(bar, 32768);
                    tma2d(db, &tm_d, ntA * 128, kb * 64, bar);
                    tma2d(db + 8192, &tm_d, ntA * 128 + 64, kb * 64, bar);
                    bulk_g2s(da, g_g + (size_t)(mb * 28 + kb) * 8192, 16384, bar);
                };
                for (int it = 3; it < 16; it++) {
                    mbar_wait_cluster(bars + 8 * (B_BE + it % 3), (it / 3 - 1) & 1);
                    load_b(it);
                    if (it == 12) { poll_count(&g_cnt2[mb], 8); load_c(0); }
                    if (it == 14) load_c(1);
                }
                mbar_wait_cluster(bars + 8 * (B_BE + 1), 0);
                load_c(2);
                mbar_wait(bars + 8 * B_BDONE, 0);
                for (int i = 3; i < 14; i++) {
                    if (i >= 6) mbar_wait(bars + 8 * (B_CE + i % 6), ((i / 6) - 1) & 1);
                    if (i == 6) { poll_count(&g_cnt2[16 + mb], 8); TL(18); }
                    load_c(i);
                }
            }
            else asm volatile("barrier.cluster.wait.acquire;" ::: "memory");
            TLDUMP;
        } else if (warp == 1) {
            asm volatile("barrier.cluster.wait.acquire.aligned;" ::: "memory");
            bar_sync(5, 288);
            if (lane == 0) { red_release(&g_cnt2[32 + (mb * 8 + nt) * FLAG_STRIDE]); TL(9); }
            __syncwarp();
            bar_sync(6, 288);
            if (lane == 0) red_release(&g_cnt2[32 + (mb * 8 + nt) * FLAG_STRIDE]);
            __syncwarp();
            bar_sync(1, 288);
            if (lane == 0) red_release(&g_cnt2[mbB]);
            __syncwarp();
            bar_sync(2, 288);
            if (lane == 0) {
                red_release(&g_cnt2[16 + mbB]);
                if (DELAYC == 9) mbar_arrive(bars + 8 * B_BDONE);
                TL(13);
            }
            __syncwarp();
            bar_sync(3, 288);
            if (lane == 0) {
                tma2d_store(&tm_out, sb, nt * 64, mb * 128);
                bulk_commit();
                bulk_wait_all();
                TL(15);
            }
            TLDUMP;
        } else {
            asm volatile("barrier.cluster.wait.acquire.aligned;" ::: "memory");
            pdl_wait();
            float2* s_rs = (float2*)(smem + F_RS);
            float* s_cs = (float*)(smem + F_CS);
            for (int c = tid - 64; c < 448; c += 64)
                s_cs[c] = __ldcg(&g_cs2[(c >= 224 ? FF - 224 : 0) + ntB * 224 + c]);
            if (tid == 96) {
                mbar_wait_cluster(bars + 8 * B_ADONE, 0);
                for (int i = 0; i < 8; i++) {
                    const int kb = (ntB + i) & 7;
                    const uint32_t bar = bars + 8 * (i < 4 ? B_HF + i : B_FA + i - 4);
                    poll_count(&g_cnt2[32 + (mbB * 8 + kb) * FLAG_STRIDE], 1);
                    mbar_expect(bar, 16384);
                    bulk_g2s(sb + kb * 16384, g_h + (size_t)(mbB * 8 + kb) * 8192, 16384, bar);
                }
            }
            __syncwarp();
            TL(17);
            for (int i = 0; i < 8; i++) mbar_wait(bars + 8 * (i < 4 ? B_HF + i : B_FA + i - 4), i < 4 ? 0 : 1);
            if (lane < 8) poll_count(&g_cnt2[32 + (mbB * 8 + lane) * FLAG_STRIDE], 2);
            __syncwarp();
            __syncwarp();
            for (int rr = tid - 64; rr < 128; rr += 64) {
                s_rs[rr] = h_row_stats(mbB * 128 + rr);
            }
            __syncwarp();
            if (lane == 0) mbar_arrive(bars + 8 * B_AUX);
            TLDUMP;
        }
    } else {
        asm volatile("setmaxnreg.inc.sync.aligned.u32 216;");
        if (warp == 4) TX(206);
        const int wgi = (warp >> 2) - 1, ww = warp & 3, ctid = tid - 128;
        const int g = lane >> 2, t = lane & 3;
        const int rl = wgi * 64 + ww * 16 + g, row = mb * 128 + rl;
        const int rgl = wgi * 8 + ww * 2;
        const float2* s_rs = (const float2*)(smem + F_RS);
        const float* s_cs = (const float*)(smem + F_CS);
        const uint32_t stl = ((lane >> 4) * 16 + rgl + ((lane >> 3) & 1)) * 128 + (lane & 7) * 16;
        uint32_t* hp = (uint32_t*)g_h + ((size_t)(mb * 8 + nt) * 8 * 16 + rgl) * 32 + lane;
        const uint32_t rbars = mapa(bars, 1 - r);
        TL(23);
        {
            uint32_t xr[16];
            const uint32_t* xp = (const uint32_t*)(x + (size_t)row * DM + nt * 64) + t;
#pragma unroll
            for (int j = 0; j < 8; j++) { xr[2 * j] = __ldg(xp + 4 * j); xr[2 * j + 1] = __ldg(xp + 8 * (DM / 2) + 4 * j); }
            float acc[32];
#pragma unroll 1
            for (int i = 0; i < 8; i++) {
                if (!(i & 1)) { mbar_wait(bars + 8 * (B_FA + (i >> 1)), 0); if (i == 0) TL(19); }
                uint64_t ad = make_desc(sb + i * 16384 + wgi * 1024, 2048, 128, 0);
                uint64_t bd = make_desc(sb + F_R2 + 32768 + i * 8192, 8192, 1024, 1);
                WG_FENCE();
#pragma unroll
                for (int k = 0; k < 4; k++) wgmma_ss_n64(acc, ad + k * 256, bd + k * 128, (i | k) != 0);
                WG_COMMIT();
            }
            wg_wait<0>();
            fence_regs(acc);
            TL(7);
            asm volatile("barrier.cluster.wait.acquire.aligned;" ::: "memory");
            bar_sync(4, 256);
            if (tid == 128) { mbar_arrive(bars + 8 * B_ADONE); mbar_arrive_remote(mapa(bars + 8 * B_ADONE, 1 - r)); }
            float v0[16], v1[16];
            float s0 = 0.f, s1 = 0.f;
#pragma unroll
            for (int j2 = 0; j2 < 4; j2++) {
                uint32_t u[4];
#pragma unroll
                for (int jj = 0; jj < 2; jj++) {
                    const int j = 2 * j2 + jj;
                    u[2 * jj] = pack_bf16(bf_lo(xr[2 * j]) + acc[4 * j], bf_hi(xr[2 * j]) + acc[4 * j + 1]);
                    u[2 * jj + 1] = pack_bf16(bf_lo(xr[2 * j + 1]) + acc[4 * j + 2], bf_hi(xr[2 * j + 1]) + acc[4 * j + 3]);
                    v0[2 * j] = bf_lo(u[2 * jj]); v0[2 * j + 1] = bf_hi(u[2 * jj]);
                    v1[2 * j] = bf_lo(u[2 * jj + 1]); v1[2 * j + 1] = bf_hi(u[2 * jj + 1]);
                    s0 += v0[2 * j] + v0[2 * j + 1];
                    s1 += v1[2 * j] + v1[2 * j + 1];
                }
                hp[j2 * 1024] = u[0]; hp[j2 * 1024 + 32] = u[1]; hp[j2 * 1024 + 512] = u[2]; hp[j2 * 1024 + 544] = u[3];
            }
            bar_arrive(5, 288);
            float m0 = s0 * (1.0f / 16), m1 = s1 * (1.0f / 16), q0 = 0.f, q1 = 0.f;
#pragma unroll
            for (int i = 0; i < 16; i++) {
                float d0 = v0[i] - m0, d1 = v1[i] - m1;
                q0 = fmaf(d0, d0, q0); q1 = fmaf(d1, d1, q1);
            }
#pragma unroll
            for (int st = 0; st < 2; st++) {
                float hn = st ? 16.f : 8.f;
                float om0 = __shfl_xor_sync(0xffffffffu, m0, 1 << st), oq0 = __shfl_xor_sync(0xffffffffu, q0, 1 << st);
                float om1 = __shfl_xor_sync(0xffffffffu, m1, 1 << st), oq1 = __shfl_xor_sync(0xffffffffu, q1, 1 << st);
                float d0 = om0 - m0, d1 = om1 - m1;
                q0 = q0 + oq0 + d0 * d0 * hn; q1 = q1 + oq1 + d1 * d1 * hn;
                m0 = 0.5f * (m0 + om0); m1 = 0.5f * (m1 + om1);
            }
            if (t == 0) {
                g_hstat[row * 8 + nt] = make_float2(m0, q0);
                g_hstat[(row + 8) * 8 + nt] = make_float2(m1, q1);
            }
            bar_arrive(6, 288);
            TL(8);
        }
        uint32_t* gp = (uint32_t*)g_g + (((size_t)mbB * 224 + ntB * 28) * 16 + rgl) * 32 + lane;
        {
            float ag[128];
#pragma unroll 1
            for (int kb = 0; kb < 8; kb++) {
                const int s = kb % 3;
                mbar_wait(bars + 8 * (kb < 4 ? B_HF + kb : B_FA + kb - 4), kb < 4 ? 0 : 1);
                mbar_wait(bars + 8 * (B_BF + s), (kb / 3) & 1);
                uint64_t ad = make_desc(sb + ((ntB + kb) & 7) * 16384 + wgi * 1024, 2048, 128, 0);
                uint64_t bd = make_desc(sb + F_R2 + s * 32768, 4096, 512, 2);
                WG_FENCE();
#pragma unroll
                for (int k = 0; k < 4; k++) wgmma_ss_n256(ag, ad + k * 256, bd + k * 64, (kb | k) != 0);
                WG_COMMIT();
                if (kb > 0) {
                    wg_wait<1>();
                    if (lane == 0) { mbar_arrive(bars + 8 * (B_BE + (kb - 1) % 3)); mbar_arrive_remote(rbars + 8 * (B_BE + (kb - 1) % 3)); }
                }
            }
            wg_wait<0>();
            if (lane == 0) { mbar_arrive(bars + 8 * (B_BE + 7 % 3)); mbar_arrive_remote(rbars + 8 * (B_BE + 7 % 3)); }
            fence_regs(ag);
            TL(10);
            mbar_wait(bars + 8 * B_AUX, 0);
            ffn_epilogue<16, false>(ag, ag + 64, s_cs, 0, gp, 0, s_rs[rl], s_rs[rl + 8], lane);
            bar_arrive(1, 288);
        }
        {
            float ag[96];
#pragma unroll 1
            for (int kb = 0; kb < 8; kb++) {
                const int it = 8 + kb, s = it % 3;
                mbar_wait(bars + 8 * (B_BF + s), (it / 3) & 1);
                uint64_t ad = make_desc(sb + ((ntB + kb) & 7) * 16384 + wgi * 1024, 2048, 128, 0);
                uint64_t bd = make_desc(sb + F_R2 + s * 32768, 4096, 512, 2);
                WG_FENCE();
#pragma unroll
                for (int k = 0; k < 4; k++) wgmma_ss_n192(ag, ad + k * 256, bd + k * 64, (kb | k) != 0);
                WG_COMMIT();
                if (kb > 0) {
                    wg_wait<1>();
                    if (lane == 0 && it < 15) { mbar_arrive(bars + 8 * (B_BE + (it - 1) % 3)); mbar_arrive_remote(rbars + 8 * (B_BE + (it - 1) % 3)); }
                }
            }
            wg_wait<0>();
            if (lane == 0) {
                mbar_arrive(bars + 8 * B_BDONE);
                mbar_arrive_remote(rbars + 8 * B_PRDY);
            }
            fence_regs(ag);
            TL(11);
            ffn_epilogue<12, false>(ag, ag + 48, s_cs, 128, gp + 16 * 512, 0, s_rs[rl], s_rs[rl + 8], lane);
            bar_arrive(2, 288);
            TL(12);
        }
        {
            uint32_t hr[16];
#pragma unroll
            for (int j = 0; j < 8; j++) { hr[2 * j] = __ldcg(hp + j * 512); hr[2 * j + 1] = __ldcg(hp + j * 512 + 32); }
            mbar_wait(bars + 8 * (B_CF + 0), 0);
            const float a0 = h_row_stats(row).x, a1 = h_row_stats(row + 8).x;
            float acc[64];
#pragma unroll 1
            for (int kb = 0; kb < 14; kb++) {
                const int s = kb % 6;
                mbar_wait(bars + 8 * (B_CF + s), (kb / 6) & 1);
                if (warp == 4) TX(96 + kb);
                uint64_t ad = make_desc(sb + c_stage_a(s, ntB) + wgi * 1024, 2048, 128, 0);
                uint64_t bd = make_desc(sb + c_stage_b(s, ntB), 8192, 1024, 1);
                WG_FENCE();
#pragma unroll
                for (int k = 0; k < 4; k++) wgmma_ss_n128(acc, ad + k * 256, bd + k * 128, (kb | k) != 0);
                WG_COMMIT();
                if (kb > 0) {
                    wg_wait<1>();
                    if (lane == 0) mbar_arrive(bars + 8 * (B_CE + (kb - 1) % 6));
                }
            }
            wg_wait<0>();
            fence_regs(acc);
            TL(14);
            mbar_wait_cluster(bars + 8 * B_PRDY, 0);
            float o[32];
            if (r == 0) xchg<0>(acc, o, sb, smem, B_XC, ctid); else xchg<1>(acc, o, sb, smem, B_XC, ctid);
            TL(22);
            bar_sync(4, 256);
            const float k0 = 0.5f * a0 * a0, k1 = 0.5f * a1 * a1;
            const int srow = wgi * 64 + ww * 16 + ((lane >> 3) & 1) * 8 + (lane & 7);
#pragma unroll
            for (int j2 = 0; j2 < 4; j2++) {
                uint32_t u[4];
#pragma unroll
                for (int jj = 0; jj < 2; jj++) {
                    const int j = 2 * j2 + jj;
                    u[2 * jj] = pack_bf16(fmaf(k0, o[4 * j], bf_lo(hr[2 * j])), fmaf(k0, o[4 * j + 1], bf_hi(hr[2 * j])));
                    u[2 * jj + 1] = pack_bf16(fmaf(k1, o[4 * j + 2], bf_lo(hr[2 * j + 1])), fmaf(k1, o[4 * j + 3], bf_hi(hr[2 * j + 1])));
                }
                const int chunk = 2 * j2 + (lane >> 4);
                stsm4(sb + srow * 128 + ((chunk ^ (lane & 7)) * 16), u[0], u[1], u[2], u[3]);
            }
            fence_proxy_async();
            bar_arrive(3, 288);
            TLDUMP;
        }
    }
}

typedef CUresult (*EncodeFn)(CUtensorMap*, CUtensorMapDataType, cuuint32_t, void*, const cuuint64_t*, const cuuint64_t*,
                             const cuuint32_t*, const cuuint32_t*, CUtensorMapInterleave, CUtensorMapSwizzle,
                             CUtensorMapL2promotion, CUtensorMapFloatOOBfill);

void encode(EncodeFn fn, CUtensorMap* m, const void* ptr, int rank, const cuuint64_t* dims, const cuuint64_t* strides,
            const cuuint32_t* box, CUtensorMapSwizzle swz) {
    cuuint32_t es[3] = {1, 1, 1};
    fn(m, CU_TENSOR_MAP_DATA_TYPE_BFLOAT16, rank, (void*)ptr, dims, strides, box, es, CU_TENSOR_MAP_INTERLEAVE_NONE, swz,
       CU_TENSOR_MAP_L2_PROMOTION_L2_256B, CU_TENSOR_MAP_FLOAT_OOB_FILL_NONE);
}

template <typename... KArgs, typename... Args>
void launch(void (*kern)(KArgs...), int grid, int block, int smem, bool pdl, Args... args) {
    cudaLaunchConfig_t cfg = {};
    cfg.gridDim = dim3(grid); cfg.blockDim = dim3(block); cfg.dynamicSmemBytes = smem;
    cfg.stream = cudaStreamPerThread;
    cudaLaunchAttribute at[1];
    at[0].id = cudaLaunchAttributeProgrammaticStreamSerialization;
    at[0].val.programmaticStreamSerializationAllowed = 1;
    cfg.attrs = at; cfg.numAttrs = pdl ? 1 : 0;
    cudaLaunchKernelEx(&cfg, kern, KArgs(args)...);
}

}

extern "C" void kernel_launch(void* const* d_in, const int* in_sizes, int n_in, void* d_out, int out_size) {
    const __nv_bfloat16* x = (const __nv_bfloat16*)d_in[0];
    const __nv_bfloat16* wqkv = (const __nv_bfloat16*)d_in[1];
    const __nv_bfloat16* wo = (const __nv_bfloat16*)d_in[2];
    const __nv_bfloat16* wgate = (const __nv_bfloat16*)d_in[4];
    const __nv_bfloat16* wup = (const __nv_bfloat16*)d_in[5];
    const __nv_bfloat16* wdown = (const __nv_bfloat16*)d_in[6];
    __nv_bfloat16* out = (__nv_bfloat16*)d_out;

    static CUtensorMap tm_x, tm_wqkv, tm_wo, tm_wg, tm_wu, tm_wd, tm_out;
    static const void* cached[7] = {nullptr, nullptr, nullptr, nullptr, nullptr, nullptr, nullptr};
    if (cached[0] != x || cached[1] != wqkv || cached[2] != wo || cached[3] != wgate || cached[4] != wup || cached[5] != wdown || cached[6] != out) {
        void* fp = nullptr;
        cudaDriverEntryPointQueryResult qr;
        cudaGetDriverEntryPoint("cuTensorMapEncodeTiled", &fp, cudaEnableDefault, &qr);
        EncodeFn fn = (EncodeFn)fp;
        { cuuint64_t d[2] = {512, 2048}, s[1] = {1024}; cuuint32_t b[2] = {64, 128};
          encode(fn, &tm_x, x, 2, d, s, b, CU_TENSOR_MAP_SWIZZLE_128B);
          encode(fn, &tm_out, out, 2, d, s, b, CU_TENSOR_MAP_SWIZZLE_128B); }
        { cuuint64_t d[3] = {64, 512, 24}, s[2] = {3072, 128}; cuuint32_t b[3] = {64, 64, 3};
          encode(fn, &tm_wqkv, wqkv, 3, d, s, b, CU_TENSOR_MAP_SWIZZLE_128B); }
        { cuuint64_t d[2] = {512, 512}, s[1] = {1024}; cuuint32_t b[2] = {64, 64};
          encode(fn, &tm_wo, wo, 2, d, s, b, CU_TENSOR_MAP_SWIZZLE_128B); }
        { cuuint64_t d[2] = {1792, 512}, s[1] = {3584}; cuuint32_t b[2] = {32, 64};
          encode(fn, &tm_wg, wgate, 2, d, s, b, CU_TENSOR_MAP_SWIZZLE_64B);
          encode(fn, &tm_wu, wup, 2, d, s, b, CU_TENSOR_MAP_SWIZZLE_64B); }
        { cuuint64_t d[2] = {512, 1792}, s[1] = {1024}; cuuint32_t b[2] = {64, 64};
          encode(fn, &tm_wd, wdown, 2, d, s, b, CU_TENSOR_MAP_SWIZZLE_128B); }
        cudaFuncSetAttribute(qkv_kernel, cudaFuncAttributeMaxDynamicSharedMemorySize, F_SMEM);
        cudaFuncSetAttribute(qkv_kernel, cudaFuncAttributePreferredSharedMemoryCarveout, 100);
        cudaFuncSetAttribute(attn_kernel, cudaFuncAttributeMaxDynamicSharedMemorySize, F_SMEM);
        cudaFuncSetAttribute(attn_kernel, cudaFuncAttributePreferredSharedMemoryCarveout, 100);
        cudaFuncSetAttribute(tail_kernel, cudaFuncAttributeMaxDynamicSharedMemorySize, F_SMEM);
        cudaFuncSetAttribute(tail_kernel, cudaFuncAttributePreferredSharedMemoryCarveout, 100);
        cached[0] = x; cached[1] = wqkv; cached[2] = wo; cached[3] = wgate; cached[4] = wup; cached[5] = wdown; cached[6] = out;
    }
    launch(qkv_kernel, 128, 384, F_SMEM, false, tm_x, tm_wqkv, x, wqkv);
    launch(attn_kernel, 132, 512, F_SMEM, true, wgate, wup, wo, wdown);
    launch(tail_kernel, 128, 384, F_SMEM, true, tm_wo, tm_wg, tm_wu, tm_wd, tm_out, x);
}
```

```cpp
#include <cuda_runtime.h>
#include <cuda_bf16.h>
#include <cuda.h>
#include <stdint.h>

#define K1_DIRECT
namespace {

constexpr int S_LEN = 2048, DM = 512, NH = 32, FF = 1792;

__device__ __align__(1024) __nv_bfloat16 g_qkv[3 * NH * S_LEN * 16];
__device__ __align__(1024) __nv_bfloat16 g_ao[S_LEN * DM];
__device__ __align__(1024) __nv_bfloat16 g_h[S_LEN * DM];
__device__ __align__(1024) __nv_bfloat16 g_g[S_LEN * FF];
__device__ __align__(16) float2 g_rowstat1[S_LEN];
__device__ float g_cs1_part[16 * 1536];
__device__ unsigned int g_cnt[32];
__device__ unsigned int g_cnt2[160];
__device__ float g_nrm[3 * NH * 128];
__device__ float2 g_hstat[S_LEN * 8];
__device__ float g_cs2[2 * FF];

#define TLDECL
#define TL(slot)
#define TLDUMP
#define TX(slot)
__device__ __forceinline__ uint32_t smem_u32(const void* p) { return (uint32_t)__cvta_generic_to_shared(p); }
__device__ __forceinline__ void mbar_init(uint32_t a, int c) { asm volatile("mbarrier.init.shared.b64 [%0], %1;" :: "r"(a), "r"(c)); }
__device__ __forceinline__ void mbar_expect(uint32_t a, int bytes) { asm volatile("mbarrier.arrive.expect_tx.shared.b64 _, [%0], %1;" :: "r"(a), "r"(bytes) : "memory"); }
__device__ __forceinline__ void mbar_arrive(uint32_t a) { asm volatile("mbarrier.arrive.shared.b64 _, [%0];" :: "r"(a) : "memory"); }
__device__ __forceinline__ void mbar_wait(uint32_t a, int parity) {
    uint32_t done;
    int it = 0;
    do {
        asm volatile("{\n.reg .pred p;\nmbarrier.try_wait.parity.shared.b64 p, [%1], %2;\nselp.u32 %0, 1, 0, p;\n}"
                     : "=r"(done) : "r"(a), "r"(parity) : "memory");
        if (++it > (1 << 24)) __trap();
    } while (!done);
}
__device__ __forceinline__ void bulk_g2s(uint32_t dst, const void* src, int bytes, uint32_t bar) {
    asm volatile("cp.async.bulk.shared::cluster.global.mbarrier::complete_tx::bytes [%0], [%1], %2, [%3];"
                 :: "r"(dst), "l"(src), "r"(bytes), "r"(bar) : "memory");
}
__device__ __forceinline__ void tma2d(uint32_t dst, const CUtensorMap* m, int c0, int c1, uint32_t bar) {
    asm volatile("cp.async.bulk.tensor.2d.shared::cluster.global.mbarrier::complete_tx::bytes [%0], [%1, {%3, %4}], [%2];"
                 :: "r"(dst), "l"(m), "r"(bar), "r"(c0), "r"(c1) : "memory");
}
__device__ __forceinline__ void tma3d(uint32_t dst, const CUtensorMap* m, int c0, int c1, int c2, uint32_t bar) {
    asm volatile("cp.async.bulk.tensor.3d.shared::cluster.global.mbarrier::complete_tx::bytes [%0], [%1, {%3, %4, %5}], [%2];"
                 :: "r"(dst), "l"(m), "r"(bar), "r"(c0), "r"(c1), "r"(c2) : "memory");
}
__device__ __forceinline__ void prefetch_tmap(const CUtensorMap* m) { asm volatile("prefetch.tensormap [%0];" :: "l"(m) : "memory"); }
__device__ __forceinline__ void pdl_wait() { asm volatile("griddepcontrol.wait;" ::: "memory"); }
__device__ __forceinline__ void pdl_launch() { asm volatile("griddepcontrol.launch_dependents;" ::: "memory"); }
__device__ __forceinline__ void fence_barrier_init() { asm volatile("fence.mbarrier_init.release.cluster;" ::: "memory"); }
__device__ __forceinline__ void fence_proxy_async() { asm volatile("fence.proxy.async.shared::cta;" ::: "memory"); }
__device__ __forceinline__ uint64_t make_desc(uint32_t saddr, uint32_t lbo, uint32_t sbo, uint32_t swz) {
    return (uint64_t)((saddr & 0x3FFFF) >> 4) | ((uint64_t)((lbo & 0x3FFFF) >> 4) << 16) |
           ((uint64_t)((sbo & 0x3FFFF) >> 4) << 32) | ((uint64_t)swz << 62);
}
#define WG_FENCE() asm volatile("wgmma.fence.sync.aligned;" ::: "memory")
#define WG_COMMIT() asm volatile("wgmma.commit_group.sync.aligned;" ::: "memory")
template <int N> __device__ __forceinline__ void wg_wait() { asm volatile("wgmma.wait_group.sync.aligned %0;" :: "n"(N) : "memory"); }
template <int N> __device__ __forceinline__ void fence_regs(float (&d)[N]) {
#pragma unroll
    for (int i = 0; i < N; i++) asm volatile("" : "+f"(d[i]) :: "memory");
}
__device__ __forceinline__ float ex2f(float x) { float y; asm("ex2.approx.ftz.f32 %0, %1;" : "=f"(y) : "f"(x)); return y; }
__device__ __forceinline__ float tanh_fast(float x) { float y; asm("tanh.approx.f32 %0, %1;" : "=f"(y) : "f"(x)); return y; }
__device__ __forceinline__ uint32_t pack_bf16(float lo, float hi) { uint32_t r; asm("cvt.rn.bf16x2.f32 %0, %1, %2;" : "=r"(r) : "f"(hi), "f"(lo)); return r; }
__device__ __forceinline__ float bf_lo(uint32_t u) { return __uint_as_float(u << 16); }
__device__ __forceinline__ float bf_hi(uint32_t u) { return __uint_as_float(u & 0xFFFF0000u); }
__device__ __forceinline__ uint32_t hfma2(uint32_t a, uint32_t b, uint32_t c) { uint32_t r; asm("fma.rn.f16x2 %0, %1, %2, %3;" : "=r"(r) : "r"(a), "r"(b), "r"(c)); return r; }
__device__ __forceinline__ uint32_t hmul2(uint32_t a, uint32_t b) { uint32_t r; asm("mul.rn.f16x2 %0, %1, %2;" : "=r"(r) : "r"(a), "r"(b)); return r; }
__device__ __forceinline__ unsigned int ld_acquire(const unsigned int* p) { unsigned int v; asm volatile("ld.acquire.gpu.u32 %0, [%1];" : "=r"(v) : "l"(p) : "memory"); return v; }
__device__ __forceinline__ void red_release(unsigned int* p) { asm volatile("red.release.gpu.global.add.u32 [%0], 1;" :: "l"(p) : "memory"); }
__device__ __forceinline__ void stsm4(uint32_t addr, uint32_t a, uint32_t b, uint32_t c, uint32_t d) {
    asm volatile("stmatrix.sync.aligned.m8n8.x4.shared.b16 [%0], {%1,%2,%3,%4};" :: "r"(addr), "r"(a), "r"(b), "r"(c), "r"(d) : "memory");
}
__device__ __forceinline__ void bulk_s2g(void* dst, uint32_t src, int bytes) {
    asm volatile("cp.async.bulk.global.shared::cta.bulk_group [%0], [%1], %2;" :: "l"(dst), "r"(src), "r"(bytes) : "memory");
}
__device__ __forceinline__ void bulk_commit() { asm volatile("cp.async.bulk.commit_group;" ::: "memory"); }
__device__ __forceinline__ void bulk_wait_all() { asm volatile("cp.async.bulk.wait_group 0;" ::: "memory"); }
__device__ __forceinline__ void bulk_wait_read() { asm volatile("cp.async.bulk.wait_group.read 0;" ::: "memory"); }
__device__ __forceinline__ void bar_sync(int id, int n) { asm volatile("bar.sync %0, %1;" :: "r"(id), "r"(n) : "memory"); }
__device__ __forceinline__ void bar_arrive(int id, int n) { asm volatile("bar.arrive %0, %1;" :: "r"(id), "r"(n) : "memory"); }
__device__ __forceinline__ float warp_sum(float v) {
#pragma unroll
    for (int o = 16; o; o >>= 1) v += __shfl_xor_sync(0xffffffffu, v, o);
    return v;
}
__device__ __forceinline__ float warp_max(float v) {
#pragma unroll
    for (int o = 16; o; o >>= 1) v = fmaxf(v, __shfl_xor_sync(0xffffffffu, v, o));
    return v;
}

__device__ __forceinline__ void wgmma_ss_n64(float (&d)[32], uint64_t adesc, uint64_t bdesc, int scale_d) {
    asm volatile("{\n.reg .pred p;\nsetp.ne.b32 p, %34, 0;\n"
      "wgmma.mma_async.sync.aligned.m64n64k16.f32.bf16.bf16 {%0,%1,%2,%3,%4,%5,%6,%7,%8,%9,%10,%11,%12,%13,%14,%15,%16,%17,%18,%19,%20,%21,%22,%23,%24,%25,%26,%27,%28,%29,%30,%31}, %32, %33, p, 1, 1, 0, 1;\n}"
      : "+f"(d[0]), "+f"(d[1]), "+f"(d[2]), "+f"(d[3]), "+f"(d[4]), "+f"(d[5]), "+f"(d[6]), "+f"(d[7]), "+f"(d[8]), "+f"(d[9]), "+f"(d[10]), "+f"(d[11]), "+f"(d[12]), "+f"(d[13]), "+f"(d[14]), "+f"(d[15]), "+f"(d[16]), "+f"(d[17]), "+f"(d[18]), "+f"(d[19]), "+f"(d[20]), "+f"(d[21]), "+f"(d[22]), "+f"(d[23]), "+f"(d[24]), "+f"(d[25]), "+f"(d[26]), "+f"(d[27]), "+f"(d[28]), "+f"(d[29]), "+f"(d[30]), "+f"(d[31])
      : "l"(adesc), "l"(bdesc), "r"(scale_d));
}
__device__ __forceinline__ void wgmma_ss_n128(float (&d)[64], uint64_t adesc, uint64_t bdesc, int scale_d) {
    asm volatile("{\n.reg .pred p;\nsetp.ne.b32 p, %66, 0;\n"
      "wgmma.mma_async.sync.aligned.m64n128k16.f32.bf16.bf16 {%0,%1,%2,%3,%4,%5,%6,%7,%8,%9,%10,%11,%12,%13,%14,%15,%16,%17,%18,%19,%20,%21,%22,%23,%24,%25,%26,%27,%28,%29,%30,%31,%32,%33,%34,%35,%36,%37,%38,%39,%40,%41,%42,%43,%44,%45,%46,%47,%48,%49,%50,%51,%52,%53,%54,%55,%56,%57,%58,%59,%60,%61,%62,%63}, %64, %65, p, 1, 1, 0, 1;\n}"
      : "+f"(d[0]), "+f"(d[1]), "+f"(d[2]), "+f"(d[3]), "+f"(d[4]), "+f"(d[5]), "+f"(d[6]), "+f"(d[7]), "+f"(d[8]), "+f"(d[9]), "+f"(d[10]), "+f"(d[11]), "+f"(d[12]), "+f"(d[13]), "+f"(d[14]), "+f"(d[15]), "+f"(d[16]), "+f"(d[17]), "+f"(d[18]), "+f"(d[19]), "+f"(d[20]), "+f"(d[21]), "+f"(d[22]), "+f"(d[23]), "+f"(d[24]), "+f"(d[25]), "+f"(d[26]), "+f"(d[27]), "+f"(d[28]), "+f"(d[29]), "+f"(d[30]), "+f"(d[31]), "+f"(d[32]), "+f"(d[33]), "+f"(d[34]), "+f"(d[35]), "+f"(d[36]), "+f"(d[37]), "+f"(d[38]), "+f"(d[39]), "+f"(d[40]), "+f"(d[41]), "+f"(d[42]), "+f"(d[43]), "+f"(d[44]), "+f"(d[45]), "+f"(d[46]), "+f"(d[47]), "+f"(d[48]), "+f"(d[49]), "+f"(d[50]), "+f"(d[51]), "+f"(d[52]), "+f"(d[53]), "+f"(d[54]), "+f"(d[55]), "+f"(d[56]), "+f"(d[57]), "+f"(d[58]), "+f"(d[59]), "+f"(d[60]), "+f"(d[61]), "+f"(d[62]), "+f"(d[63])
      : "l"(adesc), "l"(bdesc), "r"(scale_d));
}
__device__ __forceinline__ void wgmma_ss_n192(float (&d)[96], uint64_t adesc, uint64_t bdesc, int scale_d) {
    asm volatile("{\n.reg .pred p;\nsetp.ne.b32 p, %98, 0;\n"
      "wgmma.mma_async.sync.aligned.m64n192k16.f32.bf16.bf16 {%0,%1,%2,%3,%4,%5,%6,%7,%8,%9,%10,%11,%12,%13,%14,%15,%16,%17,%18,%19,%20,%21,%22,%23,%24,%25,%26,%27,%28,%29,%30,%31,%32,%33,%34,%35,%36,%37,%38,%39,%40,%41,%42,%43,%44,%45,%46,%47,%48,%49,%50,%51,%52,%53,%54,%55,%56,%57,%58,%59,%60,%61,%62,%63,%64,%65,%66,%67,%68,%69,%70,%71,%72,%73,%74,%75,%76,%77,%78,%79,%80,%81,%82,%83,%84,%85,%86,%87,%88,%89,%90,%91,%92,%93,%94,%95}, %96, %97, p, 1, 1, 0, 1;\n}"
      : "+f"(d[0]), "+f"(d[1]), "+f"(d[2]), "+f"(d[3]), "+f"(d[4]), "+f"(d[5]), "+f"(d[6]), "+f"(d[7]), "+f"(d[8]), "+f"(d[9]), "+f"(d[10]), "+f"(d[11]), "+f"(d[12]), "+f"(d[13]), "+f"(d[14]), "+f"(d[15]), "+f"(d[16]), "+f"(d[17]), "+f"(d[18]), "+f"(d[19]), "+f"(d[20]), "+f"(d[21]), "+f"(d[22]), "+f"(d[23]), "+f"(d[24]), "+f"(d[25]), "+f"(d[26]), "+f"(d[27]), "+f"(d[28]), "+f"(d[29]), "+f"(d[30]), "+f"(d[31]), "+f"(d[32]), "+f"(d[33]), "+f"(d[34]), "+f"(d[35]), "+f"(d[36]), "+f"(d[37]), "+f"(d[38]), "+f"(d[39]), "+f"(d[40]), "+f"(d[41]), "+f"(d[42]), "+f"(d[43]), "+f"(d[44]), "+f"(d[45]), "+f"(d[46]), "+f"(d[47]), "+f"(d[48]), "+f"(d[49]), "+f"(d[50]), "+f"(d[51]), "+f"(d[52]), "+f"(d[53]), "+f"(d[54]), "+f"(d[55]), "+f"(d[56]), "+f"(d[57]), "+f"(d[58]), "+f"(d[59]), "+f"(d[60]), "+f"(d[61]), "+f"(d[62]), "+f"(d[63]), "+f"(d[64]), "+f"(d[65]), "+f"(d[66]), "+f"(d[67]), "+f"(d[68]), "+f"(d[69]), "+f"(d[70]), "+f"(d[71]), "+f"(d[72]), "+f"(d[73]), "+f"(d[74]), "+f"(d[75]), "+f"(d[76]), "+f"(d[77]), "+f"(d[78]), "+f"(d[79]), "+f"(d[80]), "+f"(d[81]), "+f"(d[82]), "+f"(d[83]), "+f"(d[84]), "+f"(d[85]), "+f"(d[86]), "+f"(d[87]), "+f"(d[88]), "+f"(d[89]), "+f"(d[90]), "+f"(d[91]), "+f"(d[92]), "+f"(d[93]), "+f"(d[94]), "+f"(d[95])
      : "l"(adesc), "l"(bdesc), "r"(scale_d));
}
__device__ __forceinline__ void wgmma_ss_n256(float (&d)[128], uint64_t adesc, uint64_t bdesc, int scale_d) {
    asm volatile("{\n.reg .pred p;\nsetp.ne.b32 p, %130, 0;\n"
      "wgmma.mma_async.sync.aligned.m64n256k16.f32.bf16.bf16 {%0,%1,%2,%3,%4,%5,%6,%7,%8,%9,%10,%11,%12,%13,%14,%15,%16,%17,%18,%19,%20,%21,%22,%23,%24,%25,%26,%27,%28,%29,%30,%31,%32,%33,%34,%35,%36,%37,%38,%39,%40,%41,%42,%43,%44,%45,%46,%47,%48,%49,%50,%51,%52,%53,%54,%55,%56,%57,%58,%59,%60,%61,%62,%63,%64,%65,%66,%67,%68,%69,%70,%71,%72,%73,%74,%75,%76,%77,%78,%79,%80,%81,%82,%83,%84,%85,%86,%87,%88,%89,%90,%91,%92,%93,%94,%95,%96,%97,%98,%99,%100,%101,%102,%103,%104,%105,%106,%107,%108,%109,%110,%111,%112,%113,%114,%115,%116,%117,%118,%119,%120,%121,%122,%123,%124,%125,%126,%127}, %128, %129, p, 1, 1, 0, 1;\n}"
      : "+f"(d[0]), "+f"(d[1]), "+f"(d[2]), "+f"(d[3]), "+f"(d[4]), "+f"(d[5]), "+f"(d[6]), "+f"(d[7]), "+f"(d[8]), "+f"(d[9]), "+f"(d[10]), "+f"(d[11]), "+f"(d[12]), "+f"(d[13]), "+f"(d[14]), "+f"(d[15]), "+f"(d[16]), "+f"(d[17]), "+f"(d[18]), "+f"(d[19]), "+f"(d[20]), "+f"(d[21]), "+f"(d[22]), "+f"(d[23]), "+f"(d[24]), "+f"(d[25]), "+f"(d[26]), "+f"(d[27]), "+f"(d[28]), "+f"(d[29]), "+f"(d[30]), "+f"(d[31]), "+f"(d[32]), "+f"(d[33]), "+f"(d[34]), "+f"(d[35]), "+f"(d[36]), "+f"(d[37]), "+f"(d[38]), "+f"(d[39]), "+f"(d[40]), "+f"(d[41]), "+f"(d[42]), "+f"(d[43]), "+f"(d[44]), "+f"(d[45]), "+f"(d[46]), "+f"(d[47]), "+f"(d[48]), "+f"(d[49]), "+f"(d[50]), "+f"(d[51]), "+f"(d[52]), "+f"(d[53]), "+f"(d[54]), "+f"(d[55]), "+f"(d[56]), "+f"(d[57]), "+f"(d[58]), "+f"(d[59]), "+f"(d[60]), "+f"(d[61]), "+f"(d[62]), "+f"(d[63]), "+f"(d[64]), "+f"(d[65]), "+f"(d[66]), "+f"(d[67]), "+f"(d[68]), "+f"(d[69]), "+f"(d[70]), "+f"(d[71]), "+f"(d[72]), "+f"(d[73]), "+f"(d[74]), "+f"(d[75]), "+f"(d[76]), "+f"(d[77]), "+f"(d[78]), "+f"(d[79]), "+f"(d[80]), "+f"(d[81]), "+f"(d[82]), "+f"(d[83]), "+f"(d[84]), "+f"(d[85]), "+f"(d[86]), "+f"(d[87]), "+f"(d[88]), "+f"(d[89]), "+f"(d[90]), "+f"(d[91]), "+f"(d[92]), "+f"(d[93]), "+f"(d[94]), "+f"(d[95]), "+f"(d[96]), "+f"(d[97]), "+f"(d[98]), "+f"(d[99]), "+f"(d[100]), "+f"(d[101]), "+f"(d[102]), "+f"(d[103]), "+f"(d[104]), "+f"(d[105]), "+f"(d[106]), "+f"(d[107]), "+f"(d[108]), "+f"(d[109]), "+f"(d[110]), "+f"(d[111]), "+f"(d[112]), "+f"(d[113]), "+f"(d[114]), "+f"(d[115]), "+f"(d[116]), "+f"(d[117]), "+f"(d[118]), "+f"(d[119]), "+f"(d[120]), "+f"(d[121]), "+f"(d[122]), "+f"(d[123]), "+f"(d[124]), "+f"(d[125]), "+f"(d[126]), "+f"(d[127])
      : "l"(adesc), "l"(bdesc), "r"(scale_d));
}
__device__ __forceinline__ void qk_wgmma_n64(float (&d)[32], const uint32_t (&a)[4], uint64_t desc) {
    asm volatile("wgmma.mma_async.sync.aligned.m64n64k16.f32.bf16.bf16 {%0,%1,%2,%3,%4,%5,%6,%7,%8,%9,%10,%11,%12,%13,%14,%15,%16,%17,%18,%19,%20,%21,%22,%23,%24,%25,%26,%27,%28,%29,%30,%31}, {%32,%33,%34,%35}, %36, 0, 1, 1, 0;"
      : "=f"(d[0]), "=f"(d[1]), "=f"(d[2]), "=f"(d[3]), "=f"(d[4]), "=f"(d[5]), "=f"(d[6]), "=f"(d[7]), "=f"(d[8]), "=f"(d[9]), "=f"(d[10]), "=f"(d[11]), "=f"(d[12]), "=f"(d[13]), "=f"(d[14]), "=f"(d[15]), "=f"(d[16]), "=f"(d[17]), "=f"(d[18]), "=f"(d[19]), "=f"(d[20]), "=f"(d[21]), "=f"(d[22]), "=f"(d[23]), "=f"(d[24]), "=f"(d[25]), "=f"(d[26]), "=f"(d[27]), "=f"(d[28]), "=f"(d[29]), "=f"(d[30]), "=f"(d[31])
      : "r"(a[0]), "r"(a[1]), "r"(a[2]), "r"(a[3]), "l"(desc));
}

__device__ __forceinline__ void pv_wgmma(float (&d)[12], uint32_t a0, uint32_t a1, uint32_t a2, uint32_t a3, uint64_t desc) {
    asm volatile("wgmma.mma_async.sync.aligned.m64n24k16.f32.bf16.bf16 {%0,%1,%2,%3,%4,%5,%6,%7,%8,%9,%10,%11}, {%12,%13,%14,%15}, %16, 1, 1, 1, 1;"
      : "+f"(d[0]), "+f"(d[1]), "+f"(d[2]), "+f"(d[3]), "+f"(d[4]), "+f"(d[5]), "+f"(d[6]), "+f"(d[7]), "+f"(d[8]), "+f"(d[9]), "+f"(d[10]), "+f"(d[11])
      : "r"(a0), "r"(a1), "r"(a2), "r"(a3), "l"(desc));
}

__device__ __forceinline__ uint32_t mapa(uint32_t a, uint32_t rank) { uint32_t r; asm("mapa.shared::cluster.u32 %0, %1, %2;" : "=r"(r) : "r"(a), "r"(rank)); return r; }
__device__ __forceinline__ void mbar_arrive_remote(uint32_t a) { asm volatile("mbarrier.arrive.relaxed.cluster.shared::cluster.b64 _, [%0];" :: "r"(a) : "memory"); }
__device__ __forceinline__ void mbar_wait_cluster(uint32_t a, int parity) {
    uint32_t done;
    int it = 0;
    do {
        asm volatile("{\n.reg .pred p;\nmbarrier.try_wait.parity.acquire.cluster.shared::cta.b64 p, [%1], %2;\nselp.u32 %0, 1, 0, p;\n}"
                     : "=r"(done) : "r"(a), "r"(parity) : "memory");
        if (++it > (1 << 24)) __trap();
    } while (!done);
}
__device__ __forceinline__ void tma2d_mc(uint32_t dst, const CUtensorMap* m, int c0, int c1, uint32_t bar) {
    asm volatile("cp.async.bulk.tensor.2d.shared::cluster.global.mbarrier::complete_tx::bytes.multicast::cluster [%0], [%1, {%3, %4}], [%2], %5;"
                 :: "r"(dst), "l"(m), "r"(bar), "r"(c0), "r"(c1), "h"((uint16_t)3) : "memory");
}
__device__ __forceinline__ void bulk_g2s_mc(uint32_t dst, const void* src, int bytes, uint32_t bar) {
    asm volatile("cp.async.bulk.shared::cluster.global.mbarrier::complete_tx::bytes.multicast::cluster [%0], [%1], %2, [%3], %4;"
                 :: "r"(dst), "l"(src), "r"(bytes), "r"(bar), "h"((uint16_t)3) : "memory");
}
__device__ __forceinline__ void tile_of(int bid, int& mb, int& nt) {
    int grp = bid >> 4, in = bid & 15;
    mb = (grp >> 1) * 4 + (in >> 2);
    nt = (grp & 1) * 4 + (in & 3);
}

constexpr int K1_STAGES = 5, K1_STAGE = 16384 + 24576;
constexpr int K1_BAR = K1_STAGES * K1_STAGE, K1_RS = K1_BAR + 128, K1_CS = K1_RS + 1024, K1_SMEM = K1_CS + 768;

__device__ __forceinline__ float2 row_stats_regs(uint4 a, uint4 b) {
    float v[16];
    v[0] = bf_lo(a.x); v[1] = bf_hi(a.x); v[2] = bf_lo(a.y); v[3] = bf_hi(a.y);
    v[4] = bf_lo(a.z); v[5] = bf_hi(a.z); v[6] = bf_lo(a.w); v[7] = bf_hi(a.w);
    v[8] = bf_lo(b.x); v[9] = bf_hi(b.x); v[10] = bf_lo(b.y); v[11] = bf_hi(b.y);
    v[12] = bf_lo(b.z); v[13] = bf_hi(b.z); v[14] = bf_lo(b.w); v[15] = bf_hi(b.w);
    float s = 0.f;
#pragma unroll
    for (int i = 0; i < 16; i++) s += v[i];
    float mean = warp_sum(s) * (1.0f / DM);
    float q = 0.f;
#pragma unroll
    for (int i = 0; i < 16; i++) { float d = v[i] - mean; q = fmaf(d, d, q); }
    float var = warp_sum(q) * (1.0f / DM);
    float rstd = rsqrtf(var + 1e-5f);
    return make_float2(rstd, -mean * rstd);
}
__device__ __forceinline__ float2 row_stats_x(const __nv_bfloat16* x, int row, int lane) {
    const uint4* p = (const uint4*)(x + (size_t)row * DM);
    return row_stats_regs(__ldg(p + lane), __ldg(p + 32 + lane));
}
__device__ __forceinline__ void colsum8(const __nv_bfloat16* w, int ld, int col, int k0, int nk, float (&s)[8]) {
#pragma unroll
    for (int i = 0; i < 8; i++) s[i] = 0.f;
    for (int k = k0; k < k0 + nk; k += 8) {
        uint4 u[8];
#pragma unroll
        for (int i = 0; i < 8; i++) u[i] = __ldg((const uint4*)(w + (size_t)(k + i) * ld + col));
#pragma unroll
        for (int i = 0; i < 8; i++) {
            s[0] += bf_lo(u[i].x); s[1] += bf_hi(u[i].x); s[2] += bf_lo(u[i].y); s[3] += bf_hi(u[i].y);
            s[4] += bf_lo(u[i].z); s[5] += bf_hi(u[i].z); s[6] += bf_lo(u[i].w); s[7] += bf_hi(u[i].w);
        }
    }
}
__device__ __forceinline__ bool wait_count(const unsigned int* p, unsigned int target, int lane) {
    int ok = 1;
    if (lane == 0) {
        int it = 0;
        while (ld_acquire(p) < target) { if (++it > (1 << 18)) { ok = 0; break; } }
    }
    ok = __shfl_sync(0xffffffffu, ok, 0);
    return ok != 0;
}

__global__ void __launch_bounds__(384, 1)
qkv_kernel(const __grid_constant__ CUtensorMap tm_x, const __grid_constant__ CUtensorMap tm_w,
           const __nv_bfloat16* __restrict__ x, const __nv_bfloat16* __restrict__ wqkv) {
    extern __shared__ __align__(1024) unsigned char smem[];
    const uint32_t sb = smem_u32(smem);
    const int tid = threadIdx.x, warp = __shfl_sync(0xffffffffu, tid >> 5, 0), lane = tid & 31;
    TLDECL
    TL(0);
    int mb, nt;
    tile_of(blockIdx.x, mb, nt);
    const uint32_t full = sb + K1_BAR, empty = full + 40, auxb = full + 80;
    if (tid == 0) {
#pragma unroll
        for (int i = 0; i < K1_STAGES; i++) { mbar_init(full + 8 * i, 1); mbar_init(empty + 8 * i, 8); }
        mbar_init(auxb, 3);
        fence_barrier_init();
        for (int kb = 0; kb < K1_STAGES; kb++) {
            mbar_expect(full + 8 * kb, K1_STAGE);
            tma2d(sb + kb * K1_STAGE, &tm_x, kb * 64, mb * 128, full + 8 * kb);
            tma3d(sb + kb * K1_STAGE + 16384, &tm_w, 0, kb * 64, nt * 3, full + 8 * kb);
        }
    }
    __syncthreads();
    pdl_launch();
    if (warp == 0) {
        if (blockIdx.x == 0) g_cnt2[lane] = 0;
        if (lane < 1) g_cnt2[32 + blockIdx.x] = 0;
        if (lane == 0) {
            for (int kb = K1_STAGES; kb < 8; kb++) {
                int s = kb % K1_STAGES;
                mbar_wait(empty + 8 * s, 0);
                mbar_expect(full + 8 * s, K1_STAGE);
                tma2d(sb + s * K1_STAGE, &tm_x, kb * 64, mb * 128, full + 8 * s);
                tma3d(sb + s * K1_STAGE + 16384, &tm_w, 0, kb * 64, nt * 3, full + 8 * s);
            }
        }
    } else if (warp < 4) {
        float2* s_rs = (float2*)(smem + K1_RS);
        float* s_cs = (float*)(smem + K1_CS);
        if (warp < 3) {
            const int r0 = mb * 128 + nt * 16 + (warp - 1) * 8;
            uint4 u[16];
#pragma unroll
            for (int i = 0; i < 8; i++) {
                const uint4* p = (const uint4*)(x + (size_t)(r0 + i) * DM);
                u[2 * i] = __ldg(p + lane); u[2 * i + 1] = __ldg(p + 32 + lane);
            }
            float2 mine = make_float2(0.f, 0.f);
#pragma unroll
            for (int i = 0; i < 8; i++) {
                float2 st = row_stats_regs(u[2 * i], u[2 * i + 1]);
                if (lane == i) mine = st;
            }
            if (lane < 8) g_rowstat1[r0 + lane] = mine;
            __syncwarp();
            if (lane == 0) red_release(&g_cnt[mb]);
        } else {
            uint4 u[24];
#pragma unroll
            for (int c = 0; c < 3; c++)
#pragma unroll
                for (int i = 0; i < 8; i++)
                    u[c * 8 + i] = __ldg((const uint4*)(wqkv + (size_t)(mb * 32 + (lane >> 3) * 8 + i) * 1536 + nt * 192 + (c * 8 + (lane & 7)) * 8));
#pragma unroll
            for (int c = 0; c < 3; c++) {
                float cs[8];
#pragma unroll
                for (int i = 0; i < 8; i++) cs[i] = 0.f;
#pragma unroll
                for (int i = 0; i < 8; i++) {
                    const uint4 w = u[c * 8 + i];
                    cs[0] += bf_lo(w.x); cs[1] += bf_hi(w.x); cs[2] += bf_lo(w.y); cs[3] += bf_hi(w.y);
                    cs[4] += bf_lo(w.z); cs[5] += bf_hi(w.z); cs[6] += bf_lo(w.w); cs[7] += bf_hi(w.w);
                }
#pragma unroll
                for (int i = 0; i < 8; i++) {
                    cs[i] += __shfl_xor_sync(0xffffffffu, cs[i], 8);
                    cs[i] += __shfl_xor_sync(0xffffffffu, cs[i], 16);
                }
                if (lane < 8) {
                    float4* d = (float4*)(g_cs1_part + mb * 1536 + nt * 192 + (c * 8 + lane) * 8);
                    d[0] = make_float4(cs[0], cs[1], cs[2], cs[3]);
                    d[1] = make_float4(cs[4], cs[5], cs[6], cs[7]);
                }
            }
            __syncwarp();
            if (lane == 0) red_release(&g_cnt[16 + nt]);
        }
        TX(8 + warp);
        if (warp == 1) {
            if (wait_count(&g_cnt[mb], 16, lane)) {
#pragma unroll
                for (int i = 0; i < 4; i++) s_rs[lane + 32 * i] = __ldcg(&g_rowstat1[mb * 128 + lane + 32 * i]);
            } else {
                for (int i = 0; i < 128; i++) {
                    float2 st = row_stats_x(x, mb * 128 + i, lane);
                    if (lane == 0) s_rs[i] = st;
                }
            }
        } else {
            int c0 = (warp - 2) * 96;
            if (wait_count(&g_cnt[16 + nt], 16, lane)) {
#pragma unroll
                for (int i = 0; i < 3; i++) {
                    float s = 0.f;
#pragma unroll
                    for (int p = 0; p < 16; p++) s += __ldcg(&g_cs1_part[p * 1536 + nt * 192 + c0 + lane + 32 * i]);
                    s_cs[c0 + lane + 32 * i] = s;
                }
            } else if (lane < 12) {
                float s[8];
                colsum8(wqkv, 1536, nt * 192 + c0 + lane * 8, 0, 512, s);
#pragma unroll
                for (int i = 0; i < 8; i++) s_cs[c0 + lane * 8 + i] = s[i];
            }
        }
        __syncwarp();
        TX(12 + warp);
        if (lane == 0) mbar_arrive(auxb);
        bar_sync(2, 256 + 96);
        const int a = tid - 32;
        {
            const int hh = a >> 3, w = a & 7;
            const float4* p = (const float4*)(smem + 49152) + (hh * 256 + w * 32) / 2;
            float m = 0.f;
#pragma unroll
            for (int i = 0; i < 8; i++) {
                const int ii = (i + a) & 7;
                float4 u = p[2 * ii], v = p[2 * ii + 1];
                float n0 = u.x + u.z + v.x + v.z, n1 = u.y + u.w + v.y + v.w;
                if (!(n0 <= 3.0e38f) || !(n1 <= 3.0e38f)) m = __int_as_float(0x7f800000);
                m = fmaxf(m, fmaxf(n0, n1));
            }
            const int col0 = nt * 192 + hh * 16;
            g_nrm[((col0 >> 9) * NH + ((col0 & 511) >> 4)) * 128 + mb * 8 + w] = m;
        }
        if (a < 24) bulk_wait_all();
        TL(27);
        TLDUMP;
    } else {
        const int wgi = (warp >> 2) - 1, ww = warp & 3;
        float acc[96];
#pragma unroll 1
        for (int kb = 0; kb < 8; kb++) {
            int s = kb % K1_STAGES;
            mbar_wait(full + 8 * s, (kb / K1_STAGES) & 1);
            if (warp == 4) TX(kb);
            uint64_t ad = make_desc(sb + s * K1_STAGE + wgi * 8192, 16, 1024, 1);
            uint64_t bd = make_desc(sb + s * K1_STAGE + 16384, 8192, 1024, 1);
            WG_FENCE();
#pragma unroll
            for (int k = 0; k < 4; k++) wgmma_ss_n192(acc, ad + k * 2, bd + k * 128, (kb | k) != 0);
            WG_COMMIT();
            if (kb > 0) {
                wg_wait<1>();
                if (lane == 0) mbar_arrive(empty + 8 * ((kb - 1) % K1_STAGES));
            }
        }
        wg_wait<0>();
        fence_regs(acc);
        TL(1);
        if (warp == 4) TX(16);
        mbar_wait(auxb, 0);
        if (warp == 4) TX(17);
        bar_sync(1, 256);
        const float2* s_rs = (const float2*)(smem + K1_RS);
        const float* s_cs = (const float*)(smem + K1_CS);
        const int g = lane >> 2, t = lane & 3;
        const int rl = wgi * 64 + ww * 16 + g;
        const float2 st0 = s_rs[rl], st1 = s_rs[rl + 8];
        const float QS = 0.25f * 1.4426950408889634f;
        const uint32_t stg = sb + ((lane >> 4) * 16 + wgi * 8 + ww * 2 + ((lane >> 3) & 1)) * 128 + (lane & 7) * 16;
        float2* s_np = (float2*)(smem + 49152) + (warp - 4) * 32 + lane;
#pragma unroll
        for (int hh = 0; hh < 12; hh++) {
            const int which = (nt * 192 + hh * 16) >> 9;
            const float sc = (which == 0) ? QS : 1.0f;
            const float a0 = st0.x * sc, b0 = st0.y * sc, a1 = st1.x * sc, b1 = st1.y * sc;
            const float2 c0 = *(const float2*)(s_cs + 16 * hh + 2 * t), c1 = *(const float2*)(s_cs + 16 * hh + 8 + 2 * t);
            const float* a = acc + 8 * hh;
            float v0 = fmaf(a0, a[0], b0 * c0.x), v1 = fmaf(a0, a[1], b0 * c0.y), v2 = fmaf(a1, a[2], b1 * c0.x), v3 = fmaf(a1, a[3], b1 * c0.y);
            float v4 = fmaf(a0, a[4], b0 * c1.x), v5 = fmaf(a0, a[5], b0 * c1.y), v6 = fmaf(a1, a[6], b1 * c1.x), v7 = fmaf(a1, a[7], b1 * c1.y);
            {
                const int head = ((nt * 192 + hh * 16) & 511) >> 4;
                uint32_t* o = (uint32_t*)g_qkv + ((size_t)((which * NH + head) * 2) * 256 + mb * 16 + wgi * 8 + ww * 2) * 32 + lane;
                o[0] = pack_bf16(v0, v1); o[32] = pack_bf16(v2, v3); o[8192] = pack_bf16(v4, v5); o[8192 + 32] = pack_bf16(v6, v7);
            }
            s_np[hh * 256] = make_float2(fmaf(v0, v0, fmaf(v1, v1, fmaf(v4, v4, v5 * v5))), fmaf(v2, v2, fmaf(v3, v3, fmaf(v6, v6, v7 * v7))));
        }
        fence_proxy_async();
        bar_arrive(2, 256 + 96);
        TL(2);
        TLDUMP;
    }
}

constexpr int AT_K = 0, AT_V = 65536, AT_ONES = 131072, AT_BAR = 163840, AT_SMEM = AT_BAR + 128;
#define POLY_MASK 0x7B5A

__device__ __forceinline__ uint32_t exp2_pair_poly(float x0, float x1) {
    uint32_t t0 = __float_as_uint(x0 + 32895.0f);
    uint32_t t1 = __float_as_uint(x1 + 32895.0f);
    uint32_t gd = __byte_perm(t0, t1, 0x6420);
    uint32_t wm = __byte_perm(t0, t1, 0x5612);
    uint32_t v = hfma2(gd, 0x71477147u, 0x354f354fu);
    uint32_t z = hmul2(v, gd);
    return (wm >> 1) + z;
}
__device__ __forceinline__ uint32_t exp2_pair_mufu(float x0, float x1) { return pack_bf16(ex2f(x0), ex2f(x1)); }
template <uint32_t MASK>
__device__ __forceinline__ void exp_blocks(const float (&s)[32], uint32_t (&p)[16]) {
#pragma unroll
    for (int b = 0; b < 8; b++) {
        if ((MASK >> b) & 1) {
            p[2 * b] = exp2_pair_poly(s[4 * b], s[4 * b + 1]);
            p[2 * b + 1] = exp2_pair_poly(s[4 * b + 2], s[4 * b + 3]);
        } else {
            p[2 * b] = exp2_pair_mufu(s[4 * b], s[4 * b + 1]);
            p[2 * b + 1] = exp2_pair_mufu(s[4 * b + 2], s[4 * b + 3]);
        }
    }
}
#define PV4(P) _Pragma("unroll") for (int i = 0; i < 4; i++) { pv_wgmma(o, P[4 * i], P[4 * i + 1], P[4 * i + 2], P[4 * i + 3], vd); vd += 16; }

__device__ __forceinline__ void attn_store(float (&o)[12], int row0, int head, int lane) {
    float l0 = __shfl_sync(0xffffffffu, o[8], lane & 28);
    float l1 = __shfl_sync(0xffffffffu, o[10], lane & 28);
    float r0 = 1.0f / l0, r1 = 1.0f / l1;
    uint32_t* op = (uint32_t*)g_ao;
    int mb = row0 >> 7, rg = (row0 & 127) >> 3;
    int kb = head >> 2, kc = (head & 3) * 2;
    size_t base = (((size_t)(mb * 8 + kb) * 8 + kc) * 16 + rg) * 32 + lane;
    op[base] = pack_bf16(o[0] * r0, o[1] * r0);
    op[base + 32] = pack_bf16(o[2] * r1, o[3] * r1);
    op[base + 16 * 32] = pack_bf16(o[4] * r0, o[5] * r0);
    op[base + 16 * 32 + 32] = pack_bf16(o[6] * r1, o[7] * r1);
}

__device__ __forceinline__ void attn_load_q(uint32_t (&q)[4], const __nv_bfloat16* gq, int row0, int lane) {
    const uint32_t* qp = (const uint32_t*)gq;
    int j0 = row0 >> 3;
    q[0] = __ldcg(qp + (0 * 256 + j0) * 32 + lane);
    q[1] = __ldcg(qp + (0 * 256 + j0 + 1) * 32 + lane);
    q[2] = __ldcg(qp + (1 * 256 + j0) * 32 + lane);
    q[3] = __ldcg(qp + (1 * 256 + j0 + 1) * 32 + lane);
}

__device__ __forceinline__ void attn_tile_safe(const uint32_t (&q)[4], uint64_t kd, uint64_t vd, int row0, int head, int lane) {
    float o[12];
#pragma unroll
    for (int i = 0; i < 12; i++) o[i] = 0.f;
    float m0 = -INFINITY, m1 = -INFINITY;
    fence_regs(o);
#pragma unroll 1
    for (int j = 0; j < 32; j++) {
        float s[32];
        uint32_t p[16];
        WG_FENCE();
        qk_wgmma_n64(s, q, kd); kd += 64;
        WG_COMMIT();
        wg_wait<0>();
        fence_regs(s);
        fence_regs(o);
        float x0 = m0, x1 = m1;
#pragma unroll
        for (int b = 0; b < 8; b++) {
            x0 = fmaxf(x0, fmaxf(s[4 * b], s[4 * b + 1]));
            x1 = fmaxf(x1, fmaxf(s[4 * b + 2], s[4 * b + 3]));
        }
        x0 = fmaxf(x0, __shfl_xor_sync(0xffffffffu, x0, 1)); x0 = fmaxf(x0, __shfl_xor_sync(0xffffffffu, x0, 2));
        x1 = fmaxf(x1, __shfl_xor_sync(0xffffffffu, x1, 1)); x1 = fmaxf(x1, __shfl_xor_sync(0xffffffffu, x1, 2));
        float al0 = ex2f(m0 - x0), al1 = ex2f(m1 - x1);
        m0 = x0; m1 = x1;
#pragma unroll
        for (int i = 0; i < 3; i++) { o[4 * i] *= al0; o[4 * i + 1] *= al0; o[4 * i + 2] *= al1; o[4 * i + 3] *= al1; }
#pragma unroll
        for (int b = 0; b < 8; b++) {
            p[2 * b] = exp2_pair_mufu(s[4 * b] - m0, s[4 * b + 1] - m0);
            p[2 * b + 1] = exp2_pair_mufu(s[4 * b + 2] - m1, s[4 * b + 3] - m1);
        }
        fence_regs(o);
        WG_FENCE();
        PV4(p);
        WG_COMMIT();
        wg_wait<0>();
        fence_regs(o);
    }
    attn_store(o, row0, head, lane);
}

__global__ void __launch_bounds__(512, 1)
attn_kernel(const __nv_bfloat16* __restrict__ wg_, const __nv_bfloat16* __restrict__ wu_,
            const __nv_bfloat16* __restrict__ wo_, const __nv_bfloat16* __restrict__ wd_) {
    extern __shared__ __align__(1024) unsigned char smem[];
    const uint32_t sb = smem_u32(smem);
    const int tid = threadIdx.x, wg = tid >> 7, warp = (tid >> 5) & 3, lane = tid & 31;
    TLDECL
    pdl_launch();
    if (blockIdx.x >= 128) {
        const int e = blockIdx.x - 128;
        const __nv_bfloat16* w = (e < 2) ? wg_ : wu_;
        float* red = (float*)smem;
        const int cgrp = tid & 127, kq = tid >> 7;
        if (cgrp < 112) {
            float s[8];
            colsum8(w, FF, (e & 1) * 896 + cgrp * 8, kq * 128, 128, s);
#pragma unroll
            for (int i = 0; i < 8; i++) red[kq * 896 + cgrp * 8 + i] = s[i];
        }
        __syncthreads();
        for (int c = tid; c < 896; c += 512)
            g_cs2[(e >> 1) * FF + (e & 1) * 896 + c] = red[c] + red[896 + c] + red[1792 + c] + red[2688 + c];
        if (tid < 32) {
            const char* p0 = (const char*)wo_ + e * (DM * DM * 2 / 4);
            for (int i = lane; i < 32; i += 32)
                asm volatile("cp.async.bulk.prefetch.L2.global [%0], %1;" :: "l"(p0 + i * 4096), "r"(4096) : "memory");
            const char* p1 = (const char*)wd_ + e * (FF * DM * 2 / 4);
            for (int i = lane; i < 112; i += 32)
                asm volatile("cp.async.bulk.prefetch.L2.global [%0], %1;" :: "l"(p1 + i * 4096), "r"(4096) : "memory");
        }
        return;
    }
    const int head = blockIdx.x >> 2, qq = blockIdx.x & 3;
    const __nv_bfloat16* gq = g_qkv + (size_t)head * (S_LEN * 16);
    const __nv_bfloat16* gk = g_qkv + (size_t)(NH + head) * (S_LEN * 16);
    const __nv_bfloat16* gv = g_qkv + (size_t)(2 * NH + head) * (S_LEN * 16);
    if (tid == 0) {
        for (int i = 0; i < 8; i++) mbar_init(sb + AT_BAR + 8 * i, 1);
        fence_barrier_init();
    }
    {
        uint4 one = make_uint4(0x00003F80u, 0, 0, 0);
#pragma unroll
        for (int i = 0; i < 4; i++) *(uint4*)(smem + AT_ONES + (i * 512 + tid) * 16) = one;
        fence_proxy_async();
    }
    __syncthreads();
    TL(3);
    pdl_wait();
    TL(4);
    auto load_kv = [&](int i) {
        uint32_t bar = sb + AT_BAR + 8 * i;
        mbar_expect(bar, 16384);
        bulk_g2s(sb + AT_K + i * 4096, gk + i * 2048, 4096, bar);
        bulk_g2s(sb + AT_K + 32768 + i * 4096, gk + 16384 + i * 2048, 4096, bar);
        bulk_g2s(sb + AT_V + i * 4096, gv + i * 2048, 4096, bar);
        bulk_g2s(sb + AT_V + 32768 + i * 4096, gv + 16384 + i * 2048, 4096, bar);
    };
    if (tid == 0) { load_kv(0); load_kv(1); }
    uint32_t q[4], q2[4];
    attn_load_q(q, gq, qq * 512 + wg * 64 + warp * 16, lane);
    attn_load_q(q2, gq, qq * 512 + (4 + wg) * 64 + warp * 16, lane);
    bool fast;
    {
        const float* nq = g_nrm + (0 * NH + head) * 128 + qq * 32;
        const float* nk = g_nrm + (1 * NH + head) * 128;
        const float* nv = g_nrm + (2 * NH + head) * 128;
        float4 k4 = __ldcg((const float4*)nk + lane), v4 = __ldcg((const float4*)nv + lane);
        float qm = warp_max(__ldcg(nq + lane));
        float km = warp_max(fmaxf(fmaxf(k4.x, k4.y), fmaxf(k4.z, k4.w)));
        float vm = warp_max(fmaxf(fmaxf(v4.x, v4.y), fmaxf(v4.z, v4.w)));
        fast = __all_sync(0xffffffffu, (qm * km <= 3500.0f) && (vm <= 1.0e24f));
    }
    TL(24);
    const uint64_t kdesc0 = make_desc(sb + AT_K, 32768, 128, 0);
    const uint64_t vdesc0 = make_desc(sb + AT_V, 128, 32768, 0);
    if (!fast) {
        if (tid == 0) for (int i = 2; i < 8; i++) load_kv(i);
        for (int i = 0; i < 8; i++) mbar_wait(sb + AT_BAR + 8 * i, 0);
#pragma unroll 1
        for (int tile = 0; tile < 2; tile++) {
            const int row0 = qq * 512 + (tile * 4 + wg) * 64 + warp * 16;
            attn_tile_safe(q, kdesc0, vdesc0, row0, head, lane);
#pragma unroll
            for (int i = 0; i < 4; i++) q[i] = q2[i];
        }
        return;
    }
#pragma unroll 1
    for (int tile = 0; tile < 2; tile++) {
        const int row0 = qq * 512 + (tile * 4 + wg) * 64 + warp * 16;
        float o[12];
#pragma unroll
        for (int i = 0; i < 12; i++) o[i] = 0.f;
        fence_regs(o);
        float sa[32];
        uint32_t pa[16];
        uint64_t kd = kdesc0, vd = vdesc0;
        if (tile == 0) { mbar_wait(sb + AT_BAR, 0); TL(25); }
        WG_FENCE();
        qk_wgmma_n64(sa, q, kd); kd += 64;
        WG_COMMIT();
#pragma unroll 1
        for (int jj = 0; jj < 8; jj++) {
            if (tile == 0 && jj < 7) {
                if (tid == 0 && jj < 6) load_kv(jj + 2);
                mbar_wait(sb + AT_BAR + 8 * (jj + 1), 0);
            }
            if (wg == 0 && warp == 0) TX(128 + tile * 8 + jj);
#pragma unroll
            for (int j = 0; j < 4; j++) {
                wg_wait<0>();
                fence_regs(sa);
                if (j & 1) exp_blocks<(POLY_MASK >> 8)>(sa, pa); else exp_blocks<(POLY_MASK & 255)>(sa, pa);
                WG_FENCE();
                PV4(pa);
                qk_wgmma_n64(sa, q, kd); kd += 64;
                WG_COMMIT();
            }
        }
        wg_wait<0>();
        fence_regs(o);
        fence_regs(sa);
        if (tile == 0) TL(26);
        attn_store(o, row0, head, lane);
#pragma unroll
        for (int i = 0; i < 4; i++) q[i] = q2[i];
    }
    TL(5);
    TLDUMP;
}

#define POLL_NS 40
#define FLAG_STRIDE 1
#define DELAYC 9
constexpr int F_R2 = 131072, F_X = 196608, F_BAR = 229376;
constexpr int F_RS = F_BAR + 256, F_CS = F_RS + 1024, F_SMEM = F_CS + 1792;
enum { B_FA = 0, B_HF = 4, B_BF = 8, B_BE = 11, B_CF = 14, B_CE = 20, B_ADONE = 26, B_BDONE = 27, B_XC = 28, B_PRDY = 29, B_AUX = 30, B_NUM = 31 };

__device__ __forceinline__ void st_async4(uint32_t dst, float a, float b, float c, float d, uint32_t bar) {
    asm volatile("st.async.weak.shared::cluster.mbarrier::complete_tx::bytes.v4.f32 [%0], {%1,%2,%3,%4}, [%5];"
                 :: "r"(dst), "f"(a), "f"(b), "f"(c), "f"(d), "r"(bar) : "memory");
}
__device__ __forceinline__ void poll_count(const unsigned int* p, unsigned int target) {
    int it = 0;
    while (ld_acquire(p) < target) { if (++it > (1 << 22)) __trap(); }
    asm volatile("fence.proxy.async.global;" ::: "memory");
}
__device__ __forceinline__ void tma2d_store(const CUtensorMap* m, uint32_t src, int c0, int c1) {
    asm volatile("cp.async.bulk.tensor.2d.global.shared::cta.bulk_group [%0, {%2, %3}], [%1];" :: "l"(m), "r"(src), "r"(c0), "r"(c1) : "memory");
}
__device__ __forceinline__ float2 h_row_stats(int row) {
    const float4* hp = (const float4*)(g_hstat + (size_t)row * 8);
    float4 a = __ldcg(hp), b = __ldcg(hp + 1), c = __ldcg(hp + 2), d = __ldcg(hp + 3);
    float mean = 0.125f * (a.x + a.z + b.x + b.z + c.x + c.z + d.x + d.z);
    float m2 = a.y + a.w + b.y + b.w + c.y + c.w + d.y + d.w;
    float e;
    e = a.x - mean; m2 = fmaf(64.f * e, e, m2); e = a.z - mean; m2 = fmaf(64.f * e, e, m2);
    e = b.x - mean; m2 = fmaf(64.f * e, e, m2); e = b.z - mean; m2 = fmaf(64.f * e, e, m2);
    e = c.x - mean; m2 = fmaf(64.f * e, e, m2); e = c.z - mean; m2 = fmaf(64.f * e, e, m2);
    e = d.x - mean; m2 = fmaf(64.f * e, e, m2); e = d.z - mean; m2 = fmaf(64.f * e, e, m2);
    return make_float2(rsqrtf(m2 * (1.0f / DM) + 1e-5f), -mean);
}
__device__ __forceinline__ int c_kblock(int i, int r) {
    if (i < 6) { const int e = 2 * i + r, m = e / 3, k = e - 3 * m; return 7 * m + (k == 2 ? 4 : k); }
    const int l = 2 * (i - 6) + r, m = l >> 2, k = l & 3;
    return 7 * m + (k < 2 ? 2 + k : 3 + k);
}
__device__ __forceinline__ uint32_t c_stage_a(int s, int ntB) { return s < 4 ? ((ntB + 2 * s) & 7) * 16384 : F_R2 + (s - 4) * 32768; }
__device__ __forceinline__ uint32_t c_stage_b(int s, int ntB) { return s < 4 ? ((ntB + 2 * s + 1) & 7) * 16384 : F_R2 + (s - 4) * 32768 + 16384; }
template <int R>
__device__ __forceinline__ void xchg(float (&acc)[64], float (&o)[32], uint32_t sb, unsigned char* smem, int bar, int ctid) {
    const uint32_t dst = mapa(sb + F_X + ctid * 16, 1 - R), rb = mapa(sb + F_BAR + 8 * bar, 1 - R);
#pragma unroll
    for (int q = 0; q < 8; q++) {
        const int j = (1 - R) * 32 + 4 * q;
        st_async4(dst + q * 4096, acc[j], acc[j + 1], acc[j + 2], acc[j + 3], rb);
    }
    mbar_wait_cluster(sb + F_BAR + 8 * bar, 0);
#pragma unroll
    for (int q = 0; q < 8; q++) {
        float4 v = *(const float4*)(smem + F_X + q * 4096 + ctid * 16);
        const int j = R * 32 + 4 * q;
        o[4 * q] = acc[j] + v.x; o[4 * q + 1] = acc[j + 1] + v.y; o[4 * q + 2] = acc[j + 2] + v.z; o[4 * q + 3] = acc[j + 3] + v.w;
    }
}

template <int NB, bool STAGE>
__device__ __forceinline__ void ffn_epilogue(const float* ag, const float* au, const float* s_cs, int cs_off, uint32_t* gp, uint32_t stg,
                                             float2 st0, float2 st1, int lane) {
    const int t = lane & 3;
    const float C1 = 0.7978845608028654f, C2 = 0.044715f * 0.7978845608028654f;
    const float k10 = st0.x * C1, k20 = st0.x * st0.x * st0.x * C2, k11 = st1.x * C1, k21 = st1.x * st1.x * st1.x * C2;
#pragma unroll
    for (int j2 = 0; j2 < NB / 2; j2++) {
        uint32_t pk[4];
#pragma unroll
        for (int jj = 0; jj < 2; jj++) {
            const int j = 2 * j2 + jj;
            const float2 cg = *(const float2*)(s_cs + cs_off + 8 * j + 2 * t);
            const float2 cu = *(const float2*)(s_cs + 224 + cs_off + 8 * j + 2 * t);
            float r[4];
#pragma unroll
            for (int e = 0; e < 4; e++) {
                const float nm = (e < 2) ? st0.y : st1.y, k1 = (e < 2) ? k10 : k11, k2 = (e < 2) ? k20 : k21;
                const float tg = fmaf(nm, (e & 1) ? cg.y : cg.x, ag[4 * j + e]);
                const float tu = fmaf(nm, (e & 1) ? cu.y : cu.x, au[4 * j + e]);
                const float th = tanh_fast(tg * fmaf(tg * tg, k2, k1));
                const float p = tg * tu;
                r[e] = fmaf(p, th, p);
            }
            pk[2 * jj] = pack_bf16(r[0], r[1]);
            pk[2 * jj + 1] = pack_bf16(r[2], r[3]);
        }
        if (STAGE) {
            stsm4(stg + j2 * 4096, pk[0], pk[1], pk[2], pk[3]);
        } else {
            gp[j2 * 1024] = pk[0]; gp[j2 * 1024 + 32] = pk[1]; gp[j2 * 1024 + 512] = pk[2]; gp[j2 * 1024 + 544] = pk[3];
        }
    }
}

__global__ void __cluster_dims__(2, 1, 1) __launch_bounds__(384, 1)
tail_kernel(const __grid_constant__ CUtensorMap tm_o, const __grid_constant__ CUtensorMap tm_g,
            const __grid_constant__ CUtensorMap tm_u, const __grid_constant__ CUtensorMap tm_d,
            const __grid_constant__ CUtensorMap tm_out, const __nv_bfloat16* __restrict__ x) {
    extern __shared__ __align__(1024) unsigned char smem[];
    const uint32_t sb = smem_u32(smem);
    const uint32_t bars = sb + F_BAR;
    const int tid = threadIdx.x, warp = __shfl_sync(0xffffffffu, tid >> 5, 0), lane = tid & 31;
    TLDECL
    TL(6);
    if (warp == 4) TX(200);
    const int cl = blockIdx.x >> 1, r = blockIdx.x & 1;
    const int mb = ((cl & 7) >> 1) * 4 + (cl >> 4), ntA = (cl & 1) * 2 + ((cl >> 3) & 1);
    const int nt = ntA * 2 + r;
    const int mbB = (mb & ~1) + r, ntB = (mb & 1) * 4 + ntA;
    if (tid == 0) {
#pragma unroll
        for (int i = 0; i < B_NUM; i++) {
            const int cnt = (i >= B_BE && i < B_BE + 3) ? 16 : (i == B_BDONE) ? DELAYC : ((i >= B_CE && i < B_CE + 6) || i == B_PRDY) ? 8 : (i == B_AUX || i == B_ADONE) ? 2 : 1;
            mbar_init(bars + 8 * i, cnt);
        }
        mbar_expect(bars + 8 * B_XC, 32768);
        fence_barrier_init();
        for (int i = 0; i < 8; i++) {
            const uint32_t bar = bars + 8 * (B_FA + (i >> 1));
            if (!(i & 1)) mbar_expect(bar, 49152);
            tma2d(sb + F_R2 + 32768 + i * 8192, &tm_o, nt * 64, i * 64, bar);
        }
    }
    TL(28);
    __syncthreads();
    TL(29);
    asm volatile("barrier.cluster.arrive.relaxed.aligned;" ::: "memory");
    TL(30);
    if (warp < 4) {
        asm volatile("setmaxnreg.dec.sync.aligned.u32 56;");
        if (warp == 0) TX(205);
        if (warp == 0) {
            if (lane == 0) {
                auto load_b = [&](int it) {
                    const int s = it % 3, pass = it >> 3, kb = (ntB + it) & 7;
                    const int ng = pass ? 3 : 4, c0 = ntB * 224 + pass * 128;
                    const uint32_t bar = bars + 8 * (B_BF + s), dst = sb + F_R2 + s * 32768 + r * ng * 4096;
                    mbar_expect(bar, ng * 8192);
                    for (int i = 0; i < ng; i++) tma2d_mc(dst + i * 4096, r ? &tm_u : &tm_g, c0 + i * 32, kb * 64, bar);
                };
                asm volatile("barrier.cluster.wait.acquire;" ::: "memory");
                pdl_wait();
                TL(16);
                for (int i = 0; i < 4; i++)
                    bulk_g2s_mc(sb + (2 * i + r) * 16384, g_ao + (size_t)(mb * 8 + 2 * i + r) * 8192, 16384, bars + 8 * (B_FA + i));
                load_b(0);
                if (blockIdx.x == 0)
                    for (int i = 0; i < 32; i++) g_cnt[i] = 0;
                mbar_wait_cluster(bars + 8 * B_ADONE, 0);
                load_b(1); load_b(2);
                auto load_c = [&](int i) {
                    const int s = i % 6, kb = c_kblock(i, r);
                    const uint32_t bar = bars + 8 * (B_CF + s), da = sb + c_stage_a(s, ntB), db = sb + c_stage_b(s, ntB);
                    mbar_expect(bar, 32768);
                    tma2d(db, &tm_d, ntA * 128, kb * 64, bar);
                    tma2d(db + 8192, &tm_d, ntA * 128 + 64, kb * 64, bar);
                    bulk_g2s(da, g_g + (size_t)(mb * 28 + kb) * 8192, 16384, bar);
                };
                for (int it = 3; it < 16; it++) {
                    mbar_wait_cluster(bars + 8 * (B_BE + it % 3), (it / 3 - 1) & 1);
                    load_b(it);
                    if (it == 12) { poll_count(&g_cnt2[mb], 8); load_c(0); }
                    if (it == 14) load_c(1);
                }
                mbar_wait_cluster(bars + 8 * (B_BE + 1), 0);
                load_c(2);
                mbar_wait(bars + 8 * B_BDONE, 0);
                for (int i = 3; i < 14; i++) {
                    if (i >= 6) mbar_wait(bars + 8 * (B_CE + i % 6), ((i / 6) - 1) & 1);
                    if (i == 6) { poll_count(&g_cnt2[16 + mb], 8); TL(18); }
                    load_c(i);
                }
            }
            else asm volatile("barrier.cluster.wait.acquire;" ::: "memory");
            TLDUMP;
        } else if (warp == 1) {
            asm volatile("barrier.cluster.wait.acquire.aligned;" ::: "memory");
            bar_sync(5, 288);
            if (lane == 0) { red_release(&g_cnt2[32 + (mb * 8 + nt) * FLAG_STRIDE]); TL(9); }
            __syncwarp();
            bar_sync(6, 288);
            if (lane == 0) red_release(&g_cnt2[32 + (mb * 8 + nt) * FLAG_STRIDE]);
            __syncwarp();
            bar_sync(1, 288);
            if (lane == 0) red_release(&g_cnt2[mbB]);
            __syncwarp();
            bar_sync(2, 288);
            if (lane == 0) {
                red_release(&g_cnt2[16 + mbB]);
                if (DELAYC == 9) mbar_arrive(bars + 8 * B_BDONE);
                TL(13);
            }
            __syncwarp();
            bar_sync(3, 288);
            if (lane == 0) {
                tma2d_store(&tm_out, sb, nt * 64, mb * 128);
                bulk_commit();
                bulk_wait_all();
                TL(15);
            }
            TLDUMP;
        } else {
            asm volatile("barrier.cluster.wait.acquire.aligned;" ::: "memory");
            pdl_wait();
            float2* s_rs = (float2*)(smem + F_RS);
            float* s_cs = (float*)(smem + F_CS);
            for (int c = tid - 64; c < 448; c += 64)
                s_cs[c] = __ldcg(&g_cs2[(c >= 224 ? FF - 224 : 0) + ntB * 224 + c]);
            if (tid == 96) {
                mbar_wait_cluster(bars + 8 * B_ADONE, 0);
                for (int i = 0; i < 8; i++) {
                    const int kb = (ntB + i) & 7;
                    const uint32_t bar = bars + 8 * (i < 4 ? B_HF + i : B_FA + i - 4);
                    poll_count(&g_cnt2[32 + (mbB * 8 + kb) * FLAG_STRIDE], 1);
                    mbar_expect(bar, 16384);
                    bulk_g2s(sb + kb * 16384, g_h + (size_t)(mbB * 8 + kb) * 8192, 16384, bar);
                }
            }
            __syncwarp();
            TL(17);
            for (int i = 0; i < 8; i++) mbar_wait(bars + 8 * (i < 4 ? B_HF + i : B_FA + i - 4), i < 4 ? 0 : 1);
            if (lane < 8) poll_count(&g_cnt2[32 + (mbB * 8 + lane) * FLAG_STRIDE], 2);
            __syncwarp();
            __syncwarp();
            for (int rr = tid - 64; rr < 128; rr += 64) {
                s_rs[rr] = h_row_stats(mbB * 128 + rr);
            }
            __syncwarp();
            if (lane == 0) mbar_arrive(bars + 8 * B_AUX);
            TLDUMP;
        }
    } else {
        asm volatile("setmaxnreg.inc.sync.aligned.u32 216;");
        if (warp == 4) TX(206);
        const int wgi = (warp >> 2) - 1, ww = warp & 3, ctid = tid - 128;
        const int g = lane >> 2, t = lane & 3;
        const int rl = wgi * 64 + ww * 16 + g, row = mb * 128 + rl;
        const int rgl = wgi * 8 + ww * 2;
        const float2* s_rs = (const float2*)(smem + F_RS);
        const float* s_cs = (const float*)(smem + F_CS);
        const uint32_t stl = ((lane >> 4) * 16 + rgl + ((lane >> 3) & 1)) * 128 + (lane & 7) * 16;
        uint32_t* hp = (uint32_t*)g_h + ((size_t)(mb * 8 + nt) * 8 * 16 + rgl) * 32 + lane;
        const uint32_t rbars = mapa(bars, 1 - r);
        TL(23);
        {
            uint32_t xr[16];
            const uint32_t* xp = (const uint32_t*)(x + (size_t)row * DM + nt * 64) + t;
#pragma unroll
            for (int j = 0; j < 8; j++) { xr[2 * j] = __ldg(xp + 4 * j); xr[2 * j + 1] = __ldg(xp + 8 * (DM / 2) + 4 * j); }
            float acc[32];
#pragma unroll 1
            for (int i = 0; i < 8; i++) {
                if (!(i & 1)) { mbar_wait(bars + 8 * (B_FA + (i >> 1)), 0); if (i == 0) TL(19); }
                uint64_t ad = make_desc(sb + i * 16384 + wgi * 1024, 2048, 128, 0);
                uint64_t bd = make_desc(sb + F_R2 + 32768 + i * 8192, 8192, 1024, 1);
                WG_FENCE();
#pragma unroll
                for (int k = 0; k < 4; k++) wgmma_ss_n64(acc, ad + k * 256, bd + k * 128, (i | k) != 0);
                WG_COMMIT();
            }
            wg_wait<0>();
            fence_regs(acc);
            TL(7);
            asm volatile("barrier.cluster.wait.acquire.aligned;" ::: "memory");
            bar_sync(4, 256);
            if (tid == 128) { mbar_arrive(bars + 8 * B_ADONE); mbar_arrive_remote(mapa(bars + 8 * B_ADONE, 1 - r)); }
            float v0[16], v1[16];
            float s0 = 0.f, s1 = 0.f;
#pragma unroll
            for (int j2 = 0; j2 < 4; j2++) {
                uint32_t u[4];
#pragma unroll
                for (int jj = 0; jj < 2; jj++) {
                    const int j = 2 * j2 + jj;
                    u[2 * jj] = pack_bf16(bf_lo(xr[2 * j]) + acc[4 * j], bf_hi(xr[2 * j]) + acc[4 * j + 1]);
                    u[2 * jj + 1] = pack_bf16(bf_lo(xr[2 * j + 1]) + acc[4 * j + 2], bf_hi(xr[2 * j + 1]) + acc[4 * j + 3]);
                    v0[2 * j] = bf_lo(u[2 * jj]); v0[2 * j + 1] = bf_hi(u[2 * jj]);
                    v1[2 * j] = bf_lo(u[2 * jj + 1]); v1[2 * j + 1] = bf_hi(u[2 * jj + 1]);
                    s0 += v0[2 * j] + v0[2 * j + 1];
                    s1 += v1[2 * j] + v1[2 * j + 1];
                }
                hp[j2 * 1024] = u[0]; hp[j2 * 1024 + 32] = u[1]; hp[j2 * 1024 + 512] = u[2]; hp[j2 * 1024 + 544] = u[3];
            }
            bar_arrive(5, 288);
            float m0 = s0 * (1.0f / 16), m1 = s1 * (1.0f / 16), q0 = 0.f, q1 = 0.f;
#pragma unroll
            for (int i = 0; i < 16; i++) {
                float d0 = v0[i] - m0, d1 = v1[i] - m1;
                q0 = fmaf(d0, d0, q0); q1 = fmaf(d1, d1, q1);
            }
#pragma unroll
            for (int st = 0; st < 2; st++) {
                float hn = st ? 16.f : 8.f;
                float om0 = __shfl_xor_sync(0xffffffffu, m0, 1 << st), oq0 = __shfl_xor_sync(0xffffffffu, q0, 1 << st);
                float om1 = __shfl_xor_sync(0xffffffffu, m1, 1 << st), oq1 = __shfl_xor_sync(0xffffffffu, q1, 1 << st);
                float d0 = om0 - m0, d1 = om1 - m1;
                q0 = q0 + oq0 + d0 * d0 * hn; q1 = q1 + oq1 + d1 * d1 * hn;
                m0 = 0.5f * (m0 + om0); m1 = 0.5f * (m1 + om1);
            }
            if (t == 0) {
                g_hstat[row * 8 + nt] = make_float2(m0, q0);
                g_hstat[(row + 8) * 8 + nt] = make_float2(m1, q1);
            }
            bar_arrive(6, 288);
            TL(8);
        }
        uint32_t* gp = (uint32_t*)g_g + (((size_t)mbB * 224 + ntB * 28) * 16 + rgl) * 32 + lane;
        {
            float ag[128];
#pragma unroll 1
            for (int kb = 0; kb < 8; kb++) {
                const int s = kb % 3;
                mbar_wait(bars + 8 * (kb < 4 ? B_HF + kb : B_FA + kb - 4), kb < 4 ? 0 : 1);
                mbar_wait(bars + 8 * (B_BF + s), (kb / 3) & 1);
                uint64_t ad = make_desc(sb + ((ntB + kb) & 7) * 16384 + wgi * 1024, 2048, 128, 0);
                uint64_t bd = make_desc(sb + F_R2 + s * 32768, 4096, 512, 2);
                WG_FENCE();
#pragma unroll
                for (int k = 0; k < 4; k++) wgmma_ss_n256(ag, ad + k * 256, bd + k * 64, (kb | k) != 0);
                WG_COMMIT();
                if (kb > 0) {
                    wg_wait<1>();
                    if (lane == 0) { mbar_arrive(bars + 8 * (B_BE + (kb - 1) % 3)); mbar_arrive_remote(rbars + 8 * (B_BE + (kb - 1) % 3)); }
                }
            }
            wg_wait<0>();
            if (lane == 0) { mbar_arrive(bars + 8 * (B_BE + 7 % 3)); mbar_arrive_remote(rbars + 8 * (B_BE + 7 % 3)); }
            fence_regs(ag);
            TL(10);
            mbar_wait(bars + 8 * B_AUX, 0);
            ffn_epilogue<16, false>(ag, ag + 64, s_cs, 0, gp, 0, s_rs[rl], s_rs[rl + 8], lane);
            bar_arrive(1, 288);
        }
        {
            float ag[96];
#pragma unroll 1
            for (int kb = 0; kb < 8; kb++) {
                const int it = 8 + kb, s = it % 3;
                mbar_wait(bars + 8 * (B_BF + s), (it / 3) & 1);
                uint64_t ad = make_desc(sb + ((ntB + kb) & 7) * 16384 + wgi * 1024, 2048, 128, 0);
                uint64_t bd = make_desc(sb + F_R2 + s * 32768, 4096, 512, 2);
                WG_FENCE();
#pragma unroll
                for (int k = 0; k < 4; k++) wgmma_ss_n192(ag, ad + k * 256, bd + k * 64, (kb | k) != 0);
                WG_COMMIT();
                if (kb > 0) {
                    wg_wait<1>();
                    if (lane == 0 && it < 15) { mbar_arrive(bars + 8 * (B_BE + (it - 1) % 3)); mbar_arrive_remote(rbars + 8 * (B_BE + (it - 1) % 3)); }
                }
            }
            wg_wait<0>();
            if (lane == 0) {
                mbar_arrive(bars + 8 * B_BDONE);
                mbar_arrive_remote(rbars + 8 * B_PRDY);
            }
            fence_regs(ag);
            TL(11);
            ffn_epilogue<12, false>(ag, ag + 48, s_cs, 128, gp + 16 * 512, 0, s_rs[rl], s_rs[rl + 8], lane);
            bar_arrive(2, 288);
            TL(12);
        }
        {
            uint32_t hr[16];
#pragma unroll
            for (int j = 0; j < 8; j++) { hr[2 * j] = __ldcg(hp + j * 512); hr[2 * j + 1] = __ldcg(hp + j * 512 + 32); }
            mbar_wait(bars + 8 * (B_CF + 0), 0);
            const float a0 = h_row_stats(row).x, a1 = h_row_stats(row + 8).x;
            float acc[64];
#pragma unroll 1
            for (int kb = 0; kb < 14; kb++) {
                const int s = kb % 6;
                mbar_wait(bars + 8 * (B_CF + s), (kb / 6) & 1);
                if (warp == 4) TX(96 + kb);
                uint64_t ad = make_desc(sb + c_stage_a(s, ntB) + wgi * 1024, 2048, 128, 0);
                uint64_t bd = make_desc(sb + c_stage_b(s, ntB), 8192, 1024, 1);
                WG_FENCE();
#pragma unroll
                for (int k = 0; k < 4; k++) wgmma_ss_n128(acc, ad + k * 256, bd + k * 128, (kb | k) != 0);
                WG_COMMIT();
                if (kb > 0) {
                    wg_wait<1>();
                    if (lane == 0) mbar_arrive(bars + 8 * (B_CE + (kb - 1) % 6));
                }
            }
            wg_wait<0>();
            fence_regs(acc);
            TL(14);
            mbar_wait_cluster(bars + 8 * B_PRDY, 0);
            float o[32];
            if (r == 0) xchg<0>(acc, o, sb, smem, B_XC, ctid); else xchg<1>(acc, o, sb, smem, B_XC, ctid);
            TL(22);
            bar_sync(4, 256);
            const float k0 = 0.5f * a0 * a0, k1 = 0.5f * a1 * a1;
            const int srow = wgi * 64 + ww * 16 + ((lane >> 3) & 1) * 8 + (lane & 7);
#pragma unroll
            for (int j2 = 0; j2 < 4; j2++) {
                uint32_t u[4];
#pragma unroll
                for (int jj = 0; jj < 2; jj++) {
                    const int j = 2 * j2 + jj;
                    u[2 * jj] = pack_bf16(fmaf(k0, o[4 * j], bf_lo(hr[2 * j])), fmaf(k0, o[4 * j + 1], bf_hi(hr[2 * j])));
                    u[2 * jj + 1] = pack_bf16(fmaf(k1, o[4 * j + 2], bf_lo(hr[2 * j + 1])), fmaf(k1, o[4 * j + 3], bf_hi(hr[2 * j + 1])));
                }
                const int chunk = 2 * j2 + (lane >> 4);
                stsm4(sb + srow * 128 + ((chunk ^ (lane & 7)) * 16), u[0], u[1], u[2], u[3]);
            }
            fence_proxy_async();
            bar_arrive(3, 288);
            TLDUMP;
        }
    }
}

typedef CUresult (*EncodeFn)(CUtensorMap*, CUtensorMapDataType, cuuint32_t, void*, const cuuint64_t*, const cuuint64_t*,
                             const cuuint32_t*, const cuuint32_t*, CUtensorMapInterleave, CUtensorMapSwizzle,
                             CUtensorMapL2promotion, CUtensorMapFloatOOBfill);

void encode(EncodeFn fn, CUtensorMap* m, const void* ptr, int rank, const cuuint64_t* dims, const cuuint64_t* strides,
            const cuuint32_t* box, CUtensorMapSwizzle swz) {
    cuuint32_t es[3] = {1, 1, 1};
    fn(m, CU_TENSOR_MAP_DATA_TYPE_BFLOAT16, rank, (void*)ptr, dims, strides, box, es, CU_TENSOR_MAP_INTERLEAVE_NONE, swz,
       CU_TENSOR_MAP_L2_PROMOTION_L2_256B, CU_TENSOR_MAP_FLOAT_OOB_FILL_NONE);
}

template <typename... KArgs, typename... Args>
void launch(void (*kern)(KArgs...), int grid, int block, int smem, bool pdl, Args... args) {
    cudaLaunchConfig_t cfg = {};
    cfg.gridDim = dim3(grid); cfg.blockDim = dim3(block); cfg.dynamicSmemBytes = smem;
    cfg.stream = cudaStreamPerThread;
    cudaLaunchAttribute at[1];
    at[0].id = cudaLaunchAttributeProgrammaticStreamSerialization;
    at[0].val.programmaticStreamSerializationAllowed = 1;
    cfg.attrs = at; cfg.numAttrs = pdl ? 1 : 0;
    cudaLaunchKernelEx(&cfg, kern, KArgs(args)...);
}

}

extern "C" void kernel_launch(void* const* d_in, const int* in_sizes, int n_in, void* d_out, int out_size) {
    const __nv_bfloat16* x = (const __nv_bfloat16*)d_in[0];
    const __nv_bfloat16* wqkv = (const __nv_bfloat16*)d_in[1];
    const __nv_bfloat16* wo = (const __nv_bfloat16*)d_in[2];
    const __nv_bfloat16* wgate = (const __nv_bfloat16*)d_in[4];
    const __nv_bfloat16* wup = (const __nv_bfloat16*)d_in[5];
    const __nv_bfloat16* wdown = (const __nv_bfloat16*)d_in[6];
    __nv_bfloat16* out = (__nv_bfloat16*)d_out;

    static CUtensorMap tm_x, tm_wqkv, tm_wo, tm_wg, tm_wu, tm_wd, tm_out;
    static const void* cached[7] = {nullptr, nullptr, nullptr, nullptr, nullptr, nullptr, nullptr};
    if (cached[0] != x || cached[1] != wqkv || cached[2] != wo || cached[3] != wgate || cached[4] != wup || cached[5] != wdown || cached[6] != out) {
        void* fp = nullptr;
        cudaDriverEntryPointQueryResult qr;
        cudaGetDriverEntryPoint("cuTensorMapEncodeTiled", &fp, cudaEnableDefault, &qr);
        EncodeFn fn = (EncodeFn)fp;
        { cuuint64_t d[2] = {512, 2048}, s[1] = {1024}; cuuint32_t b[2] = {64, 128};
          encode(fn, &tm_x, x, 2, d, s, b, CU_TENSOR_MAP_SWIZZLE_128B);
          encode(fn, &tm_out, out, 2, d, s, b, CU_TENSOR_MAP_SWIZZLE_128B); }
        { cuuint64_t d[3] = {64, 512, 24}, s[2] = {3072, 128}; cuuint32_t b[3] = {64, 64, 3};
          encode(fn, &tm_wqkv, wqkv, 3, d, s, b, CU_TENSOR_MAP_SWIZZLE_128B); }
        { cuuint64_t d[2] = {512, 512}, s[1] = {1024}; cuuint32_t b[2] = {64, 64};
          encode(fn, &tm_wo, wo, 2, d, s, b, CU_TENSOR_MAP_SWIZZLE_128B); }
        { cuuint64_t d[2] = {1792, 512}, s[1] = {3584}; cuuint32_t b[2] = {32, 64};
          encode(fn, &tm_wg, wgate, 2, d, s, b, CU_TENSOR_MAP_SWIZZLE_64B);
          encode(fn, &tm_wu, wup, 2, d, s, b, CU_TENSOR_MAP_SWIZZLE_64B); }
        { cuuint64_t d[2] = {512, 1792}, s[1] = {1024}; cuuint32_t b[2] = {64, 64};
          encode(fn, &tm_wd, wdown, 2, d, s, b, CU_TENSOR_MAP_SWIZZLE_128B); }
        cudaFuncSetAttribute(qkv_kernel, cudaFuncAttributeMaxDynamicSharedMemorySize, F_SMEM);
        cudaFuncSetAttribute(qkv_kernel, cudaFuncAttributePreferredSharedMemoryCarveout, 100);
        cudaFuncSetAttribute(attn_kernel, cudaFuncAttributeMaxDynamicSharedMemorySize, F_SMEM);
        cudaFuncSetAttribute(attn_kernel, cudaFuncAttributePreferredSharedMemoryCarveout, 100);
        cudaFuncSetAttribute(tail_kernel, cudaFuncAttributeMaxDynamicSharedMemorySize, F_SMEM);
        cudaFuncSetAttribute(tail_kernel, cudaFuncAttributePreferredSharedMemoryCarveout, 100);
        cached[0] = x; cached[1] = wqkv; cached[2] = wo; cached[3] = wgate; cached[4] = wup; cached[5] = wdown; cached[6] = out;
    }
    launch(qkv_kernel, 128, 384, F_SMEM, false, tm_x, tm_wqkv, x, wqkv);
    launch(attn_kernel, 132, 512, F_SMEM, true, wgate, wup, wo, wdown);
    launch(tail_kernel, 128, 384, F_SMEM, true, tm_wo, tm_wg, tm_wu, tm_wd, tm_out, x);
}
```

```cpp
#include <cuda_runtime.h>
#include <cuda_bf16.h>
#include <cuda.h>
#include <stdint.h>

#define K1_DIRECT
namespace {

constexpr int S_LEN = 2048, DM = 512, NH = 32, FF = 1792;

__device__ __align__(1024) __nv_bfloat16 g_qkv[3 * NH * S_LEN * 16];
__device__ __align__(1024) __nv_bfloat16 g_ao[S_LEN * DM];
__device__ __align__(1024) __nv_bfloat16 g_h[S_LEN * DM];
__device__ __align__(1024) __nv_bfloat16 g_g[S_LEN * FF];
__device__ __align__(16) float2 g_rowstat1[S_LEN];
__device__ float g_cs1_part[16 * 1536];
__device__ unsigned int g_cnt[32];
__device__ unsigned int g_cnt2[160];
__device__ float g_nrm[3 * NH * 128];
__device__ float2 g_hstat[S_LEN * 8];
__device__ float g_cs2[2 * FF];

#define TLDECL
#define TL(slot)
#define TLDUMP
#define TX(slot)
__device__ __forceinline__ uint32_t smem_u32(const void* p) { return (uint32_t)__cvta_generic_to_shared(p); }
__device__ __forceinline__ void mbar_init(uint32_t a, int c) { asm volatile("mbarrier.init.shared.b64 [%0], %1;" :: "r"(a), "r"(c)); }
__device__ __forceinline__ void mbar_expect(uint32_t a, int bytes) { asm volatile("mbarrier.arrive.expect_tx.shared.b64 _, [%0], %1;" :: "r"(a), "r"(bytes) : "memory"); }
__device__ __forceinline__ void mbar_arrive(uint32_t a) { asm volatile("mbarrier.arrive.shared.b64 _, [%0];" :: "r"(a) : "memory"); }
__device__ __forceinline__ void mbar_wait(uint32_t a, int parity) {
    uint32_t done;
    int it = 0;
    do {
        asm volatile("{\n.reg .pred p;\nmbarrier.try_wait.parity.shared.b64 p, [%1], %2;\nselp.u32 %0, 1, 0, p;\n}"
                     : "=r"(done) : "r"(a), "r"(parity) : "memory");
        if (++it > (1 << 24)) __trap();
    } while (!done);
}
__device__ __forceinline__ void bulk_g2s(uint32_t dst, const void* src, int bytes, uint32_t bar) {
    asm volatile("cp.async.bulk.shared::cluster.global.mbarrier::complete_tx::bytes [%0], [%1], %2, [%3];"
                 :: "r"(dst), "l"(src), "r"(bytes), "r"(bar) : "memory");
}
__device__ __forceinline__ void tma2d(uint32_t dst, const CUtensorMap* m, int c0, int c1, uint32_t bar) {
    asm volatile("cp.async.bulk.tensor.2d.shared::cluster.global.mbarrier::complete_tx::bytes [%0], [%1, {%3, %4}], [%2];"
                 :: "r"(dst), "l"(m), "r"(bar), "r"(c0), "r"(c1) : "memory");
}
__device__ __forceinline__ void tma3d(uint32_t dst, const CUtensorMap* m, int c0, int c1, int c2, uint32_t bar) {
    asm volatile("cp.async.bulk.tensor.3d.shared::cluster.global.mbarrier::complete_tx::bytes [%0], [%1, {%3, %4, %5}], [%2];"
                 :: "r"(dst), "l"(m), "r"(bar), "r"(c0), "r"(c1), "r"(c2) : "memory");
}
__device__ __forceinline__ void prefetch_tmap(const CUtensorMap* m) { asm volatile("prefetch.tensormap [%0];" :: "l"(m) : "memory"); }
__device__ __forceinline__ void pdl_wait() { asm volatile("griddepcontrol.wait;" ::: "memory"); }
__device__ __forceinline__ void pdl_launch() { asm volatile("griddepcontrol.launch_dependents;" ::: "memory"); }
__device__ __forceinline__ void fence_barrier_init() { asm volatile("fence.mbarrier_init.release.cluster;" ::: "memory"); }
__device__ __forceinline__ void fence_proxy_async() { asm volatile("fence.proxy.async.shared::cta;" ::: "memory"); }
__device__ __forceinline__ uint64_t make_desc(uint32_t saddr, uint32_t lbo, uint32_t sbo, uint32_t swz) {
    return (uint64_t)((saddr & 0x3FFFF) >> 4) | ((uint64_t)((lbo & 0x3FFFF) >> 4) << 16) |
           ((uint64_t)((sbo & 0x3FFFF) >> 4) << 32) | ((uint64_t)swz << 62);
}
#define WG_FENCE() asm volatile("wgmma.fence.sync.aligned;" ::: "memory")
#define WG_COMMIT() asm volatile("wgmma.commit_group.sync.aligned;" ::: "memory")
template <int N> __device__ __forceinline__ void wg_wait() { asm volatile("wgmma.wait_group.sync.aligned %0;" :: "n"(N) : "memory"); }
template <int N> __device__ __forceinline__ void fence_regs(float (&d)[N]) {
#pragma unroll
    for (int i = 0; i < N; i++) asm volatile("" : "+f"(d[i]) :: "memory");
}
__device__ __forceinline__ float ex2f(float x) { float y; asm("ex2.approx.ftz.f32 %0, %1;" : "=f"(y) : "f"(x)); return y; }
__device__ __forceinline__ float tanh_fast(float x) { float y; asm("tanh.approx.f32 %0, %1;" : "=f"(y) : "f"(x)); return y; }
__device__ __forceinline__ uint32_t pack_bf16(float lo, float hi) { uint32_t r; asm("cvt.rn.bf16x2.f32 %0, %1, %2;" : "=r"(r) : "f"(hi), "f"(lo)); return r; }
__device__ __forceinline__ float bf_lo(uint32_t u) { return __uint_as_float(u << 16); }
__device__ __forceinline__ float bf_hi(uint32_t u) { return __uint_as_float(u & 0xFFFF0000u); }
__device__ __forceinline__ uint32_t hfma2(uint32_t a, uint32_t b, uint32_t c) { uint32_t r; asm("fma.rn.f16x2 %0, %1, %2, %3;" : "=r"(r) : "r"(a), "r"(b), "r"(c)); return r; }
__device__ __forceinline__ uint32_t hmul2(uint32_t a, uint32_t b) { uint32_t r; asm("mul.rn.f16x2 %0, %1, %2;" : "=r"(r) : "r"(a), "r"(b)); return r; }
__device__ __forceinline__ unsigned int ld_acquire(const unsigned int* p) { unsigned int v; asm volatile("ld.acquire.gpu.u32 %0, [%1];" : "=r"(v) : "l"(p) : "memory"); return v; }
__device__ __forceinline__ void red_release(unsigned int* p) { asm volatile("red.release.gpu.global.add.u32 [%0], 1;" :: "l"(p) : "memory"); }
__device__ __forceinline__ void stsm4(uint32_t addr, uint32_t a, uint32_t b, uint32_t c, uint32_t d) {
    asm volatile("stmatrix.sync.aligned.m8n8.x4.shared.b16 [%0], {%1,%2,%3,%4};" :: "r"(addr), "r"(a), "r"(b), "r"(c), "r"(d) : "memory");
}
__device__ __forceinline__ void bulk_s2g(void* dst, uint32_t src, int bytes) {
    asm volatile("cp.async.bulk.global.shared::cta.bulk_group [%0], [%1], %2;" :: "l"(dst), "r"(src), "r"(bytes) : "memory");
}
__device__ __forceinline__ void bulk_commit() { asm volatile("cp.async.bulk.commit_group;" ::: "memory"); }
__device__ __forceinline__ void bulk_wait_all() { asm volatile("cp.async.bulk.wait_group 0;" ::: "memory"); }
__device__ __forceinline__ void bulk_wait_read() { asm volatile("cp.async.bulk.wait_group.read 0;" ::: "memory"); }
__device__ __forceinline__ void bar_sync(int id, int n) { asm volatile("bar.sync %0, %1;" :: "r"(id), "r"(n) : "memory"); }
__device__ __forceinline__ void bar_arrive(int id, int n) { asm volatile("bar.arrive %0, %1;" :: "r"(id), "r"(n) : "memory"); }
__device__ __forceinline__ float warp_sum(float v) {
#pragma unroll
    for (int o = 16; o; o >>= 1) v += __shfl_xor_sync(0xffffffffu, v, o);
    return v;
}
__device__ __forceinline__ float warp_max(float v) {
#pragma unroll
    for (int o = 16; o; o >>= 1) v = fmaxf(v, __shfl_xor_sync(0xffffffffu, v, o));
    return v;
}

__device__ __forceinline__ void wgmma_ss_n64(float (&d)[32], uint64_t adesc, uint64_t bdesc, int scale_d) {
    asm volatile("{\n.reg .pred p;\nsetp.ne.b32 p, %34, 0;\n"
      "wgmma.mma_async.sync.aligned.m64n64k16.f32.bf16.bf16 {%0,%1,%2,%3,%4,%5,%6,%7,%8,%9,%10,%11,%12,%13,%14,%15,%16,%17,%18,%19,%20,%21,%22,%23,%24,%25,%26,%27,%28,%29,%30,%31}, %32, %33, p, 1, 1, 0, 1;\n}"
      : "+f"(d[0]), "+f"(d[1]), "+f"(d[2]), "+f"(d[3]), "+f"(d[4]), "+f"(d[5]), "+f"(d[6]), "+f"(d[7]), "+f"(d[8]), "+f"(d[9]), "+f"(d[10]), "+f"(d[11]), "+f"(d[12]), "+f"(d[13]), "+f"(d[14]), "+f"(d[15]), "+f"(d[16]), "+f"(d[17]), "+f"(d[18]), "+f"(d[19]), "+f"(d[20]), "+f"(d[21]), "+f"(d[22]), "+f"(d[23]), "+f"(d[24]), "+f"(d[25]), "+f"(d[26]), "+f"(d[27]), "+f"(d[28]), "+f"(d[29]), "+f"(d[30]), "+f"(d[31])
      : "l"(adesc), "l"(bdesc), "r"(scale_d));
}
__device__ __forceinline__ void wgmma_ss_n128(float (&d)[64], uint64_t adesc, uint64_t bdesc, int scale_d) {
    asm volatile("{\n.reg .pred p;\nsetp.ne.b32 p, %66, 0;\n"
      "wgmma.mma_async.sync.aligned.m64n128k16.f32.bf16.bf16 {%0,%1,%2,%3,%4,%5,%6,%7,%8,%9,%10,%11,%12,%13,%14,%15,%16,%17,%18,%19,%20,%21,%22,%23,%24,%25,%26,%27,%28,%29,%30,%31,%32,%33,%34,%35,%36,%37,%38,%39,%40,%41,%42,%43,%44,%45,%46,%47,%48,%49,%50,%51,%52,%53,%54,%55,%56,%57,%58,%59,%60,%61,%62,%63}, %64, %65, p, 1, 1, 0, 1;\n}"
      : "+f"(d[0]), "+f"(d[1]), "+f"(d[2]), "+f"(d[3]), "+f"(d[4]), "+f"(d[5]), "+f"(d[6]), "+f"(d[7]), "+f"(d[8]), "+f"(d[9]), "+f"(d[10]), "+f"(d[11]), "+f"(d[12]), "+f"(d[13]), "+f"(d[14]), "+f"(d[15]), "+f"(d[16]), "+f"(d[17]), "+f"(d[18]), "+f"(d[19]), "+f"(d[20]), "+f"(d[21]), "+f"(d[22]), "+f"(d[23]), "+f"(d[24]), "+f"(d[25]), "+f"(d[26]), "+f"(d[27]), "+f"(d[28]), "+f"(d[29]), "+f"(d[30]), "+f"(d[31]), "+f"(d[32]), "+f"(d[33]), "+f"(d[34]), "+f"(d[35]), "+f"(d[36]), "+f"(d[37]), "+f"(d[38]), "+f"(d[39]), "+f"(d[40]), "+f"(d[41]), "+f"(d[42]), "+f"(d[43]), "+f"(d[44]), "+f"(d[45]), "+f"(d[46]), "+f"(d[47]), "+f"(d[48]), "+f"(d[49]), "+f"(d[50]), "+f"(d[51]), "+f"(d[52]), "+f"(d[53]), "+f"(d[54]), "+f"(d[55]), "+f"(d[56]), "+f"(d[57]), "+f"(d[58]), "+f"(d[59]), "+f"(d[60]), "+f"(d[61]), "+f"(d[62]), "+f"(d[63])
      : "l"(adesc), "l"(bdesc), "r"(scale_d));
}
__device__ __forceinline__ void wgmma_ss_n192(float (&d)[96], uint64_t adesc, uint64_t bdesc, int scale_d) {
    asm volatile("{\n.reg .pred p;\nsetp.ne.b32 p, %98, 0;\n"
      "wgmma.mma_async.sync.aligned.m64n192k16.f32.bf16.bf16 {%0,%1,%2,%3,%4,%5,%6,%7,%8,%9,%10,%11,%12,%13,%14,%15,%16,%17,%18,%19,%20,%21,%22,%23,%24,%25,%26,%27,%28,%29,%30,%31,%32,%33,%34,%35,%36,%37,%38,%39,%40,%41,%42,%43,%44,%45,%46,%47,%48,%49,%50,%51,%52,%53,%54,%55,%56,%57,%58,%59,%60,%61,%62,%63,%64,%65,%66,%67,%68,%69,%70,%71,%72,%73,%74,%75,%76,%77,%78,%79,%80,%81,%82,%83,%84,%85,%86,%87,%88,%89,%90,%91,%92,%93,%94,%95}, %96, %97, p, 1, 1, 0, 1;\n}"
      : "+f"(d[0]), "+f"(d[1]), "+f"(d[2]), "+f"(d[3]), "+f"(d[4]), "+f"(d[5]), "+f"(d[6]), "+f"(d[7]), "+f"(d[8]), "+f"(d[9]), "+f"(d[10]), "+f"(d[11]), "+f"(d[12]), "+f"(d[13]), "+f"(d[14]), "+f"(d[15]), "+f"(d[16]), "+f"(d[17]), "+f"(d[18]), "+f"(d[19]), "+f"(d[20]), "+f"(d[21]), "+f"(d[22]), "+f"(d[23]), "+f"(d[24]), "+f"(d[25]), "+f"(d[26]), "+f"(d[27]), "+f"(d[28]), "+f"(d[29]), "+f"(d[30]), "+f"(d[31]), "+f"(d[32]), "+f"(d[33]), "+f"(d[34]), "+f"(d[35]), "+f"(d[36]), "+f"(d[37]), "+f"(d[38]), "+f"(d[39]), "+f"(d[40]), "+f"(d[41]), "+f"(d[42]), "+f"(d[43]), "+f"(d[44]), "+f"(d[45]), "+f"(d[46]), "+f"(d[47]), "+f"(d[48]), "+f"(d[49]), "+f"(d[50]), "+f"(d[51]), "+f"(d[52]), "+f"(d[53]), "+f"(d[54]), "+f"(d[55]), "+f"(d[56]), "+f"(d[57]), "+f"(d[58]), "+f"(d[59]), "+f"(d[60]), "+f"(d[61]), "+f"(d[62]), "+f"(d[63]), "+f"(d[64]), "+f"(d[65]), "+f"(d[66]), "+f"(d[67]), "+f"(d[68]), "+f"(d[69]), "+f"(d[70]), "+f"(d[71]), "+f"(d[72]), "+f"(d[73]), "+f"(d[74]), "+f"(d[75]), "+f"(d[76]), "+f"(d[77]), "+f"(d[78]), "+f"(d[79]), "+f"(d[80]), "+f"(d[81]), "+f"(d[82]), "+f"(d[83]), "+f"(d[84]), "+f"(d[85]), "+f"(d[86]), "+f"(d[87]), "+f"(d[88]), "+f"(d[89]), "+f"(d[90]), "+f"(d[91]), "+f"(d[92]), "+f"(d[93]), "+f"(d[94]), "+f"(d[95])
      : "l"(adesc), "l"(bdesc), "r"(scale_d));
}
__device__ __forceinline__ void wgmma_ss_n256(float (&d)[128], uint64_t adesc, uint64_t bdesc, int scale_d) {
    asm volatile("{\n.reg .pred p;\nsetp.ne.b32 p, %130, 0;\n"
      "wgmma.mma_async.sync.aligned.m64n256k16.f32.bf16.bf16 {%0,%1,%2,%3,%4,%5,%6,%7,%8,%9,%10,%11,%12,%13,%14,%15,%16,%17,%18,%19,%20,%21,%22,%23,%24,%25,%26,%27,%28,%29,%30,%31,%32,%33,%34,%35,%36,%37,%38,%39,%40,%41,%42,%43,%44,%45,%46,%47,%48,%49,%50,%51,%52,%53,%54,%55,%56,%57,%58,%59,%60,%61,%62,%63,%64,%65,%66,%67,%68,%69,%70,%71,%72,%73,%74,%75,%76,%77,%78,%79,%80,%81,%82,%83,%84,%85,%86,%87,%88,%89,%90,%91,%92,%93,%94,%95,%96,%97,%98,%99,%100,%101,%102,%103,%104,%105,%106,%107,%108,%109,%110,%111,%112,%113,%114,%115,%116,%117,%118,%119,%120,%121,%122,%123,%124,%125,%126,%127}, %128, %129, p, 1, 1, 0, 1;\n}"
      : "+f"(d[0]), "+f"(d[1]), "+f"(d[2]), "+f"(d[3]), "+f"(d[4]), "+f"(d[5]), "+f"(d[6]), "+f"(d[7]), "+f"(d[8]), "+f"(d[9]), "+f"(d[10]), "+f"(d[11]), "+f"(d[12]), "+f"(d[13]), "+f"(d[14]), "+f"(d[15]), "+f"(d[16]), "+f"(d[17]), "+f"(d[18]), "+f"(d[19]), "+f"(d[20]), "+f"(d[21]), "+f"(d[22]), "+f"(d[23]), "+f"(d[24]), "+f"(d[25]), "+f"(d[26]), "+f"(d[27]), "+f"(d[28]), "+f"(d[29]), "+f"(d[30]), "+f"(d[31]), "+f"(d[32]), "+f"(d[33]), "+f"(d[34]), "+f"(d[35]), "+f"(d[36]), "+f"(d[37]), "+f"(d[38]), "+f"(d[39]), "+f"(d[40]), "+f"(d[41]), "+f"(d[42]), "+f"(d[43]), "+f"(d[44]), "+f"(d[45]), "+f"(d[46]), "+f"(d[47]), "+f"(d[48]), "+f"(d[49]), "+f"(d[50]), "+f"(d[51]), "+f"(d[52]), "+f"(d[53]), "+f"(d[54]), "+f"(d[55]), "+f"(d[56]), "+f"(d[57]), "+f"(d[58]), "+f"(d[59]), "+f"(d[60]), "+f"(d[61]), "+f"(d[62]), "+f"(d[63]), "+f"(d[64]), "+f"(d[65]), "+f"(d[66]), "+f"(d[67]), "+f"(d[68]), "+f"(d[69]), "+f"(d[70]), "+f"(d[71]), "+f"(d[72]), "+f"(d[73]), "+f"(d[74]), "+f"(d[75]), "+f"(d[76]), "+f"(d[77]), "+f"(d[78]), "+f"(d[79]), "+f"(d[80]), "+f"(d[81]), "+f"(d[82]), "+f"(d[83]), "+f"(d[84]), "+f"(d[85]), "+f"(d[86]), "+f"(d[87]), "+f"(d[88]), "+f"(d[89]), "+f"(d[90]), "+f"(d[91]), "+f"(d[92]), "+f"(d[93]), "+f"(d[94]), "+f"(d[95]), "+f"(d[96]), "+f"(d[97]), "+f"(d[98]), "+f"(d[99]), "+f"(d[100]), "+f"(d[101]), "+f"(d[102]), "+f"(d[103]), "+f"(d[104]), "+f"(d[105]), "+f"(d[106]), "+f"(d[107]), "+f"(d[108]), "+f"(d[109]), "+f"(d[110]), "+f"(d[111]), "+f"(d[112]), "+f"(d[113]), "+f"(d[114]), "+f"(d[115]), "+f"(d[116]), "+f"(d[117]), "+f"(d[118]), "+f"(d[119]), "+f"(d[120]), "+f"(d[121]), "+f"(d[122]), "+f"(d[123]), "+f"(d[124]), "+f"(d[125]), "+f"(d[126]), "+f"(d[127])
      : "l"(adesc), "l"(bdesc), "r"(scale_d));
}
__device__ __forceinline__ void qk_wgmma_n64(float (&d)[32], const uint32_t (&a)[4], uint64_t desc) {
    asm volatile("wgmma.mma_async.sync.aligned.m64n64k16.f32.bf16.bf16 {%0,%1,%2,%3,%4,%5,%6,%7,%8,%9,%10,%11,%12,%13,%14,%15,%16,%17,%18,%19,%20,%21,%22,%23,%24,%25,%26,%27,%28,%29,%30,%31}, {%32,%33,%34,%35}, %36, 0, 1, 1, 0;"
      : "=f"(d[0]), "=f"(d[1]), "=f"(d[2]), "=f"(d[3]), "=f"(d[4]), "=f"(d[5]), "=f"(d[6]), "=f"(d[7]), "=f"(d[8]), "=f"(d[9]), "=f"(d[10]), "=f"(d[11]), "=f"(d[12]), "=f"(d[13]), "=f"(d[14]), "=f"(d[15]), "=f"(d[16]), "=f"(d[17]), "=f"(d[18]), "=f"(d[19]), "=f"(d[20]), "=f"(d[21]), "=f"(d[22]), "=f"(d[23]), "=f"(d[24]), "=f"(d[25]), "=f"(d[26]), "=f"(d[27]), "=f"(d[28]), "=f"(d[29]), "=f"(d[30]), "=f"(d[31])
      : "r"(a[0]), "r"(a[1]), "r"(a[2]), "r"(a[3]), "l"(desc));
}

__device__ __forceinline__ void pv_wgmma(float (&d)[12], uint32_t a0, uint32_t a1, uint32_t a2, uint32_t a3, uint64_t desc) {
    asm volatile("wgmma.mma_async.sync.aligned.m64n24k16.f32.bf16.bf16 {%0,%1,%2,%3,%4,%5,%6,%7,%8,%9,%10,%11}, {%12,%13,%14,%15}, %16, 1, 1, 1, 1;"
      : "+f"(d[0]), "+f"(d[1]), "+f"(d[2]), "+f"(d[3]), "+f"(d[4]), "+f"(d[5]), "+f"(d[6]), "+f"(d[7]), "+f"(d[8]), "+f"(d[9]), "+f"(d[10]), "+f"(d[11])
      : "r"(a0), "r"(a1), "r"(a2), "r"(a3), "l"(desc));
}

__device__ __forceinline__ uint32_t mapa(uint32_t a, uint32_t rank) { uint32_t r; asm("mapa.shared::cluster.u32 %0, %1, %2;" : "=r"(r) : "r"(a), "r"(rank)); return r; }
__device__ __forceinline__ void mbar_arrive_remote(uint32_t a) { asm volatile("mbarrier.arrive.relaxed.cluster.shared::cluster.b64 _, [%0];" :: "r"(a) : "memory"); }
__device__ __forceinline__ void mbar_wait_cluster(uint32_t a, int parity) {
    uint32_t done;
    int it = 0;
    do {
        asm volatile("{\n.reg .pred p;\nmbarrier.try_wait.parity.acquire.cluster.shared::cta.b64 p, [%1], %2;\nselp.u32 %0, 1, 0, p;\n}"
                     : "=r"(done) : "r"(a), "r"(parity) : "memory");
        if (++it > (1 << 24)) __trap();
    } while (!done);
}
__device__ __forceinline__ void tma2d_mc(uint32_t dst, const CUtensorMap* m, int c0, int c1, uint32_t bar) {
    asm volatile("cp.async.bulk.tensor.2d.shared::cluster.global.mbarrier::complete_tx::bytes.multicast::cluster [%0], [%1, {%3, %4}], [%2], %5;"
                 :: "r"(dst), "l"(m), "r"(bar), "r"(c0), "r"(c1), "h"((uint16_t)3) : "memory");
}
__device__ __forceinline__ void bulk_g2s_mc(uint32_t dst, const void* src, int bytes, uint32_t bar) {
    asm volatile("cp.async.bulk.shared::cluster.global.mbarrier::complete_tx::bytes.multicast::cluster [%0], [%1], %2, [%3], %4;"
                 :: "r"(dst), "l"(src), "r"(bytes), "r"(bar), "h"((uint16_t)3) : "memory");
}
__device__ __forceinline__ void tile_of(int bid, int& mb, int& nt) {
    int grp = bid >> 4, in = bid & 15;
    mb = (grp >> 1) * 4 + (in >> 2);
    nt = (grp & 1) * 4 + (in & 3);
}

constexpr int K1_STAGES = 5, K1_STAGE = 16384 + 24576;
constexpr int K1_BAR = K1_STAGES * K1_STAGE, K1_RS = K1_BAR + 128, K1_CS = K1_RS + 1024, K1_SMEM = K1_CS + 768;

__device__ __forceinline__ float2 row_stats_regs(uint4 a, uint4 b) {
    float v[16];
    v[0] = bf_lo(a.x); v[1] = bf_hi(a.x); v[2] = bf_lo(a.y); v[3] = bf_hi(a.y);
    v[4] = bf_lo(a.z); v[5] = bf_hi(a.z); v[6] = bf_lo(a.w); v[7] = bf_hi(a.w);
    v[8] = bf_lo(b.x); v[9] = bf_hi(b.x); v[10] = bf_lo(b.y); v[11] = bf_hi(b.y);
    v[12] = bf_lo(b.z); v[13] = bf_hi(b.z); v[14] = bf_lo(b.w); v[15] = bf_hi(b.w);
    float s = 0.f;
#pragma unroll
    for (int i = 0; i < 16; i++) s += v[i];
    float mean = warp_sum(s) * (1.0f / DM);
    float q = 0.f;
#pragma unroll
    for (int i = 0; i < 16; i++) { float d = v[i] - mean; q = fmaf(d, d, q); }
    float var = warp_sum(q) * (1.0f / DM);
    float rstd = rsqrtf(var + 1e-5f);
    return make_float2(rstd, -mean * rstd);
}
__device__ __forceinline__ float2 row_stats_x(const __nv_bfloat16* x, int row, int lane) {
    const uint4* p = (const uint4*)(x + (size_t)row * DM);
    return row_stats_regs(__ldg(p + lane), __ldg(p + 32 + lane));
}
__device__ __forceinline__ void colsum8(const __nv_bfloat16* w, int ld, int col, int k0, int nk, float (&s)[8]) {
#pragma unroll
    for (int i = 0; i < 8; i++) s[i] = 0.f;
    for (int k = k0; k < k0 + nk; k += 8) {
        uint4 u[8];
#pragma unroll
        for (int i = 0; i < 8; i++) u[i] = __ldg((const uint4*)(w + (size_t)(k + i) * ld + col));
#pragma unroll
        for (int i = 0; i < 8; i++) {
            s[0] += bf_lo(u[i].x); s[1] += bf_hi(u[i].x); s[2] += bf_lo(u[i].y); s[3] += bf_hi(u[i].y);
            s[4] += bf_lo(u[i].z); s[5] += bf_hi(u[i].z); s[6] += bf_lo(u[i].w); s[7] += bf_hi(u[i].w);
        }
    }
}
__device__ __forceinline__ bool wait_count(const unsigned int* p, unsigned int target, int lane) {
    int ok = 1;
    if (lane == 0) {
        int it = 0;
        while (ld_acquire(p) < target) { if (++it > (1 << 18)) { ok = 0; break; } }
    }
    ok = __shfl_sync(0xffffffffu, ok, 0);
    return ok != 0;
}

__global__ void __launch_bounds__(384, 1)
qkv_kernel(const __grid_constant__ CUtensorMap tm_x, const __grid_constant__ CUtensorMap tm_w,
           const __nv_bfloat16* __restrict__ x, const __nv_bfloat16* __restrict__ wqkv) {
    extern __shared__ __align__(1024) unsigned char smem[];
    const uint32_t sb = smem_u32(smem);
    const int tid = threadIdx.x, warp = __shfl_sync(0xffffffffu, tid >> 5, 0), lane = tid & 31;
    TLDECL
    TL(0);
    int mb, nt;
    tile_of(blockIdx.x, mb, nt);
    const uint32_t full = sb + K1_BAR, empty = full + 40, auxb = full + 80;
    if (tid == 0) {
#pragma unroll
        for (int i = 0; i < K1_STAGES; i++) { mbar_init(full + 8 * i, 1); mbar_init(empty + 8 * i, 8); }
        mbar_init(auxb, 3);
        fence_barrier_init();
        for (int kb = 0; kb < K1_STAGES; kb++) {
            mbar_expect(full + 8 * kb, K1_STAGE);
            tma2d(sb + kb * K1_STAGE, &tm_x, kb * 64, mb * 128, full + 8 * kb);
            tma3d(sb + kb * K1_STAGE + 16384, &tm_w, 0, kb * 64, nt * 3, full + 8 * kb);
        }
    }
    pdl_launch();
    if (warp == 0) { __syncwarp(); bar_arrive(3, 288); bar_arrive(4, 128); }
    else if (warp >= 4) bar_sync(3, 288);
    if (warp == 1 || warp == 2) {
        const int r0 = mb * 128 + nt * 16 + (warp - 1) * 8;
        uint4 u[16];
#pragma unroll
        for (int i = 0; i < 8; i++) {
            const uint4* p = (const uint4*)(x + (size_t)(r0 + i) * DM);
            u[2 * i] = __ldg(p + lane); u[2 * i + 1] = __ldg(p + 32 + lane);
        }
        float2 mine = make_float2(0.f, 0.f);
#pragma unroll
        for (int i = 0; i < 8; i++) {
            float2 st = row_stats_regs(u[2 * i], u[2 * i + 1]);
            if (lane == i) mine = st;
        }
        if (lane < 8) g_rowstat1[r0 + lane] = mine;
        __syncwarp();
        if (lane == 0) red_release(&g_cnt[mb]);
    } else if (warp == 3) {
        uint4 u[24];
#pragma unroll
        for (int c = 0; c < 3; c++)
#pragma unroll
            for (int i = 0; i < 8; i++)
                u[c * 8 + i] = __ldg((const uint4*)(wqkv + (size_t)(mb * 32 + (lane >> 3) * 8 + i) * 1536 + nt * 192 + (c * 8 + (lane & 7)) * 8));
#pragma unroll
        for (int c = 0; c < 3; c++) {
            float cs[8];
#pragma unroll
            for (int i = 0; i < 8; i++) cs[i] = 0.f;
#pragma unroll
            for (int i = 0; i < 8; i++) {
                const uint4 w = u[c * 8 + i];
                cs[0] += bf_lo(w.x); cs[1] += bf_hi(w.x); cs[2] += bf_lo(w.y); cs[3] += bf_hi(w.y);
                cs[4] += bf_lo(w.z); cs[5] += bf_hi(w.z); cs[6] += bf_lo(w.w); cs[7] += bf_hi(w.w);
            }
#pragma unroll
            for (int i = 0; i < 8; i++) {
                cs[i] += __shfl_xor_sync(0xffffffffu, cs[i], 8);
                cs[i] += __shfl_xor_sync(0xffffffffu, cs[i], 16);
            }
            if (lane < 8) {
                float4* d = (float4*)(g_cs1_part + mb * 1536 + nt * 192 + (c * 8 + lane) * 8);
                d[0] = make_float4(cs[0], cs[1], cs[2], cs[3]);
                d[1] = make_float4(cs[4], cs[5], cs[6], cs[7]);
            }
        }
        __syncwarp();
        if (lane == 0) red_release(&g_cnt[16 + nt]);
    }
    if (warp == 0) {
        if (blockIdx.x == 0) g_cnt2[lane] = 0;
        if (lane < 1) g_cnt2[32 + blockIdx.x] = 0;
        if (lane == 0) {
            for (int kb = K1_STAGES; kb < 8; kb++) {
                int s = kb % K1_STAGES;
                mbar_wait(empty + 8 * s, 0);
                mbar_expect(full + 8 * s, K1_STAGE);
                tma2d(sb + s * K1_STAGE, &tm_x, kb * 64, mb * 128, full + 8 * s);
                tma3d(sb + s * K1_STAGE + 16384, &tm_w, 0, kb * 64, nt * 3, full + 8 * s);
            }
        }
    } else if (warp < 4) {
        float2* s_rs = (float2*)(smem + K1_RS);
        float* s_cs = (float*)(smem + K1_CS);
        TL(20);
        bar_sync(4, 128);
        TX(8 + warp);
        if (warp == 1) {
            if (wait_count(&g_cnt[mb], 16, lane)) {
#pragma unroll
                for (int i = 0; i < 4; i++) s_rs[lane + 32 * i] = __ldcg(&g_rowstat1[mb * 128 + lane + 32 * i]);
            } else {
                for (int i = 0; i < 128; i++) {
                    float2 st = row_stats_x(x, mb * 128 + i, lane);
                    if (lane == 0) s_rs[i] = st;
                }
            }
        } else {
            int c0 = (warp - 2) * 96;
            if (wait_count(&g_cnt[16 + nt], 16, lane)) {
#pragma unroll
                for (int i = 0; i < 3; i++) {
                    float s = 0.f;
#pragma unroll
                    for (int p = 0; p < 16; p++) s += __ldcg(&g_cs1_part[p * 1536 + nt * 192 + c0 + lane + 32 * i]);
                    s_cs[c0 + lane + 32 * i] = s;
                }
            } else if (lane < 12) {
                float s[8];
                colsum8(wqkv, 1536, nt * 192 + c0 + lane * 8, 0, 512, s);
#pragma unroll
                for (int i = 0; i < 8; i++) s_cs[c0 + lane * 8 + i] = s[i];
            }
        }
        __syncwarp();
        TL(21);
        if (lane == 0) mbar_arrive(auxb);
        bar_sync(2, 256 + 96);
        const int a = tid - 32;
        {
            const int hh = a >> 3, w = a & 7;
            const float4* p = (const float4*)(smem + 49152) + (hh * 256 + w * 32) / 2;
            float m = 0.f;
#pragma unroll
            for (int i = 0; i < 8; i++) {
                const int ii = (i + a) & 7;
                float4 u = p[2 * ii], v = p[2 * ii + 1];
                float n0 = u.x + u.z + v.x + v.z, n1 = u.y + u.w + v.y + v.w;
                if (!(n0 <= 3.0e38f) || !(n1 <= 3.0e38f)) m = __int_as_float(0x7f800000);
                m = fmaxf(m, fmaxf(n0, n1));
            }
            const int col0 = nt * 192 + hh * 16;
            g_nrm[((col0 >> 9) * NH + ((col0 & 511) >> 4)) * 128 + mb * 8 + w] = m;
        }
        if (a < 24) bulk_wait_all();
        TL(27);
        TLDUMP;
    } else {
        const int wgi = (warp >> 2) - 1, ww = warp & 3;
        float acc[96];
#pragma unroll 1
        for (int kb = 0; kb < 8; kb++) {
            int s = kb % K1_STAGES;
            mbar_wait(full + 8 * s, (kb / K1_STAGES) & 1);
            if (warp == 4) TX(kb);
            uint64_t ad = make_desc(sb + s * K1_STAGE + wgi * 8192, 16, 1024, 1);
            uint64_t bd = make_desc(sb + s * K1_STAGE + 16384, 8192, 1024, 1);
            WG_FENCE();
#pragma unroll
            for (int k = 0; k < 4; k++) wgmma_ss_n192(acc, ad + k * 2, bd + k * 128, (kb | k) != 0);
            WG_COMMIT();
            if (kb > 0) {
                wg_wait<1>();
                if (lane == 0) mbar_arrive(empty + 8 * ((kb - 1) % K1_STAGES));
            }
        }
        wg_wait<0>();
        fence_regs(acc);
        TL(1);
        if (warp == 4) TX(16);
        mbar_wait(auxb, 0);
        if (warp == 4) TX(17);
        bar_sync(1, 256);
        const float2* s_rs = (const float2*)(smem + K1_RS);
        const float* s_cs = (const float*)(smem + K1_CS);
        const int g = lane >> 2, t = lane & 3;
        const int rl = wgi * 64 + ww * 16 + g;
        const float2 st0 = s_rs[rl], st1 = s_rs[rl + 8];
        const float QS = 0.25f * 1.4426950408889634f;
        const uint32_t stg = sb + ((lane >> 4) * 16 + wgi * 8 + ww * 2 + ((lane >> 3) & 1)) * 128 + (lane & 7) * 16;
        float2* s_np = (float2*)(smem + 49152) + (warp - 4) * 32 + lane;
#pragma unroll
        for (int hh = 0; hh < 12; hh++) {
            const int which = (nt * 192 + hh * 16) >> 9;
            const float sc = (which == 0) ? QS : 1.0f;
            const float a0 = st0.x * sc, b0 = st0.y * sc, a1 = st1.x * sc, b1 = st1.y * sc;
            const float2 c0 = *(const float2*)(s_cs + 16 * hh + 2 * t), c1 = *(const float2*)(s_cs + 16 * hh + 8 + 2 * t);
            const float* a = acc + 8 * hh;
            float v0 = fmaf(a0, a[0], b0 * c0.x), v1 = fmaf(a0, a[1], b0 * c0.y), v2 = fmaf(a1, a[2], b1 * c0.x), v3 = fmaf(a1, a[3], b1 * c0.y);
            float v4 = fmaf(a0, a[4], b0 * c1.x), v5 = fmaf(a0, a[5], b0 * c1.y), v6 = fmaf(a1, a[6], b1 * c1.x), v7 = fmaf(a1, a[7], b1 * c1.y);
            {
                const int head = ((nt * 192 + hh * 16) & 511) >> 4;
                uint32_t* o = (uint32_t*)g_qkv + ((size_t)((which * NH + head) * 2) * 256 + mb * 16 + wgi * 8 + ww * 2) * 32 + lane;
                o[0] = pack_bf16(v0, v1); o[32] = pack_bf16(v2, v3); o[8192] = pack_bf16(v4, v5); o[8192 + 32] = pack_bf16(v6, v7);
            }
            s_np[hh * 256] = make_float2(fmaf(v0, v0, fmaf(v1, v1, fmaf(v4, v4, v5 * v5))), fmaf(v2, v2, fmaf(v3, v3, fmaf(v6, v6, v7 * v7))));
        }
        fence_proxy_async();
        bar_arrive(2, 256 + 96);
        TL(2);
        TLDUMP;
    }
}

constexpr int AT_K = 0, AT_V = 65536, AT_ONES = 131072, AT_BAR = 163840, AT_SMEM = AT_BAR + 128;
#define POLY_MASK 0x7B5A

__device__ __forceinline__ uint32_t exp2_pair_poly(float x0, float x1) {
    uint32_t t0 = __float_as_uint(x0 + 32895.0f);
    uint32_t t1 = __float_as_uint(x1 + 32895.0f);
    uint32_t gd = __byte_perm(t0, t1, 0x6420);
    uint32_t wm = __byte_perm(t0, t1, 0x5612);
    uint32_t v = hfma2(gd, 0x71477147u, 0x354f354fu);
    uint32_t z = hmul2(v, gd);
    return (wm >> 1) + z;
}
__device__ __forceinline__ uint32_t exp2_pair_mufu(float x0, float x1) { return pack_bf16(ex2f(x0), ex2f(x1)); }
template <uint32_t MASK>
__device__ __forceinline__ void exp_blocks(const float (&s)[32], uint32_t (&p)[16]) {
#pragma unroll
    for (int b = 0; b < 8; b++) {
        if ((MASK >> b) & 1) {
            p[2 * b] = exp2_pair_poly(s[4 * b], s[4 * b + 1]);
            p[2 * b + 1] = exp2_pair_poly(s[4 * b + 2], s[4 * b + 3]);
        } else {
            p[2 * b] = exp2_pair_mufu(s[4 * b], s[4 * b + 1]);
            p[2 * b + 1] = exp2_pair_mufu(s[4 * b + 2], s[4 * b + 3]);
        }
    }
}
#define PV4(P) _Pragma("unroll") for (int i = 0; i < 4; i++) { pv_wgmma(o, P[4 * i], P[4 * i + 1], P[4 * i + 2], P[4 * i + 3], vd); vd += 16; }

__device__ __forceinline__ void attn_store(float (&o)[12], int row0, int head, int lane) {
    float l0 = __shfl_sync(0xffffffffu, o[8], lane & 28);
    float l1 = __shfl_sync(0xffffffffu, o[10], lane & 28);
    float r0 = 1.0f / l0, r1 = 1.0f / l1;
    uint32_t* op = (uint32_t*)g_ao;
    int mb = row0 >> 7, rg = (row0 & 127) >> 3;
    int kb = head >> 2, kc = (head & 3) * 2;
    size_t base = (((size_t)(mb * 8 + kb) * 8 + kc) * 16 + rg) * 32 + lane;
    op[base] = pack_bf16(o[0] * r0, o[1] * r0);
    op[base + 32] = pack_bf16(o[2] * r1, o[3] * r1);
    op[base + 16 * 32] = pack_bf16(o[4] * r0, o[5] * r0);
    op[base + 16 * 32 + 32] = pack_bf16(o[6] * r1, o[7] * r1);
}

__device__ __forceinline__ void attn_load_q(uint32_t (&q)[4], const __nv_bfloat16* gq, int row0, int lane) {
    const uint32_t* qp = (const uint32_t*)gq;
    int j0 = row0 >> 3;
    q[0] = __ldcg(qp + (0 * 256 + j0) * 32 + lane);
    q[1] = __ldcg(qp + (0 * 256 + j0 + 1) * 32 + lane);
    q[2] = __ldcg(qp + (1 * 256 + j0) * 32 + lane);
    q[3] = __ldcg(qp + (1 * 256 + j0 + 1) * 32 + lane);
}

__device__ __forceinline__ void attn_tile_safe(const uint32_t (&q)[4], uint64_t kd, uint64_t vd, int row0, int head, int lane) {
    float o[12];
#pragma unroll
    for (int i = 0; i < 12; i++) o[i] = 0.f;
    float m0 = -INFINITY, m1 = -INFINITY;
    fence_regs(o);
#pragma unroll 1
    for (int j = 0; j < 32; j++) {
        float s[32];
        uint32_t p[16];
        WG_FENCE();
        qk_wgmma_n64(s, q, kd); kd += 64;
        WG_COMMIT();
        wg_wait<0>();
        fence_regs(s);
        fence_regs(o);
        float x0 = m0, x1 = m1;
#pragma unroll
        for (int b = 0; b < 8; b++) {
            x0 = fmaxf(x0, fmaxf(s[4 * b], s[4 * b + 1]));
            x1 = fmaxf(x1, fmaxf(s[4 * b + 2], s[4 * b + 3]));
        }
        x0 = fmaxf(x0, __shfl_xor_sync(0xffffffffu, x0, 1)); x0 = fmaxf(x0, __shfl_xor_sync(0xffffffffu, x0, 2));
        x1 = fmaxf(x1, __shfl_xor_sync(0xffffffffu, x1, 1)); x1 = fmaxf(x1, __shfl_xor_sync(0xffffffffu, x1, 2));
        float al0 = ex2f(m0 - x0), al1 = ex2f(m1 - x1);
        m0 = x0; m1 = x1;
#pragma unroll
        for (int i = 0; i < 3; i++) { o[4 * i] *= al0; o[4 * i + 1] *= al0; o[4 * i + 2] *= al1; o[4 * i + 3] *= al1; }
#pragma unroll
        for (int b = 0; b < 8; b++) {
            p[2 * b] = exp2_pair_mufu(s[4 * b] - m0, s[4 * b + 1] - m0);
            p[2 * b + 1] = exp2_pair_mufu(s[4 * b + 2] - m1, s[4 * b + 3] - m1);
        }
        fence_regs(o);
        WG_FENCE();
        PV4(p);
        WG_COMMIT();
        wg_wait<0>();
        fence_regs(o);
    }
    attn_store(o, row0, head, lane);
}

__global__ void __launch_bounds__(512, 1)
attn_kernel(const __nv_bfloat16* __restrict__ wg_, const __nv_bfloat16* __restrict__ wu_,
            const __nv_bfloat16* __restrict__ wo_, const __nv_bfloat16* __restrict__ wd_) {
    extern __shared__ __align__(1024) unsigned char smem[];
    const uint32_t sb = smem_u32(smem);
    const int tid = threadIdx.x, wg = tid >> 7, warp = (tid >> 5) & 3, lane = tid & 31;
    TLDECL
    pdl_launch();
    if (blockIdx.x >= 128) {
        const int e = blockIdx.x - 128;
        const __nv_bfloat16* w = (e < 2) ? wg_ : wu_;
        float* red = (float*)smem;
        const int cgrp = tid & 127, kq = tid >> 7;
        if (cgrp < 112) {
            float s[8];
            colsum8(w, FF, (e & 1) * 896 + cgrp * 8, kq * 128, 128, s);
#pragma unroll
            for (int i = 0; i < 8; i++) red[kq * 896 + cgrp * 8 + i] = s[i];
        }
        __syncthreads();
        for (int c = tid; c < 896; c += 512)
            g_cs2[(e >> 1) * FF + (e & 1) * 896 + c] = red[c] + red[896 + c] + red[1792 + c] + red[2688 + c];
        if (tid < 32) {
            const char* p0 = (const char*)wo_ + e * (DM * DM * 2 / 4);
            for (int i = lane; i < 32; i += 32)
                asm volatile("cp.async.bulk.prefetch.L2.global [%0], %1;" :: "l"(p0 + i * 4096), "r"(4096) : "memory");
            const char* p1 = (const char*)wd_ + e * (FF * DM * 2 / 4);
            for (int i = lane; i < 112; i += 32)
                asm volatile("cp.async.bulk.prefetch.L2.global [%0], %1;" :: "l"(p1 + i * 4096), "r"(4096) : "memory");
        }
        return;
    }
    const int head = blockIdx.x >> 2, qq = blockIdx.x & 3;
    const __nv_bfloat16* gq = g_qkv + (size_t)head * (S_LEN * 16);
    const __nv_bfloat16* gk = g_qkv + (size_t)(NH + head) * (S_LEN * 16);
    const __nv_bfloat16* gv = g_qkv + (size_t)(2 * NH + head) * (S_LEN * 16);
    if (tid == 0) {
        for (int i = 0; i < 8; i++) mbar_init(sb + AT_BAR + 8 * i, 1);
        fence_barrier_init();
    }
    {
        uint4 one = make_uint4(0x00003F80u, 0, 0, 0);
#pragma unroll
        for (int i = 0; i < 4; i++) *(uint4*)(smem + AT_ONES + (i * 512 + tid) * 16) = one;
        fence_proxy_async();
    }
    __syncthreads();
    TL(3);
    pdl_wait();
    TL(4);
    auto load_kv = [&](int i) {
        uint32_t bar = sb + AT_BAR + 8 * i;
        mbar_expect(bar, 16384);
        bulk_g2s(sb + AT_K + i * 4096, gk + i * 2048, 4096, bar);
        bulk_g2s(sb + AT_K + 32768 + i * 4096, gk + 16384 + i * 2048, 4096, bar);
        bulk_g2s(sb + AT_V + i * 4096, gv + i * 2048, 4096, bar);
        bulk_g2s(sb + AT_V + 32768 + i * 4096, gv + 16384 + i * 2048, 4096, bar);
    };
    if (tid == 0) { load_kv(0); load_kv(1); }
    uint32_t q[4], q2[4];
    attn_load_q(q, gq, qq * 512 + wg * 64 + warp * 16, lane);
    attn_load_q(q2, gq, qq * 512 + (4 + wg) * 64 + warp * 16, lane);
    bool fast;
    {
        const float* nq = g_nrm + (0 * NH + head) * 128 + qq * 32;
        const float* nk = g_nrm + (1 * NH + head) * 128;
        const float* nv = g_nrm + (2 * NH + head) * 128;
        float4 k4 = __ldcg((const float4*)nk + lane), v4 = __ldcg((const float4*)nv + lane);
        float qm = warp_max(__ldcg(nq + lane));
        float km = warp_max(fmaxf(fmaxf(k4.x, k4.y), fmaxf(k4.z, k4.w)));
        float vm = warp_max(fmaxf(fmaxf(v4.x, v4.y), fmaxf(v4.z, v4.w)));
        fast = __all_sync(0xffffffffu, (qm * km <= 3500.0f) && (vm <= 1.0e24f));
    }
    TL(24);
    const uint64_t kdesc0 = make_desc(sb + AT_K, 32768, 128, 0);
    const uint64_t vdesc0 = make_desc(sb + AT_V, 128, 32768, 0);
    if (!fast) {
        if (tid == 0) for (int i = 2; i < 8; i++) load_kv(i);
        for (int i = 0; i < 8; i++) mbar_wait(sb + AT_BAR + 8 * i, 0);
#pragma unroll 1
        for (int tile = 0; tile < 2; tile++) {
            const int row0 = qq * 512 + (tile * 4 + wg) * 64 + warp * 16;
            attn_tile_safe(q, kdesc0, vdesc0, row0, head, lane);
#pragma unroll
            for (int i = 0; i < 4; i++) q[i] = q2[i];
        }
        return;
    }
#pragma unroll 1
    for (int tile = 0; tile < 2; tile++) {
        const int row0 = qq * 512 + (tile * 4 + wg) * 64 + warp * 16;
        float o[12];
#pragma unroll
        for (int i = 0; i < 12; i++) o[i] = 0.f;
        fence_regs(o);
        float sa[32];
        uint32_t pa[16];
        uint64_t kd = kdesc0, vd = vdesc0;
        if (tile == 0) { mbar_wait(sb + AT_BAR, 0); TL(25); }
        WG_FENCE();
        qk_wgmma_n64(sa, q, kd); kd += 64;
        WG_COMMIT();
#pragma unroll 1
        for (int jj = 0; jj < 8; jj++) {
            if (tile == 0 && jj < 7) {
                if (tid == 0 && jj < 6) load_kv(jj + 2);
                mbar_wait(sb + AT_BAR + 8 * (jj + 1), 0);
            }
            if (wg == 0 && warp == 0) TX(128 + tile * 8 + jj);
#pragma unroll
            for (int j = 0; j < 4; j++) {
                wg_wait<0>();
                fence_regs(sa);
                if (j & 1) exp_blocks<(POLY_MASK >> 8)>(sa, pa); else exp_blocks<(POLY_MASK & 255)>(sa, pa);
                WG_FENCE();
                PV4(pa);
                qk_wgmma_n64(sa, q, kd); kd += 64;
                WG_COMMIT();
            }
        }
        wg_wait<0>();
        fence_regs(o);
        fence_regs(sa);
        if (tile == 0) TL(26);
        attn_store(o, row0, head, lane);
#pragma unroll
        for (int i = 0; i < 4; i++) q[i] = q2[i];
    }
    TL(5);
    TLDUMP;
}

#define POLL_NS 40
#define FLAG_STRIDE 1
#define DELAYC 9
constexpr int F_R2 = 131072, F_X = 196608, F_BAR = 229376;
constexpr int F_RS = F_BAR + 256, F_CS = F_RS + 1024, F_SMEM = F_CS + 1792;
enum { B_FA = 0, B_HF = 4, B_BF = 8, B_BE = 11, B_CF = 14, B_CE = 20, B_ADONE = 26, B_BDONE = 27, B_XC = 28, B_PRDY = 29, B_AUX = 30, B_NUM = 31 };

__device__ __forceinline__ void st_async4(uint32_t dst, float a, float b, float c, float d, uint32_t bar) {
    asm volatile("st.async.weak.shared::cluster.mbarrier::complete_tx::bytes.v4.f32 [%0], {%1,%2,%3,%4}, [%5];"
                 :: "r"(dst), "f"(a), "f"(b), "f"(c), "f"(d), "r"(bar) : "memory");
}
__device__ __forceinline__ void poll_count(const unsigned int* p, unsigned int target) {
    int it = 0;
    while (ld_acquire(p) < target) { if (++it > (1 << 22)) __trap(); }
    asm volatile("fence.proxy.async.global;" ::: "memory");
}
__device__ __forceinline__ void tma2d_store(const CUtensorMap* m, uint32_t src, int c0, int c1) {
    asm volatile("cp.async.bulk.tensor.2d.global.shared::cta.bulk_group [%0, {%2, %3}], [%1];" :: "l"(m), "r"(src), "r"(c0), "r"(c1) : "memory");
}
__device__ __forceinline__ float2 h_row_stats(int row) {
    const float4* hp = (const float4*)(g_hstat + (size_t)row * 8);
    float4 a = __ldcg(hp), b = __ldcg(hp + 1), c = __ldcg(hp + 2), d = __ldcg(hp + 3);
    float mean = 0.125f * (a.x + a.z + b.x + b.z + c.x + c.z + d.x + d.z);
    float m2 = a.y + a.w + b.y + b.w + c.y + c.w + d.y + d.w;
    float e;
    e = a.x - mean; m2 = fmaf(64.f * e, e, m2); e = a.z - mean; m2 = fmaf(64.f * e, e, m2);
    e = b.x - mean; m2 = fmaf(64.f * e, e, m2); e = b.z - mean; m2 = fmaf(64.f * e, e, m2);
    e = c.x - mean; m2 = fmaf(64.f * e, e, m2); e = c.z - mean; m2 = fmaf(64.f * e, e, m2);
    e = d.x - mean; m2 = fmaf(64.f * e, e, m2); e = d.z - mean; m2 = fmaf(64.f * e, e, m2);
    return make_float2(rsqrtf(m2 * (1.0f / DM) + 1e-5f), -mean);
}
__device__ __forceinline__ int c_kblock(int i, int r) {
    if (i < 6) { const int e = 2 * i + r, m = e / 3, k = e - 3 * m; return 7 * m + (k == 2 ? 4 : k); }
    const int l = 2 * (i - 6) + r, m = l >> 2, k = l & 3;
    return 7 * m + (k < 2 ? 2 + k : 3 + k);
}
__device__ __forceinline__ uint32_t c_stage_a(int s, int ntB) { return s < 4 ? ((ntB + 2 * s) & 7) * 16384 : F_R2 + (s - 4) * 32768; }
__device__ __forceinline__ uint32_t c_stage_b(int s, int ntB) { return s < 4 ? ((ntB + 2 * s + 1) & 7) * 16384 : F_R2 + (s - 4) * 32768 + 16384; }
template <int R>
__device__ __forceinline__ void xchg(float (&acc)[64], float (&o)[32], uint32_t sb, unsigned char* smem, int bar, int ctid) {
    const uint32_t dst = mapa(sb + F_X + ctid * 16, 1 - R), rb = mapa(sb + F_BAR + 8 * bar, 1 - R);
#pragma unroll
    for (int q = 0; q < 8; q++) {
        const int j = (1 - R) * 32 + 4 * q;
        st_async4(dst + q * 4096, acc[j], acc[j + 1], acc[j + 2], acc[j + 3], rb);
    }
    mbar_wait_cluster(sb + F_BAR + 8 * bar, 0);
#pragma unroll
    for (int q = 0; q < 8; q++) {
        float4 v = *(const float4*)(smem + F_X + q * 4096 + ctid * 16);
        const int j = R * 32 + 4 * q;
        o[4 * q] = acc[j] + v.x; o[4 * q + 1] = acc[j + 1] + v.y; o[4 * q + 2] = acc[j + 2] + v.z; o[4 * q + 3] = acc[j + 3] + v.w;
    }
}

template <int NB, bool STAGE>
__device__ __forceinline__ void ffn_epilogue(const float* ag, const float* au, const float* s_cs, int cs_off, uint32_t* gp, uint32_t stg,
                                             float2 st0, float2 st1, int lane) {
    const int t = lane & 3;
    const float C1 = 0.7978845608028654f, C2 = 0.044715f * 0.7978845608028654f;
    const float k10 = st0.x * C1, k20 = st0.x * st0.x * st0.x * C2, k11 = st1.x * C1, k21 = st1.x * st1.x * st1.x * C2;
#pragma unroll
    for (int j2 = 0; j2 < NB / 2; j2++) {
        uint32_t pk[4];
#pragma unroll
        for (int jj = 0; jj < 2; jj++) {
            const int j = 2 * j2 + jj;
            const float2 cg = *(const float2*)(s_cs + cs_off + 8 * j + 2 * t);
            const float2 cu = *(const float2*)(s_cs + 224 + cs_off + 8 * j + 2 * t);
            float r[4];
#pragma unroll
            for (int e = 0; e < 4; e++) {
                const float nm = (e < 2) ? st0.y : st1.y, k1 = (e < 2) ? k10 : k11, k2 = (e < 2) ? k20 : k21;
                const float tg = fmaf(nm, (e & 1) ? cg.y : cg.x, ag[4 * j + e]);
                const float tu = fmaf(nm, (e & 1) ? cu.y : cu.x, au[4 * j + e]);
                const float th = tanh_fast(tg * fmaf(tg * tg, k2, k1));
                const float p = tg * tu;
                r[e] = fmaf(p, th, p);
            }
            pk[2 * jj] = pack_bf16(r[0], r[1]);
            pk[2 * jj + 1] = pack_bf16(r[2], r[3]);
        }
        if (STAGE) {
            stsm4(stg + j2 * 4096, pk[0], pk[1], pk[2], pk[3]);
        } else {
            gp[j2 * 1024] = pk[0]; gp[j2 * 1024 + 32] = pk[1]; gp[j2 * 1024 + 512] = pk[2]; gp[j2 * 1024 + 544] = pk[3];
        }
    }
}

__global__ void __cluster_dims__(2, 1, 1) __launch_bounds__(384, 1)
tail_kernel(const __grid_constant__ CUtensorMap tm_o, const __grid_constant__ CUtensorMap tm_g,
            const __grid_constant__ CUtensorMap tm_u, const __grid_constant__ CUtensorMap tm_d,
            const __grid_constant__ CUtensorMap tm_out, const __nv_bfloat16* __restrict__ x) {
    extern __shared__ __align__(1024) unsigned char smem[];
    const uint32_t sb = smem_u32(smem);
    const uint32_t bars = sb + F_BAR;
    const int tid = threadIdx.x, warp = __shfl_sync(0xffffffffu, tid >> 5, 0), lane = tid & 31;
    TLDECL
    TL(6);
    if (warp == 4) TX(200);
    const int cl = blockIdx.x >> 1, r = blockIdx.x & 1;
    const int mb = ((cl & 7) >> 1) * 4 + (cl >> 4), ntA = (cl & 1) * 2 + ((cl >> 3) & 1);
    const int nt = ntA * 2 + r;
    const int mbB = (mb & ~1) + r, ntB = (mb & 1) * 4 + ntA;
    if (tid == 0) {
#pragma unroll
        for (int i = 0; i < B_NUM; i++) {
            const int cnt = (i >= B_BE && i < B_BE + 3) ? 16 : (i == B_BDONE) ? DELAYC : ((i >= B_CE && i < B_CE + 6) || i == B_PRDY) ? 8 : (i == B_AUX || i == B_ADONE) ? 2 : 1;
            mbar_init(bars + 8 * i, cnt);
        }
        mbar_expect(bars + 8 * B_XC, 32768);
        fence_barrier_init();
        for (int i = 0; i < 8; i++) {
            const uint32_t bar = bars + 8 * (B_FA + (i >> 1));
            if (!(i & 1)) mbar_expect(bar, 49152);
            tma2d(sb + F_R2 + 32768 + i * 8192, &tm_o, nt * 64, i * 64, bar);
        }
    }
    TL(28);
    __syncthreads();
    TL(29);
    asm volatile("barrier.cluster.arrive.relaxed.aligned;" ::: "memory");
    TL(30);
    if (warp < 4) {
        asm volatile("setmaxnreg.dec.sync.aligned.u32 56;");
        if (warp == 0) TX(205);
        if (warp == 0) {
            if (lane == 0) {
                auto load_b = [&](int it) {
                    const int s = it % 3, pass = it >> 3, kb = (ntB + it) & 7;
                    const int ng = pass ? 3 : 4, c0 = ntB * 224 + pass * 128;
                    const uint32_t bar = bars + 8 * (B_BF + s), dst = sb + F_R2 + s * 32768 + r * ng * 4096;
                    mbar_expect(bar, ng * 8192);
                    for (int i = 0; i < ng; i++) tma2d_mc(dst + i * 4096, r ? &tm_u : &tm_g, c0 + i * 32, kb * 64, bar);
                };
                asm volatile("barrier.cluster.wait.acquire;" ::: "memory");
                pdl_wait();
                TL(16);
                for (int i = 0; i < 4; i++)
                    bulk_g2s_mc(sb + (2 * i + r) * 16384, g_ao + (size_t)(mb * 8 + 2 * i + r) * 8192, 16384, bars + 8 * (B_FA + i));
                load_b(0);
                if (blockIdx.x == 0)
                    for (int i = 0; i < 32; i++) g_cnt[i] = 0;
                mbar_wait_cluster(bars + 8 * B_ADONE, 0);
                load_b(1); load_b(2);
                auto load_c = [&](int i) {
                    const int s = i % 6, kb = c_kblock(i, r);
                    const uint32_t bar = bars + 8 * (B_CF + s), da = sb + c_stage_a(s, ntB), db = sb + c_stage_b(s, ntB);
                    mbar_expect(bar, 32768);
                    tma2d(db, &tm_d, ntA * 128, kb * 64, bar);
                    tma2d(db + 8192, &tm_d, ntA * 128 + 64, kb * 64, bar);
                    bulk_g2s(da, g_g + (size_t)(mb * 28 + kb) * 8192, 16384, bar);
                };
                for (int it = 3; it < 16; it++) {
                    mbar_wait_cluster(bars + 8 * (B_BE + it % 3), (it / 3 - 1) & 1);
                    load_b(it);
                    if (it == 12) { poll_count(&g_cnt2[mb], 8); load_c(0); }
                    if (it == 14) load_c(1);
                }
                mbar_wait_cluster(bars + 8 * (B_BE + 1), 0);
                load_c(2);
                mbar_wait(bars + 8 * B_BDONE, 0);
                for (int i = 3; i < 14; i++) {
                    if (i >= 6) mbar_wait(bars + 8 * (B_CE + i % 6), ((i / 6) - 1) & 1);
                    if (i == 6) { poll_count(&g_cnt2[16 + mb], 8); TL(18); }
                    load_c(i);
                }
            }
            else asm volatile("barrier.cluster.wait.acquire;" ::: "memory");
            TLDUMP;
        } else if (warp == 1) {
            asm volatile("barrier.cluster.wait.acquire.aligned;" ::: "memory");
            bar_sync(5, 288);
            if (lane == 0) { red_release(&g_cnt2[32 + (mb * 8 + nt) * FLAG_STRIDE]); TL(9); }
            __syncwarp();
            bar_sync(6, 288);
            if (lane == 0) red_release(&g_cnt2[32 + (mb * 8 + nt) * FLAG_STRIDE]);
            __syncwarp();
            bar_sync(1, 288);
            if (lane == 0) red_release(&g_cnt2[mbB]);
            __syncwarp();
            bar_sync(2, 288);
            if (lane == 0) {
                red_release(&g_cnt2[16 + mbB]);
                if (DELAYC == 9) mbar_arrive(bars + 8 * B_BDONE);
                TL(13);
            }
            __syncwarp();
            bar_sync(3, 288);
            if (lane == 0) {
                tma2d_store(&tm_out, sb, nt * 64, mb * 128);
                bulk_commit();
                bulk_wait_all();
                TL(15);
            }
            TLDUMP;
        } else {
            asm volatile("barrier.cluster.wait.acquire.aligned;" ::: "memory");
            pdl_wait();
            float2* s_rs = (float2*)(smem + F_RS);
            float* s_cs = (float*)(smem + F_CS);
            for (int c = tid - 64; c < 448; c += 64)
                s_cs[c] = __ldcg(&g_cs2[(c >= 224 ? FF - 224 : 0) + ntB * 224 + c]);
            if (tid == 96) {
                mbar_wait_cluster(bars + 8 * B_ADONE, 0);
                for (int i = 0; i < 8; i++) {
                    const int kb = (ntB + i) & 7;
                    const uint32_t bar = bars + 8 * (i < 4 ? B_HF + i : B_FA + i - 4);
                    poll_count(&g_cnt2[32 + (mbB * 8 + kb) * FLAG_STRIDE], 1);
                    mbar_expect(bar, 16384);
                    bulk_g2s(sb + kb * 16384, g_h + (size_t)(mbB * 8 + kb) * 8192, 16384, bar);
                }
            }
            __syncwarp();
            TL(17);
            for (int i = 0; i < 8; i++) mbar_wait(bars + 8 * (i < 4 ? B_HF + i : B_FA + i - 4), i < 4 ? 0 : 1);
            if (lane < 8) poll_count(&g_cnt2[32 + (mbB * 8 + lane) * FLAG_STRIDE], 2);
            __syncwarp();
            __syncwarp();
            for (int rr = tid - 64; rr < 128; rr += 64) {
                s_rs[rr] = h_row_stats(mbB * 128 + rr);
            }
            __syncwarp();
            if (lane == 0) mbar_arrive(bars + 8 * B_AUX);
            TLDUMP;
        }
    } else {
        asm volatile("setmaxnreg.inc.sync.aligned.u32 216;");
        if (warp == 4) TX(206);
        const int wgi = (warp >> 2) - 1, ww = warp & 3, ctid = tid - 128;
        const int g = lane >> 2, t = lane & 3;
        const int rl = wgi * 64 + ww * 16 + g, row = mb * 128 + rl;
        const int rgl = wgi * 8 + ww * 2;
        const float2* s_rs = (const float2*)(smem + F_RS);
        const float* s_cs = (const float*)(smem + F_CS);
        const uint32_t stl = ((lane >> 4) * 16 + rgl + ((lane >> 3) & 1)) * 128 + (lane & 7) * 16;
        uint32_t* hp = (uint32_t*)g_h + ((size_t)(mb * 8 + nt) * 8 * 16 + rgl) * 32 + lane;
        const uint32_t rbars = mapa(bars, 1 - r);
        TL(23);
        {
            uint32_t xr[16];
            const uint32_t* xp = (const uint32_t*)(x + (size_t)row * DM + nt * 64) + t;
#pragma unroll
            for (int j = 0; j < 8; j++) { xr[2 * j] = __ldg(xp + 4 * j); xr[2 * j + 1] = __ldg(xp + 8 * (DM / 2) + 4 * j); }
            float acc[32];
#pragma unroll 1
            for (int i = 0; i < 8; i++) {
                if (!(i & 1)) { mbar_wait(bars + 8 * (B_FA + (i >> 1)), 0); if (i == 0) TL(19); }
                uint64_t ad = make_desc(sb + i * 16384 + wgi * 1024, 2048, 128, 0);
                uint64_t bd = make_desc(sb + F_R2 + 32768 + i * 8192, 8192, 1024, 1);
                WG_FENCE();
#pragma unroll
                for (int k = 0; k < 4; k++) wgmma_ss_n64(acc, ad + k * 256, bd + k * 128, (i | k) != 0);
                WG_COMMIT();
            }
            wg_wait<0>();
            fence_regs(acc);
            TL(7);
            asm volatile("barrier.cluster.wait.acquire.aligned;" ::: "memory");
            bar_sync(4, 256);
            if (tid == 128) { mbar_arrive(bars + 8 * B_ADONE); mbar_arrive_remote(mapa(bars + 8 * B_ADONE, 1 - r)); }
            float v0[16], v1[16];
            float s0 = 0.f, s1 = 0.f;
#pragma unroll
            for (int j2 = 0; j2 < 4; j2++) {
                uint32_t u[4];
#pragma unroll
                for (int jj = 0; jj < 2; jj++) {
                    const int j = 2 * j2 + jj;
                    u[2 * jj] = pack_bf16(bf_lo(xr[2 * j]) + acc[4 * j], bf_hi(xr[2 * j]) + acc[4 * j + 1]);
                    u[2 * jj + 1] = pack_bf16(bf_lo(xr[2 * j + 1]) + acc[4 * j + 2], bf_hi(xr[2 * j + 1]) + acc[4 * j + 3]);
                    v0[2 * j] = bf_lo(u[2 * jj]); v0[2 * j + 1] = bf_hi(u[2 * jj]);
                    v1[2 * j] = bf_lo(u[2 * jj + 1]); v1[2 * j + 1] = bf_hi(u[2 * jj + 1]);
                    s0 += v0[2 * j] + v0[2 * j + 1];
                    s1 += v1[2 * j] + v1[2 * j + 1];
                }
                hp[j2 * 1024] = u[0]; hp[j2 * 1024 + 32] = u[1]; hp[j2 * 1024 + 512] = u[2]; hp[j2 * 1024 + 544] = u[3];
            }
            bar_arrive(5, 288);
            float m0 = s0 * (1.0f / 16), m1 = s1 * (1.0f / 16), q0 = 0.f, q1 = 0.f;
#pragma unroll
            for (int i = 0; i < 16; i++) {
                float d0 = v0[i] - m0, d1 = v1[i] - m1;
                q0 = fmaf(d0, d0, q0); q1 = fmaf(d1, d1, q1);
            }
#pragma unroll
            for (int st = 0; st < 2; st++) {
                float hn = st ? 16.f : 8.f;
                float om0 = __shfl_xor_sync(0xffffffffu, m0, 1 << st), oq0 = __shfl_xor_sync(0xffffffffu, q0, 1 << st);
                float om1 = __shfl_xor_sync(0xffffffffu, m1, 1 << st), oq1 = __shfl_xor_sync(0xffffffffu, q1, 1 << st);
                float d0 = om0 - m0, d1 = om1 - m1;
                q0 = q0 + oq0 + d0 * d0 * hn; q1 = q1 + oq1 + d1 * d1 * hn;
                m0 = 0.5f * (m0 + om0); m1 = 0.5f * (m1 + om1);
            }
            if (t == 0) {
                g_hstat[row * 8 + nt] = make_float2(m0, q0);
                g_hstat[(row + 8) * 8 + nt] = make_float2(m1, q1);
            }
            bar_arrive(6, 288);
            TL(8);
        }
        uint32_t* gp = (uint32_t*)g_g + (((size_t)mbB * 224 + ntB * 28) * 16 + rgl) * 32 + lane;
        {
            float ag[128];
#pragma unroll 1
            for (int kb = 0; kb < 8; kb++) {
                const int s = kb % 3;
                mbar_wait(bars + 8 * (kb < 4 ? B_HF + kb : B_FA + kb - 4), kb < 4 ? 0 : 1);
                mbar_wait(bars + 8 * (B_BF + s), (kb / 3) & 1);
                uint64_t ad = make_desc(sb + ((ntB + kb) & 7) * 16384 + wgi * 1024, 2048, 128, 0);
                uint64_t bd = make_desc(sb + F_R2 + s * 32768, 4096, 512, 2);
                WG_FENCE();
#pragma unroll
                for (int k = 0; k < 4; k++) wgmma_ss_n256(ag, ad + k * 256, bd + k * 64, (kb | k) != 0);
                WG_COMMIT();
                if (kb > 0) {
                    wg_wait<1>();
                    if (lane == 0) { mbar_arrive(bars + 8 * (B_BE + (kb - 1) % 3)); mbar_arrive_remote(rbars + 8 * (B_BE + (kb - 1) % 3)); }
                }
            }
            wg_wait<0>();
            if (lane == 0) { mbar_arrive(bars + 8 * (B_BE + 7 % 3)); mbar_arrive_remote(rbars + 8 * (B_BE + 7 % 3)); }
            fence_regs(ag);
            TL(10);
            mbar_wait(bars + 8 * B_AUX, 0);
            ffn_epilogue<16, false>(ag, ag + 64, s_cs, 0, gp, 0, s_rs[rl], s_rs[rl + 8], lane);
            bar_arrive(1, 288);
        }
        {
            float ag[96];
#pragma unroll 1
            for (int kb = 0; kb < 8; kb++) {
                const int it = 8 + kb, s = it % 3;
                mbar_wait(bars + 8 * (B_BF + s), (it / 3) & 1);
                uint64_t ad = make_desc(sb + ((ntB + kb) & 7) * 16384 + wgi * 1024, 2048, 128, 0);
                uint64_t bd = make_desc(sb + F_R2 + s * 32768, 4096, 512, 2);
                WG_FENCE();
#pragma unroll
                for (int k = 0; k < 4; k++) wgmma_ss_n192(ag, ad + k * 256, bd + k * 64, (kb | k) != 0);
                WG_COMMIT();
                if (kb > 0) {
                    wg_wait<1>();
                    if (lane == 0 && it < 15) { mbar_arrive(bars + 8 * (B_BE + (it - 1) % 3)); mbar_arrive_remote(rbars + 8 * (B_BE + (it - 1) % 3)); }
                }
            }
            wg_wait<0>();
            if (lane == 0) {
                mbar_arrive(bars + 8 * B_BDONE);
                mbar_arrive_remote(rbars + 8 * B_PRDY);
            }
            fence_regs(ag);
            TL(11);
            ffn_epilogue<12, false>(ag, ag + 48, s_cs, 128, gp + 16 * 512, 0, s_rs[rl], s_rs[rl + 8], lane);
            bar_arrive(2, 288);
            TL(12);
        }
        {
            uint32_t hr[16];
#pragma unroll
            for (int j = 0; j < 8; j++) { hr[2 * j] = __ldcg(hp + j * 512); hr[2 * j + 1] = __ldcg(hp + j * 512 + 32); }
            mbar_wait(bars + 8 * (B_CF + 0), 0);
            const float a0 = h_row_stats(row).x, a1 = h_row_stats(row + 8).x;
            float acc[64];
#pragma unroll 1
            for (int kb = 0; kb < 14; kb++) {
                const int s = kb % 6;
                mbar_wait(bars + 8 * (B_CF + s), (kb / 6) & 1);
                if (warp == 4) TX(96 + kb);
                uint64_t ad = make_desc(sb + c_stage_a(s, ntB) + wgi * 1024, 2048, 128, 0);
                uint64_t bd = make_desc(sb + c_stage_b(s, ntB), 8192, 1024, 1);
                WG_FENCE();
#pragma unroll
                for (int k = 0; k < 4; k++) wgmma_ss_n128(acc, ad + k * 256, bd + k * 128, (kb | k) != 0);
                WG_COMMIT();
                if (kb > 0) {
                    wg_wait<1>();
                    if (lane == 0) mbar_arrive(bars + 8 * (B_CE + (kb - 1) % 6));
                }
            }
            wg_wait<0>();
            fence_regs(acc);
            TL(14);
            mbar_wait_cluster(bars + 8 * B_PRDY, 0);
            float o[32];
            if (r == 0) xchg<0>(acc, o, sb, smem, B_XC, ctid); else xchg<1>(acc, o, sb, smem, B_XC, ctid);
            TL(22);
            bar_sync(4, 256);
            const float k0 = 0.5f * a0 * a0, k1 = 0.5f * a1 * a1;
            const int srow = wgi * 64 + ww * 16 + ((lane >> 3) & 1) * 8 + (lane & 7);
#pragma unroll
            for (int j2 = 0; j2 < 4; j2++) {
                uint32_t u[4];
#pragma unroll
                for (int jj = 0; jj < 2; jj++) {
                    const int j = 2 * j2 + jj;
                    u[2 * jj] = pack_bf16(fmaf(k0, o[4 * j], bf_lo(hr[2 * j])), fmaf(k0, o[4 * j + 1], bf_hi(hr[2 * j])));
                    u[2 * jj + 1] = pack_bf16(fmaf(k1, o[4 * j + 2], bf_lo(hr[2 * j + 1])), fmaf(k1, o[4 * j + 3], bf_hi(hr[2 * j + 1])));
                }
                const int chunk = 2 * j2 + (lane >> 4);
                stsm4(sb + srow * 128 + ((chunk ^ (lane & 7)) * 16), u[0], u[1], u[2], u[3]);
            }
            fence_proxy_async();
            bar_arrive(3, 288);
            TLDUMP;
        }
    }
}

typedef CUresult (*EncodeFn)(CUtensorMap*, CUtensorMapDataType, cuuint32_t, void*, const cuuint64_t*, const cuuint64_t*,
                             const cuuint32_t*, const cuuint32_t*, CUtensorMapInterleave, CUtensorMapSwizzle,
                             CUtensorMapL2promotion, CUtensorMapFloatOOBfill);

void encode(EncodeFn fn, CUtensorMap* m, const void* ptr, int rank, const cuuint64_t* dims, const cuuint64_t* strides,
            const cuuint32_t* box, CUtensorMapSwizzle swz) {
    cuuint32_t es[3] = {1, 1, 1};
    fn(m, CU_TENSOR_MAP_DATA_TYPE_BFLOAT16, rank, (void*)ptr, dims, strides, box, es, CU_TENSOR_MAP_INTERLEAVE_NONE, swz,
       CU_TENSOR_MAP_L2_PROMOTION_L2_256B, CU_TENSOR_MAP_FLOAT_OOB_FILL_NONE);
}

template <typename... KArgs, typename... Args>
void launch(void (*kern)(KArgs...), int grid, int block, int smem, bool pdl, Args... args) {
    cudaLaunchConfig_t cfg = {};
    cfg.gridDim = dim3(grid); cfg.blockDim = dim3(block); cfg.dynamicSmemBytes = smem;
    cfg.stream = cudaStreamPerThread;
    cudaLaunchAttribute at[1];
    at[0].id = cudaLaunchAttributeProgrammaticStreamSerialization;
    at[0].val.programmaticStreamSerializationAllowed = 1;
    cfg.attrs = at; cfg.numAttrs = pdl ? 1 : 0;
    cudaLaunchKernelEx(&cfg, kern, KArgs(args)...);
}

}

extern "C" void kernel_launch(void* const* d_in, const int* in_sizes, int n_in, void* d_out, int out_size) {
    const __nv_bfloat16* x = (const __nv_bfloat16*)d_in[0];
    const __nv_bfloat16* wqkv = (const __nv_bfloat16*)d_in[1];
    const __nv_bfloat16* wo = (const __nv_bfloat16*)d_in[2];
    const __nv_bfloat16* wgate = (const __nv_bfloat16*)d_in[4];
    const __nv_bfloat16* wup = (const __nv_bfloat16*)d_in[5];
    const __nv_bfloat16* wdown = (const __nv_bfloat16*)d_in[6];
    __nv_bfloat16* out = (__nv_bfloat16*)d_out;

    static CUtensorMap tm_x, tm_wqkv, tm_wo, tm_wg, tm_wu, tm_wd, tm_out;
    static const void* cached[7] = {nullptr, nullptr, nullptr, nullptr, nullptr, nullptr, nullptr};
    if (cached[0] != x || cached[1] != wqkv || cached[2] != wo || cached[3] != wgate || cached[4] != wup || cached[5] != wdown || cached[6] != out) {
        void* fp = nullptr;
        cudaDriverEntryPointQueryResult qr;
        cudaGetDriverEntryPoint("cuTensorMapEncodeTiled", &fp, cudaEnableDefault, &qr);
        EncodeFn fn = (EncodeFn)fp;
        { cuuint64_t d[2] = {512, 2048}, s[1] = {1024}; cuuint32_t b[2] = {64, 128};
          encode(fn, &tm_x, x, 2, d, s, b, CU_TENSOR_MAP_SWIZZLE_128B);
          encode(fn, &tm_out, out, 2, d, s, b, CU_TENSOR_MAP_SWIZZLE_128B); }
        { cuuint64_t d[3] = {64, 512, 24}, s[2] = {3072, 128}; cuuint32_t b[3] = {64, 64, 3};
          encode(fn, &tm_wqkv, wqkv, 3, d, s, b, CU_TENSOR_MAP_SWIZZLE_128B); }
        { cuuint64_t d[2] = {512, 512}, s[1] = {1024}; cuuint32_t b[2] = {64, 64};
          encode(fn, &tm_wo, wo, 2, d, s, b, CU_TENSOR_MAP_SWIZZLE_128B); }
        { cuuint64_t d[2] = {1792, 512}, s[1] = {3584}; cuuint32_t b[2] = {32, 64};
          encode(fn, &tm_wg, wgate, 2, d, s, b, CU_TENSOR_MAP_SWIZZLE_64B);
          encode(fn, &tm_wu, wup, 2, d, s, b, CU_TENSOR_MAP_SWIZZLE_64B); }
        { cuuint64_t d[2] = {512, 1792}, s[1] = {1024}; cuuint32_t b[2] = {64, 64};
          encode(fn, &tm_wd, wdown, 2, d, s, b, CU_TENSOR_MAP_SWIZZLE_128B); }
        cudaFuncSetAttribute(qkv_kernel, cudaFuncAttributeMaxDynamicSharedMemorySize, F_SMEM);
        cudaFuncSetAttribute(qkv_kernel, cudaFuncAttributePreferredSharedMemoryCarveout, 100);
        cudaFuncSetAttribute(attn_kernel, cudaFuncAttributeMaxDynamicSharedMemorySize, F_SMEM);
        cudaFuncSetAttribute(attn_kernel, cudaFuncAttributePreferredSharedMemoryCarveout, 100);
        cudaFuncSetAttribute(tail_kernel, cudaFuncAttributeMaxDynamicSharedMemorySize, F_SMEM);
        cudaFuncSetAttribute(tail_kernel, cudaFuncAttributePreferredSharedMemoryCarveout, 100);
        cached[0] = x; cached[1] = wqkv; cached[2] = wo; cached[3] = wgate; cached[4] = wup; cached[5] = wdown; cached[6] = out;
    }
    launch(qkv_kernel, 128, 384, F_SMEM, false, tm_x, tm_wqkv, x, wqkv);
    launch(attn_kernel, 132, 512, F_SMEM, true, wgate, wup, wo, wdown);
    launch(tail_kernel, 128, 384, F_SMEM, true, tm_wo, tm_wg, tm_wu, tm_wd, tm_out, x);
}
```

```cpp
#include <cuda_runtime.h>
#include <cuda_bf16.h>
#include <cuda.h>
#include <stdint.h>

#define K1_DIRECT
namespace {

constexpr int S_LEN = 2048, DM = 512, NH = 32, FF = 1792;

__device__ __align__(1024) __nv_bfloat16 g_qkv[3 * NH * S_LEN * 16];
__device__ __align__(1024) __nv_bfloat16 g_ao[S_LEN * DM];
__device__ __align__(1024) __nv_bfloat16 g_h[S_LEN * DM];
__device__ __align__(1024) __nv_bfloat16 g_g[S_LEN * FF];
__device__ __align__(16) float2 g_rowstat1[S_LEN];
__device__ float g_cs1_part[16 * 1536];
__device__ unsigned int g_cnt[32];
__device__ unsigned int g_cnt2[160];
__device__ float g_nrm[3 * NH * 128];
__device__ float2 g_hstat[S_LEN * 8];
__device__ float g_cs2[2 * FF];

#define TLDECL
#define TL(slot)
#define TLDUMP
#define TX(slot)
__device__ __forceinline__ uint32_t smem_u32(const void* p) { return (uint32_t)__cvta_generic_to_shared(p); }
__device__ __forceinline__ void mbar_init(uint32_t a, int c) { asm volatile("mbarrier.init.shared.b64 [%0], %1;" :: "r"(a), "r"(c)); }
__device__ __forceinline__ void mbar_expect(uint32_t a, int bytes) { asm volatile("mbarrier.arrive.expect_tx.shared.b64 _, [%0], %1;" :: "r"(a), "r"(bytes) : "memory"); }
__device__ __forceinline__ void mbar_arrive(uint32_t a) { asm volatile("mbarrier.arrive.shared.b64 _, [%0];" :: "r"(a) : "memory"); }
__device__ __forceinline__ void mbar_wait(uint32_t a, int parity) {
    uint32_t done;
    int it = 0;
    do {
        asm volatile("{\n.reg .pred p;\nmbarrier.try_wait.parity.shared.b64 p, [%1], %2;\nselp.u32 %0, 1, 0, p;\n}"
                     : "=r"(done) : "r"(a), "r"(parity) : "memory");
        if (++it > (1 << 24)) __trap();
    } while (!done);
}
__device__ __forceinline__ void bulk_g2s(uint32_t dst, const void* src, int bytes, uint32_t bar) {
    asm volatile("cp.async.bulk.shared::cluster.global.mbarrier::complete_tx::bytes [%0], [%1], %2, [%3];"
                 :: "r"(dst), "l"(src), "r"(bytes), "r"(bar) : "memory");
}
__device__ __forceinline__ void tma2d(uint32_t dst, const CUtensorMap* m, int c0, int c1, uint32_t bar) {
    asm volatile("cp.async.bulk.tensor.2d.shared::cluster.global.mbarrier::complete_tx::bytes [%0], [%1, {%3, %4}], [%2];"
                 :: "r"(dst), "l"(m), "r"(bar), "r"(c0), "r"(c1) : "memory");
}
__device__ __forceinline__ void tma3d(uint32_t dst, const CUtensorMap* m, int c0, int c1, int c2, uint32_t bar) {
    asm volatile("cp.async.bulk.tensor.3d.shared::cluster.global.mbarrier::complete_tx::bytes [%0], [%1, {%3, %4, %5}], [%2];"
                 :: "r"(dst), "l"(m), "r"(bar), "r"(c0), "r"(c1), "r"(c2) : "memory");
}
__device__ __forceinline__ void prefetch_tmap(const CUtensorMap* m) { asm volatile("prefetch.tensormap [%0];" :: "l"(m) : "memory"); }
__device__ __forceinline__ void pdl_wait() { asm volatile("griddepcontrol.wait;" ::: "memory"); }
__device__ __forceinline__ void pdl_launch() { asm volatile("griddepcontrol.launch_dependents;" ::: "memory"); }
__device__ __forceinline__ void fence_barrier_init() { asm volatile("fence.mbarrier_init.release.cluster;" ::: "memory"); }
__device__ __forceinline__ void fence_proxy_async() { asm volatile("fence.proxy.async.shared::cta;" ::: "memory"); }
__device__ __forceinline__ uint64_t make_desc(uint32_t saddr, uint32_t lbo, uint32_t sbo, uint32_t swz) {
    return (uint64_t)((saddr & 0x3FFFF) >> 4) | ((uint64_t)((lbo & 0x3FFFF) >> 4) << 16) |
           ((uint64_t)((sbo & 0x3FFFF) >> 4) << 32) | ((uint64_t)swz << 62);
}
#define WG_FENCE() asm volatile("wgmma.fence.sync.aligned;" ::: "memory")
#define WG_COMMIT() asm volatile("wgmma.commit_group.sync.aligned;" ::: "memory")
template <int N> __device__ __forceinline__ void wg_wait() { asm volatile("wgmma.wait_group.sync.aligned %0;" :: "n"(N) : "memory"); }
template <int N> __device__ __forceinline__ void fence_regs(float (&d)[N]) {
#pragma unroll
    for (int i = 0; i < N; i++) asm volatile("" : "+f"(d[i]) :: "memory");
}
__device__ __forceinline__ float ex2f(float x) { float y; asm("ex2.approx.ftz.f32 %0, %1;" : "=f"(y) : "f"(x)); return y; }
__device__ __forceinline__ float tanh_fast(float x) { float y; asm("tanh.approx.f32 %0, %1;" : "=f"(y) : "f"(x)); return y; }
__device__ __forceinline__ uint32_t pack_bf16(float lo, float hi) { uint32_t r; asm("cvt.rn.bf16x2.f32 %0, %1, %2;" : "=r"(r) : "f"(hi), "f"(lo)); return r; }
__device__ __forceinline__ float bf_lo(uint32_t u) { return __uint_as_float(u << 16); }
__device__ __forceinline__ float bf_hi(uint32_t u) { return __uint_as_float(u & 0xFFFF0000u); }
__device__ __forceinline__ uint32_t hfma2(uint32_t a, uint32_t b, uint32_t c) { uint32_t r; asm("fma.rn.f16x2 %0, %1, %2, %3;" : "=r"(r) : "r"(a), "r"(b), "r"(c)); return r; }
__device__ __forceinline__ uint32_t hmul2(uint32_t a, uint32_t b) { uint32_t r; asm("mul.rn.f16x2 %0, %1, %2;" : "=r"(r) : "r"(a), "r"(b)); return r; }
__device__ __forceinline__ unsigned int ld_acquire(const unsigned int* p) { unsigned int v; asm volatile("ld.acquire.gpu.u32 %0, [%1];" : "=r"(v) : "l"(p) : "memory"); return v; }
__device__ __forceinline__ void red_release(unsigned int* p) { asm volatile("red.release.gpu.global.add.u32 [%0], 1;" :: "l"(p) : "memory"); }
__device__ __forceinline__ void stsm4(uint32_t addr, uint32_t a, uint32_t b, uint32_t c, uint32_t d) {
    asm volatile("stmatrix.sync.aligned.m8n8.x4.shared.b16 [%0], {%1,%2,%3,%4};" :: "r"(addr), "r"(a), "r"(b), "r"(c), "r"(d) : "memory");
}
__device__ __forceinline__ void bulk_s2g(void* dst, uint32_t src, int bytes) {
    asm volatile("cp.async.bulk.global.shared::cta.bulk_group [%0], [%1], %2;" :: "l"(dst), "r"(src), "r"(bytes) : "memory");
}
__device__ __forceinline__ void bulk_commit() { asm volatile("cp.async.bulk.commit_group;" ::: "memory"); }
__device__ __forceinline__ void bulk_wait_all() { asm volatile("cp.async.bulk.wait_group 0;" ::: "memory"); }
__device__ __forceinline__ void bulk_wait_read() { asm volatile("cp.async.bulk.wait_group.read 0;" ::: "memory"); }
__device__ __forceinline__ void bar_sync(int id, int n) { asm volatile("bar.sync %0, %1;" :: "r"(id), "r"(n) : "memory"); }
__device__ __forceinline__ void bar_arrive(int id, int n) { asm volatile("bar.arrive %0, %1;" :: "r"(id), "r"(n) : "memory"); }
__device__ __forceinline__ float warp_sum(float v) {
#pragma unroll
    for (int o = 16; o; o >>= 1) v += __shfl_xor_sync(0xffffffffu, v, o);
    return v;
}
__device__ __forceinline__ float warp_max(float v) {
#pragma unroll
    for (int o = 16; o; o >>= 1) v = fmaxf(v, __shfl_xor_sync(0xffffffffu, v, o));
    return v;
}

__device__ __forceinline__ void wgmma_ss_n64(float (&d)[32], uint64_t adesc, uint64_t bdesc, int scale_d) {
    asm volatile("{\n.reg .pred p;\nsetp.ne.b32 p, %34, 0;\n"
      "wgmma.mma_async.sync.aligned.m64n64k16.f32.bf16.bf16 {%0,%1,%2,%3,%4,%5,%6,%7,%8,%9,%10,%11,%12,%13,%14,%15,%16,%17,%18,%19,%20,%21,%22,%23,%24,%25,%26,%27,%28,%29,%30,%31}, %32, %33, p, 1, 1, 0, 1;\n}"
      : "+f"(d[0]), "+f"(d[1]), "+f"(d[2]), "+f"(d[3]), "+f"(d[4]), "+f"(d[5]), "+f"(d[6]), "+f"(d[7]), "+f"(d[8]), "+f"(d[9]), "+f"(d[10]), "+f"(d[11]), "+f"(d[12]), "+f"(d[13]), "+f"(d[14]), "+f"(d[15]), "+f"(d[16]), "+f"(d[17]), "+f"(d[18]), "+f"(d[19]), "+f"(d[20]), "+f"(d[21]), "+f"(d[22]), "+f"(d[23]), "+f"(d[24]), "+f"(d[25]), "+f"(d[26]), "+f"(d[27]), "+f"(d[28]), "+f"(d[29]), "+f"(d[30]), "+f"(d[31])
      : "l"(adesc), "l"(bdesc), "r"(scale_d));
}
__device__ __forceinline__ void wgmma_ss_n128(float (&d)[64], uint64_t adesc, uint64_t bdesc, int scale_d) {
    asm volatile("{\n.reg .pred p;\nsetp.ne.b32 p, %66, 0;\n"
      "wgmma.mma_async.sync.aligned.m64n128k16.f32.bf16.bf16 {%0,%1,%2,%3,%4,%5,%6,%7,%8,%9,%10,%11,%12,%13,%14,%15,%16,%17,%18,%19,%20,%21,%22,%23,%24,%25,%26,%27,%28,%29,%30,%31,%32,%33,%34,%35,%36,%37,%38,%39,%40,%41,%42,%43,%44,%45,%46,%47,%48,%49,%50,%51,%52,%53,%54,%55,%56,%57,%58,%59,%60,%61,%62,%63}, %64, %65, p, 1, 1, 0, 1;\n}"
      : "+f"(d[0]), "+f"(d[1]), "+f"(d[2]), "+f"(d[3]), "+f"(d[4]), "+f"(d[5]), "+f"(d[6]), "+f"(d[7]), "+f"(d[8]), "+f"(d[9]), "+f"(d[10]), "+f"(d[11]), "+f"(d[12]), "+f"(d[13]), "+f"(d[14]), "+f"(d[15]), "+f"(d[16]), "+f"(d[17]), "+f"(d[18]), "+f"(d[19]), "+f"(d[20]), "+f"(d[21]), "+f"(d[22]), "+f"(d[23]), "+f"(d[24]), "+f"(d[25]), "+f"(d[26]), "+f"(d[27]), "+f"(d[28]), "+f"(d[29]), "+f"(d[30]), "+f"(d[31]), "+f"(d[32]), "+f"(d[33]), "+f"(d[34]), "+f"(d[35]), "+f"(d[36]), "+f"(d[37]), "+f"(d[38]), "+f"(d[39]), "+f"(d[40]), "+f"(d[41]), "+f"(d[42]), "+f"(d[43]), "+f"(d[44]), "+f"(d[45]), "+f"(d[46]), "+f"(d[47]), "+f"(d[48]), "+f"(d[49]), "+f"(d[50]), "+f"(d[51]), "+f"(d[52]), "+f"(d[53]), "+f"(d[54]), "+f"(d[55]), "+f"(d[56]), "+f"(d[57]), "+f"(d[58]), "+f"(d[59]), "+f"(d[60]), "+f"(d[61]), "+f"(d[62]), "+f"(d[63])
      : "l"(adesc), "l"(bdesc), "r"(scale_d));
}
__device__ __forceinline__ void wgmma_ss_n192(float (&d)[96], uint64_t adesc, uint64_t bdesc, int scale_d) {
    asm volatile("{\n.reg .pred p;\nsetp.ne.b32 p, %98, 0;\n"
      "wgmma.mma_async.sync.aligned.m64n192k16.f32.bf16.bf16 {%0,%1,%2,%3,%4,%5,%6,%7,%8,%9,%10,%11,%12,%13,%14,%15,%16,%17,%18,%19,%20,%21,%22,%23,%24,%25,%26,%27,%28,%29,%30,%31,%32,%33,%34,%35,%36,%37,%38,%39,%40,%41,%42,%43,%44,%45,%46,%47,%48,%49,%50,%51,%52,%53,%54,%55,%56,%57,%58,%59,%60,%61,%62,%63,%64,%65,%66,%67,%68,%69,%70,%71,%72,%73,%74,%75,%76,%77,%78,%79,%80,%81,%82,%83,%84,%85,%86,%87,%88,%89,%90,%91,%92,%93,%94,%95}, %96, %97, p, 1, 1, 0, 1;\n}"
      : "+f"(d[0]), "+f"(d[1]), "+f"(d[2]), "+f"(d[3]), "+f"(d[4]), "+f"(d[5]), "+f"(d[6]), "+f"(d[7]), "+f"(d[8]), "+f"(d[9]), "+f"(d[10]), "+f"(d[11]), "+f"(d[12]), "+f"(d[13]), "+f"(d[14]), "+f"(d[15]), "+f"(d[16]), "+f"(d[17]), "+f"(d[18]), "+f"(d[19]), "+f"(d[20]), "+f"(d[21]), "+f"(d[22]), "+f"(d[23]), "+f"(d[24]), "+f"(d[25]), "+f"(d[26]), "+f"(d[27]), "+f"(d[28]), "+f"(d[29]), "+f"(d[30]), "+f"(d[31]), "+f"(d[32]), "+f"(d[33]), "+f"(d[34]), "+f"(d[35]), "+f"(d[36]), "+f"(d[37]), "+f"(d[38]), "+f"(d[39]), "+f"(d[40]), "+f"(d[41]), "+f"(d[42]), "+f"(d[43]), "+f"(d[44]), "+f"(d[45]), "+f"(d[46]), "+f"(d[47]), "+f"(d[48]), "+f"(d[49]), "+f"(d[50]), "+f"(d[51]), "+f"(d[52]), "+f"(d[53]), "+f"(d[54]), "+f"(d[55]), "+f"(d[56]), "+f"(d[57]), "+f"(d[58]), "+f"(d[59]), "+f"(d[60]), "+f"(d[61]), "+f"(d[62]), "+f"(d[63]), "+f"(d[64]), "+f"(d[65]), "+f"(d[66]), "+f"(d[67]), "+f"(d[68]), "+f"(d[69]), "+f"(d[70]), "+f"(d[71]), "+f"(d[72]), "+f"(d[73]), "+f"(d[74]), "+f"(d[75]), "+f"(d[76]), "+f"(d[77]), "+f"(d[78]), "+f"(d[79]), "+f"(d[80]), "+f"(d[81]), "+f"(d[82]), "+f"(d[83]), "+f"(d[84]), "+f"(d[85]), "+f"(d[86]), "+f"(d[87]), "+f"(d[88]), "+f"(d[89]), "+f"(d[90]), "+f"(d[91]), "+f"(d[92]), "+f"(d[93]), "+f"(d[94]), "+f"(d[95])
      : "l"(adesc), "l"(bdesc), "r"(scale_d));
}
__device__ __forceinline__ void wgmma_ss_n256(float (&d)[128], uint64_t adesc, uint64_t bdesc, int scale_d) {
    asm volatile("{\n.reg .pred p;\nsetp.ne.b32 p, %130, 0;\n"
      "wgmma.mma_async.sync.aligned.m64n256k16.f32.bf16.bf16 {%0,%1,%2,%3,%4,%5,%6,%7,%8,%9,%10,%11,%12,%13,%14,%15,%16,%17,%18,%19,%20,%21,%22,%23,%24,%25,%26,%27,%28,%29,%30,%31,%32,%33,%34,%35,%36,%37,%38,%39,%40,%41,%42,%43,%44,%45,%46,%47,%48,%49,%50,%51,%52,%53,%54,%55,%56,%57,%58,%59,%60,%61,%62,%63,%64,%65,%66,%67,%68,%69,%70,%71,%72,%73,%74,%75,%76,%77,%78,%79,%80,%81,%82,%83,%84,%85,%86,%87,%88,%89,%90,%91,%92,%93,%94,%95,%96,%97,%98,%99,%100,%101,%102,%103,%104,%105,%106,%107,%108,%109,%110,%111,%112,%113,%114,%115,%116,%117,%118,%119,%120,%121,%122,%123,%124,%125,%126,%127}, %128, %129, p, 1, 1, 0, 1;\n}"
      : "+f"(d[0]), "+f"(d[1]), "+f"(d[2]), "+f"(d[3]), "+f"(d[4]), "+f"(d[5]), "+f"(d[6]), "+f"(d[7]), "+f"(d[8]), "+f"(d[9]), "+f"(d[10]), "+f"(d[11]), "+f"(d[12]), "+f"(d[13]), "+f"(d[14]), "+f"(d[15]), "+f"(d[16]), "+f"(d[17]), "+f"(d[18]), "+f"(d[19]), "+f"(d[20]), "+f"(d[21]), "+f"(d[22]), "+f"(d[23]), "+f"(d[24]), "+f"(d[25]), "+f"(d[26]), "+f"(d[27]), "+f"(d[28]), "+f"(d[29]), "+f"(d[30]), "+f"(d[31]), "+f"(d[32]), "+f"(d[33]), "+f"(d[34]), "+f"(d[35]), "+f"(d[36]), "+f"(d[37]), "+f"(d[38]), "+f"(d[39]), "+f"(d[40]), "+f"(d[41]), "+f"(d[42]), "+f"(d[43]), "+f"(d[44]), "+f"(d[45]), "+f"(d[46]), "+f"(d[47]), "+f"(d[48]), "+f"(d[49]), "+f"(d[50]), "+f"(d[51]), "+f"(d[52]), "+f"(d[53]), "+f"(d[54]), "+f"(d[55]), "+f"(d[56]), "+f"(d[57]), "+f"(d[58]), "+f"(d[59]), "+f"(d[60]), "+f"(d[61]), "+f"(d[62]), "+f"(d[63]), "+f"(d[64]), "+f"(d[65]), "+f"(d[66]), "+f"(d[67]), "+f"(d[68]), "+f"(d[69]), "+f"(d[70]), "+f"(d[71]), "+f"(d[72]), "+f"(d[73]), "+f"(d[74]), "+f"(d[75]), "+f"(d[76]), "+f"(d[77]), "+f"(d[78]), "+f"(d[79]), "+f"(d[80]), "+f"(d[81]), "+f"(d[82]), "+f"(d[83]), "+f"(d[84]), "+f"(d[85]), "+f"(d[86]), "+f"(d[87]), "+f"(d[88]), "+f"(d[89]), "+f"(d[90]), "+f"(d[91]), "+f"(d[92]), "+f"(d[93]), "+f"(d[94]), "+f"(d[95]), "+f"(d[96]), "+f"(d[97]), "+f"(d[98]), "+f"(d[99]), "+f"(d[100]), "+f"(d[101]), "+f"(d[102]), "+f"(d[103]), "+f"(d[104]), "+f"(d[105]), "+f"(d[106]), "+f"(d[107]), "+f"(d[108]), "+f"(d[109]), "+f"(d[110]), "+f"(d[111]), "+f"(d[112]), "+f"(d[113]), "+f"(d[114]), "+f"(d[115]), "+f"(d[116]), "+f"(d[117]), "+f"(d[118]), "+f"(d[119]), "+f"(d[120]), "+f"(d[121]), "+f"(d[122]), "+f"(d[123]), "+f"(d[124]), "+f"(d[125]), "+f"(d[126]), "+f"(d[127])
      : "l"(adesc), "l"(bdesc), "r"(scale_d));
}
__device__ __forceinline__ void qk_wgmma_n64(float (&d)[32], const uint32_t (&a)[4], uint64_t desc) {
    asm volatile("wgmma.mma_async.sync.aligned.m64n64k16.f32.bf16.bf16 {%0,%1,%2,%3,%4,%5,%6,%7,%8,%9,%10,%11,%12,%13,%14,%15,%16,%17,%18,%19,%20,%21,%22,%23,%24,%25,%26,%27,%28,%29,%30,%31}, {%32,%33,%34,%35}, %36, 0, 1, 1, 0;"
      : "=f"(d[0]), "=f"(d[1]), "=f"(d[2]), "=f"(d[3]), "=f"(d[4]), "=f"(d[5]), "=f"(d[6]), "=f"(d[7]), "=f"(d[8]), "=f"(d[9]), "=f"(d[10]), "=f"(d[11]), "=f"(d[12]), "=f"(d[13]), "=f"(d[14]), "=f"(d[15]), "=f"(d[16]), "=f"(d[17]), "=f"(d[18]), "=f"(d[19]), "=f"(d[20]), "=f"(d[21]), "=f"(d[22]), "=f"(d[23]), "=f"(d[24]), "=f"(d[25]), "=f"(d[26]), "=f"(d[27]), "=f"(d[28]), "=f"(d[29]), "=f"(d[30]), "=f"(d[31])
      : "r"(a[0]), "r"(a[1]), "r"(a[2]), "r"(a[3]), "l"(desc));
}

__device__ __forceinline__ void pv_wgmma(float (&d)[12], uint32_t a0, uint32_t a1, uint32_t a2, uint32_t a3, uint64_t desc) {
    asm volatile("wgmma.mma_async.sync.aligned.m64n24k16.f32.bf16.bf16 {%0,%1,%2,%3,%4,%5,%6,%7,%8,%9,%10,%11}, {%12,%13,%14,%15}, %16, 1, 1, 1, 1;"
      : "+f"(d[0]), "+f"(d[1]), "+f"(d[2]), "+f"(d[3]), "+f"(d[4]), "+f"(d[5]), "+f"(d[6]), "+f"(d[7]), "+f"(d[8]), "+f"(d[9]), "+f"(d[10]), "+f"(d[11])
      : "r"(a0), "r"(a1), "r"(a2), "r"(a3), "l"(desc));
}

__device__ __forceinline__ uint32_t mapa(uint32_t a, uint32_t rank) { uint32_t r; asm("mapa.shared::cluster.u32 %0, %1, %2;" : "=r"(r) : "r"(a), "r"(rank)); return r; }
__device__ __forceinline__ void mbar_arrive_remote(uint32_t a) { asm volatile("mbarrier.arrive.relaxed.cluster.shared::cluster.b64 _, [%0];" :: "r"(a) : "memory"); }
__device__ __forceinline__ void mbar_wait_cluster(uint32_t a, int parity) {
    uint32_t done;
    int it = 0;
    do {
        asm volatile("{\n.reg .pred p;\nmbarrier.try_wait.parity.acquire.cluster.shared::cta.b64 p, [%1], %2;\nselp.u32 %0, 1, 0, p;\n}"
                     : "=r"(done) : "r"(a), "r"(parity) : "memory");
        if (++it > (1 << 24)) __trap();
    } while (!done);
}
__device__ __forceinline__ void tma2d_mc(uint32_t dst, const CUtensorMap* m, int c0, int c1, uint32_t bar) {
    asm volatile("cp.async.bulk.tensor.2d.shared::cluster.global.mbarrier::complete_tx::bytes.multicast::cluster [%0], [%1, {%3, %4}], [%2], %5;"
                 :: "r"(dst), "l"(m), "r"(bar), "r"(c0), "r"(c1), "h"((uint16_t)3) : "memory");
}
__device__ __forceinline__ void bulk_g2s_mc(uint32_t dst, const void* src, int bytes, uint32_t bar) {
    asm volatile("cp.async.bulk.shared::cluster.global.mbarrier::complete_tx::bytes.multicast::cluster [%0], [%1], %2, [%3], %4;"
                 :: "r"(dst), "l"(src), "r"(bytes), "r"(bar), "h"((uint16_t)3) : "memory");
}
__device__ __forceinline__ void tile_of(int bid, int& mb, int& nt) {
    int grp = bid >> 4, in = bid & 15;
    mb = (grp >> 1) * 4 + (in >> 2);
    nt = (grp & 1) * 4 + (in & 3);
}

constexpr int K1_STAGES = 5, K1_STAGE = 16384 + 24576;
constexpr int K1_BAR = K1_STAGES * K1_STAGE, K1_RS = K1_BAR + 128, K1_CS = K1_RS + 1024, K1_SMEM = K1_CS + 768;

__device__ __forceinline__ float2 row_stats_regs(uint4 a, uint4 b) {
    float v[16];
    v[0] = bf_lo(a.x); v[1] = bf_hi(a.x); v[2] = bf_lo(a.y); v[3] = bf_hi(a.y);
    v[4] = bf_lo(a.z); v[5] = bf_hi(a.z); v[6] = bf_lo(a.w); v[7] = bf_hi(a.w);
    v[8] = bf_lo(b.x); v[9] = bf_hi(b.x); v[10] = bf_lo(b.y); v[11] = bf_hi(b.y);
    v[12] = bf_lo(b.z); v[13] = bf_hi(b.z); v[14] = bf_lo(b.w); v[15] = bf_hi(b.w);
    float s = 0.f;
#pragma unroll
    for (int i = 0; i < 16; i++) s += v[i];
    float mean = warp_sum(s) * (1.0f / DM);
    float q = 0.f;
#pragma unroll
    for (int i = 0; i < 16; i++) { float d = v[i] - mean; q = fmaf(d, d, q); }
    float var = warp_sum(q) * (1.0f / DM);
    float rstd = rsqrtf(var + 1e-5f);
    return make_float2(rstd, -mean * rstd);
}
__device__ __forceinline__ float2 row_stats_x(const __nv_bfloat16* x, int row, int lane) {
    const uint4* p = (const uint4*)(x + (size_t)row * DM);
    return row_stats_regs(__ldg(p + lane), __ldg(p + 32 + lane));
}
__device__ __forceinline__ void colsum8(const __nv_bfloat16* w, int ld, int col, int k0, int nk, float (&s)[8]) {
#pragma unroll
    for (int i = 0; i < 8; i++) s[i] = 0.f;
    for (int k = k0; k < k0 + nk; k += 8) {
        uint4 u[8];
#pragma unroll
        for (int i = 0; i < 8; i++) u[i] = __ldg((const uint4*)(w + (size_t)(k + i) * ld + col));
#pragma unroll
        for (int i = 0; i < 8; i++) {
            s[0] += bf_lo(u[i].x); s[1] += bf_hi(u[i].x); s[2] += bf_lo(u[i].y); s[3] += bf_hi(u[i].y);
            s[4] += bf_lo(u[i].z); s[5] += bf_hi(u[i].z); s[6] += bf_lo(u[i].w); s[7] += bf_hi(u[i].w);
        }
    }
}
__device__ __forceinline__ bool wait_count(const unsigned int* p, unsigned int target, int lane) {
    int ok = 1;
    if (lane == 0) {
        int it = 0;
        while (ld_acquire(p) < target) { if (++it > (1 << 18)) { ok = 0; break; } }
    }
    ok = __shfl_sync(0xffffffffu, ok, 0);
    return ok != 0;
}

__global__ void __launch_bounds__(384, 1)
qkv_kernel(const __grid_constant__ CUtensorMap tm_x, const __grid_constant__ CUtensorMap tm_w,
           const __nv_bfloat16* __restrict__ x, const __nv_bfloat16* __restrict__ wqkv) {
    extern __shared__ __align__(1024) unsigned char smem[];
    const uint32_t sb = smem_u32(smem);
    const int tid = threadIdx.x, warp = __shfl_sync(0xffffffffu, tid >> 5, 0), lane = tid & 31;
    TLDECL
    TL(0);
    int mb, nt;
    tile_of(blockIdx.x, mb, nt);
    const uint32_t full = sb + K1_BAR, empty = full + 40, auxb = full + 80;
    if (tid == 0) {
#pragma unroll
        for (int i = 0; i < K1_STAGES; i++) { mbar_init(full + 8 * i, 1); mbar_init(empty + 8 * i, 8); }
        mbar_init(auxb, 3);
        fence_barrier_init();
        for (int kb = 0; kb < K1_STAGES; kb++) {
            mbar_expect(full + 8 * kb, K1_STAGE);
            tma2d(sb + kb * K1_STAGE, &tm_x, kb * 64, mb * 128, full + 8 * kb);
            tma3d(sb + kb * K1_STAGE + 16384, &tm_w, 0, kb * 64, nt * 3, full + 8 * kb);
        }
    }
    __syncthreads();
    pdl_launch();
    if (warp == 0) {
        if (blockIdx.x == 0) g_cnt2[lane] = 0;
        if (lane < 1) g_cnt2[32 + blockIdx.x] = 0;
        if (lane == 0) {
            for (int kb = K1_STAGES; kb < 8; kb++) {
                int s = kb % K1_STAGES;
                mbar_wait(empty + 8 * s, 0);
                mbar_expect(full + 8 * s, K1_STAGE);
                tma2d(sb + s * K1_STAGE, &tm_x, kb * 64, mb * 128, full + 8 * s);
                tma3d(sb + s * K1_STAGE + 16384, &tm_w, 0, kb * 64, nt * 3, full + 8 * s);
            }
        }
    } else if (warp < 4) {
        float2* s_rs = (float2*)(smem + K1_RS);
        float* s_cs = (float*)(smem + K1_CS);
        {
            float cs[8];
            const int cg = (warp - 1) * 8 + (lane & 7);
            colsum8(wqkv, 1536, nt * 192 + cg * 8, mb * 32 + (lane >> 3) * 8, 8, cs);
#pragma unroll
            for (int i = 0; i < 8; i++) {
                cs[i] += __shfl_xor_sync(0xffffffffu, cs[i], 8);
                cs[i] += __shfl_xor_sync(0xffffffffu, cs[i], 16);
            }
            if (lane < 8) {
                float4* d = (float4*)(g_cs1_part + mb * 1536 + nt * 192 + cg * 8);
                d[0] = make_float4(cs[0], cs[1], cs[2], cs[3]);
                d[1] = make_float4(cs[4], cs[5], cs[6], cs[7]);
            }
            __syncwarp();
            if (warp == 1) {
                bar_sync(3, 288);
                if (lane == 0) red_release(&g_cnt[mb]);
            }
            if (lane == 0) red_release(&g_cnt[16 + nt]);
        }
        TL(20);
        TX(8 + warp);
        if (warp == 1) {
            if (wait_count(&g_cnt[mb], 8, lane)) {
#pragma unroll
                for (int i = 0; i < 4; i++) s_rs[lane + 32 * i] = __ldcg(&g_rowstat1[mb * 128 + lane + 32 * i]);
            } else {
                for (int i = 0; i < 128; i++) {
                    float2 st = row_stats_x(x, mb * 128 + i, lane);
                    if (lane == 0) s_rs[i] = st;
                }
            }
        } else {
            int c0 = (warp - 2) * 96;
            if (wait_count(&g_cnt[16 + nt], 48, lane)) {
#pragma unroll
                for (int i = 0; i < 3; i++) {
                    float s = 0.f;
#pragma unroll
                    for (int p = 0; p < 16; p++) s += __ldcg(&g_cs1_part[p * 1536 + nt * 192 + c0 + lane + 32 * i]);
                    s_cs[c0 + lane + 32 * i] = s;
                }
            } else if (lane < 12) {
                float s[8];
                colsum8(wqkv, 1536, nt * 192 + c0 + lane * 8, 0, 512, s);
#pragma unroll
                for (int i = 0; i < 8; i++) s_cs[c0 + lane * 8 + i] = s[i];
            }
        }
        __syncwarp();
        TL(21);
        if (lane == 0) mbar_arrive(auxb);
        bar_sync(2, 256 + 96);
        const int a = tid - 32;
        {
            const int hh = a >> 3, w = a & 7;
            const float4* p = (const float4*)(smem + 49152) + (hh * 256 + w * 32) / 2;
            float m = 0.f;
#pragma unroll
            for (int i = 0; i < 8; i++) {
                const int ii = (i + a) & 7;
                float4 u = p[2 * ii], v = p[2 * ii + 1];
                float n0 = u.x + u.z + v.x + v.z, n1 = u.y + u.w + v.y + v.w;
                if (!(n0 <= 3.0e38f) || !(n1 <= 3.0e38f)) m = __int_as_float(0x7f800000);
                m = fmaxf(m, fmaxf(n0, n1));
            }
            const int col0 = nt * 192 + hh * 16;
            g_nrm[((col0 >> 9) * NH + ((col0 & 511) >> 4)) * 128 + mb * 8 + w] = m;
        }
        if (a < 24) bulk_wait_all();
        TL(27);
        TLDUMP;
    } else {
        const int wgi = (warp >> 2) - 1, ww = warp & 3;
        {
            const int r0 = mb * 128 + nt * 16 + (warp - 4) * 2;
            const uint4* p = (const uint4*)(x + (size_t)r0 * DM);
            const uint4 u0 = __ldg(p + lane), u1 = __ldg(p + 32 + lane), u2 = __ldg(p + 64 + lane), u3 = __ldg(p + 96 + lane);
            const float2 sa = row_stats_regs(u0, u1), sb2 = row_stats_regs(u2, u3);
            if (lane == 0) *(float4*)(g_rowstat1 + r0) = make_float4(sa.x, sa.y, sb2.x, sb2.y);
            bar_arrive(3, 288);
        }
        float acc[96];
#pragma unroll 1
        for (int kb = 0; kb < 8; kb++) {
            int s = kb % K1_STAGES;
            mbar_wait(full + 8 * s, (kb / K1_STAGES) & 1);
            if (warp == 4) TX(kb);
            uint64_t ad = make_desc(sb + s * K1_STAGE + wgi * 8192, 16, 1024, 1);
            uint64_t bd = make_desc(sb + s * K1_STAGE + 16384, 8192, 1024, 1);
            WG_FENCE();
#pragma unroll
            for (int k = 0; k < 4; k++) wgmma_ss_n192(acc, ad + k * 2, bd + k * 128, (kb | k) != 0);
            WG_COMMIT();
            if (kb > 0) {
                wg_wait<1>();
                if (lane == 0) mbar_arrive(empty + 8 * ((kb - 1) % K1_STAGES));
            }
        }
        wg_wait<0>();
        fence_regs(acc);
        TL(1);
        if (warp == 4) TX(16);
        mbar_wait(auxb, 0);
        if (warp == 4) TX(17);
        bar_sync(1, 256);
        const float2* s_rs = (const float2*)(smem + K1_RS);
        const float* s_cs = (const float*)(smem + K1_CS);
        const int g = lane >> 2, t = lane & 3;
        const int rl = wgi * 64 + ww * 16 + g;
        const float2 st0 = s_rs[rl], st1 = s_rs[rl + 8];
        const float QS = 0.25f * 1.4426950408889634f;
        const uint32_t stg = sb + ((lane >> 4) * 16 + wgi * 8 + ww * 2 + ((lane >> 3) & 1)) * 128 + (lane & 7) * 16;
        float2* s_np = (float2*)(smem + 49152) + (warp - 4) * 32 + lane;
#pragma unroll
        for (int hh = 0; hh < 12; hh++) {
            const int which = (nt * 192 + hh * 16) >> 9;
            const float sc = (which == 0) ? QS : 1.0f;
            const float a0 = st0.x * sc, b0 = st0.y * sc, a1 = st1.x * sc, b1 = st1.y * sc;
            const float2 c0 = *(const float2*)(s_cs + 16 * hh + 2 * t), c1 = *(const float2*)(s_cs + 16 * hh + 8 + 2 * t);
            const float* a = acc + 8 * hh;
            float v0 = fmaf(a0, a[0], b0 * c0.x), v1 = fmaf(a0, a[1], b0 * c0.y), v2 = fmaf(a1, a[2], b1 * c0.x), v3 = fmaf(a1, a[3], b1 * c0.y);
            float v4 = fmaf(a0, a[4], b0 * c1.x), v5 = fmaf(a0, a[5], b0 * c1.y), v6 = fmaf(a1, a[6], b1 * c1.x), v7 = fmaf(a1, a[7], b1 * c1.y);
            {
                const int head = ((nt * 192 + hh * 16) & 511) >> 4;
                uint32_t* o = (uint32_t*)g_qkv + ((size_t)((which * NH + head) * 2) * 256 + mb * 16 + wgi * 8 + ww * 2) * 32 + lane;
                o[0] = pack_bf16(v0, v1); o[32] = pack_bf16(v2, v3); o[8192] = pack_bf16(v4, v5); o[8192 + 32] = pack_bf16(v6, v7);
            }
            s_np[hh * 256] = make_float2(fmaf(v0, v0, fmaf(v1, v1, fmaf(v4, v4, v5 * v5))), fmaf(v2, v2, fmaf(v3, v3, fmaf(v6, v6, v7 * v7))));
        }
        fence_proxy_async();
        bar_arrive(2, 256 + 96);
        TL(2);
        TLDUMP;
    }
}

constexpr int AT_K = 0, AT_V = 65536, AT_ONES = 131072, AT_BAR = 163840, AT_SMEM = AT_BAR + 128;
#define POLY_MASK 0x7B5A

__device__ __forceinline__ uint32_t exp2_pair_poly(float x0, float x1) {
    uint32_t t0 = __float_as_uint(x0 + 32895.0f);
    uint32_t t1 = __float_as_uint(x1 + 32895.0f);
    uint32_t gd = __byte_perm(t0, t1, 0x6420);
    uint32_t wm = __byte_perm(t0, t1, 0x5612);
    uint32_t v = hfma2(gd, 0x71477147u, 0x354f354fu);
    uint32_t z = hmul2(v, gd);
    return (wm >> 1) + z;
}
__device__ __forceinline__ uint32_t exp2_pair_mufu(float x0, float x1) { return pack_bf16(ex2f(x0), ex2f(x1)); }
template <uint32_t MASK>
__device__ __forceinline__ void exp_blocks(const float (&s)[32], uint32_t (&p)[16]) {
#pragma unroll
    for (int b = 0; b < 8; b++) {
        if ((MASK >> b) & 1) {
            p[2 * b] = exp2_pair_poly(s[4 * b], s[4 * b + 1]);
            p[2 * b + 1] = exp2_pair_poly(s[4 * b + 2], s[4 * b + 3]);
        } else {
            p[2 * b] = exp2_pair_mufu(s[4 * b], s[4 * b + 1]);
            p[2 * b + 1] = exp2_pair_mufu(s[4 * b + 2], s[4 * b + 3]);
        }
    }
}
#define PV4(P) _Pragma("unroll") for (int i = 0; i < 4; i++) { pv_wgmma(o, P[4 * i], P[4 * i + 1], P[4 * i + 2], P[4 * i + 3], vd); vd += 16; }

__device__ __forceinline__ void attn_store(float (&o)[12], int row0, int head, int lane) {
    float l0 = __shfl_sync(0xffffffffu, o[8], lane & 28);
    float l1 = __shfl_sync(0xffffffffu, o[10], lane & 28);
    float r0 = 1.0f / l0, r1 = 1.0f / l1;
    uint32_t* op = (uint32_t*)g_ao;
    int mb = row0 >> 7, rg = (row0 & 127) >> 3;
    int kb = head >> 2, kc = (head & 3) * 2;
    size_t base = (((size_t)(mb * 8 + kb) * 8 + kc) * 16 + rg) * 32 + lane;
    op[base] = pack_bf16(o[0] * r0, o[1] * r0);
    op[base + 32] = pack_bf16(o[2] * r1, o[3] * r1);
    op[base + 16 * 32] = pack_bf16(o[4] * r0, o[5] * r0);
    op[base + 16 * 32 + 32] = pack_bf16(o[6] * r1, o[7] * r1);
}

__device__ __forceinline__ void attn_load_q(uint32_t (&q)[4], const __nv_bfloat16* gq, int row0, int lane) {
    const uint32_t* qp = (const uint32_t*)gq;
    int j0 = row0 >> 3;
    q[0] = __ldcg(qp + (0 * 256 + j0) * 32 + lane);
    q[1] = __ldcg(qp + (0 * 256 + j0 + 1) * 32 + lane);
    q[2] = __ldcg(qp + (1 * 256 + j0) * 32 + lane);
    q[3] = __ldcg(qp + (1 * 256 + j0 + 1) * 32 + lane);
}

__device__ __forceinline__ void attn_tile_safe(const uint32_t (&q)[4], uint64_t kd, uint64_t vd, int row0, int head, int lane) {
    float o[12];
#pragma unroll
    for (int i = 0; i < 12; i++) o[i] = 0.f;
    float m0 = -INFINITY, m1 = -INFINITY;
    fence_regs(o);
#pragma unroll 1
    for (int j = 0; j < 32; j++) {
        float s[32];
        uint32_t p[16];
        WG_FENCE();
        qk_wgmma_n64(s, q, kd); kd += 64;
        WG_COMMIT();
        wg_wait<0>();
        fence_regs(s);
        fence_regs(o);
        float x0 = m0, x1 = m1;
#pragma unroll
        for (int b = 0; b < 8; b++) {
            x0 = fmaxf(x0, fmaxf(s[4 * b], s[4 * b + 1]));
            x1 = fmaxf(x1, fmaxf(s[4 * b + 2], s[4 * b + 3]));
        }
        x0 = fmaxf(x0, __shfl_xor_sync(0xffffffffu, x0, 1)); x0 = fmaxf(x0, __shfl_xor_sync(0xffffffffu, x0, 2));
        x1 = fmaxf(x1, __shfl_xor_sync(0xffffffffu, x1, 1)); x1 = fmaxf(x1, __shfl_xor_sync(0xffffffffu, x1, 2));
        float al0 = ex2f(m0 - x0), al1 = ex2f(m1 - x1);
        m0 = x0; m1 = x1;
#pragma unroll
        for (int i = 0; i < 3; i++) { o[4 * i] *= al0; o[4 * i + 1] *= al0; o[4 * i + 2] *= al1; o[4 * i + 3] *= al1; }
#pragma unroll
        for (int b = 0; b < 8; b++) {
            p[2 * b] = exp2_pair_mufu(s[4 * b] - m0, s[4 * b + 1] - m0);
            p[2 * b + 1] = exp2_pair_mufu(s[4 * b + 2] - m1, s[4 * b + 3] - m1);
        }
        fence_regs(o);
        WG_FENCE();
        PV4(p);
        WG_COMMIT();
        wg_wait<0>();
        fence_regs(o);
    }
    attn_store(o, row0, head, lane);
}

__global__ void __launch_bounds__(512, 1)
attn_kernel(const __nv_bfloat16* __restrict__ wg_, const __nv_bfloat16* __restrict__ wu_,
            const __nv_bfloat16* __restrict__ wo_, const __nv_bfloat16* __restrict__ wd_) {
    extern __shared__ __align__(1024) unsigned char smem[];
    const uint32_t sb = smem_u32(smem);
    const int tid = threadIdx.x, wg = tid >> 7, warp = (tid >> 5) & 3, lane = tid & 31;
    TLDECL
    pdl_launch();
    if (blockIdx.x >= 128) {
        const int e = blockIdx.x - 128;
        const __nv_bfloat16* w = (e < 2) ? wg_ : wu_;
        float* red = (float*)smem;
        const int cgrp = tid & 127, kq = tid >> 7;
        if (cgrp < 112) {
            float s[8];
            colsum8(w, FF, (e & 1) * 896 + cgrp * 8, kq * 128, 128, s);
#pragma unroll
            for (int i = 0; i < 8; i++) red[kq * 896 + cgrp * 8 + i] = s[i];
        }
        __syncthreads();
        for (int c = tid; c < 896; c += 512)
            g_cs2[(e >> 1) * FF + (e & 1) * 896 + c] = red[c] + red[896 + c] + red[1792 + c] + red[2688 + c];
        if (tid < 32) {
            const char* p0 = (const char*)wo_ + e * (DM * DM * 2 / 4);
            for (int i = lane; i < 32; i += 32)
                asm volatile("cp.async.bulk.prefetch.L2.global [%0], %1;" :: "l"(p0 + i * 4096), "r"(4096) : "memory");
            const char* p1 = (const char*)wd_ + e * (FF * DM * 2 / 4);
            for (int i = lane; i < 112; i += 32)
                asm volatile("cp.async.bulk.prefetch.L2.global [%0], %1;" :: "l"(p1 + i * 4096), "r"(4096) : "memory");
        }
        return;
    }
    const int head = blockIdx.x >> 2, qq = blockIdx.x & 3;
    const __nv_bfloat16* gq = g_qkv + (size_t)head * (S_LEN * 16);
    const __nv_bfloat16* gk = g_qkv + (size_t)(NH + head) * (S_LEN * 16);
    const __nv_bfloat16* gv = g_qkv + (size_t)(2 * NH + head) * (S_LEN * 16);
    if (tid == 0) {
        for (int i = 0; i < 8; i++) mbar_init(sb + AT_BAR + 8 * i, 1);
        fence_barrier_init();
    }
    {
        uint4 one = make_uint4(0x00003F80u, 0, 0, 0);
#pragma unroll
        for (int i = 0; i < 4; i++) *(uint4*)(smem + AT_ONES + (i * 512 + tid) * 16) = one;
        fence_proxy_async();
    }
    __syncthreads();
    TL(3);
    pdl_wait();
    TL(4);
    auto load_kv = [&](int i) {
        uint32_t bar = sb + AT_BAR + 8 * i;
        mbar_expect(bar, 16384);
        bulk_g2s(sb + AT_K + i * 4096, gk + i * 2048, 4096, bar);
        bulk_g2s(sb + AT_K + 32768 + i * 4096, gk + 16384 + i * 2048, 4096, bar);
        bulk_g2s(sb + AT_V + i * 4096, gv + i * 2048, 4096, bar);
        bulk_g2s(sb + AT_V + 32768 + i * 4096, gv + 16384 + i * 2048, 4096, bar);
    };
    if (tid == 0) { load_kv(0); load_kv(1); }
    uint32_t q[4], q2[4];
    attn_load_q(q, gq, qq * 512 + wg * 64 + warp * 16, lane);
    attn_load_q(q2, gq, qq * 512 + (4 + wg) * 64 + warp * 16, lane);
    bool fast;
    {
        const float* nq = g_nrm + (0 * NH + head) * 128 + qq * 32;
        const float* nk = g_nrm + (1 * NH + head) * 128;
        const float* nv = g_nrm + (2 * NH + head) * 128;
        float4 k4 = __ldcg((const float4*)nk + lane), v4 = __ldcg((const float4*)nv + lane);
        float qm = warp_max(__ldcg(nq + lane));
        float km = warp_max(fmaxf(fmaxf(k4.x, k4.y), fmaxf(k4.z, k4.w)));
        float vm = warp_max(fmaxf(fmaxf(v4.x, v4.y), fmaxf(v4.z, v4.w)));
        fast = __all_sync(0xffffffffu, (qm * km <= 3500.0f) && (vm <= 1.0e24f));
    }
    TL(24);
    const uint64_t kdesc0 = make_desc(sb + AT_K, 32768, 128, 0);
    const uint64_t vdesc0 = make_desc(sb + AT_V, 128, 32768, 0);
    if (!fast) {
        if (tid == 0) for (int i = 2; i < 8; i++) load_kv(i);
        for (int i = 0; i < 8; i++) mbar_wait(sb + AT_BAR + 8 * i, 0);
#pragma unroll 1
        for (int tile = 0; tile < 2; tile++) {
            const int row0 = qq * 512 + (tile * 4 + wg) * 64 + warp * 16;
            attn_tile_safe(q, kdesc0, vdesc0, row0, head, lane);
#pragma unroll
            for (int i = 0; i < 4; i++) q[i] = q2[i];
        }
        return;
    }
#pragma unroll 1
    for (int tile = 0; tile < 2; tile++) {
        const int row0 = qq * 512 + (tile * 4 + wg) * 64 + warp * 16;
        float o[12];
#pragma unroll
        for (int i = 0; i < 12; i++) o[i] = 0.f;
        fence_regs(o);
        float sa[32];
        uint32_t pa[16];
        uint64_t kd = kdesc0, vd = vdesc0;
        if (tile == 0) { mbar_wait(sb + AT_BAR, 0); TL(25); }
        WG_FENCE();
        qk_wgmma_n64(sa, q, kd); kd += 64;
        WG_COMMIT();
#pragma unroll 1
        for (int jj = 0; jj < 8; jj++) {
            if (tile == 0 && jj < 7) {
                if (tid == 0 && jj < 6) load_kv(jj + 2);
                mbar_wait(sb + AT_BAR + 8 * (jj + 1), 0);
            }
            if (wg == 0 && warp == 0) TX(128 + tile * 8 + jj);
#pragma unroll
            for (int j = 0; j < 4; j++) {
                wg_wait<0>();
                fence_regs(sa);
                if (j & 1) exp_blocks<(POLY_MASK >> 8)>(sa, pa); else exp_blocks<(POLY_MASK & 255)>(sa, pa);
                WG_FENCE();
                PV4(pa);
                qk_wgmma_n64(sa, q, kd); kd += 64;
                WG_COMMIT();
            }
        }
        wg_wait<0>();
        fence_regs(o);
        fence_regs(sa);
        if (tile == 0) TL(26);
        attn_store(o, row0, head, lane);
#pragma unroll
        for (int i = 0; i < 4; i++) q[i] = q2[i];
    }
    TL(5);
    TLDUMP;
}

#define POLL_NS 40
#define FLAG_STRIDE 1
#define DELAYC 9
constexpr int F_R2 = 131072, F_X = 196608, F_BAR = 229376;
constexpr int F_RS = F_BAR + 256, F_CS = F_RS + 1024, F_SMEM = F_CS + 1792;
enum { B_FA = 0, B_HF = 4, B_BF = 8, B_BE = 11, B_CF = 14, B_CE = 20, B_ADONE = 26, B_BDONE = 27, B_XC = 28, B_PRDY = 29, B_AUX = 30, B_NUM = 31 };

__device__ __forceinline__ void st_async4(uint32_t dst, float a, float b, float c, float d, uint32_t bar) {
    asm volatile("st.async.weak.shared::cluster.mbarrier::complete_tx::bytes.v4.f32 [%0], {%1,%2,%3,%4}, [%5];"
                 :: "r"(dst), "f"(a), "f"(b), "f"(c), "f"(d), "r"(bar) : "memory");
}
__device__ __forceinline__ void poll_count(const unsigned int* p, unsigned int target) {
    int it = 0;
    while (ld_acquire(p) < target) { if (++it > (1 << 22)) __trap(); }
    asm volatile("fence.proxy.async.global;" ::: "memory");
}
__device__ __forceinline__ void tma2d_store(const CUtensorMap* m, uint32_t src, int c0, int c1) {
    asm volatile("cp.async.bulk.tensor.2d.global.shared::cta.bulk_group [%0, {%2, %3}], [%1];" :: "l"(m), "r"(src), "r"(c0), "r"(c1) : "memory");
}
__device__ __forceinline__ float2 h_row_stats(int row) {
    const float4* hp = (const float4*)(g_hstat + (size_t)row * 8);
    float4 a = __ldcg(hp), b = __ldcg(hp + 1), c = __ldcg(hp + 2), d = __ldcg(hp + 3);
    float mean = 0.125f * (a.x + a.z + b.x + b.z + c.x + c.z + d.x + d.z);
    float m2 = a.y + a.w + b.y + b.w + c.y + c.w + d.y + d.w;
    float e;
    e = a.x - mean; m2 = fmaf(64.f * e, e, m2); e = a.z - mean; m2 = fmaf(64.f * e, e, m2);
    e = b.x - mean; m2 = fmaf(64.f * e, e, m2); e = b.z - mean; m2 = fmaf(64.f * e, e, m2);
    e = c.x - mean; m2 = fmaf(64.f * e, e, m2); e = c.z - mean; m2 = fmaf(64.f * e, e, m2);
    e = d.x - mean; m2 = fmaf(64.f * e, e, m2); e = d.z - mean; m2 = fmaf(64.f * e, e, m2);
    return make_float2(rsqrtf(m2 * (1.0f / DM) + 1e-5f), -mean);
}
__device__ __forceinline__ int c_kblock(int i, int r) {
    if (i < 6) { const int e = 2 * i + r, m = e / 3, k = e - 3 * m; return 7 * m + (k == 2 ? 4 : k); }
    const int l = 2 * (i - 6) + r, m = l >> 2, k = l & 3;
    return 7 * m + (k < 2 ? 2 + k : 3 + k);
}
__device__ __forceinline__ uint32_t c_stage_a(int s, int ntB) { return s < 4 ? ((ntB + 2 * s) & 7) * 16384 : F_R2 + (s - 4) * 32768; }
__device__ __forceinline__ uint32_t c_stage_b(int s, int ntB) { return s < 4 ? ((ntB + 2 * s + 1) & 7) * 16384 : F_R2 + (s - 4) * 32768 + 16384; }
template <int R>
__device__ __forceinline__ void xchg(float (&acc)[64], float (&o)[32], uint32_t sb, unsigned char* smem, int bar, int ctid) {
    const uint32_t dst = mapa(sb + F_X + ctid * 16, 1 - R), rb = mapa(sb + F_BAR + 8 * bar, 1 - R);
#pragma unroll
    for (int q = 0; q < 8; q++) {
        const int j = (1 - R) * 32 + 4 * q;
        st_async4(dst + q * 4096, acc[j], acc[j + 1], acc[j + 2], acc[j + 3], rb);
    }
    mbar_wait_cluster(sb + F_BAR + 8 * bar, 0);
#pragma unroll
    for (int q = 0; q < 8; q++) {
        float4 v = *(const float4*)(smem + F_X + q * 4096 + ctid * 16);
        const int j = R * 32 + 4 * q;
        o[4 * q] = acc[j] + v.x; o[4 * q + 1] = acc[j + 1] + v.y; o[4 * q + 2] = acc[j + 2] + v.z; o[4 * q + 3] = acc[j + 3] + v.w;
    }
}

template <int NB, bool STAGE>
__device__ __forceinline__ void ffn_epilogue(const float* ag, const float* au, const float* s_cs, int cs_off, uint32_t* gp, uint32_t stg,
                                             float2 st0, float2 st1, int lane) {
    const int t = lane & 3;
    const float C1 = 0.7978845608028654f, C2 = 0.044715f * 0.7978845608028654f;
    const float k10 = st0.x * C1, k20 = st0.x * st0.x * st0.x * C2, k11 = st1.x * C1, k21 = st1.x * st1.x * st1.x * C2;
#pragma unroll
    for (int j2 = 0; j2 < NB / 2; j2++) {
        uint32_t pk[4];
#pragma unroll
        for (int jj = 0; jj < 2; jj++) {
            const int j = 2 * j2 + jj;
            const float2 cg = *(const float2*)(s_cs + cs_off + 8 * j + 2 * t);
            const float2 cu = *(const float2*)(s_cs + 224 + cs_off + 8 * j + 2 * t);
            float r[4];
#pragma unroll
            for (int e = 0; e < 4; e++) {
                const float nm = (e < 2) ? st0.y : st1.y, k1 = (e < 2) ? k10 : k11, k2 = (e < 2) ? k20 : k21;
                const float tg = fmaf(nm, (e & 1) ? cg.y : cg.x, ag[4 * j + e]);
                const float tu = fmaf(nm, (e & 1) ? cu.y : cu.x, au[4 * j + e]);
                const float th = tanh_fast(tg * fmaf(tg * tg, k2, k1));
                const float p = tg * tu;
                r[e] = fmaf(p, th, p);
            }
            pk[2 * jj] = pack_bf16(r[0], r[1]);
            pk[2 * jj + 1] = pack_bf16(r[2], r[3]);
        }
        if (STAGE) {
            stsm4(stg + j2 * 4096, pk[0], pk[1], pk[2], pk[3]);
        } else {
            gp[j2 * 1024] = pk[0]; gp[j2 * 1024 + 32] = pk[1]; gp[j2 * 1024 + 512] = pk[2]; gp[j2 * 1024 + 544] = pk[3];
        }
    }
}

__global__ void __cluster_dims__(2, 1, 1) __launch_bounds__(384, 1)
tail_kernel(const __grid_constant__ CUtensorMap tm_o, const __grid_constant__ CUtensorMap tm_g,
            const __grid_constant__ CUtensorMap tm_u, const __grid_constant__ CUtensorMap tm_d,
            const __grid_constant__ CUtensorMap tm_out, const __nv_bfloat16* __restrict__ x) {
    extern __shared__ __align__(1024) unsigned char smem[];
    const uint32_t sb = smem_u32(smem);
    const uint32_t bars = sb + F_BAR;
    const int tid = threadIdx.x, warp = __shfl_sync(0xffffffffu, tid >> 5, 0), lane = tid & 31;
    TLDECL
    TL(6);
    if (warp == 4) TX(200);
    const int cl = blockIdx.x >> 1, r = blockIdx.x & 1;
    const int mb = ((cl & 7) >> 1) * 4 + (cl >> 4), ntA = (cl & 1) * 2 + ((cl >> 3) & 1);
    const int nt = ntA * 2 + r;
    const int mbB = (mb & ~1) + r, ntB = (mb & 1) * 4 + ntA;
    if (tid == 0) {
#pragma unroll
        for (int i = 0; i < B_NUM; i++) {
            const int cnt = (i >= B_BE && i < B_BE + 3) ? 16 : (i == B_BDONE) ? DELAYC : ((i >= B_CE && i < B_CE + 6) || i == B_PRDY) ? 8 : (i == B_AUX || i == B_ADONE) ? 2 : 1;
            mbar_init(bars + 8 * i, cnt);
        }
        mbar_expect(bars + 8 * B_XC, 32768);
        fence_barrier_init();
        for (int i = 0; i < 8; i++) {
            const uint32_t bar = bars + 8 * (B_FA + (i >> 1));
            if (!(i & 1)) mbar_expect(bar, 49152);
            tma2d(sb + F_R2 + 32768 + i * 8192, &tm_o, nt * 64, i * 64, bar);
        }
    }
    TL(28);
    __syncthreads();
    TL(29);
    asm volatile("barrier.cluster.arrive.relaxed.aligned;" ::: "memory");
    TL(30);
    if (warp < 4) {
        asm volatile("setmaxnreg.dec.sync.aligned.u32 56;");
        if (warp == 0) TX(205);
        if (warp == 0) {
            if (lane == 0) {
                auto load_b = [&](int it) {
                    const int s = it % 3, pass = it >> 3, kb = (ntB + it) & 7;
                    const int ng = pass ? 3 : 4, c0 = ntB * 224 + pass * 128;
                    const uint32_t bar = bars + 8 * (B_BF + s), dst = sb + F_R2 + s * 32768 + r * ng * 4096;
                    mbar_expect(bar, ng * 8192);
                    for (int i = 0; i < ng; i++) tma2d_mc(dst + i * 4096, r ? &tm_u : &tm_g, c0 + i * 32, kb * 64, bar);
                };
                asm volatile("barrier.cluster.wait.acquire;" ::: "memory");
                pdl_wait();
                TL(16);
                for (int i = 0; i < 4; i++)
                    bulk_g2s_mc(sb + (2 * i + r) * 16384, g_ao + (size_t)(mb * 8 + 2 * i + r) * 8192, 16384, bars + 8 * (B_FA + i));
                load_b(0);
                if (blockIdx.x == 0)
                    for (int i = 0; i < 32; i++) g_cnt[i] = 0;
                mbar_wait_cluster(bars + 8 * B_ADONE, 0);
                load_b(1); load_b(2);
                auto load_c = [&](int i) {
                    const int s = i % 6, kb = c_kblock(i, r);
                    const uint32_t bar = bars + 8 * (B_CF + s), da = sb + c_stage_a(s, ntB), db = sb + c_stage_b(s, ntB);
                    mbar_expect(bar, 32768);
                    tma2d(db, &tm_d, ntA * 128, kb * 64, bar);
                    tma2d(db + 8192, &tm_d, ntA * 128 + 64, kb * 64, bar);
                    bulk_g2s(da, g_g + (size_t)(mb * 28 + kb) * 8192, 16384, bar);
                };
                for (int it = 3; it < 16; it++) {
                    mbar_wait_cluster(bars + 8 * (B_BE + it % 3), (it / 3 - 1) & 1);
                    load_b(it);
                    if (it == 12) { poll_count(&g_cnt2[mb], 8); load_c(0); }
                    if (it == 14) load_c(1);
                }
                mbar_wait_cluster(bars + 8 * (B_BE + 1), 0);
                load_c(2);
                mbar_wait(bars + 8 * B_BDONE, 0);
                for (int i = 3; i < 14; i++) {
                    if (i >= 6) mbar_wait(bars + 8 * (B_CE + i % 6), ((i / 6) - 1) & 1);
                    if (i == 6) { poll_count(&g_cnt2[16 + mb], 8); TL(18); }
                    load_c(i);
                }
            }
            else asm volatile("barrier.cluster.wait.acquire;" ::: "memory");
            TLDUMP;
        } else if (warp == 1) {
            asm volatile("barrier.cluster.wait.acquire.aligned;" ::: "memory");
            bar_sync(5, 288);
            if (lane == 0) { red_release(&g_cnt2[32 + (mb * 8 + nt) * FLAG_STRIDE]); TL(9); }
            __syncwarp();
            bar_sync(6, 288);
            if (lane == 0) red_release(&g_cnt2[32 + (mb * 8 + nt) * FLAG_STRIDE]);
            __syncwarp();
            bar_sync(1, 288);
            if (lane == 0) red_release(&g_cnt2[mbB]);
            __syncwarp();
            bar_sync(2, 288);
            if (lane == 0) {
                red_release(&g_cnt2[16 + mbB]);
                if (DELAYC == 9) mbar_arrive(bars + 8 * B_BDONE);
                TL(13);
            }
            __syncwarp();
            bar_sync(3, 288);
            if (lane == 0) {
                tma2d_store(&tm_out, sb, nt * 64, mb * 128);
                bulk_commit();
                bulk_wait_all();
                TL(15);
            }
            TLDUMP;
        } else {
            asm volatile("barrier.cluster.wait.acquire.aligned;" ::: "memory");
            pdl_wait();
            float2* s_rs = (float2*)(smem + F_RS);
            float* s_cs = (float*)(smem + F_CS);
            for (int c = tid - 64; c < 448; c += 64)
                s_cs[c] = __ldcg(&g_cs2[(c >= 224 ? FF - 224 : 0) + ntB * 224 + c]);
            if (tid == 96) {
                mbar_wait_cluster(bars + 8 * B_ADONE, 0);
                for (int i = 0; i < 8; i++) {
                    const int kb = (ntB + i) & 7;
                    const uint32_t bar = bars + 8 * (i < 4 ? B_HF + i : B_FA + i - 4);
                    poll_count(&g_cnt2[32 + (mbB * 8 + kb) * FLAG_STRIDE], 1);
                    mbar_expect(bar, 16384);
                    bulk_g2s(sb + kb * 16384, g_h + (size_t)(mbB * 8 + kb) * 8192, 16384, bar);
                }
            }
            __syncwarp();
            TL(17);
            for (int i = 0; i < 8; i++) mbar_wait(bars + 8 * (i < 4 ? B_HF + i : B_FA + i - 4), i < 4 ? 0 : 1);
            if (lane < 8) poll_count(&g_cnt2[32 + (mbB * 8 + lane) * FLAG_STRIDE], 2);
            __syncwarp();
            __syncwarp();
            for (int rr = tid - 64; rr < 128; rr += 64) {
                s_rs[rr] = h_row_stats(mbB * 128 + rr);
            }
            __syncwarp();
            if (lane == 0) mbar_arrive(bars + 8 * B_AUX);
            TLDUMP;
        }
    } else {
        asm volatile("setmaxnreg.inc.sync.aligned.u32 216;");
        if (warp == 4) TX(206);
        const int wgi = (warp >> 2) - 1, ww = warp & 3, ctid = tid - 128;
        const int g = lane >> 2, t = lane & 3;
        const int rl = wgi * 64 + ww * 16 + g, row = mb * 128 + rl;
        const int rgl = wgi * 8 + ww * 2;
        const float2* s_rs = (const float2*)(smem + F_RS);
        const float* s_cs = (const float*)(smem + F_CS);
        const uint32_t stl = ((lane >> 4) * 16 + rgl + ((lane >> 3) & 1)) * 128 + (lane & 7) * 16;
        uint32_t* hp = (uint32_t*)g_h + ((size_t)(mb * 8 + nt) * 8 * 16 + rgl) * 32 + lane;
        const uint32_t rbars = mapa(bars, 1 - r);
        TL(23);
        {
            uint32_t xr[16];
            const uint32_t* xp = (const uint32_t*)(x + (size_t)row * DM + nt * 64) + t;
#pragma unroll
            for (int j = 0; j < 8; j++) { xr[2 * j] = __ldg(xp + 4 * j); xr[2 * j + 1] = __ldg(xp + 8 * (DM / 2) + 4 * j); }
            float acc[32];
#pragma unroll 1
            for (int i = 0; i < 8; i++) {
                if (!(i & 1)) { mbar_wait(bars + 8 * (B_FA + (i >> 1)), 0); if (i == 0) TL(19); }
                uint64_t ad = make_desc(sb + i * 16384 + wgi * 1024, 2048, 128, 0);
                uint64_t bd = make_desc(sb + F_R2 + 32768 + i * 8192, 8192, 1024, 1);
                WG_FENCE();
#pragma unroll
                for (int k = 0; k < 4; k++) wgmma_ss_n64(acc, ad + k * 256, bd + k * 128, (i | k) != 0);
                WG_COMMIT();
            }
            wg_wait<0>();
            fence_regs(acc);
            TL(7);
            asm volatile("barrier.cluster.wait.acquire.aligned;" ::: "memory");
            bar_sync(4, 256);
            if (tid == 128) { mbar_arrive(bars + 8 * B_ADONE); mbar_arrive_remote(mapa(bars + 8 * B_ADONE, 1 - r)); }
            float v0[16], v1[16];
            float s0 = 0.f, s1 = 0.f;
#pragma unroll
            for (int j2 = 0; j2 < 4; j2++) {
                uint32_t u[4];
#pragma unroll
                for (int jj = 0; jj < 2; jj++) {
                    const int j = 2 * j2 + jj;
                    u[2 * jj] = pack_bf16(bf_lo(xr[2 * j]) + acc[4 * j], bf_hi(xr[2 * j]) + acc[4 * j + 1]);
                    u[2 * jj + 1] = pack_bf16(bf_lo(xr[2 * j + 1]) + acc[4 * j + 2], bf_hi(xr[2 * j + 1]) + acc[4 * j + 3]);
                    v0[2 * j] = bf_lo(u[2 * jj]); v0[2 * j + 1] = bf_hi(u[2 * jj]);
                    v1[2 * j] = bf_lo(u[2 * jj + 1]); v1[2 * j + 1] = bf_hi(u[2 * jj + 1]);
                    s0 += v0[2 * j] + v0[2 * j + 1];
                    s1 += v1[2 * j] + v1[2 * j + 1];
                }
                hp[j2 * 1024] = u[0]; hp[j2 * 1024 + 32] = u[1]; hp[j2 * 1024 + 512] = u[2]; hp[j2 * 1024 + 544] = u[3];
            }
            bar_arrive(5, 288);
            float m0 = s0 * (1.0f / 16), m1 = s1 * (1.0f / 16), q0 = 0.f, q1 = 0.f;
#pragma unroll
            for (int i = 0; i < 16; i++) {
                float d0 = v0[i] - m0, d1 = v1[i] - m1;
                q0 = fmaf(d0, d0, q0); q1 = fmaf(d1, d1, q1);
            }
#pragma unroll
            for (int st = 0; st < 2; st++) {
                float hn = st ? 16.f : 8.f;
                float om0 = __shfl_xor_sync(0xffffffffu, m0, 1 << st), oq0 = __shfl_xor_sync(0xffffffffu, q0, 1 << st);
                float om1 = __shfl_xor_sync(0xffffffffu, m1, 1 << st), oq1 = __shfl_xor_sync(0xffffffffu, q1, 1 << st);
                float d0 = om0 - m0, d1 = om1 - m1;
                q0 = q0 + oq0 + d0 * d0 * hn; q1 = q1 + oq1 + d1 * d1 * hn;
                m0 = 0.5f * (m0 + om0); m1 = 0.5f * (m1 + om1);
            }
            if (t == 0) {
                g_hstat[row * 8 + nt] = make_float2(m0, q0);
                g_hstat[(row + 8) * 8 + nt] = make_float2(m1, q1);
            }
            bar_arrive(6, 288);
            TL(8);
        }
        uint32_t* gp = (uint32_t*)g_g + (((size_t)mbB * 224 + ntB * 28) * 16 + rgl) * 32 + lane;
        {
            float ag[128];
#pragma unroll 1
            for (int kb = 0; kb < 8; kb++) {
                const int s = kb % 3;
                mbar_wait(bars + 8 * (kb < 4 ? B_HF + kb : B_FA + kb - 4), kb < 4 ? 0 : 1);
                mbar_wait(bars + 8 * (B_BF + s), (kb / 3) & 1);
                uint64_t ad = make_desc(sb + ((ntB + kb) & 7) * 16384 + wgi * 1024, 2048, 128, 0);
                uint64_t bd = make_desc(sb + F_R2 + s * 32768, 4096, 512, 2);
                WG_FENCE();
#pragma unroll
                for (int k = 0; k < 4; k++) wgmma_ss_n256(ag, ad + k * 256, bd + k * 64, (kb | k) != 0);
                WG_COMMIT();
                if (kb > 0) {
                    wg_wait<1>();
                    if (lane == 0) { mbar_arrive(bars + 8 * (B_BE + (kb - 1) % 3)); mbar_arrive_remote(rbars + 8 * (B_BE + (kb - 1) % 3)); }
                }
            }
            wg_wait<0>();
            if (lane == 0) { mbar_arrive(bars + 8 * (B_BE + 7 % 3)); mbar_arrive_remote(rbars + 8 * (B_BE + 7 % 3)); }
            fence_regs(ag);
            TL(10);
            mbar_wait(bars + 8 * B_AUX, 0);
            ffn_epilogue<16, false>(ag, ag + 64, s_cs, 0, gp, 0, s_rs[rl], s_rs[rl + 8], lane);
            bar_arrive(1, 288);
        }
        {
            float ag[96];
#pragma unroll 1
            for (int kb = 0; kb < 8; kb++) {
                const int it = 8 + kb, s = it % 3;
                mbar_wait(bars + 8 * (B_BF + s), (it / 3) & 1);
                uint64_t ad = make_desc(sb + ((ntB + kb) & 7) * 16384 + wgi * 1024, 2048, 128, 0);
                uint64_t bd = make_desc(sb + F_R2 + s * 32768, 4096, 512, 2);
                WG_FENCE();
#pragma unroll
                for (int k = 0; k < 4; k++) wgmma_ss_n192(ag, ad + k * 256, bd + k * 64, (kb | k) != 0);
                WG_COMMIT();
                if (kb > 0) {
                    wg_wait<1>();
                    if (lane == 0 && it < 15) { mbar_arrive(bars + 8 * (B_BE + (it - 1) % 3)); mbar_arrive_remote(rbars + 8 * (B_BE + (it - 1) % 3)); }
                }
            }
            wg_wait<0>();
            if (lane == 0) {
                mbar_arrive(bars + 8 * B_BDONE);
                mbar_arrive_remote(rbars + 8 * B_PRDY);
            }
            fence_regs(ag);
            TL(11);
            ffn_epilogue<12, false>(ag, ag + 48, s_cs, 128, gp + 16 * 512, 0, s_rs[rl], s_rs[rl + 8], lane);
            bar_arrive(2, 288);
            TL(12);
        }
        {
            uint32_t hr[16];
#pragma unroll
            for (int j = 0; j < 8; j++) { hr[2 * j] = __ldcg(hp + j * 512); hr[2 * j + 1] = __ldcg(hp + j * 512 + 32); }
            mbar_wait(bars + 8 * (B_CF + 0), 0);
            const float a0 = h_row_stats(row).x, a1 = h_row_stats(row + 8).x;
            float acc[64];
#pragma unroll 1
            for (int kb = 0; kb < 14; kb++) {
                const int s = kb % 6;
                mbar_wait(bars + 8 * (B_CF + s), (kb / 6) & 1);
                if (warp == 4) TX(96 + kb);
                uint64_t ad = make_desc(sb + c_stage_a(s, ntB) + wgi * 1024, 2048, 128, 0);
                uint64_t bd = make_desc(sb + c_stage_b(s, ntB), 8192, 1024, 1);
                WG_FENCE();
#pragma unroll
                for (int k = 0; k < 4; k++) wgmma_ss_n128(acc, ad + k * 256, bd + k * 128, (kb | k) != 0);
                WG_COMMIT();
                if (kb > 0) {
                    wg_wait<1>();
                    if (lane == 0) mbar_arrive(bars + 8 * (B_CE + (kb - 1) % 6));
                }
            }
            wg_wait<0>();
            fence_regs(acc);
            TL(14);
            mbar_wait_cluster(bars + 8 * B_PRDY, 0);
            float o[32];
            if (r == 0) xchg<0>(acc, o, sb, smem, B_XC, ctid); else xchg<1>(acc, o, sb, smem, B_XC, ctid);
            TL(22);
            bar_sync(4, 256);
            const float k0 = 0.5f * a0 * a0, k1 = 0.5f * a1 * a1;
            const int srow = wgi * 64 + ww * 16 + ((lane >> 3) & 1) * 8 + (lane & 7);
#pragma unroll
            for (int j2 = 0; j2 < 4; j2++) {
                uint32_t u[4];
#pragma unroll
                for (int jj = 0; jj < 2; jj++) {
                    const int j = 2 * j2 + jj;
                    u[2 * jj] = pack_bf16(fmaf(k0, o[4 * j], bf_lo(hr[2 * j])), fmaf(k0, o[4 * j + 1], bf_hi(hr[2 * j])));
                    u[2 * jj + 1] = pack_bf16(fmaf(k1, o[4 * j + 2], bf_lo(hr[2 * j + 1])), fmaf(k1, o[4 * j + 3], bf_hi(hr[2 * j + 1])));
                }
                const int chunk = 2 * j2 + (lane >> 4);
                stsm4(sb + srow * 128 + ((chunk ^ (lane & 7)) * 16), u[0], u[1], u[2], u[3]);
            }
            fence_proxy_async();
            bar_arrive(3, 288);
            TLDUMP;
        }
    }
}

typedef CUresult (*EncodeFn)(CUtensorMap*, CUtensorMapDataType, cuuint32_t, void*, const cuuint64_t*, const cuuint64_t*,
                             const cuuint32_t*, const cuuint32_t*, CUtensorMapInterleave, CUtensorMapSwizzle,
                             CUtensorMapL2promotion, CUtensorMapFloatOOBfill);

void encode(EncodeFn fn, CUtensorMap* m, const void* ptr, int rank, const cuuint64_t* dims, const cuuint64_t* strides,
            const cuuint32_t* box, CUtensorMapSwizzle swz) {
    cuuint32_t es[3] = {1, 1, 1};
    fn(m, CU_TENSOR_MAP_DATA_TYPE_BFLOAT16, rank, (void*)ptr, dims, strides, box, es, CU_TENSOR_MAP_INTERLEAVE_NONE, swz,
       CU_TENSOR_MAP_L2_PROMOTION_L2_256B, CU_TENSOR_MAP_FLOAT_OOB_FILL_NONE);
}

template <typename... KArgs, typename... Args>
void launch(void (*kern)(KArgs...), int grid, int block, int smem, bool pdl, Args... args) {
    cudaLaunchConfig_t cfg = {};
    cfg.gridDim = dim3(grid); cfg.blockDim = dim3(block); cfg.dynamicSmemBytes = smem;
    cfg.stream = cudaStreamPerThread;
    cudaLaunchAttribute at[1];
    at[0].id = cudaLaunchAttributeProgrammaticStreamSerialization;
    at[0].val.programmaticStreamSerializationAllowed = 1;
    cfg.attrs = at; cfg.numAttrs = pdl ? 1 : 0;
    cudaLaunchKernelEx(&cfg, kern, KArgs(args)...);
}

}

extern "C" void kernel_launch(void* const* d_in, const int* in_sizes, int n_in, void* d_out, int out_size) {
    const __nv_bfloat16* x = (const __nv_bfloat16*)d_in[0];
    const __nv_bfloat16* wqkv = (const __nv_bfloat16*)d_in[1];
    const __nv_bfloat16* wo = (const __nv_bfloat16*)d_in[2];
    const __nv_bfloat16* wgate = (const __nv_bfloat16*)d_in[4];
    const __nv_bfloat16* wup = (const __nv_bfloat16*)d_in[5];
    const __nv_bfloat16* wdown = (const __nv_bfloat16*)d_in[6];
    __nv_bfloat16* out = (__nv_bfloat16*)d_out;

    static CUtensorMap tm_x, tm_wqkv, tm_wo, tm_wg, tm_wu, tm_wd, tm_out;
    static const void* cached[7] = {nullptr, nullptr, nullptr, nullptr, nullptr, nullptr, nullptr};
    if (cached[0] != x || cached[1] != wqkv || cached[2] != wo || cached[3] != wgate || cached[4] != wup || cached[5] != wdown || cached[6] != out) {
        void* fp = nullptr;
        cudaDriverEntryPointQueryResult qr;
        cudaGetDriverEntryPoint("cuTensorMapEncodeTiled", &fp, cudaEnableDefault, &qr);
        EncodeFn fn = (EncodeFn)fp;
        { cuuint64_t d[2] = {512, 2048}, s[1] = {1024}; cuuint32_t b[2] = {64, 128};
          encode(fn, &tm_x, x, 2, d, s, b, CU_TENSOR_MAP_SWIZZLE_128B);
          encode(fn, &tm_out, out, 2, d, s, b, CU_TENSOR_MAP_SWIZZLE_128B); }
        { cuuint64_t d[3] = {64, 512, 24}, s[2] = {3072, 128}; cuuint32_t b[3] = {64, 64, 3};
          encode(fn, &tm_wqkv, wqkv, 3, d, s, b, CU_TENSOR_MAP_SWIZZLE_128B); }
        { cuuint64_t d[2] = {512, 512}, s[1] = {1024}; cuuint32_t b[2] = {64, 64};
          encode(fn, &tm_wo, wo, 2, d, s, b, CU_TENSOR_MAP_SWIZZLE_128B); }
        { cuuint64_t d[2] = {1792, 512}, s[1] = {3584}; cuuint32_t b[2] = {32, 64};
          encode(fn, &tm_wg, wgate, 2, d, s, b, CU_TENSOR_MAP_SWIZZLE_64B);
          encode(fn, &tm_wu, wup, 2, d, s, b, CU_TENSOR_MAP_SWIZZLE_64B); }
        { cuuint64_t d[2] = {512, 1792}, s[1] = {1024}; cuuint32_t b[2] = {64, 64};
          encode(fn, &tm_wd, wdown, 2, d, s, b, CU_TENSOR_MAP_SWIZZLE_128B); }
        cudaFuncSetAttribute(qkv_kernel, cudaFuncAttributeMaxDynamicSharedMemorySize, F_SMEM);
        cudaFuncSetAttribute(qkv_kernel, cudaFuncAttributePreferredSharedMemoryCarveout, 100);
        cudaFuncSetAttribute(attn_kernel, cudaFuncAttributeMaxDynamicSharedMemorySize, F_SMEM);
        cudaFuncSetAttribute(attn_kernel, cudaFuncAttributePreferredSharedMemoryCarveout, 100);
        cudaFuncSetAttribute(tail_kernel, cudaFuncAttributeMaxDynamicSharedMemorySize, F_SMEM);
        cudaFuncSetAttribute(tail_kernel, cudaFuncAttributePreferredSharedMemoryCarveout, 100);
        cached[0] = x; cached[1] = wqkv; cached[2] = wo; cached[3] = wgate; cached[4] = wup; cached[5] = wdown; cached[6] = out;
    }
    launch(qkv_kernel, 128, 384, F_SMEM, false, tm_x, tm_wqkv, x, wqkv);
    launch(attn_kernel, 132, 512, F_SMEM, true, wgate, wup, wo, wdown);
    launch(tail_kernel, 128, 384, F_SMEM, true, tm_wo, tm_wg, tm_wu, tm_wd, tm_out, x);
}
```

```cpp
#include <cuda_runtime.h>
#include <cuda_bf16.h>
#include <cuda.h>
#include <stdint.h>

namespace {

constexpr int S_LEN = 2048, DM = 512, NH = 32, FF = 1792;

__device__ __align__(1024) __nv_bfloat16 g_qkv[3 * NH * S_LEN * 16];
__device__ __align__(1024) __nv_bfloat16 g_ao[S_LEN * DM];
__device__ __align__(1024) __nv_bfloat16 g_h[S_LEN * DM];
__device__ __align__(1024) __nv_bfloat16 g_g[S_LEN * FF];
__device__ __align__(16) float2 g_rowstat1[S_LEN];
__device__ __align__(16) float g_cs1_part[16 * 1536];
__device__ unsigned int g_cnt[32];
__device__ unsigned int g_cnt2[160];
__device__ __align__(16) float g_nrm[3 * NH * 128];
__device__ __align__(16) float2 g_hstat[S_LEN * 8];
__device__ float g_cs2[2 * FF];

__device__ __forceinline__ uint32_t smem_u32(const void* p) { return (uint32_t)__cvta_generic_to_shared(p); }
__device__ __forceinline__ void mbar_init(uint32_t a, int c) { asm volatile("mbarrier.init.shared.b64 [%0], %1;" :: "r"(a), "r"(c)); }
__device__ __forceinline__ void mbar_expect(uint32_t a, int bytes) { asm volatile("mbarrier.arrive.expect_tx.shared.b64 _, [%0], %1;" :: "r"(a), "r"(bytes) : "memory"); }
__device__ __forceinline__ void mbar_arrive(uint32_t a) { asm volatile("mbarrier.arrive.shared.b64 _, [%0];" :: "r"(a) : "memory"); }
__device__ __forceinline__ void mbar_wait(uint32_t a, int parity) {
    uint32_t done;
    int it = 0;
    do {
        asm volatile("{\n.reg .pred p;\nmbarrier.try_wait.parity.shared.b64 p, [%1], %2;\nselp.u32 %0, 1, 0, p;\n}"
                     : "=r"(done) : "r"(a), "r"(parity) : "memory");
        if (++it > (1 << 24)) __trap();
    } while (!done);
}
__device__ __forceinline__ void bulk_g2s(uint32_t dst, const void* src, int bytes, uint32_t bar) {
    asm volatile("cp.async.bulk.shared::cluster.global.mbarrier::complete_tx::bytes [%0], [%1], %2, [%3];"
                 :: "r"(dst), "l"(src), "r"(bytes), "r"(bar) : "memory");
}
__device__ __forceinline__ void tma2d(uint32_t dst, const CUtensorMap* m, int c0, int c1, uint32_t bar) {
    asm volatile("cp.async.bulk.tensor.2d.shared::cluster.global.mbarrier::complete_tx::bytes [%0], [%1, {%3, %4}], [%2];"
                 :: "r"(dst), "l"(m), "r"(bar), "r"(c0), "r"(c1) : "memory");
}
__device__ __forceinline__ void tma3d(uint32_t dst, const CUtensorMap* m, int c0, int c1, int c2, uint32_t bar) {
    asm volatile("cp.async.bulk.tensor.3d.shared::cluster.global.mbarrier::complete_tx::bytes [%0], [%1, {%3, %4, %5}], [%2];"
                 :: "r"(dst), "l"(m), "r"(bar), "r"(c0), "r"(c1), "r"(c2) : "memory");
}
__device__ __forceinline__ void pdl_wait() { asm volatile("griddepcontrol.wait;" ::: "memory"); }
__device__ __forceinline__ void pdl_launch() { asm volatile("griddepcontrol.launch_dependents;" ::: "memory"); }
__device__ __forceinline__ void fence_barrier_init() { asm volatile("fence.mbarrier_init.release.cluster;" ::: "memory"); }
__device__ __forceinline__ void fence_proxy_async() { asm volatile("fence.proxy.async.shared::cta;" ::: "memory"); }
__device__ __forceinline__ uint64_t make_desc(uint32_t saddr, uint32_t lbo, uint32_t sbo, uint32_t swz) {
    return (uint64_t)((saddr & 0x3FFFF) >> 4) | ((uint64_t)((lbo & 0x3FFFF) >> 4) << 16) |
           ((uint64_t)((sbo & 0x3FFFF) >> 4) << 32) | ((uint64_t)swz << 62);
}
#define WG_FENCE() asm volatile("wgmma.fence.sync.aligned;" ::: "memory")
#define WG_COMMIT() asm volatile("wgmma.commit_group.sync.aligned;" ::: "memory")
template <int N> __device__ __forceinline__ void wg_wait() { asm volatile("wgmma.wait_group.sync.aligned %0;" :: "n"(N) : "memory"); }
template <int N> __device__ __forceinline__ void fence_regs(float (&d)[N]) {
#pragma unroll
    for (int i = 0; i < N; i++) asm volatile("" : "+f"(d[i]) :: "memory");
}
__device__ __forceinline__ float ex2f(float x) { float y; asm("ex2.approx.ftz.f32 %0, %1;" : "=f"(y) : "f"(x)); return y; }
__device__ __forceinline__ float tanh_fast(float x) { float y; asm("tanh.approx.f32 %0, %1;" : "=f"(y) : "f"(x)); return y; }
__device__ __forceinline__ uint32_t pack_bf16(float lo, float hi) { uint32_t r; asm("cvt.rn.bf16x2.f32 %0, %1, %2;" : "=r"(r) : "f"(hi), "f"(lo)); return r; }
__device__ __forceinline__ float bf_lo(uint32_t u) { return __uint_as_float(u << 16); }
__device__ __forceinline__ float bf_hi(uint32_t u) { return __uint_as_float(u & 0xFFFF0000u); }
__device__ __forceinline__ uint32_t hfma2(uint32_t a, uint32_t b, uint32_t c) { uint32_t r; asm("fma.rn.f16x2 %0, %1, %2, %3;" : "=r"(r) : "r"(a), "r"(b), "r"(c)); return r; }
__device__ __forceinline__ uint32_t hmul2(uint32_t a, uint32_t b) { uint32_t r; asm("mul.rn.f16x2 %0, %1, %2;" : "=r"(r) : "r"(a), "r"(b)); return r; }
__device__ __forceinline__ unsigned int ld_acquire(const unsigned int* p) { unsigned int v; asm volatile("ld.acquire.gpu.u32 %0, [%1];" : "=r"(v) : "l"(p) : "memory"); return v; }
__device__ __forceinline__ void red_release(unsigned int* p) { asm volatile("red.release.gpu.global.add.u32 [%0], 1;" :: "l"(p) : "memory"); }
__device__ __forceinline__ void stsm4(uint32_t addr, uint32_t a, uint32_t b, uint32_t c, uint32_t d) {
    asm volatile("stmatrix.sync.aligned.m8n8.x4.shared.b16 [%0], {%1,%2,%3,%4};" :: "r"(addr), "r"(a), "r"(b), "r"(c), "r"(d) : "memory");
}
__device__ __forceinline__ void bulk_commit() { asm volatile("cp.async.bulk.commit_group;" ::: "memory"); }
__device__ __forceinline__ void bulk_wait_all() { asm volatile("cp.async.bulk.wait_group 0;" ::: "memory"); }
__device__ __forceinline__ void bar_sync(int id, int n) { asm volatile("bar.sync %0, %1;" :: "r"(id), "r"(n) : "memory"); }
__device__ __forceinline__ void bar_arrive(int id, int n) { asm volatile("bar.arrive %0, %1;" :: "r"(id), "r"(n) : "memory"); }
__device__ __forceinline__ float warp_sum(float v) {
#pragma unroll
    for (int o = 16; o; o >>= 1) v += __shfl_xor_sync(0xffffffffu, v, o);
    return v;
}
__device__ __forceinline__ float warp_max(float v) {
#pragma unroll
    for (int o = 16; o; o >>= 1) v = fmaxf(v, __shfl_xor_sync(0xffffffffu, v, o));
    return v;
}

__device__ __forceinline__ void wgmma_ss_n64(float (&d)[32], uint64_t adesc, uint64_t bdesc, int scale_d) {
    asm volatile("{\n.reg .pred p;\nsetp.ne.b32 p, %34, 0;\n"
      "wgmma.mma_async.sync.aligned.m64n64k16.f32.bf16.bf16 {%0,%1,%2,%3,%4,%5,%6,%7,%8,%9,%10,%11,%12,%13,%14,%15,%16,%17,%18,%19,%20,%21,%22,%23,%24,%25,%26,%27,%28,%29,%30,%31}, %32, %33, p, 1, 1, 0, 1;\n}"
      : "+f"(d[0]), "+f"(d[1]), "+f"(d[2]), "+f"(d[3]), "+f"(d[4]), "+f"(d[5]), "+f"(d[6]), "+f"(d[7]), "+f"(d[8]), "+f"(d[9]), "+f"(d[10]), "+f"(d[11]), "+f"(d[12]), "+f"(d[13]), "+f"(d[14]), "+f"(d[15]), "+f"(d[16]), "+f"(d[17]), "+f"(d[18]), "+f"(d[19]), "+f"(d[20]), "+f"(d[21]), "+f"(d[22]), "+f"(d[23]), "+f"(d[24]), "+f"(d[25]), "+f"(d[26]), "+f"(d[27]), "+f"(d[28]), "+f"(d[29]), "+f"(d[30]), "+f"(d[31])
      : "l"(adesc), "l"(bdesc), "r"(scale_d));
}
__device__ __forceinline__ void wgmma_ss_n128(float (&d)[64], uint64_t adesc, uint64_t bdesc, int scale_d) {
    asm volatile("{\n.reg .pred p;\nsetp.ne.b32 p, %66, 0;\n"
      "wgmma.mma_async.sync.aligned.m64n128k16.f32.bf16.bf16 {%0,%1,%2,%3,%4,%5,%6,%7,%8,%9,%10,%11,%12,%13,%14,%15,%16,%17,%18,%19,%20,%21,%22,%23,%24,%25,%26,%27,%28,%29,%30,%31,%32,%33,%34,%35,%36,%37,%38,%39,%40,%41,%42,%43,%44,%45,%46,%47,%48,%49,%50,%51,%52,%53,%54,%55,%56,%57,%58,%59,%60,%61,%62,%63}, %64, %65, p, 1, 1, 0, 1;\n}"
      : "+f"(d[0]), "+f"(d[1]), "+f"(d[2]), "+f"(d[3]), "+f"(d[4]), "+f"(d[5]), "+f"(d[6]), "+f"(d[7]), "+f"(d[8]), "+f"(d[9]), "+f"(d[10]), "+f"(d[11]), "+f"(d[12]), "+f"(d[13]), "+f"(d[14]), "+f"(d[15]), "+f"(d[16]), "+f"(d[17]), "+f"(d[18]), "+f"(d[19]), "+f"(d[20]), "+f"(d[21]), "+f"(d[22]), "+f"(d[23]), "+f"(d[24]), "+f"(d[25]), "+f"(d[26]), "+f"(d[27]), "+f"(d[28]), "+f"(d[29]), "+f"(d[30]), "+f"(d[31]), "+f"(d[32]), "+f"(d[33]), "+f"(d[34]), "+f"(d[35]), "+f"(d[36]), "+f"(d[37]), "+f"(d[38]), "+f"(d[39]), "+f"(d[40]), "+f"(d[41]), "+f"(d[42]), "+f"(d[43]), "+f"(d[44]), "+f"(d[45]), "+f"(d[46]), "+f"(d[47]), "+f"(d[48]), "+f"(d[49]), "+f"(d[50]), "+f"(d[51]), "+f"(d[52]), "+f"(d[53]), "+f"(d[54]), "+f"(d[55]), "+f"(d[56]), "+f"(d[57]), "+f"(d[58]), "+f"(d[59]), "+f"(d[60]), "+f"(d[61]), "+f"(d[62]), "+f"(d[63])
      : "l"(adesc), "l"(bdesc), "r"(scale_d));
}
__device__ __forceinline__ void wgmma_ss_n192(float (&d)[96], uint64_t adesc, uint64_t bdesc, int scale_d) {
    asm volatile("{\n.reg .pred p;\nsetp.ne.b32 p, %98, 0;\n"
      "wgmma.mma_async.sync.aligned.m64n192k16.f32.bf16.bf16 {%0,%1,%2,%3,%4,%5,%6,%7,%8,%9,%10,%11,%12,%13,%14,%15,%16,%17,%18,%19,%20,%21,%22,%23,%24,%25,%26,%27,%28,%29,%30,%31,%32,%33,%34,%35,%36,%37,%38,%39,%40,%41,%42,%43,%44,%45,%46,%47,%48,%49,%50,%51,%52,%53,%54,%55,%56,%57,%58,%59,%60,%61,%62,%63,%64,%65,%66,%67,%68,%69,%70,%71,%72,%73,%74,%75,%76,%77,%78,%79,%80,%81,%82,%83,%84,%85,%86,%87,%88,%89,%90,%91,%92,%93,%94,%95}, %96, %97, p, 1, 1, 0, 1;\n}"
      : "+f"(d[0]), "+f"(d[1]), "+f"(d[2]), "+f"(d[3]), "+f"(d[4]), "+f"(d[5]), "+f"(d[6]), "+f"(d[7]), "+f"(d[8]), "+f"(d[9]), "+f"(d[10]), "+f"(d[11]), "+f"(d[12]), "+f"(d[13]), "+f"(d[14]), "+f"(d[15]), "+f"(d[16]), "+f"(d[17]), "+f"(d[18]), "+f"(d[19]), "+f"(d[20]), "+f"(d[21]), "+f"(d[22]), "+f"(d[23]), "+f"(d[24]), "+f"(d[25]), "+f"(d[26]), "+f"(d[27]), "+f"(d[28]), "+f"(d[29]), "+f"(d[30]), "+f"(d[31]), "+f"(d[32]), "+f"(d[33]), "+f"(d[34]), "+f"(d[35]), "+f"(d[36]), "+f"(d[37]), "+f"(d[38]), "+f"(d[39]), "+f"(d[40]), "+f"(d[41]), "+f"(d[42]), "+f"(d[43]), "+f"(d[44]), "+f"(d[45]), "+f"(d[46]), "+f"(d[47]), "+f"(d[48]), "+f"(d[49]), "+f"(d[50]), "+f"(d[51]), "+f"(d[52]), "+f"(d[53]), "+f"(d[54]), "+f"(d[55]), "+f"(d[56]), "+f"(d[57]), "+f"(d[58]), "+f"(d[59]), "+f"(d[60]), "+f"(d[61]), "+f"(d[62]), "+f"(d[63]), "+f"(d[64]), "+f"(d[65]), "+f"(d[66]), "+f"(d[67]), "+f"(d[68]), "+f"(d[69]), "+f"(d[70]), "+f"(d[71]), "+f"(d[72]), "+f"(d[73]), "+f"(d[74]), "+f"(d[75]), "+f"(d[76]), "+f"(d[77]), "+f"(d[78]), "+f"(d[79]), "+f"(d[80]), "+f"(d[81]), "+f"(d[82]), "+f"(d[83]), "+f"(d[84]), "+f"(d[85]), "+f"(d[86]), "+f"(d[87]), "+f"(d[88]), "+f"(d[89]), "+f"(d[90]), "+f"(d[91]), "+f"(d[92]), "+f"(d[93]), "+f"(d[94]), "+f"(d[95])
      : "l"(adesc), "l"(bdesc), "r"(scale_d));
}
__device__ __forceinline__ void wgmma_ss_n256(float (&d)[128], uint64_t adesc, uint64_t bdesc, int scale_d) {
    asm volatile("{\n.reg .pred p;\nsetp.ne.b32 p, %130, 0;\n"
      "wgmma.mma_async.sync.aligned.m64n256k16.f32.bf16.bf16 {%0,%1,%2,%3,%4,%5,%6,%7,%8,%9,%10,%11,%12,%13,%14,%15,%16,%17,%18,%19,%20,%21,%22,%23,%24,%25,%26,%27,%28,%29,%30,%31,%32,%33,%34,%35,%36,%37,%38,%39,%40,%41,%42,%43,%44,%45,%46,%47,%48,%49,%50,%51,%52,%53,%54,%55,%56,%57,%58,%59,%60,%61,%62,%63,%64,%65,%66,%67,%68,%69,%70,%71,%72,%73,%74,%75,%76,%77,%78,%79,%80,%81,%82,%83,%84,%85,%86,%87,%88,%89,%90,%91,%92,%93,%94,%95,%96,%97,%98,%99,%100,%101,%102,%103,%104,%105,%106,%107,%108,%109,%110,%111,%112,%113,%114,%115,%116,%117,%118,%119,%120,%121,%122,%123,%124,%125,%126,%127}, %128, %129, p, 1, 1, 0, 1;\n}"
      : "+f"(d[0]), "+f"(d[1]), "+f"(d[2]), "+f"(d[3]), "+f"(d[4]), "+f"(d[5]), "+f"(d[6]), "+f"(d[7]), "+f"(d[8]), "+f"(d[9]), "+f"(d[10]), "+f"(d[11]), "+f"(d[12]), "+f"(d[13]), "+f"(d[14]), "+f"(d[15]), "+f"(d[16]), "+f"(d[17]), "+f"(d[18]), "+f"(d[19]), "+f"(d[20]), "+f"(d[21]), "+f"(d[22]), "+f"(d[23]), "+f"(d[24]), "+f"(d[25]), "+f"(d[26]), "+f"(d[27]), "+f"(d[28]), "+f"(d[29]), "+f"(d[30]), "+f"(d[31]), "+f"(d[32]), "+f"(d[33]), "+f"(d[34]), "+f"(d[35]), "+f"(d[36]), "+f"(d[37]), "+f"(d[38]), "+f"(d[39]), "+f"(d[40]), "+f"(d[41]), "+f"(d[42]), "+f"(d[43]), "+f"(d[44]), "+f"(d[45]), "+f"(d[46]), "+f"(d[47]), "+f"(d[48]), "+f"(d[49]), "+f"(d[50]), "+f"(d[51]), "+f"(d[52]), "+f"(d[53]), "+f"(d[54]), "+f"(d[55]), "+f"(d[56]), "+f"(d[57]), "+f"(d[58]), "+f"(d[59]), "+f"(d[60]), "+f"(d[61]), "+f"(d[62]), "+f"(d[63]), "+f"(d[64]), "+f"(d[65]), "+f"(d[66]), "+f"(d[67]), "+f"(d[68]), "+f"(d[69]), "+f"(d[70]), "+f"(d[71]), "+f"(d[72]), "+f"(d[73]), "+f"(d[74]), "+f"(d[75]), "+f"(d[76]), "+f"(d[77]), "+f"(d[78]), "+f"(d[79]), "+f"(d[80]), "+f"(d[81]), "+f"(d[82]), "+f"(d[83]), "+f"(d[84]), "+f"(d[85]), "+f"(d[86]), "+f"(d[87]), "+f"(d[88]), "+f"(d[89]), "+f"(d[90]), "+f"(d[91]), "+f"(d[92]), "+f"(d[93]), "+f"(d[94]), "+f"(d[95]), "+f"(d[96]), "+f"(d[97]), "+f"(d[98]), "+f"(d[99]), "+f"(d[100]), "+f"(d[101]), "+f"(d[102]), "+f"(d[103]), "+f"(d[104]), "+f"(d[105]), "+f"(d[106]), "+f"(d[107]), "+f"(d[108]), "+f"(d[109]), "+f"(d[110]), "+f"(d[111]), "+f"(d[112]), "+f"(d[113]), "+f"(d[114]), "+f"(d[115]), "+f"(d[116]), "+f"(d[117]), "+f"(d[118]), "+f"(d[119]), "+f"(d[120]), "+f"(d[121]), "+f"(d[122]), "+f"(d[123]), "+f"(d[124]), "+f"(d[125]), "+f"(d[126]), "+f"(d[127])
      : "l"(adesc), "l"(bdesc), "r"(scale_d));
}
__device__ __forceinline__ void qk_wgmma_n64(float (&d)[32], const uint32_t (&a)[4], uint64_t desc) {
    asm volatile("wgmma.mma_async.sync.aligned.m64n64k16.f32.bf16.bf16 {%0,%1,%2,%3,%4,%5,%6,%7,%8,%9,%10,%11,%12,%13,%14,%15,%16,%17,%18,%19,%20,%21,%22,%23,%24,%25,%26,%27,%28,%29,%30,%31}, {%32,%33,%34,%35}, %36, 0, 1, 1, 0;"
      : "=f"(d[0]), "=f"(d[1]), "=f"(d[2]), "=f"(d[3]), "=f"(d[4]), "=f"(d[5]), "=f"(d[6]), "=f"(d[7]), "=f"(d[8]), "=f"(d[9]), "=f"(d[10]), "=f"(d[11]), "=f"(d[12]), "=f"(d[13]), "=f"(d[14]), "=f"(d[15]), "=f"(d[16]), "=f"(d[17]), "=f"(d[18]), "=f"(d[19]), "=f"(d[20]), "=f"(d[21]), "=f"(d[22]), "=f"(d[23]), "=f"(d[24]), "=f"(d[25]), "=f"(d[26]), "=f"(d[27]), "=f"(d[28]), "=f"(d[29]), "=f"(d[30]), "=f"(d[31])
      : "r"(a[0]), "r"(a[1]), "r"(a[2]), "r"(a[3]), "l"(desc));
}

__device__ __forceinline__ void pv_wgmma(float (&d)[12], uint32_t a0, uint32_t a1, uint32_t a2, uint32_t a3, uint64_t desc) {
    asm volatile("wgmma.mma_async.sync.aligned.m64n24k16.f32.bf16.bf16 {%0,%1,%2,%3,%4,%5,%6,%7,%8,%9,%10,%11}, {%12,%13,%14,%15}, %16, 1, 1, 1, 1;"
      : "+f"(d[0]), "+f"(d[1]), "+f"(d[2]), "+f"(d[3]), "+f"(d[4]), "+f"(d[5]), "+f"(d[6]), "+f"(d[7]), "+f"(d[8]), "+f"(d[9]), "+f"(d[10]), "+f"(d[11])
      : "r"(a0), "r"(a1), "r"(a2), "r"(a3), "l"(desc));
}

__device__ __forceinline__ uint32_t mapa(uint32_t a, uint32_t rank) { uint32_t r; asm("mapa.shared::cluster.u32 %0, %1, %2;" : "=r"(r) : "r"(a), "r"(rank)); return r; }
__device__ __forceinline__ void mbar_arrive_remote(uint32_t a) { asm volatile("mbarrier.arrive.relaxed.cluster.shared::cluster.b64 _, [%0];" :: "r"(a) : "memory"); }
__device__ __forceinline__ void mbar_wait_cluster(uint32_t a, int parity) {
    uint32_t done;
    int it = 0;
    do {
        asm volatile("{\n.reg .pred p;\nmbarrier.try_wait.parity.acquire.cluster.shared::cta.b64 p, [%1], %2;\nselp.u32 %0, 1, 0, p;\n}"
                     : "=r"(done) : "r"(a), "r"(parity) : "memory");
        if (++it > (1 << 24)) __trap();
    } while (!done);
}
__device__ __forceinline__ void tma2d_mc(uint32_t dst, const CUtensorMap* m, int c0, int c1, uint32_t bar) {
    asm volatile("cp.async.bulk.tensor.2d.shared::cluster.global.mbarrier::complete_tx::bytes.multicast::cluster [%0], [%1, {%3, %4}], [%2], %5;"
                 :: "r"(dst), "l"(m), "r"(bar), "r"(c0), "r"(c1), "h"((uint16_t)3) : "memory");
}
__device__ __forceinline__ void bulk_g2s_mc(uint32_t dst, const void* src, int bytes, uint32_t bar) {
    asm volatile("cp.async.bulk.shared::cluster.global.mbarrier::complete_tx::bytes.multicast::cluster [%0], [%1], %2, [%3], %4;"
                 :: "r"(dst), "l"(src), "r"(bytes), "r"(bar), "h"((uint16_t)3) : "memory");
}
__device__ __forceinline__ void tile_of(int bid, int& mb, int& nt) {
    int grp = bid >> 4, in = bid & 15;
    mb = (grp >> 1) * 4 + (in >> 2);
    nt = (grp & 1) * 4 + (in & 3);
}

constexpr int K1_STAGES = 5, K1_STAGE = 16384 + 24576;
constexpr int K1_BAR = K1_STAGES * K1_STAGE, K1_RS = K1_BAR + 128, K1_CS = K1_RS + 1024, K1_SMEM = K1_CS + 768;

__device__ __forceinline__ float2 row_stats_regs(uint4 a, uint4 b) {
    float v[16];
    v[0] = bf_lo(a.x); v[1] = bf_hi(a.x); v[2] = bf_lo(a.y); v[3] = bf_hi(a.y);
    v[4] = bf_lo(a.z); v[5] = bf_hi(a.z); v[6] = bf_lo(a.w); v[7] = bf_hi(a.w);
    v[8] = bf_lo(b.x); v[9] = bf_hi(b.x); v[10] = bf_lo(b.y); v[11] = bf_hi(b.y);
    v[12] = bf_lo(b.z); v[13] = bf_hi(b.z); v[14] = bf_lo(b.w); v[15] = bf_hi(b.w);
    float s = 0.f;
#pragma unroll
    for (int i = 0; i < 16; i++) s += v[i];
    float mean = warp_sum(s) * (1.0f / DM);
    float q = 0.f;
#pragma unroll
    for (int i = 0; i < 16; i++) { float d = v[i] - mean; q = fmaf(d, d, q); }
    float var = warp_sum(q) * (1.0f / DM);
    float rstd = rsqrtf(var + 1e-5f);
    return make_float2(rstd, -mean * rstd);
}
__device__ __forceinline__ float2 row_stats_x(const __nv_bfloat16* x, int row, int lane) {
    const uint4* p = (const uint4*)(x + (size_t)row * DM);
    return row_stats_regs(__ldg(p + lane), __ldg(p + 32 + lane));
}
__device__ __forceinline__ void colsum8(const __nv_bfloat16* w, int ld, int col, int k0, int nk, float (&s)[8]) {
#pragma unroll
    for (int i = 0; i < 8; i++) s[i] = 0.f;
    for (int k = k0; k < k0 + nk; k += 8) {
        uint4 u[8];
#pragma unroll
        for (int i = 0; i < 8; i++) u[i] = __ldg((const uint4*)(w + (size_t)(k + i) * ld + col));
#pragma unroll
        for (int i = 0; i < 8; i++) {
            s[0] += bf_lo(u[i].x); s[1] += bf_hi(u[i].x); s[2] += bf_lo(u[i].y); s[3] += bf_hi(u[i].y);
            s[4] += bf_lo(u[i].z); s[5] += bf_hi(u[i].z); s[6] += bf_lo(u[i].w); s[7] += bf_hi(u[i].w);
        }
    }
}
__device__ __forceinline__ bool wait_count(const unsigned int* p, unsigned int target, int lane) {
    int ok = 1;
    if (lane == 0) {
        int it = 0;
        while (ld_acquire(p) < target) { if (++it > (1 << 18)) { ok = 0; break; } }
    }
    ok = __shfl_sync(0xffffffffu, ok, 0);
    return ok != 0;
}

__global__ void __launch_bounds__(384, 1)
qkv_kernel(const __grid_constant__ CUtensorMap tm_x, const __grid_constant__ CUtensorMap tm_w,
           const __nv_bfloat16* __restrict__ x, const __nv_bfloat16* __restrict__ wqkv) {
    extern __shared__ __align__(1024) unsigned char smem[];
    const uint32_t sb = smem_u32(smem);
    const int tid = threadIdx.x, warp = __shfl_sync(0xffffffffu, tid >> 5, 0), lane = tid & 31;
    int mb, nt;
    tile_of(blockIdx.x, mb, nt);
    const uint32_t full = sb + K1_BAR, empty = full + 40, auxb = full + 80;
    if (tid == 0) {
#pragma unroll
        for (int i = 0; i < K1_STAGES; i++) { mbar_init(full + 8 * i, 1); mbar_init(empty + 8 * i, 8); }
        mbar_init(auxb, 3);
        fence_barrier_init();
        for (int kb = 0; kb < K1_STAGES; kb++) {
            mbar_expect(full + 8 * kb, K1_STAGE);
            tma2d(sb + kb * K1_STAGE, &tm_x, kb * 64, mb * 128, full + 8 * kb);
            tma3d(sb + kb * K1_STAGE + 16384, &tm_w, 0, kb * 64, nt * 3, full + 8 * kb);
        }
    }
    __syncthreads();
    pdl_launch();
    if (warp == 0) {
        if (blockIdx.x == 0) g_cnt2[lane] = 0;
        if (lane == 0) {
            g_cnt2[32 + blockIdx.x] = 0;
            for (int kb = K1_STAGES; kb < 8; kb++) {
                int s = kb % K1_STAGES;
                mbar_wait(empty + 8 * s, 0);
                mbar_expect(full + 8 * s, K1_STAGE);
                tma2d(sb + s * K1_STAGE, &tm_x, kb * 64, mb * 128, full + 8 * s);
                tma3d(sb + s * K1_STAGE + 16384, &tm_w, 0, kb * 64, nt * 3, full + 8 * s);
            }
        }
    } else if (warp < 4) {
        float2* s_rs = (float2*)(smem + K1_RS);
        float* s_cs = (float*)(smem + K1_CS);
        if (warp < 3) {
            const int r0 = mb * 128 + nt * 16 + (warp - 1) * 8;
            uint4 u[16];
#pragma unroll
            for (int i = 0; i < 8; i++) {
                const uint4* p = (const uint4*)(x + (size_t)(r0 + i) * DM);
                u[2 * i] = __ldg(p + lane); u[2 * i + 1] = __ldg(p + 32 + lane);
            }
            float2 mine = make_float2(0.f, 0.f);
#pragma unroll
            for (int i = 0; i < 8; i++) {
                float2 st = row_stats_regs(u[2 * i], u[2 * i + 1]);
                if (lane == i) mine = st;
            }
            if (lane < 8) g_rowstat1[r0 + lane] = mine;
            __syncwarp();
            if (lane == 0) red_release(&g_cnt[mb]);
        } else {
            uint4 u[24];
#pragma unroll
            for (int c = 0; c < 3; c++)
#pragma unroll
                for (int i = 0; i < 8; i++)
                    u[c * 8 + i] = __ldg((const uint4*)(wqkv + (size_t)(mb * 32 + (lane >> 3) * 8 + i) * 1536 + nt * 192 + (c * 8 + (lane & 7)) * 8));
#pragma unroll
            for (int c = 0; c < 3; c++) {
                float cs[8];
#pragma unroll
                for (int i = 0; i < 8; i++) cs[i] = 0.f;
#pragma unroll
                for (int i = 0; i < 8; i++) {
                    const uint4 w = u[c * 8 + i];
                    cs[0] += bf_lo(w.x); cs[1] += bf_hi(w.x); cs[2] += bf_lo(w.y); cs[3] += bf_hi(w.y);
                    cs[4] += bf_lo(w.z); cs[5] += bf_hi(w.z); cs[6] += bf_lo(w.w); cs[7] += bf_hi(w.w);
                }
#pragma unroll
                for (int i = 0; i < 8; i++) {
                    cs[i] += __shfl_xor_sync(0xffffffffu, cs[i], 8);
                    cs[i] += __shfl_xor_sync(0xffffffffu, cs[i], 16);
                }
                if (lane < 8) {
                    float4* d = (float4*)(g_cs1_part + mb * 1536 + nt * 192 + (c * 8 + lane) * 8);
                    d[0] = make_float4(cs[0], cs[1], cs[2], cs[3]);
                    d[1] = make_float4(cs[4], cs[5], cs[6], cs[7]);
                }
            }
            __syncwarp();
            if (lane == 0) red_release(&g_cnt[16 + nt]);
        }
        if (warp == 1) {
            if (wait_count(&g_cnt[mb], 16, lane)) {
#pragma unroll
                for (int i = 0; i < 4; i++) s_rs[lane + 32 * i] = __ldcg(&g_rowstat1[mb * 128 + lane + 32 * i]);
            } else {
                for (int i = 0; i < 128; i++) {
                    float2 st = row_stats_x(x, mb * 128 + i, lane);
                    if (lane == 0) s_rs[i] = st;
                }
            }
        } else {
            int c0 = (warp - 2) * 96;
            if (wait_count(&g_cnt[16 + nt], 16, lane)) {
#pragma unroll
                for (int i = 0; i < 3; i++) {
                    float s = 0.f;
#pragma unroll
                    for (int p = 0; p < 16; p++) s += __ldcg(&g_cs1_part[p * 1536 + nt * 192 + c0 + lane + 32 * i]);
                    s_cs[c0 + lane + 32 * i] = s;
                }
            } else if (lane < 12) {
                float s[8];
                colsum8(wqkv, 1536, nt * 192 + c0 + lane * 8, 0, 512, s);
#pragma unroll
                for (int i = 0; i < 8; i++) s_cs[c0 + lane * 8 + i] = s[i];
            }
        }
        __syncwarp();
        if (lane == 0) mbar_arrive(auxb);
        bar_sync(2, 256 + 96);
        const int a = tid - 32;
        {
            const int hh = a >> 3, w = a & 7;
            const float4* p = (const float4*)(smem + 49152) + (hh * 256 + w * 32) / 2;
            float m = 0.f;
#pragma unroll
            for (int i = 0; i < 8; i++) {
                const int ii = (i + a) & 7;
                float4 u = p[2 * ii], v = p[2 * ii + 1];
                float n0 = u.x + u.z + v.x + v.z, n1 = u.y + u.w + v.y + v.w;
                if (!(n0 <= 3.0e38f) || !(n1 <= 3.0e38f)) m = __int_as_float(0x7f800000);
                m = fmaxf(m, fmaxf(n0, n1));
            }
            const int col0 = nt * 192 + hh * 16;
            g_nrm[((col0 >> 9) * NH + ((col0 & 511) >> 4)) * 128 + mb * 8 + w] = m;
        }
    } else {
        const int wgi = (warp >> 2) - 1, ww = warp & 3;
        float acc[96];
#pragma unroll 1
        for (int kb = 0; kb < 8; kb++) {
            int s = kb % K1_STAGES;
            mbar_wait(full + 8 * s, (kb / K1_STAGES) & 1);
            uint64_t ad = make_desc(sb + s * K1_STAGE + wgi * 8192, 16, 1024, 1);
            uint64_t bd = make_desc(sb + s * K1_STAGE + 16384, 8192, 1024, 1);
            WG_FENCE();
#pragma unroll
            for (int k = 0; k < 4; k++) wgmma_ss_n192(acc, ad + k * 2, bd + k * 128, (kb | k) != 0);
            WG_COMMIT();
            if (kb > 0) {
                wg_wait<1>();
                if (lane == 0) mbar_arrive(empty + 8 * ((kb - 1) % K1_STAGES));
            }
        }
        wg_wait<0>();
        fence_regs(acc);
        mbar_wait(auxb, 0);
        bar_sync(1, 256);
        const float2* s_rs = (const float2*)(smem + K1_RS);
        const float* s_cs = (const float*)(smem + K1_CS);
        const int g = lane >> 2, t = lane & 3;
        const int rl = wgi * 64 + ww * 16 + g;
        const float2 st0 = s_rs[rl], st1 = s_rs[rl + 8];
        const float QS = 0.25f * 1.4426950408889634f;
        float2* s_np = (float2*)(smem + 49152) + (warp - 4) * 32 + lane;
#pragma unroll
        for (int hh = 0; hh < 12; hh++) {
            const int which = (nt * 192 + hh * 16) >> 9;
            const float sc = (which == 0) ? QS : 1.0f;
            const float a0 = st0.x * sc, b0 = st0.y * sc, a1 = st1.x * sc, b1 = st1.y * sc;
            const float2 c0 = *(const float2*)(s_cs + 16 * hh + 2 * t), c1 = *(const float2*)(s_cs + 16 * hh + 8 + 2 * t);
            const float* a = acc + 8 * hh;
            float v0 = fmaf(a0, a[0], b0 * c0.x), v1 = fmaf(a0, a[1], b0 * c0.y), v2 = fmaf(a1, a[2], b1 * c0.x), v3 = fmaf(a1, a[3], b1 * c0.y);
            float v4 = fmaf(a0, a[4], b0 * c1.x), v5 = fmaf(a0, a[5], b0 * c1.y), v6 = fmaf(a1, a[6], b1 * c1.x), v7 = fmaf(a1, a[7], b1 * c1.y);
            {
                const int head = ((nt * 192 + hh * 16) & 511) >> 4;
                uint32_t* o = (uint32_t*)g_qkv + ((size_t)((which * NH + head) * 2) * 256 + mb * 16 + wgi * 8 + ww * 2) * 32 + lane;
                o[0] = pack_bf16(v0, v1); o[32] = pack_bf16(v2, v3); o[8192] = pack_bf16(v4, v5); o[8192 + 32] = pack_bf16(v6, v7);
            }
            s_np[hh * 256] = make_float2(fmaf(v0, v0, fmaf(v1, v1, fmaf(v4, v4, v5 * v5))), fmaf(v2, v2, fmaf(v3, v3, fmaf(v6, v6, v7 * v7))));
        }
        bar_arrive(2, 256 + 96);
    }
}

constexpr int AT_K = 0, AT_V = 65536, AT_ONES = 131072, AT_BAR = 163840, AT_SMEM = AT_BAR + 128;
constexpr uint32_t POLY_MASK = 0x7B5A;

__device__ __forceinline__ uint32_t exp2_pair_poly(float x0, float x1) {
    uint32_t t0 = __float_as_uint(x0 + 32895.0f);
    uint32_t t1 = __float_as_uint(x1 + 32895.0f);
    uint32_t gd = __byte_perm(t0, t1, 0x6420);
    uint32_t wm = __byte_perm(t0, t1, 0x5612);
    uint32_t v = hfma2(gd, 0x712d712du, 0x355c355cu);
    uint32_t z = hmul2(v, gd);
    return (wm >> 1) + z;
}
__device__ __forceinline__ uint32_t exp2_pair_mufu(float x0, float x1) { return pack_bf16(ex2f(x0), ex2f(x1)); }
template <uint32_t MASK>
__device__ __forceinline__ void exp_blocks(const float (&s)[32], uint32_t (&p)[16]) {
#pragma unroll
    for (int b = 0; b < 8; b++) {
        if ((MASK >> b) & 1) {
            p[2 * b] = exp2_pair_poly(s[4 * b], s[4 * b + 1]);
            p[2 * b + 1] = exp2_pair_poly(s[4 * b + 2], s[4 * b + 3]);
        } else {
            p[2 * b] = exp2_pair_mufu(s[4 * b], s[4 * b + 1]);
            p[2 * b + 1] = exp2_pair_mufu(s[4 * b + 2], s[4 * b + 3]);
        }
    }
}
#define PV4(P) _Pragma("unroll") for (int i = 0; i < 4; i++) { pv_wgmma(o, P[4 * i], P[4 * i + 1], P[4 * i + 2], P[4 * i + 3], vd); vd += 16; }

__device__ __forceinline__ void attn_store(float (&o)[12], int row0, int head, int lane) {
    float l0 = __shfl_sync(0xffffffffu, o[8], lane & 28);
    float l1 = __shfl_sync(0xffffffffu, o[10], lane & 28);
    float r0 = 1.0f / l0, r1 = 1.0f / l1;
    uint32_t* op = (uint32_t*)g_ao;
    int mb = row0 >> 7, rg = (row0 & 127) >> 3;
    int kb = head >> 2, kc = (head & 3) * 2;
    size_t base = (((size_t)(mb * 8 + kb) * 8 + kc) * 16 + rg) * 32 + lane;
    op[base] = pack_bf16(o[0] * r0, o[1] * r0);
    op[base + 32] = pack_bf16(o[2] * r1, o[3] * r1);
    op[base + 16 * 32] = pack_bf16(o[4] * r0, o[5] * r0);
    op[base + 16 * 32 + 32] = pack_bf16(o[6] * r1, o[7] * r1);
}

__device__ __forceinline__ void attn_load_q(uint32_t (&q)[4], const __nv_bfloat16* gq, int row0, int lane) {
    const uint32_t* qp = (const uint32_t*)gq;
    int j0 = row0 >> 3;
    q[0] = __ldcg(qp + (0 * 256 + j0) * 32 + lane);
    q[1] = __ldcg(qp + (0 * 256 + j0 + 1) * 32 + lane);
    q[2] = __ldcg(qp + (1 * 256 + j0) * 32 + lane);
    q[3] = __ldcg(qp + (1 * 256 + j0 + 1) * 32 + lane);
}

__device__ __forceinline__ void attn_tile_safe(const uint32_t (&q)[4], uint64_t kd, uint64_t vd, int row0, int head, int lane) {
    float o[12];
#pragma unroll
    for (int i = 0; i < 12; i++) o[i] = 0.f;
    float m0 = -INFINITY, m1 = -INFINITY;
    fence_regs(o);
#pragma unroll 1
    for (int j = 0; j < 32; j++) {
        float s[32];
        uint32_t p[16];
        WG_FENCE();
        qk_wgmma_n64(s, q, kd); kd += 64;
        WG_COMMIT();
        wg_wait<0>();
        fence_regs(s);
        fence_regs(o);
        float x0 = m0, x1 = m1;
#pragma unroll
        for (int b = 0; b < 8; b++) {
            x0 = fmaxf(x0, fmaxf(s[4 * b], s[4 * b + 1]));
            x1 = fmaxf(x1, fmaxf(s[4 * b + 2], s[4 * b + 3]));
        }
        x0 = fmaxf(x0, __shfl_xor_sync(0xffffffffu, x0, 1)); x0 = fmaxf(x0, __shfl_xor_sync(0xffffffffu, x0, 2));
        x1 = fmaxf(x1, __shfl_xor_sync(0xffffffffu, x1, 1)); x1 = fmaxf(x1, __shfl_xor_sync(0xffffffffu, x1, 2));
        float al0 = ex2f(m0 - x0), al1 = ex2f(m1 - x1);
        m0 = x0; m1 = x1;
#pragma unroll
        for (int i = 0; i < 3; i++) { o[4 * i] *= al0; o[4 * i + 1] *= al0; o[4 * i + 2] *= al1; o[4 * i + 3] *= al1; }
#pragma unroll
        for (int b = 0; b < 8; b++) {
            p[2 * b] = exp2_pair_mufu(s[4 * b] - m0, s[4 * b + 1] - m0);
            p[2 * b + 1] = exp2_pair_mufu(s[4 * b + 2] - m1, s[4 * b + 3] - m1);
        }
        fence_regs(o);
        WG_FENCE();
        PV4(p);
        WG_COMMIT();
        wg_wait<0>();
        fence_regs(o);
    }
    attn_store(o, row0, head, lane);
}

__global__ void __launch_bounds__(512, 1)
attn_kernel(const __nv_bfloat16* __restrict__ wg_, const __nv_bfloat16* __restrict__ wu_,
            const __nv_bfloat16* __restrict__ wo_, const __nv_bfloat16* __restrict__ wd_) {
    extern __shared__ __align__(1024) unsigned char smem[];
    const uint32_t sb = smem_u32(smem);
    const int tid = threadIdx.x, wg = tid >> 7, warp = (tid >> 5) & 3, lane = tid & 31;
    pdl_launch();
    if (blockIdx.x >= 128) {
        const int e = blockIdx.x - 128;
        const __nv_bfloat16* w = (e < 2) ? wg_ : wu_;
        float* red = (float*)smem;
        const int cgrp = tid & 127, kq = tid >> 7;
        if (cgrp < 112) {
            float s[8];
            colsum8(w, FF, (e & 1) * 896 + cgrp * 8, kq * 128, 128, s);
#pragma unroll
            for (int i = 0; i < 8; i++) red[kq * 896 + cgrp * 8 + i] = s[i];
        }
        __syncthreads();
        for (int c = tid; c < 896; c += 512)
            g_cs2[(e >> 1) * FF + (e & 1) * 896 + c] = red[c] + red[896 + c] + red[1792 + c] + red[2688 + c];
        if (tid < 32) {
            const char* p0 = (const char*)wo_ + e * (DM * DM * 2 / 4);
            for (int i = lane; i < 32; i += 32)
                asm volatile("cp.async.bulk.prefetch.L2.global [%0], %1;" :: "l"(p0 + i * 4096), "r"(4096) : "memory");
            const char* p1 = (const char*)wd_ + e * (FF * DM * 2 / 4);
            for (int i = lane; i < 112; i += 32)
                asm volatile("cp.async.bulk.prefetch.L2.global [%0], %1;" :: "l"(p1 + i * 4096), "r"(4096) : "memory");
        }
        return;
    }
    const int head = blockIdx.x >> 2, qq = blockIdx.x & 3;
    const __nv_bfloat16* gq = g_qkv + (size_t)head * (S_LEN * 16);
    const __nv_bfloat16* gk = g_qkv + (size_t)(NH + head) * (S_LEN * 16);
    const __nv_bfloat16* gv = g_qkv + (size_t)(2 * NH + head) * (S_LEN * 16);
    if (tid == 0) {
        for (int i = 0; i < 8; i++) mbar_init(sb + AT_BAR + 8 * i, 1);
        fence_barrier_init();
    }
    {
        uint4 one = make_uint4(0x00003F80u, 0, 0, 0);
#pragma unroll
        for (int i = 0; i < 4; i++) *(uint4*)(smem + AT_ONES + (i * 512 + tid) * 16) = one;
        fence_proxy_async();
    }
    __syncthreads();
    pdl_wait();
    auto load_kv = [&](int i) {
        uint32_t bar = sb + AT_BAR + 8 * i;
        mbar_expect(bar, 16384);
        bulk_g2s(sb + AT_K + i * 4096, gk + i * 2048, 4096, bar);
        bulk_g2s(sb + AT_K + 32768 + i * 4096, gk + 16384 + i * 2048, 4096, bar);
        bulk_g2s(sb + AT_V + i * 4096, gv + i * 2048, 4096, bar);
        bulk_g2s(sb + AT_V + 32768 + i * 4096, gv + 16384 + i * 2048, 4096, bar);
    };
    if (tid == 0) { load_kv(0); load_kv(1); }
    uint32_t q[4], q2[4];
    attn_load_q(q, gq, qq * 512 + wg * 64 + warp * 16, lane);
    attn_load_q(q2, gq, qq * 512 + (4 + wg) * 64 + warp * 16, lane);
    bool fast;
    {
        const float* nq = g_nrm + (0 * NH + head) * 128 + qq * 32;
        const float* nk = g_nrm + (1 * NH + head) * 128;
        const float* nv = g_nrm + (2 * NH + head) * 128;
        float4 k4 = __ldcg((const float4*)nk + lane), v4 = __ldcg((const float4*)nv + lane);
        float qm = warp_max(__ldcg(nq + lane));
        float km = warp_max(fmaxf(fmaxf(k4.x, k4.y), fmaxf(k4.z, k4.w)));
        float vm = warp_max(fmaxf(fmaxf(v4.x, v4.y), fmaxf(v4.z, v4.w)));
        fast = __all_sync(0xffffffffu, (qm * km <= 3500.0f) && (vm <= 1.0e24f));
    }
    const uint64_t kdesc0 = make_desc(sb + AT_K, 32768, 128, 0);
    const uint64_t vdesc0 = make_desc(sb + AT_V, 128, 32768, 0);
    if (!fast) {
        if (tid == 0) for (int i = 2; i < 8; i++) load_kv(i);
        for (int i = 0; i < 8; i++) mbar_wait(sb + AT_BAR + 8 * i, 0);
#pragma unroll 1
        for (int tile = 0; tile < 2; tile++) {
            const int row0 = qq * 512 + (tile * 4 + wg) * 64 + warp * 16;
            attn_tile_safe(q, kdesc0, vdesc0, row0, head, lane);
#pragma unroll
            for (int i = 0; i < 4; i++) q[i] = q2[i];
        }
        return;
    }
#pragma unroll 1
    for (int tile = 0; tile < 2; tile++) {
        const int row0 = qq * 512 + (tile * 4 + wg) * 64 + warp * 16;
        float o[12];
#pragma unroll
        for (int i = 0; i < 12; i++) o[i] = 0.f;
        fence_regs(o);
        float sa[32];
        uint32_t pa[16];
        uint64_t kd = kdesc0, vd = vdesc0;
        if (tile == 0) { mbar_wait(sb + AT_BAR, 0); }
        WG_FENCE();
        qk_wgmma_n64(sa, q, kd); kd += 64;
        WG_COMMIT();
#pragma unroll 1
        for (int jj = 0; jj < 8; jj++) {
            if (tile == 0 && jj < 7) {
                if (tid == 0 && jj < 6) load_kv(jj + 2);
                mbar_wait(sb + AT_BAR + 8 * (jj + 1), 0);
            }
#pragma unroll
            for (int j = 0; j < 4; j++) {
                wg_wait<0>();
                fence_regs(sa);
                if (j & 1) exp_blocks<(POLY_MASK >> 8)>(sa, pa); else exp_blocks<(POLY_MASK & 255)>(sa, pa);
                WG_FENCE();
                PV4(pa);
                qk_wgmma_n64(sa, q, kd); kd += 64;
                WG_COMMIT();
            }
        }
        wg_wait<0>();
        fence_regs(o);
        fence_regs(sa);
        attn_store(o, row0, head, lane);
#pragma unroll
        for (int i = 0; i < 4; i++) q[i] = q2[i];
    }
}

constexpr int F_R2 = 131072, F_X = 196608, F_BAR = 229376;
constexpr int F_RS = F_BAR + 256, F_CS = F_RS + 1024, F_SMEM = F_CS + 1792;
enum { B_FA = 0, B_HF = 4, B_BF = 8, B_BE = 11, B_CF = 14, B_CE = 20, B_ADONE = 26, B_BDONE = 27, B_XC = 28, B_PRDY = 29, B_AUX = 30, B_NUM = 31 };

__device__ __forceinline__ void st_async4(uint32_t dst, float a, float b, float c, float d, uint32_t bar) {
    asm volatile("st.async.weak.shared::cluster.mbarrier::complete_tx::bytes.v4.f32 [%0], {%1,%2,%3,%4}, [%5];"
                 :: "r"(dst), "f"(a), "f"(b), "f"(c), "f"(d), "r"(bar) : "memory");
}
__device__ __forceinline__ void poll_count(const unsigned int* p, unsigned int target) {
    int it = 0;
    while (ld_acquire(p) < target) { if (++it > (1 << 22)) __trap(); }
    asm volatile("fence.proxy.async.global;" ::: "memory");
}
__device__ __forceinline__ void tma2d_store(const CUtensorMap* m, uint32_t src, int c0, int c1) {
    asm volatile("cp.async.bulk.tensor.2d.global.shared::cta.bulk_group [%0, {%2, %3}], [%1];" :: "l"(m), "r"(src), "r"(c0), "r"(c1) : "memory");
}
__device__ __forceinline__ float2 h_row_stats(int row) {
    const float4* hp = (const float4*)(g_hstat + (size_t)row * 8);
    float4 a = __ldcg(hp), b = __ldcg(hp + 1), c = __ldcg(hp + 2), d = __ldcg(hp + 3);
    float mean = 0.125f * (a.x + a.z + b.x + b.z + c.x + c.z + d.x + d.z);
    float m2 = a.y + a.w + b.y + b.w + c.y + c.w + d.y + d.w;
    float e;
    e = a.x - mean; m2 = fmaf(64.f * e, e, m2); e = a.z - mean; m2 = fmaf(64.f * e, e, m2);
    e = b.x - mean; m2 = fmaf(64.f * e, e, m2); e = b.z - mean; m2 = fmaf(64.f * e, e, m2);
    e = c.x - mean; m2 = fmaf(64.f * e, e, m2); e = c.z - mean; m2 = fmaf(64.f * e, e, m2);
    e = d.x - mean; m2 = fmaf(64.f * e, e, m2); e = d.z - mean; m2 = fmaf(64.f * e, e, m2);
    return make_float2(rsqrtf(m2 * (1.0f / DM) + 1e-5f), -mean);
}
__device__ __forceinline__ int c_kblock(int i, int r) {
    if (i < 6) { const int e = 2 * i + r, m = e / 3, k = e - 3 * m; return 7 * m + (k == 2 ? 4 : k); }
    const int l = 2 * (i - 6) + r, m = l >> 2, k = l & 3;
    return 7 * m + (k < 2 ? 2 + k : 3 + k);
}
__device__ __forceinline__ uint32_t c_stage_a(int s, int ntB) { return s < 4 ? ((ntB + 2 * s) & 7) * 16384 : F_R2 + (s - 4) * 32768; }
__device__ __forceinline__ uint32_t c_stage_b(int s, int ntB) { return s < 4 ? ((ntB + 2 * s + 1) & 7) * 16384 : F_R2 + (s - 4) * 32768 + 16384; }
template <int R>
__device__ __forceinline__ void xchg(float (&acc)[64], float (&o)[32], uint32_t sb, unsigned char* smem, int bar, int ctid) {
    const uint32_t dst = mapa(sb + F_X + ctid * 16, 1 - R), rb = mapa(sb + F_BAR + 8 * bar, 1 - R);
#pragma unroll
    for (int q = 0; q < 8; q++) {
        const int j = (1 - R) * 32 + 4 * q;
        st_async4(dst + q * 4096, acc[j], acc[j + 1], acc[j + 2], acc[j + 3], rb);
    }
    mbar_wait_cluster(sb + F_BAR + 8 * bar, 0);
#pragma unroll
    for (int q = 0; q < 8; q++) {
        float4 v = *(const float4*)(smem + F_X + q * 4096 + ctid * 16);
        const int j = R * 32 + 4 * q;
        o[4 * q] = acc[j] + v.x; o[4 * q + 1] = acc[j + 1] + v.y; o[4 * q + 2] = acc[j + 2] + v.z; o[4 * q + 3] = acc[j + 3] + v.w;
    }
}

template <int NB, bool STAGE>
__device__ __forceinline__ void ffn_epilogue(const float* ag, const float* au, const float* s_cs, int cs_off, uint32_t* gp, uint32_t stg,
                                             float2 st0, float2 st1, int lane) {
    const int t = lane & 3;
    const float C1 = 0.7978845608028654f, C2 = 0.044715f * 0.7978845608028654f;
    const float k10 = st0.x * C1, k20 = st0.x * st0.x * st0.x * C2, k11 = st1.x * C1, k21 = st1.x * st1.x * st1.x * C2;
#pragma unroll
    for (int j2 = 0; j2 < NB / 2; j2++) {
        uint32_t pk[4];
#pragma unroll
        for (int jj = 0; jj < 2; jj++) {
            const int j = 2 * j2 + jj;
            const float2 cg = *(const float2*)(s_cs + cs_off + 8 * j + 2 * t);
            const float2 cu = *(const float2*)(s_cs + 224 + cs_off + 8 * j + 2 * t);
            float r[4];
#pragma unroll
            for (int e = 0; e < 4; e++) {
                const float nm = (e < 2) ? st0.y : st1.y, k1 = (e < 2) ? k10 : k11, k2 = (e < 2) ? k20 : k21;
                const float tg = fmaf(nm, (e & 1) ? cg.y : cg.x, ag[4 * j + e]);
                const float tu = fmaf(nm, (e & 1) ? cu.y : cu.x, au[4 * j + e]);
                const float th = tanh_fast(tg * fmaf(tg * tg, k2, k1));
                const float p = tg * tu;
                r[e] = fmaf(p, th, p);
            }
            pk[2 * jj] = pack_bf16(r[0], r[1]);
            pk[2 * jj + 1] = pack_bf16(r[2], r[3]);
        }
        if (STAGE) {
            stsm4(stg + j2 * 4096, pk[0], pk[1], pk[2], pk[3]);
        } else {
            gp[j2 * 1024] = pk[0]; gp[j2 * 1024 + 32] = pk[1]; gp[j2 * 1024 + 512] = pk[2]; gp[j2 * 1024 + 544] = pk[3];
        }
    }
}

__global__ void __cluster_dims__(2, 1, 1) __launch_bounds__(384, 1)
tail_kernel(const __grid_constant__ CUtensorMap tm_o, const __grid_constant__ CUtensorMap tm_g,
            const __grid_constant__ CUtensorMap tm_u, const __grid_constant__ CUtensorMap tm_d,
            const __grid_constant__ CUtensorMap tm_out, const __nv_bfloat16* __restrict__ x) {
    extern __shared__ __align__(1024) unsigned char smem[];
    const uint32_t sb = smem_u32(smem);
    const uint32_t bars = sb + F_BAR;
    const int tid = threadIdx.x, warp = __shfl_sync(0xffffffffu, tid >> 5, 0), lane = tid & 31;
    const int cl = blockIdx.x >> 1, r = blockIdx.x & 1;
    const int mb = ((cl & 7) >> 1) * 4 + (cl >> 4), ntA = (cl & 1) * 2 + ((cl >> 3) & 1);
    const int nt = ntA * 2 + r;
    const int mbB = (mb & ~1) + r, ntB = (mb & 1) * 4 + ntA;
    if (tid == 0) {
#pragma unroll
        for (int i = 0; i < B_NUM; i++) {
            const int cnt = (i >= B_BE && i < B_BE + 3) ? 16 : (i == B_BDONE) ? 9 : ((i >= B_CE && i < B_CE + 6) || i == B_PRDY) ? 8 : (i == B_AUX || i == B_ADONE) ? 2 : 1;
            mbar_init(bars + 8 * i, cnt);
        }
        mbar_expect(bars + 8 * B_XC, 32768);
        fence_barrier_init();
        for (int i = 0; i < 8; i++) {
            const uint32_t bar = bars + 8 * (B_FA + (i >> 1));
            if (!(i & 1)) mbar_expect(bar, 49152);
            tma2d(sb + F_R2 + 32768 + i * 8192, &tm_o, nt * 64, i * 64, bar);
        }
    }
    __syncthreads();
    asm volatile("barrier.cluster.arrive.relaxed.aligned;" ::: "memory");
    if (warp < 4) {
        asm volatile("setmaxnreg.dec.sync.aligned.u32 56;");
        if (warp == 0) {
            if (lane == 0) {
                auto load_b = [&](int it) {
                    const int s = it % 3, pass = it >> 3, kb = (ntB + it) & 7;
                    const int ng = pass ? 3 : 4, c0 = ntB * 224 + pass * 128;
                    const uint32_t bar = bars + 8 * (B_BF + s), dst = sb + F_R2 + s * 32768 + r * ng * 4096;
                    mbar_expect(bar, ng * 8192);
                    for (int i = 0; i < ng; i++) tma2d_mc(dst + i * 4096, r ? &tm_u : &tm_g, c0 + i * 32, kb * 64, bar);
                };
                asm volatile("barrier.cluster.wait.acquire;" ::: "memory");
                pdl_wait();
                for (int i = 0; i < 4; i++)
                    bulk_g2s_mc(sb + (2 * i + r) * 16384, g_ao + (size_t)(mb * 8 + 2 * i + r) * 8192, 16384, bars + 8 * (B_FA + i));
                load_b(0);
                if (blockIdx.x == 0)
                    for (int i = 0; i < 32; i++) g_cnt[i] = 0;
                mbar_wait_cluster(bars + 8 * B_ADONE, 0);
                load_b(1); load_b(2);
                auto load_c = [&](int i) {
                    const int s = i % 6, kb = c_kblock(i, r);
                    const uint32_t bar = bars + 8 * (B_CF + s), da = sb + c_stage_a(s, ntB), db = sb + c_stage_b(s, ntB);
                    mbar_expect(bar, 32768);
                    tma2d(db, &tm_d, ntA * 128, kb * 64, bar);
                    tma2d(db + 8192, &tm_d, ntA * 128 + 64, kb * 64, bar);
                    bulk_g2s(da, g_g + (size_t)(mb * 28 + kb) * 8192, 16384, bar);
                };
                for (int it = 3; it < 16; it++) {
                    mbar_wait_cluster(bars + 8 * (B_BE + it % 3), (it / 3 - 1) & 1);
                    load_b(it);
                    if (it == 12) { poll_count(&g_cnt2[mb], 8); load_c(0); }
                    if (it == 14) load_c(1);
                }
                mbar_wait_cluster(bars + 8 * (B_BE + 1), 0);
                load_c(2);
                mbar_wait(bars + 8 * B_BDONE, 0);
                for (int i = 3; i < 14; i++) {
                    if (i >= 6) mbar_wait(bars + 8 * (B_CE + i % 6), ((i / 6) - 1) & 1);
                    if (i == 6) { poll_count(&g_cnt2[16 + mb], 8); }
                    load_c(i);
                }
            }
            else asm volatile("barrier.cluster.wait.acquire;" ::: "memory");
        } else if (warp == 1) {
            asm volatile("barrier.cluster.wait.acquire.aligned;" ::: "memory");
            bar_sync(5, 288);
            if (lane == 0) { red_release(&g_cnt2[32 + (mb * 8 + nt)]); }
            __syncwarp();
            bar_sync(6, 288);
            if (lane == 0) red_release(&g_cnt2[32 + (mb * 8 + nt)]);
            __syncwarp();
            bar_sync(1, 288);
            if (lane == 0) red_release(&g_cnt2[mbB]);
            __syncwarp();
            bar_sync(2, 288);
            if (lane == 0) {
                red_release(&g_cnt2[16 + mbB]);
                mbar_arrive(bars + 8 * B_BDONE);
            }
            __syncwarp();
            bar_sync(3, 288);
            if (lane == 0) {
                tma2d_store(&tm_out, sb, nt * 64, mb * 128);
                bulk_commit();
                bulk_wait_all();
            }
        } else {
            asm volatile("barrier.cluster.wait.acquire.aligned;" ::: "memory");
            pdl_wait();
            float2* s_rs = (float2*)(smem + F_RS);
            float* s_cs = (float*)(smem + F_CS);
            for (int c = tid - 64; c < 448; c += 64)
                s_cs[c] = __ldcg(&g_cs2[(c >= 224 ? FF - 224 : 0) + ntB * 224 + c]);
            if (tid == 96) {
                mbar_wait_cluster(bars + 8 * B_ADONE, 0);
                for (int i = 0; i < 8; i++) {
                    const int kb = (ntB + i) & 7;
                    const uint32_t bar = bars + 8 * (i < 4 ? B_HF + i : B_FA + i - 4);
                    poll_count(&g_cnt2[32 + (mbB * 8 + kb)], 1);
                    mbar_expect(bar, 16384);
                    bulk_g2s(sb + kb * 16384, g_h + (size_t)(mbB * 8 + kb) * 8192, 16384, bar);
                }
            }
            __syncwarp();
            for (int i = 0; i < 8; i++) mbar_wait(bars + 8 * (i < 4 ? B_HF + i : B_FA + i - 4), i < 4 ? 0 : 1);
            if (lane < 8) poll_count(&g_cnt2[32 + (mbB * 8 + lane)], 2);
            __syncwarp();
            __syncwarp();
            for (int rr = tid - 64; rr < 128; rr += 64) {
                s_rs[rr] = h_row_stats(mbB * 128 + rr);
            }
            __syncwarp();
            if (lane == 0) mbar_arrive(bars + 8 * B_AUX);
        }
    } else {
        asm volatile("setmaxnreg.inc.sync.aligned.u32 216;");
        const int wgi = (warp >> 2) - 1, ww = warp & 3, ctid = tid - 128;
        const int g = lane >> 2, t = lane & 3;
        const int rl = wgi * 64 + ww * 16 + g, row = mb * 128 + rl;
        const int rgl = wgi * 8 + ww * 2;
        const float2* s_rs = (const float2*)(smem + F_RS);
        const float* s_cs = (const float*)(smem + F_CS);
        uint32_t* hp = (uint32_t*)g_h + ((size_t)(mb * 8 + nt) * 8 * 16 + rgl) * 32 + lane;
        const uint32_t rbars = mapa(bars, 1 - r);
        {
            uint32_t xr[16];
            const uint32_t* xp = (const uint32_t*)(x + (size_t)row * DM + nt * 64) + t;
#pragma unroll
            for (int j = 0; j < 8; j++) { xr[2 * j] = __ldg(xp + 4 * j); xr[2 * j + 1] = __ldg(xp + 8 * (DM / 2) + 4 * j); }
            float acc[32];
#pragma unroll 1
            for (int i = 0; i < 8; i++) {
                if (!(i & 1)) { mbar_wait(bars + 8 * (B_FA + (i >> 1)), 0); }
                uint64_t ad = make_desc(sb + i * 16384 + wgi * 1024, 2048, 128, 0);
                uint64_t bd = make_desc(sb + F_R2 + 32768 + i * 8192, 8192, 1024, 1);
                WG_FENCE();
#pragma unroll
                for (int k = 0; k < 4; k++) wgmma_ss_n64(acc, ad + k * 256, bd + k * 128, (i | k) != 0);
                WG_COMMIT();
            }
            wg_wait<0>();
            fence_regs(acc);
            asm volatile("barrier.cluster.wait.acquire.aligned;" ::: "memory");
            bar_sync(4, 256);
            if (tid == 128) { mbar_arrive(bars + 8 * B_ADONE); mbar_arrive_remote(mapa(bars + 8 * B_ADONE, 1 - r)); }
            float v0[16], v1[16];
            float s0 = 0.f, s1 = 0.f;
#pragma unroll
            for (int j2 = 0; j2 < 4; j2++) {
                uint32_t u[4];
#pragma unroll
                for (int jj = 0; jj < 2; jj++) {
                    const int j = 2 * j2 + jj;
                    u[2 * jj] = pack_bf16(bf_lo(xr[2 * j]) + acc[4 * j], bf_hi(xr[2 * j]) + acc[4 * j + 1]);
                    u[2 * jj + 1] = pack_bf16(bf_lo(xr[2 * j + 1]) + acc[4 * j + 2], bf_hi(xr[2 * j + 1]) + acc[4 * j + 3]);
                    v0[2 * j] = bf_lo(u[2 * jj]); v0[2 * j + 1] = bf_hi(u[2 * jj]);
                    v1[2 * j] = bf_lo(u[2 * jj + 1]); v1[2 * j + 1] = bf_hi(u[2 * jj + 1]);
                    s0 += v0[2 * j] + v0[2 * j + 1];
                    s1 += v1[2 * j] + v1[2 * j + 1];
                }
                hp[j2 * 1024] = u[0]; hp[j2 * 1024 + 32] = u[1]; hp[j2 * 1024 + 512] = u[2]; hp[j2 * 1024 + 544] = u[3];
            }
            bar_arrive(5, 288);
            float m0 = s0 * (1.0f / 16), m1 = s1 * (1.0f / 16), q0 = 0.f, q1 = 0.f;
#pragma unroll
            for (int i = 0; i < 16; i++) {
                float d0 = v0[i] - m0, d1 = v1[i] - m1;
                q0 = fmaf(d0, d0, q0); q1 = fmaf(d1, d1, q1);
            }
#pragma unroll
            for (int st = 0; st < 2; st++) {
                float hn = st ? 16.f : 8.f;
                float om0 = __shfl_xor_sync(0xffffffffu, m0, 1 << st), oq0 = __shfl_xor_sync(0xffffffffu, q0, 1 << st);
                float om1 = __shfl_xor_sync(0xffffffffu, m1, 1 << st), oq1 = __shfl_xor_sync(0xffffffffu, q1, 1 << st);
                float d0 = om0 - m0, d1 = om1 - m1;
                q0 = q0 + oq0 + d0 * d0 * hn; q1 = q1 + oq1 + d1 * d1 * hn;
                m0 = 0.5f * (m0 + om0); m1 = 0.5f * (m1 + om1);
            }
            if (t == 0) {
                g_hstat[row * 8 + nt] = make_float2(m0, q0);
                g_hstat[(row + 8) * 8 + nt] = make_float2(m1, q1);
            }
            bar_arrive(6, 288);
        }
        uint32_t* gp = (uint32_t*)g_g + (((size_t)mbB * 224 + ntB * 28) * 16 + rgl) * 32 + lane;
        {
            float ag[128];
#pragma unroll 1
            for (int kb = 0; kb < 8; kb++) {
                const int s = kb % 3;
                mbar_wait(bars + 8 * (kb < 4 ? B_HF + kb : B_FA + kb - 4), kb < 4 ? 0 : 1);
                mbar_wait(bars + 8 * (B_BF + s), (kb / 3) & 1);
                uint64_t ad = make_desc(sb + ((ntB + kb) & 7) * 16384 + wgi * 1024, 2048, 128, 0);
                uint64_t bd = make_desc(sb + F_R2 + s * 32768, 4096, 512, 2);
                WG_FENCE();
#pragma unroll
                for (int k = 0; k < 4; k++) wgmma_ss_n256(ag, ad + k * 256, bd + k * 64, (kb | k) != 0);
                WG_COMMIT();
                if (kb > 0) {
                    wg_wait<1>();
                    if (lane == 0) { mbar_arrive(bars + 8 * (B_BE + (kb - 1) % 3)); mbar_arrive_remote(rbars + 8 * (B_BE + (kb - 1) % 3)); }
                }
            }
            wg_wait<0>();
            if (lane == 0) { mbar_arrive(bars + 8 * (B_BE + 7 % 3)); mbar_arrive_remote(rbars + 8 * (B_BE + 7 % 3)); }
            fence_regs(ag);
            mbar_wait(bars + 8 * B_AUX, 0);
            ffn_epilogue<16, false>(ag, ag + 64, s_cs, 0, gp, 0, s_rs[rl], s_rs[rl + 8], lane);
            bar_arrive(1, 288);
        }
        {
            float ag[96];
#pragma unroll 1
            for (int kb = 0; kb < 8; kb++) {
                const int it = 8 + kb, s = it % 3;
                mbar_wait(bars + 8 * (B_BF + s), (it / 3) & 1);
                uint64_t ad = make_desc(sb + ((ntB + kb) & 7) * 16384 + wgi * 1024, 2048, 128, 0);
                uint64_t bd = make_desc(sb + F_R2 + s * 32768, 4096, 512, 2);
                WG_FENCE();
#pragma unroll
                for (int k = 0; k < 4; k++) wgmma_ss_n192(ag, ad + k * 256, bd + k * 64, (kb | k) != 0);
                WG_COMMIT();
                if (kb > 0) {
                    wg_wait<1>();
                    if (lane == 0 && it < 15) { mbar_arrive(bars + 8 * (B_BE + (it - 1) % 3)); mbar_arrive_remote(rbars + 8 * (B_BE + (it - 1) % 3)); }
                }
            }
            wg_wait<0>();
            if (lane == 0) {
                mbar_arrive(bars + 8 * B_BDONE);
                mbar_arrive_remote(rbars + 8 * B_PRDY);
            }
            fence_regs(ag);
            ffn_epilogue<12, false>(ag, ag + 48, s_cs, 128, gp + 16 * 512, 0, s_rs[rl], s_rs[rl + 8], lane);
            bar_arrive(2, 288);
        }
        {
            uint32_t hr[16];
#pragma unroll
            for (int j = 0; j < 8; j++) { hr[2 * j] = __ldcg(hp + j * 512); hr[2 * j + 1] = __ldcg(hp + j * 512 + 32); }
            mbar_wait(bars + 8 * (B_CF + 0), 0);
            const float a0 = h_row_stats(row).x, a1 = h_row_stats(row + 8).x;
            float acc[64];
#pragma unroll 1
            for (int kb = 0; kb < 14; kb++) {
                const int s = kb % 6;
                mbar_wait(bars + 8 * (B_CF + s), (kb / 6) & 1);
                uint64_t ad = make_desc(sb + c_stage_a(s, ntB) + wgi * 1024, 2048, 128, 0);
                uint64_t bd = make_desc(sb + c_stage_b(s, ntB), 8192, 1024, 1);
                WG_FENCE();
#pragma unroll
                for (int k = 0; k < 4; k++) wgmma_ss_n128(acc, ad + k * 256, bd + k * 128, (kb | k) != 0);
                WG_COMMIT();
                if (kb > 0) {
                    wg_wait<1>();
                    if (lane == 0) mbar_arrive(bars + 8 * (B_CE + (kb - 1) % 6));
                }
            }
            wg_wait<0>();
            fence_regs(acc);
            mbar_wait_cluster(bars + 8 * B_PRDY, 0);
            float o[32];
            if (r == 0) xchg<0>(acc, o, sb, smem, B_XC, ctid); else xchg<1>(acc, o, sb, smem, B_XC, ctid);
            bar_sync(4, 256);
            const float k0 = 0.5f * a0 * a0, k1 = 0.5f * a1 * a1;
            const int srow = wgi * 64 + ww * 16 + ((lane >> 3) & 1) * 8 + (lane & 7);
#pragma unroll
            for (int j2 = 0; j2 < 4; j2++) {
                uint32_t u[4];
#pragma unroll
                for (int jj = 0; jj < 2; jj++) {
                    const int j = 2 * j2 + jj;
                    u[2 * jj] = pack_bf16(fmaf(k0, o[4 * j], bf_lo(hr[2 * j])), fmaf(k0, o[4 * j + 1], bf_hi(hr[2 * j])));
                    u[2 * jj + 1] = pack_bf16(fmaf(k1, o[4 * j + 2], bf_lo(hr[2 * j + 1])), fmaf(k1, o[4 * j + 3], bf_hi(hr[2 * j + 1])));
                }
                const int chunk = 2 * j2 + (lane >> 4);
                stsm4(sb + srow * 128 + ((chunk ^ (lane & 7)) * 16), u[0], u[1], u[2], u[3]);
            }
            fence_proxy_async();
            bar_arrive(3, 288);
        }
    }
}


static_assert(K1_SMEM <= F_SMEM && AT_SMEM <= F_SMEM && F_SMEM <= 232448, "shared memory budget");

typedef CUresult (*EncodeFn)(CUtensorMap*, CUtensorMapDataType, cuuint32_t, void*, const cuuint64_t*, const cuuint64_t*,
                             const cuuint32_t*, const cuuint32_t*, CUtensorMapInterleave, CUtensorMapSwizzle,
                             CUtensorMapL2promotion, CUtensorMapFloatOOBfill);

void encode(EncodeFn fn, CUtensorMap* m, const void* ptr, int rank, const cuuint64_t* dims, const cuuint64_t* strides,
            const cuuint32_t* box, CUtensorMapSwizzle swz) {
    cuuint32_t es[3] = {1, 1, 1};
    fn(m, CU_TENSOR_MAP_DATA_TYPE_BFLOAT16, rank, (void*)ptr, dims, strides, box, es, CU_TENSOR_MAP_INTERLEAVE_NONE, swz,
       CU_TENSOR_MAP_L2_PROMOTION_L2_256B, CU_TENSOR_MAP_FLOAT_OOB_FILL_NONE);
}

template <typename... KArgs, typename... Args>
void launch(void (*kern)(KArgs...), int grid, int block, int smem, bool pdl, Args... args) {
    cudaLaunchConfig_t cfg = {};
    cfg.gridDim = dim3(grid); cfg.blockDim = dim3(block); cfg.dynamicSmemBytes = smem;
    cfg.stream = cudaStreamPerThread;
    cudaLaunchAttribute at[1];
    at[0].id = cudaLaunchAttributeProgrammaticStreamSerialization;
    at[0].val.programmaticStreamSerializationAllowed = 1;
    cfg.attrs = at; cfg.numAttrs = pdl ? 1 : 0;
    cudaLaunchKernelEx(&cfg, kern, KArgs(args)...);
}

}

extern "C" void kernel_launch(void* const* d_in, const int* in_sizes, int n_in, void* d_out, int out_size) {
    const __nv_bfloat16* x = (const __nv_bfloat16*)d_in[0];
    const __nv_bfloat16* wqkv = (const __nv_bfloat16*)d_in[1];
    const __nv_bfloat16* wo = (const __nv_bfloat16*)d_in[2];
    const __nv_bfloat16* wgate = (const __nv_bfloat16*)d_in[4];
    const __nv_bfloat16* wup = (const __nv_bfloat16*)d_in[5];
    const __nv_bfloat16* wdown = (const __nv_bfloat16*)d_in[6];
    __nv_bfloat16* out = (__nv_bfloat16*)d_out;

    static CUtensorMap tm_x, tm_wqkv, tm_wo, tm_wg, tm_wu, tm_wd, tm_out;
    static const void* cached[7] = {nullptr, nullptr, nullptr, nullptr, nullptr, nullptr, nullptr};
    if (cached[0] != x || cached[1] != wqkv || cached[2] != wo || cached[3] != wgate || cached[4] != wup || cached[5] != wdown || cached[6] != out) {
        void* fp = nullptr;
        cudaDriverEntryPointQueryResult qr;
        cudaGetDriverEntryPoint("cuTensorMapEncodeTiled", &fp, cudaEnableDefault, &qr);
        EncodeFn fn = (EncodeFn)fp;
        { cuuint64_t d[2] = {512, 2048}, s[1] = {1024}; cuuint32_t b[2] = {64, 128};
          encode(fn, &tm_x, x, 2, d, s, b, CU_TENSOR_MAP_SWIZZLE_128B);
          encode(fn, &tm_out, out, 2, d, s, b, CU_TENSOR_MAP_SWIZZLE_128B); }
        { cuuint64_t d[3] = {64, 512, 24}, s[2] = {3072, 128}; cuuint32_t b[3] = {64, 64, 3};
          encode(fn, &tm_wqkv, wqkv, 3, d, s, b, CU_TENSOR_MAP_SWIZZLE_128B); }
        { cuuint64_t d[2] = {512, 512}, s[1] = {1024}; cuuint32_t b[2] = {64, 64};
          encode(fn, &tm_wo, wo, 2, d, s, b, CU_TENSOR_MAP_SWIZZLE_128B); }
        { cuuint64_t d[2] = {1792, 512}, s[1] = {3584}; cuuint32_t b[2] = {32, 64};
          encode(fn, &tm_wg, wgate, 2, d, s, b, CU_TENSOR_MAP_SWIZZLE_64B);
          encode(fn, &tm_wu, wup, 2, d, s, b, CU_TENSOR_MAP_SWIZZLE_64B); }
        { cuuint64_t d[2] = {512, 1792}, s[1] = {1024}; cuuint32_t b[2] = {64, 64};
          encode(fn, &tm_wd, wdown, 2, d, s, b, CU_TENSOR_MAP_SWIZZLE_128B); }
        cudaFuncSetAttribute(qkv_kernel, cudaFuncAttributeMaxDynamicSharedMemorySize, F_SMEM);
        cudaFuncSetAttribute(qkv_kernel, cudaFuncAttributePreferredSharedMemoryCarveout, 100);
        cudaFuncSetAttribute(attn_kernel, cudaFuncAttributeMaxDynamicSharedMemorySize, F_SMEM);
        cudaFuncSetAttribute(attn_kernel, cudaFuncAttributePreferredSharedMemoryCarveout, 100);
        cudaFuncSetAttribute(tail_kernel, cudaFuncAttributeMaxDynamicSharedMemorySize, F_SMEM);
        cudaFuncSetAttribute(tail_kernel, cudaFuncAttributePreferredSharedMemoryCarveout, 100);
        cached[0] = x; cached[1] = wqkv; cached[2] = wo; cached[3] = wgate; cached[4] = wup; cached[5] = wdown; cached[6] = out;
    }
    launch(qkv_kernel, 128, 384, F_SMEM, false, tm_x, tm_wqkv, x, wqkv);
    launch(attn_kernel, 132, 512, F_SMEM, true, wgate, wup, wo, wdown);
    launch(tail_kernel, 128, 384, F_SMEM, true, tm_wo, tm_wg, tm_wu, tm_wd, tm_out, x);
}
```

```cpp
#include <cuda_runtime.h>
#include <cuda_bf16.h>
#include <cuda.h>
#include <stdint.h>

namespace {

constexpr int S_LEN = 2048, DM = 512, NH = 32, FF = 1792;

__device__ __align__(1024) __nv_bfloat16 g_qkv[3 * NH * S_LEN * 16];
__device__ __align__(1024) __nv_bfloat16 g_ao[S_LEN * DM];
__device__ __align__(1024) __nv_bfloat16 g_h[S_LEN * DM];
__device__ __align__(1024) __nv_bfloat16 g_g[S_LEN * FF];
__device__ __align__(16) float2 g_rowstat1[S_LEN];
__device__ __align__(16) float g_cs1_part[16 * 1536];
__device__ unsigned int g_cnt[32];
__device__ unsigned int g_cnt2[160];
__device__ __align__(16) float g_nrm[3 * NH * 128];
__device__ __align__(16) float2 g_hstat[S_LEN * 8];
__device__ float g_cs2[2 * FF];

__device__ __forceinline__ uint32_t smem_u32(const void* p) { return (uint32_t)__cvta_generic_to_shared(p); }
__device__ __forceinline__ void mbar_init(uint32_t a, int c) { asm volatile("mbarrier.init.shared.b64 [%0], %1;" :: "r"(a), "r"(c)); }
__device__ __forceinline__ void mbar_expect(uint32_t a, int bytes) { asm volatile("mbarrier.arrive.expect_tx.shared.b64 _, [%0], %1;" :: "r"(a), "r"(bytes) : "memory"); }
__device__ __forceinline__ void mbar_arrive(uint32_t a) { asm volatile("mbarrier.arrive.shared.b64 _, [%0];" :: "r"(a) : "memory"); }
__device__ __forceinline__ void mbar_wait(uint32_t a, int parity) {
    uint32_t done;
    int it = 0;
    do {
        asm volatile("{\n.reg .pred p;\nmbarrier.try_wait.parity.shared.b64 p, [%1], %2;\nselp.u32 %0, 1, 0, p;\n}"
                     : "=r"(done) : "r"(a), "r"(parity) : "memory");
        if (++it > (1 << 24)) __trap();
    } while (!done);
}
__device__ __forceinline__ void bulk_g2s(uint32_t dst, const void* src, int bytes, uint32_t bar) {
    asm volatile("cp.async.bulk.shared::cluster.global.mbarrier::complete_tx::bytes [%0], [%1], %2, [%3];"
                 :: "r"(dst), "l"(src), "r"(bytes), "r"(bar) : "memory");
}
__device__ __forceinline__ void tma2d(uint32_t dst, const CUtensorMap* m, int c0, int c1, uint32_t bar) {
    asm volatile("cp.async.bulk.tensor.2d.shared::cluster.global.mbarrier::complete_tx::bytes [%0], [%1, {%3, %4}], [%2];"
                 :: "r"(dst), "l"(m), "r"(bar), "r"(c0), "r"(c1) : "memory");
}
__device__ __forceinline__ void tma3d(uint32_t dst, const CUtensorMap* m, int c0, int c1, int c2, uint32_t bar) {
    asm volatile("cp.async.bulk.tensor.3d.shared::cluster.global.mbarrier::complete_tx::bytes [%0], [%1, {%3, %4, %5}], [%2];"
                 :: "r"(dst), "l"(m), "r"(bar), "r"(c0), "r"(c1), "r"(c2) : "memory");
}
__device__ __forceinline__ void pdl_wait() { asm volatile("griddepcontrol.wait;" ::: "memory"); }
__device__ __forceinline__ void pdl_launch() { asm volatile("griddepcontrol.launch_dependents;" ::: "memory"); }
__device__ __forceinline__ void fence_barrier_init() { asm volatile("fence.mbarrier_init.release.cluster;" ::: "memory"); }
__device__ __forceinline__ void fence_proxy_async() { asm volatile("fence.proxy.async.shared::cta;" ::: "memory"); }
__device__ __forceinline__ uint64_t make_desc(uint32_t saddr, uint32_t lbo, uint32_t sbo, uint32_t swz) {
    return (uint64_t)((saddr & 0x3FFFF) >> 4) | ((uint64_t)((lbo & 0x3FFFF) >> 4) << 16) |
           ((uint64_t)((sbo & 0x3FFFF) >> 4) << 32) | ((uint64_t)swz << 62);
}
#define WG_FENCE() asm volatile("wgmma.fence.sync.aligned;" ::: "memory")
#define WG_COMMIT() asm volatile("wgmma.commit_group.sync.aligned;" ::: "memory")
template <int N> __device__ __forceinline__ void wg_wait() { asm volatile("wgmma.wait_group.sync.aligned %0;" :: "n"(N) : "memory"); }
template <int N> __device__ __forceinline__ void fence_regs(float (&d)[N]) {
#pragma unroll
    for (int i = 0; i < N; i++) asm volatile("" : "+f"(d[i]) :: "memory");
}
__device__ __forceinline__ float ex2f(float x) { float y; asm("ex2.approx.ftz.f32 %0, %1;" : "=f"(y) : "f"(x)); return y; }
__device__ __forceinline__ float tanh_fast(float x) { float y; asm("tanh.approx.f32 %0, %1;" : "=f"(y) : "f"(x)); return y; }
__device__ __forceinline__ uint32_t pack_bf16(float lo, float hi) { uint32_t r; asm("cvt.rn.bf16x2.f32 %0, %1, %2;" : "=r"(r) : "f"(hi), "f"(lo)); return r; }
__device__ __forceinline__ float bf_lo(uint32_t u) { return __uint_as_float(u << 16); }
__device__ __forceinline__ float bf_hi(uint32_t u) { return __uint_as_float(u & 0xFFFF0000u); }
__device__ __forceinline__ uint32_t hfma2(uint32_t a, uint32_t b, uint32_t c) { uint32_t r; asm("fma.rn.f16x2 %0, %1, %2, %3;" : "=r"(r) : "r"(a), "r"(b), "r"(c)); return r; }
__device__ __forceinline__ uint32_t hmul2(uint32_t a, uint32_t b) { uint32_t r; asm("mul.rn.f16x2 %0, %1, %2;" : "=r"(r) : "r"(a), "r"(b)); return r; }
__device__ __forceinline__ unsigned int ld_acquire(const unsigned int* p) { unsigned int v; asm volatile("ld.acquire.gpu.u32 %0, [%1];" : "=r"(v) : "l"(p) : "memory"); return v; }
__device__ __forceinline__ void red_release(unsigned int* p) { asm volatile("red.release.gpu.global.add.u32 [%0], 1;" :: "l"(p) : "memory"); }
__device__ __forceinline__ void stsm4(uint32_t addr, uint32_t a, uint32_t b, uint32_t c, uint32_t d) {
    asm volatile("stmatrix.sync.aligned.m8n8.x4.shared.b16 [%0], {%1,%2,%3,%4};" :: "r"(addr), "r"(a), "r"(b), "r"(c), "r"(d) : "memory");
}
__device__ __forceinline__ void bulk_commit() { asm volatile("cp.async.bulk.commit_group;" ::: "memory"); }
__device__ __forceinline__ void bulk_wait_all() { asm volatile("cp.async.bulk.wait_group 0;" ::: "memory"); }
__device__ __forceinline__ void bar_sync(int id, int n) { asm volatile("bar.sync %0, %1;" :: "r"(id), "r"(n) : "memory"); }
__device__ __forceinline__ void bar_arrive(int id, int n) { asm volatile("bar.arrive %0, %1;" :: "r"(id), "r"(n) : "memory"); }
__device__ __forceinline__ float warp_sum(float v) {
#pragma unroll
    for (int o = 16; o; o >>= 1) v += __shfl_xor_sync(0xffffffffu, v, o);
    return v;
}
__device__ __forceinline__ float warp_max(float v) {
#pragma unroll
    for (int o = 16; o; o >>= 1) v = fmaxf(v, __shfl_xor_sync(0xffffffffu, v, o));
    return v;
}

__device__ __forceinline__ void wgmma_ss_n64(float (&d)[32], uint64_t adesc, uint64_t bdesc, int scale_d) {
    asm volatile("{\n.reg .pred p;\nsetp.ne.b32 p, %34, 0;\n"
      "wgmma.mma_async.sync.aligned.m64n64k16.f32.bf16.bf16 {%0,%1,%2,%3,%4,%5,%6,%7,%8,%9,%10,%11,%12,%13,%14,%15,%16,%17,%18,%19,%20,%21,%22,%23,%24,%25,%26,%27,%28,%29,%30,%31}, %32, %33, p, 1, 1, 0, 1;\n}"
      : "+f"(d[0]), "+f"(d[1]), "+f"(d[2]), "+f"(d[3]), "+f"(d[4]), "+f"(d[5]), "+f"(d[6]), "+f"(d[7]), "+f"(d[8]), "+f"(d[9]), "+f"(d[10]), "+f"(d[11]), "+f"(d[12]), "+f"(d[13]), "+f"(d[14]), "+f"(d[15]), "+f"(d[16]), "+f"(d[17]), "+f"(d[18]), "+f"(d[19]), "+f"(d[20]), "+f"(d[21]), "+f"(d[22]), "+f"(d[23]), "+f"(d[24]), "+f"(d[25]), "+f"(d[26]), "+f"(d[27]), "+f"(d[28]), "+f"(d[29]), "+f"(d[30]), "+f"(d[31])
      : "l"(adesc), "l"(bdesc), "r"(scale_d));
}
__device__ __forceinline__ void wgmma_ss_n128(float (&d)[64], uint64_t adesc, uint64_t bdesc, int scale_d) {
    asm volatile("{\n.reg .pred p;\nsetp.ne.b32 p, %66, 0;\n"
      "wgmma.mma_async.sync.aligned.m64n128k16.f32.bf16.bf16 {%0,%1,%2,%3,%4,%5,%6,%7,%8,%9,%10,%11,%12,%13,%14,%15,%16,%17,%18,%19,%20,%21,%22,%23,%24,%25,%26,%27,%28,%29,%30,%31,%32,%33,%34,%35,%36,%37,%38,%39,%40,%41,%42,%43,%44,%45,%46,%47,%48,%49,%50,%51,%52,%53,%54,%55,%56,%57,%58,%59,%60,%61,%62,%63}, %64, %65, p, 1, 1, 0, 1;\n}"
      : "+f"(d[0]), "+f"(d[1]), "+f"(d[2]), "+f"(d[3]), "+f"(d[4]), "+f"(d[5]), "+f"(d[6]), "+f"(d[7]), "+f"(d[8]), "+f"(d[9]), "+f"(d[10]), "+f"(d[11]), "+f"(d[12]), "+f"(d[13]), "+f"(d[14]), "+f"(d[15]), "+f"(d[16]), "+f"(d[17]), "+f"(d[18]), "+f"(d[19]), "+f"(d[20]), "+f"(d[21]), "+f"(d[22]), "+f"(d[23]), "+f"(d[24]), "+f"(d[25]), "+f"(d[26]), "+f"(d[27]), "+f"(d[28]), "+f"(d[29]), "+f"(d[30]), "+f"(d[31]), "+f"(d[32]), "+f"(d[33]), "+f"(d[34]), "+f"(d[35]), "+f"(d[36]), "+f"(d[37]), "+f"(d[38]), "+f"(d[39]), "+f"(d[40]), "+f"(d[41]), "+f"(d[42]), "+f"(d[43]), "+f"(d[44]), "+f"(d[45]), "+f"(d[46]), "+f"(d[47]), "+f"(d[48]), "+f"(d[49]), "+f"(d[50]), "+f"(d[51]), "+f"(d[52]), "+f"(d[53]), "+f"(d[54]), "+f"(d[55]), "+f"(d[56]), "+f"(d[57]), "+f"(d[58]), "+f"(d[59]), "+f"(d[60]), "+f"(d[61]), "+f"(d[62]), "+f"(d[63])
      : "l"(adesc), "l"(bdesc), "r"(scale_d));
}
__device__ __forceinline__ void wgmma_ss_n192(float (&d)[96], uint64_t adesc, uint64_t bdesc, int scale_d) {
    asm volatile("{\n.reg .pred p;\nsetp.ne.b32 p, %98, 0;\n"
      "wgmma.mma_async.sync.aligned.m64n192k16.f32.bf16.bf16 {%0,%1,%2,%3,%4,%5,%6,%7,%8,%9,%10,%11,%12,%13,%14,%15,%16,%17,%18,%19,%20,%21,%22,%23,%24,%25,%26,%27,%28,%29,%30,%31,%32,%33,%34,%35,%36,%37,%38,%39,%40,%41,%42,%43,%44,%45,%46,%47,%48,%49,%50,%51,%52,%53,%54,%55,%56,%57,%58,%59,%60,%61,%62,%63,%64,%65,%66,%67,%68,%69,%70,%71,%72,%73,%74,%75,%76,%77,%78,%79,%80,%81,%82,%83,%84,%85,%86,%87,%88,%89,%90,%91,%92,%93,%94,%95}, %96, %97, p, 1, 1, 0, 1;\n}"
      : "+f"(d[0]), "+f"(d[1]), "+f"(d[2]), "+f"(d[3]), "+f"(d[4]), "+f"(d[5]), "+f"(d[6]), "+f"(d[7]), "+f"(d[8]), "+f"(d[9]), "+f"(d[10]), "+f"(d[11]), "+f"(d[12]), "+f"(d[13]), "+f"(d[14]), "+f"(d[15]), "+f"(d[16]), "+f"(d[17]), "+f"(d[18]), "+f"(d[19]), "+f"(d[20]), "+f"(d[21]), "+f"(d[22]), "+f"(d[23]), "+f"(d[24]), "+f"(d[25]), "+f"(d[26]), "+f"(d[27]), "+f"(d[28]), "+f"(d[29]), "+f"(d[30]), "+f"(d[31]), "+f"(d[32]), "+f"(d[33]), "+f"(d[34]), "+f"(d[35]), "+f"(d[36]), "+f"(d[37]), "+f"(d[38]), "+f"(d[39]), "+f"(d[40]), "+f"(d[41]), "+f"(d[42]), "+f"(d[43]), "+f"(d[44]), "+f"(d[45]), "+f"(d[46]), "+f"(d[47]), "+f"(d[48]), "+f"(d[49]), "+f"(d[50]), "+f"(d[51]), "+f"(d[52]), "+f"(d[53]), "+f"(d[54]), "+f"(d[55]), "+f"(d[56]), "+f"(d[57]), "+f"(d[58]), "+f"(d[59]), "+f"(d[60]), "+f"(d[61]), "+f"(d[62]), "+f"(d[63]), "+f"(d[64]), "+f"(d[65]), "+f"(d[66]), "+f"(d[67]), "+f"(d[68]), "+f"(d[69]), "+f"(d[70]), "+f"(d[71]), "+f"(d[72]), "+f"(d[73]), "+f"(d[74]), "+f"(d[75]), "+f"(d[76]), "+f"(d[77]), "+f"(d[78]), "+f"(d[79]), "+f"(d[80]), "+f"(d[81]), "+f"(d[82]), "+f"(d[83]), "+f"(d[84]), "+f"(d[85]), "+f"(d[86]), "+f"(d[87]), "+f"(d[88]), "+f"(d[89]), "+f"(d[90]), "+f"(d[91]), "+f"(d[92]), "+f"(d[93]), "+f"(d[94]), "+f"(d[95])
      : "l"(adesc), "l"(bdesc), "r"(scale_d));
}
__device__ __forceinline__ void wgmma_ss_n256(float (&d)[128], uint64_t adesc, uint64_t bdesc, int scale_d) {
    asm volatile("{\n.reg .pred p;\nsetp.ne.b32 p, %130, 0;\n"
      "wgmma.mma_async.sync.aligned.m64n256k16.f32.bf16.bf16 {%0,%1,%2,%3,%4,%5,%6,%7,%8,%9,%10,%11,%12,%13,%14,%15,%16,%17,%18,%19,%20,%21,%22,%23,%24,%25,%26,%27,%28,%29,%30,%31,%32,%33,%34,%35,%36,%37,%38,%39,%40,%41,%42,%43,%44,%45,%46,%47,%48,%49,%50,%51,%52,%53,%54,%55,%56,%57,%58,%59,%60,%61,%62,%63,%64,%65,%66,%67,%68,%69,%70,%71,%72,%73,%74,%75,%76,%77,%78,%79,%80,%81,%82,%83,%84,%85,%86,%87,%88,%89,%90,%91,%92,%93,%94,%95,%96,%97,%98,%99,%100,%101,%102,%103,%104,%105,%106,%107,%108,%109,%110,%111,%112,%113,%114,%115,%116,%117,%118,%119,%120,%121,%122,%123,%124,%125,%126,%127}, %128, %129, p, 1, 1, 0, 1;\n}"
      : "+f"(d[0]), "+f"(d[1]), "+f"(d[2]), "+f"(d[3]), "+f"(d[4]), "+f"(d[5]), "+f"(d[6]), "+f"(d[7]), "+f"(d[8]), "+f"(d[9]), "+f"(d[10]), "+f"(d[11]), "+f"(d[12]), "+f"(d[13]), "+f"(d[14]), "+f"(d[15]), "+f"(d[16]), "+f"(d[17]), "+f"(d[18]), "+f"(d[19]), "+f"(d[20]), "+f"(d[21]), "+f"(d[22]), "+f"(d[23]), "+f"(d[24]), "+f"(d[25]), "+f"(d[26]), "+f"(d[27]), "+f"(d[28]), "+f"(d[29]), "+f"(d[30]), "+f"(d[31]), "+f"(d[32]), "+f"(d[33]), "+f"(d[34]), "+f"(d[35]), "+f"(d[36]), "+f"(d[37]), "+f"(d[38]), "+f"(d[39]), "+f"(d[40]), "+f"(d[41]), "+f"(d[42]), "+f"(d[43]), "+f"(d[44]), "+f"(d[45]), "+f"(d[46]), "+f"(d[47]), "+f"(d[48]), "+f"(d[49]), "+f"(d[50]), "+f"(d[51]), "+f"(d[52]), "+f"(d[53]), "+f"(d[54]), "+f"(d[55]), "+f"(d[56]), "+f"(d[57]), "+f"(d[58]), "+f"(d[59]), "+f"(d[60]), "+f"(d[61]), "+f"(d[62]), "+f"(d[63]), "+f"(d[64]), "+f"(d[65]), "+f"(d[66]), "+f"(d[67]), "+f"(d[68]), "+f"(d[69]), "+f"(d[70]), "+f"(d[71]), "+f"(d[72]), "+f"(d[73]), "+f"(d[74]), "+f"(d[75]), "+f"(d[76]), "+f"(d[77]), "+f"(d[78]), "+f"(d[79]), "+f"(d[80]), "+f"(d[81]), "+f"(d[82]), "+f"(d[83]), "+f"(d[84]), "+f"(d[85]), "+f"(d[86]), "+f"(d[87]), "+f"(d[88]), "+f"(d[89]), "+f"(d[90]), "+f"(d[91]), "+f"(d[92]), "+f"(d[93]), "+f"(d[94]), "+f"(d[95]), "+f"(d[96]), "+f"(d[97]), "+f"(d[98]), "+f"(d[99]), "+f"(d[100]), "+f"(d[101]), "+f"(d[102]), "+f"(d[103]), "+f"(d[104]), "+f"(d[105]), "+f"(d[106]), "+f"(d[107]), "+f"(d[108]), "+f"(d[109]), "+f"(d[110]), "+f"(d[111]), "+f"(d[112]), "+f"(d[113]), "+f"(d[114]), "+f"(d[115]), "+f"(d[116]), "+f"(d[117]), "+f"(d[118]), "+f"(d[119]), "+f"(d[120]), "+f"(d[121]), "+f"(d[122]), "+f"(d[123]), "+f"(d[124]), "+f"(d[125]), "+f"(d[126]), "+f"(d[127])
      : "l"(adesc), "l"(bdesc), "r"(scale_d));
}
__device__ __forceinline__ void qk_wgmma_n64(float (&d)[32], const uint32_t (&a)[4], uint64_t desc) {
    asm volatile("wgmma.mma_async.sync.aligned.m64n64k16.f32.bf16.bf16 {%0,%1,%2,%3,%4,%5,%6,%7,%8,%9,%10,%11,%12,%13,%14,%15,%16,%17,%18,%19,%20,%21,%22,%23,%24,%25,%26,%27,%28,%29,%30,%31}, {%32,%33,%34,%35}, %36, 0, 1, 1, 0;"
      : "=f"(d[0]), "=f"(d[1]), "=f"(d[2]), "=f"(d[3]), "=f"(d[4]), "=f"(d[5]), "=f"(d[6]), "=f"(d[7]), "=f"(d[8]), "=f"(d[9]), "=f"(d[10]), "=f"(d[11]), "=f"(d[12]), "=f"(d[13]), "=f"(d[14]), "=f"(d[15]), "=f"(d[16]), "=f"(d[17]), "=f"(d[18]), "=f"(d[19]), "=f"(d[20]), "=f"(d[21]), "=f"(d[22]), "=f"(d[23]), "=f"(d[24]), "=f"(d[25]), "=f"(d[26]), "=f"(d[27]), "=f"(d[28]), "=f"(d[29]), "=f"(d[30]), "=f"(d[31])
      : "r"(a[0]), "r"(a[1]), "r"(a[2]), "r"(a[3]), "l"(desc));
}

__device__ __forceinline__ void pv_wgmma(float (&d)[12], uint32_t a0, uint32_t a1, uint32_t a2, uint32_t a3, uint64_t desc) {
    asm volatile("wgmma.mma_async.sync.aligned.m64n24k16.f32.bf16.bf16 {%0,%1,%2,%3,%4,%5,%6,%7,%8,%9,%10,%11}, {%12,%13,%14,%15}, %16, 1, 1, 1, 1;"
      : "+f"(d[0]), "+f"(d[1]), "+f"(d[2]), "+f"(d[3]), "+f"(d[4]), "+f"(d[5]), "+f"(d[6]), "+f"(d[7]), "+f"(d[8]), "+f"(d[9]), "+f"(d[10]), "+f"(d[11])
      : "r"(a0), "r"(a1), "r"(a2), "r"(a3), "l"(desc));
}

__device__ __forceinline__ uint32_t mapa(uint32_t a, uint32_t rank) { uint32_t r; asm("mapa.shared::cluster.u32 %0, %1, %2;" : "=r"(r) : "r"(a), "r"(rank)); return r; }
__device__ __forceinline__ void mbar_arrive_remote(uint32_t a) { asm volatile("mbarrier.arrive.relaxed.cluster.shared::cluster.b64 _, [%0];" :: "r"(a) : "memory"); }
__device__ __forceinline__ void mbar_wait_cluster(uint32_t a, int parity) {
    uint32_t done;
    int it = 0;
    do {
        asm volatile("{\n.reg .pred p;\nmbarrier.try_wait.parity.acquire.cluster.shared::cta.b64 p, [%1], %2;\nselp.u32 %0, 1, 0, p;\n}"
                     : "=r"(done) : "r"(a), "r"(parity) : "memory");
        if (++it > (1 << 24)) __trap();
    } while (!done);
}
__device__ __forceinline__ void tma2d_mc(uint32_t dst, const CUtensorMap* m, int c0, int c1, uint32_t bar) {
    asm volatile("cp.async.bulk.tensor.2d.shared::cluster.global.mbarrier::complete_tx::bytes.multicast::cluster [%0], [%1, {%3, %4}], [%2], %5;"
                 :: "r"(dst), "l"(m), "r"(bar), "r"(c0), "r"(c1), "h"((uint16_t)3) : "memory");
}
__device__ __forceinline__ void bulk_g2s_mc(uint32_t dst, const void* src, int bytes, uint32_t bar) {
    asm volatile("cp.async.bulk.shared::cluster.global.mbarrier::complete_tx::bytes.multicast::cluster [%0], [%1], %2, [%3], %4;"
                 :: "r"(dst), "l"(src), "r"(bytes), "r"(bar), "h"((uint16_t)3) : "memory");
}
__device__ __forceinline__ void tile_of(int bid, int& mb, int& nt) {
    int grp = bid >> 4, in = bid & 15;
    mb = (grp >> 1) * 4 + (in >> 2);
    nt = (grp & 1) * 4 + (in & 3);
}

constexpr int K1_STAGES = 5, K1_STAGE = 16384 + 24576;
constexpr int K1_BAR = K1_STAGES * K1_STAGE, K1_RS = K1_BAR + 128, K1_CS = K1_RS + 1024, K1_SMEM = K1_CS + 768;

__device__ __forceinline__ float2 row_stats_regs(uint4 a, uint4 b) {
    float v[16];
    v[0] = bf_lo(a.x); v[1] = bf_hi(a.x); v[2] = bf_lo(a.y); v[3] = bf_hi(a.y);
    v[4] = bf_lo(a.z); v[5] = bf_hi(a.z); v[6] = bf_lo(a.w); v[7] = bf_hi(a.w);
    v[8] = bf_lo(b.x); v[9] = bf_hi(b.x); v[10] = bf_lo(b.y); v[11] = bf_hi(b.y);
    v[12] = bf_lo(b.z); v[13] = bf_hi(b.z); v[14] = bf_lo(b.w); v[15] = bf_hi(b.w);
    float s = 0.f;
#pragma unroll
    for (int i = 0; i < 16; i++) s += v[i];
    float mean = warp_sum(s) * (1.0f / DM);
    float q = 0.f;
#pragma unroll
    for (int i = 0; i < 16; i++) { float d = v[i] - mean; q = fmaf(d, d, q); }
    float var = warp_sum(q) * (1.0f / DM);
    float rstd = rsqrtf(var + 1e-5f);
    return make_float2(rstd, -mean * rstd);
}
__device__ __forceinline__ float2 row_stats_x(const __nv_bfloat16* x, int row, int lane) {
    const uint4* p = (const uint4*)(x + (size_t)row * DM);
    return row_stats_regs(__ldg(p + lane), __ldg(p + 32 + lane));
}
__device__ __forceinline__ void colsum8(const __nv_bfloat16* w, int ld, int col, int k0, int nk, float (&s)[8]) {
#pragma unroll
    for (int i = 0; i < 8; i++) s[i] = 0.f;
    for (int k = k0; k < k0 + nk; k += 8) {
        uint4 u[8];
#pragma unroll
        for (int i = 0; i < 8; i++) u[i] = __ldg((const uint4*)(w + (size_t)(k + i) * ld + col));
#pragma unroll
        for (int i = 0; i < 8; i++) {
            s[0] += bf_lo(u[i].x); s[1] += bf_hi(u[i].x); s[2] += bf_lo(u[i].y); s[3] += bf_hi(u[i].y);
            s[4] += bf_lo(u[i].z); s[5] += bf_hi(u[i].z); s[6] += bf_lo(u[i].w); s[7] += bf_hi(u[i].w);
        }
    }
}
__device__ __forceinline__ bool wait_count(const unsigned int* p, unsigned int target, int lane) {
    int ok = 1;
    if (lane == 0) {
        int it = 0;
        while (ld_acquire(p) < target) { if (++it > (1 << 18)) { ok = 0; break; } }
    }
    ok = __shfl_sync(0xffffffffu, ok, 0);
    return ok != 0;
}

__global__ void __launch_bounds__(384, 1)
qkv_kernel(const __grid_constant__ CUtensorMap tm_x, const __grid_constant__ CUtensorMap tm_w,
           const __nv_bfloat16* __restrict__ x, const __nv_bfloat16* __restrict__ wqkv) {
    extern __shared__ __align__(1024) unsigned char smem[];
    const uint32_t sb = smem_u32(smem);
    const int tid = threadIdx.x, warp = __shfl_sync(0xffffffffu, tid >> 5, 0), lane = tid & 31;
    int mb, nt;
    tile_of(blockIdx.x, mb, nt);
    const uint32_t full = sb + K1_BAR, empty = full + 40, auxb = full + 80;
    if (tid == 0) {
#pragma unroll
        for (int i = 0; i < K1_STAGES; i++) { mbar_init(full + 8 * i, 1); mbar_init(empty + 8 * i, 8); }
        mbar_init(auxb, 3);
        fence_barrier_init();
        for (int kb = 0; kb < K1_STAGES; kb++) {
            mbar_expect(full + 8 * kb, K1_STAGE);
            tma2d(sb + kb * K1_STAGE, &tm_x, kb * 64, mb * 128, full + 8 * kb);
            tma3d(sb + kb * K1_STAGE + 16384, &tm_w, 0, kb * 64, nt * 3, full + 8 * kb);
        }
    }
    __syncthreads();
    pdl_launch();
    if (warp == 0) {
        if (blockIdx.x == 0) g_cnt2[lane] = 0;
        if (lane == 0) {
            g_cnt2[32 + blockIdx.x] = 0;
            for (int kb = K1_STAGES; kb < 8; kb++) {
                int s = kb % K1_STAGES;
                mbar_wait(empty + 8 * s, 0);
                mbar_expect(full + 8 * s, K1_STAGE);
                tma2d(sb + s * K1_STAGE, &tm_x, kb * 64, mb * 128, full + 8 * s);
                tma3d(sb + s * K1_STAGE + 16384, &tm_w, 0, kb * 64, nt * 3, full + 8 * s);
            }
        }
    } else if (warp < 4) {
        float2* s_rs = (float2*)(smem + K1_RS);
        float* s_cs = (float*)(smem + K1_CS);
        if (warp < 3) {
            const int r0 = mb * 128 + nt * 16 + (warp - 1) * 8;
            uint4 u[16];
#pragma unroll
            for (int i = 0; i < 8; i++) {
                const uint4* p = (const uint4*)(x + (size_t)(r0 + i) * DM);
                u[2 * i] = __ldg(p + lane); u[2 * i + 1] = __ldg(p + 32 + lane);
            }
            float2 mine = make_float2(0.f, 0.f);
#pragma unroll
            for (int i = 0; i < 8; i++) {
                float2 st = row_stats_regs(u[2 * i], u[2 * i + 1]);
                if (lane == i) mine = st;
            }
            if (lane < 8) g_rowstat1[r0 + lane] = mine;
            __syncwarp();
            if (lane == 0) red_release(&g_cnt[mb]);
        } else {
            uint4 u[24];
#pragma unroll
            for (int c = 0; c < 3; c++)
#pragma unroll
                for (int i = 0; i < 8; i++)
                    u[c * 8 + i] = __ldg((const uint4*)(wqkv + (size_t)(mb * 32 + (lane >> 3) * 8 + i) * 1536 + nt * 192 + (c * 8 + (lane & 7)) * 8));
#pragma unroll
            for (int c = 0; c < 3; c++) {
                float cs[8];
#pragma unroll
                for (int i = 0; i < 8; i++) cs[i] = 0.f;
#pragma unroll
                for (int i = 0; i < 8; i++) {
                    const uint4 w = u[c * 8 + i];
                    cs[0] += bf_lo(w.x); cs[1] += bf_hi(w.x); cs[2] += bf_lo(w.y); cs[3] += bf_hi(w.y);
                    cs[4] += bf_lo(w.z); cs[5] += bf_hi(w.z); cs[6] += bf_lo(w.w); cs[7] += bf_hi(w.w);
                }
#pragma unroll
                for (int i = 0; i < 8; i++) {
                    cs[i] += __shfl_xor_sync(0xffffffffu, cs[i], 8);
                    cs[i] += __shfl_xor_sync(0xffffffffu, cs[i], 16);
                }
                if (lane < 8) {
                    float4* d = (float4*)(g_cs1_part + mb * 1536 + nt * 192 + (c * 8 + lane) * 8);
                    d[0] = make_float4(cs[0], cs[1], cs[2], cs[3]);
                    d[1] = make_float4(cs[4], cs[5], cs[6], cs[7]);
                }
            }
            __syncwarp();
            if (lane == 0) red_release(&g_cnt[16 + nt]);
        }
        if (warp == 1) {
            if (wait_count(&g_cnt[mb], 16, lane)) {
#pragma unroll
                for (int i = 0; i < 4; i++) s_rs[lane + 32 * i] = __ldcg(&g_rowstat1[mb * 128 + lane + 32 * i]);
            } else {
                for (int i = 0; i < 128; i++) {
                    float2 st = row_stats_x(x, mb * 128 + i, lane);
                    if (lane == 0) s_rs[i] = st;
                }
            }
        } else {
            int c0 = (warp - 2) * 96;
            if (wait_count(&g_cnt[16 + nt], 16, lane)) {
#pragma unroll
                for (int i = 0; i < 3; i++) {
                    float s = 0.f;
#pragma unroll
                    for (int p = 0; p < 16; p++) s += __ldcg(&g_cs1_part[p * 1536 + nt * 192 + c0 + lane + 32 * i]);
                    s_cs[c0 + lane + 32 * i] = s;
                }
            } else if (lane < 12) {
                float s[8];
                colsum8(wqkv, 1536, nt * 192 + c0 + lane * 8, 0, 512, s);
#pragma unroll
                for (int i = 0; i < 8; i++) s_cs[c0 + lane * 8 + i] = s[i];
            }
        }
        __syncwarp();
        if (lane == 0) mbar_arrive(auxb);
        bar_sync(2, 256 + 96);
        const int a = tid - 32;
        {
            const int hh = a >> 3, w = a & 7;
            const float4* p = (const float4*)(smem + 49152) + (hh * 256 + w * 32) / 2;
            float m = 0.f;
#pragma unroll
            for (int i = 0; i < 8; i++) {
                const int ii = (i + a) & 7;
                float4 u = p[2 * ii], v = p[2 * ii + 1];
                float n0 = u.x + u.z + v.x + v.z, n1 = u.y + u.w + v.y + v.w;
                if (!(n0 <= 3.0e38f) || !(n1 <= 3.0e38f)) m = __int_as_float(0x7f800000);
                m = fmaxf(m, fmaxf(n0, n1));
            }
            const int col0 = nt * 192 + hh * 16;
            g_nrm[((col0 >> 9) * NH + ((col0 & 511) >> 4)) * 128 + mb * 8 + w] = m;
        }
    } else {
        const int wgi = (warp >> 2) - 1, ww = warp & 3;
        float acc[96];
#pragma unroll 1
        for (int kb = 0; kb < 8; kb++) {
            int s = kb % K1_STAGES;
            mbar_wait(full + 8 * s, (kb / K1_STAGES) & 1);
            uint64_t ad = make_desc(sb + s * K1_STAGE + wgi * 8192, 16, 1024, 1);
            uint64_t bd = make_desc(sb + s * K1_STAGE + 16384, 8192, 1024, 1);
            WG_FENCE();
#pragma unroll
            for (int k = 0; k < 4; k++) wgmma_ss_n192(acc, ad + k * 2, bd + k * 128, (kb | k) != 0);
            WG_COMMIT();
            if (kb > 0) {
                wg_wait<1>();
                if (lane == 0) mbar_arrive(empty + 8 * ((kb - 1) % K1_STAGES));
            }
        }
        wg_wait<0>();
        fence_regs(acc);
        mbar_wait(auxb, 0);
        bar_sync(1, 256);
        const float2* s_rs = (const float2*)(smem + K1_RS);
        const float* s_cs = (const float*)(smem + K1_CS);
        const int g = lane >> 2, t = lane & 3;
        const int rl = wgi * 64 + ww * 16 + g;
        const float2 st0 = s_rs[rl], st1 = s_rs[rl + 8];
        const float QS = 0.25f * 1.4426950408889634f;
        float2* s_np = (float2*)(smem + 49152) + (warp - 4) * 32 + lane;
#pragma unroll
        for (int hh = 0; hh < 12; hh++) {
            const int which = (nt * 192 + hh * 16) >> 9;
            const float sc = (which == 0) ? QS : 1.0f;
            const float a0 = st0.x * sc, b0 = st0.y * sc, a1 = st1.x * sc, b1 = st1.y * sc;
            const float2 c0 = *(const float2*)(s_cs + 16 * hh + 2 * t), c1 = *(const float2*)(s_cs + 16 * hh + 8 + 2 * t);
            const float* a = acc + 8 * hh;
            float v0 = fmaf(a0, a[0], b0 * c0.x), v1 = fmaf(a0, a[1], b0 * c0.y), v2 = fmaf(a1, a[2], b1 * c0.x), v3 = fmaf(a1, a[3], b1 * c0.y);
            float v4 = fmaf(a0, a[4], b0 * c1.x), v5 = fmaf(a0, a[5], b0 * c1.y), v6 = fmaf(a1, a[6], b1 * c1.x), v7 = fmaf(a1, a[7], b1 * c1.y);
            {
                const int head = ((nt * 192 + hh * 16) & 511) >> 4;
                uint32_t* o = (uint32_t*)g_qkv + ((size_t)((which * NH + head) * 2) * 256 + mb * 16 + wgi * 8 + ww * 2) * 32 + lane;
                o[0] = pack_bf16(v0, v1); o[32] = pack_bf16(v2, v3); o[8192] = pack_bf16(v4, v5); o[8192 + 32] = pack_bf16(v6, v7);
            }
            s_np[hh * 256] = make_float2(fmaf(v0, v0, fmaf(v1, v1, fmaf(v4, v4, v5 * v5))), fmaf(v2, v2, fmaf(v3, v3, fmaf(v6, v6, v7 * v7))));
        }
        bar_arrive(2, 256 + 96);
    }
}

constexpr int AT_K = 0, AT_V = 65536, AT_ONES = 131072, AT_BAR = 163840, AT_SMEM = AT_BAR + 128;
constexpr uint32_t POLY_MASK = 0x7B5A;

__device__ __forceinline__ uint32_t exp2_pair_poly(float x0, float x1) {
    uint32_t t0 = __float_as_uint(x0 + 32895.0f);
    uint32_t t1 = __float_as_uint(x1 + 32895.0f);
    uint32_t gd = __byte_perm(t0, t1, 0x6420);
    uint32_t wm = __byte_perm(t0, t1, 0x5612);
    uint32_t v = hfma2(gd, 0x712d712du, 0x355c355cu);
    uint32_t z = hmul2(v, gd);
    return (wm >> 1) + z;
}
__device__ __forceinline__ uint32_t exp2_pair_mufu(float x0, float x1) { return pack_bf16(ex2f(x0), ex2f(x1)); }
template <uint32_t MASK>
__device__ __forceinline__ void exp_blocks(const float (&s)[32], uint32_t (&p)[16]) {
#pragma unroll
    for (int b = 0; b < 8; b++) {
        if ((MASK >> b) & 1) {
            p[2 * b] = exp2_pair_poly(s[4 * b], s[4 * b + 1]);
            p[2 * b + 1] = exp2_pair_poly(s[4 * b + 2], s[4 * b + 3]);
        } else {
            p[2 * b] = exp2_pair_mufu(s[4 * b], s[4 * b + 1]);
            p[2 * b + 1] = exp2_pair_mufu(s[4 * b + 2], s[4 * b + 3]);
        }
    }
}
#define PV4(P) _Pragma("unroll") for (int i = 0; i < 4; i++) { pv_wgmma(o, P[4 * i], P[4 * i + 1], P[4 * i + 2], P[4 * i + 3], vd); vd += 16; }

__device__ __forceinline__ void attn_store(float (&o)[12], int row0, int head, int lane) {
    float l0 = __shfl_sync(0xffffffffu, o[8], lane & 28);
    float l1 = __shfl_sync(0xffffffffu, o[10], lane & 28);
    float r0 = 1.0f / l0, r1 = 1.0f / l1;
    uint32_t* op = (uint32_t*)g_ao;
    int mb = row0 >> 7, rg = (row0 & 127) >> 3;
    int kb = head >> 2, kc = (head & 3) * 2;
    size_t base = (((size_t)(mb * 8 + kb) * 8 + kc) * 16 + rg) * 32 + lane;
    op[base] = pack_bf16(o[0] * r0, o[1] * r0);
    op[base + 32] = pack_bf16(o[2] * r1, o[3] * r1);
    op[base + 16 * 32] = pack_bf16(o[4] * r0, o[5] * r0);
    op[base + 16 * 32 + 32] = pack_bf16(o[6] * r1, o[7] * r1);
}

__device__ __forceinline__ void attn_load_q(uint32_t (&q)[4], const __nv_bfloat16* gq, int row0, int lane) {
    const uint32_t* qp = (const uint32_t*)gq;
    int j0 = row0 >> 3;
    q[0] = __ldcg(qp + (0 * 256 + j0) * 32 + lane);
    q[1] = __ldcg(qp + (0 * 256 + j0 + 1) * 32 + lane);
    q[2] = __ldcg(qp + (1 * 256 + j0) * 32 + lane);
    q[3] = __ldcg(qp + (1 * 256 + j0 + 1) * 32 + lane);
}

__device__ __forceinline__ void attn_tile_safe(const uint32_t (&q)[4], uint64_t kd, uint64_t vd, int row0, int head, int lane) {
    float o[12];
#pragma unroll
    for (int i = 0; i < 12; i++) o[i] = 0.f;
    float m0 = -INFINITY, m1 = -INFINITY;
    fence_regs(o);
#pragma unroll 1
    for (int j = 0; j < 32; j++) {
        float s[32];
        uint32_t p[16];
        WG_FENCE();
        qk_wgmma_n64(s, q, kd); kd += 64;
        WG_COMMIT();
        wg_wait<0>();
        fence_regs(s);
        fence_regs(o);
        float x0 = m0, x1 = m1;
#pragma unroll
        for (int b = 0; b < 8; b++) {
            x0 = fmaxf(x0, fmaxf(s[4 * b], s[4 * b + 1]));
            x1 = fmaxf(x1, fmaxf(s[4 * b + 2], s[4 * b + 3]));
        }
        x0 = fmaxf(x0, __shfl_xor_sync(0xffffffffu, x0, 1)); x0 = fmaxf(x0, __shfl_xor_sync(0xffffffffu, x0, 2));
        x1 = fmaxf(x1, __shfl_xor_sync(0xffffffffu, x1, 1)); x1 = fmaxf(x1, __shfl_xor_sync(0xffffffffu, x1, 2));
        float al0 = ex2f(m0 - x0), al1 = ex2f(m1 - x1);
        m0 = x0; m1 = x1;
#pragma unroll
        for (int i = 0; i < 3; i++) { o[4 * i] *= al0; o[4 * i + 1] *= al0; o[4 * i + 2] *= al1; o[4 * i + 3] *= al1; }
#pragma unroll
        for (int b = 0; b < 8; b++) {
            p[2 * b] = exp2_pair_mufu(s[4 * b] - m0, s[4 * b + 1] - m0);
            p[2 * b + 1] = exp2_pair_mufu(s[4 * b + 2] - m1, s[4 * b + 3] - m1);
        }
        fence_regs(o);
        WG_FENCE();
        PV4(p);
        WG_COMMIT();
        wg_wait<0>();
        fence_regs(o);
    }
    attn_store(o, row0, head, lane);
}

__global__ void __launch_bounds__(512, 1)
attn_kernel(const __nv_bfloat16* __restrict__ wg_, const __nv_bfloat16* __restrict__ wu_,
            const __nv_bfloat16* __restrict__ wo_, const __nv_bfloat16* __restrict__ wd_) {
    extern __shared__ __align__(1024) unsigned char smem[];
    const uint32_t sb = smem_u32(smem);
    const int tid = threadIdx.x, wg = tid >> 7, warp = (tid >> 5) & 3, lane = tid & 31;
    pdl_launch();
    if (blockIdx.x >= 128) {
        const int e = blockIdx.x - 128;
        const __nv_bfloat16* w = (e < 2) ? wg_ : wu_;
        float* red = (float*)smem;
        const int cgrp = tid & 127, kq = tid >> 7;
        if (cgrp < 112) {
            float s[8];
            colsum8(w, FF, (e & 1) * 896 + cgrp * 8, kq * 128, 128, s);
#pragma unroll
            for (int i = 0; i < 8; i++) red[kq * 896 + cgrp * 8 + i] = s[i];
        }
        __syncthreads();
        for (int c = tid; c < 896; c += 512)
            g_cs2[(e >> 1) * FF + (e & 1) * 896 + c] = red[c] + red[896 + c] + red[1792 + c] + red[2688 + c];
        if (tid < 32) {
            const char* p0 = (const char*)wo_ + e * (DM * DM * 2 / 4);
            for (int i = lane; i < 32; i += 32)
                asm volatile("cp.async.bulk.prefetch.L2.global [%0], %1;" :: "l"(p0 + i * 4096), "r"(4096) : "memory");
            const char* p1 = (const char*)wd_ + e * (FF * DM * 2 / 4);
            for (int i = lane; i < 112; i += 32)
                asm volatile("cp.async.bulk.prefetch.L2.global [%0], %1;" :: "l"(p1 + i * 4096), "r"(4096) : "memory");
        }
        return;
    }
    const int head = blockIdx.x >> 2, qq = blockIdx.x & 3;
    const __nv_bfloat16* gq = g_qkv + (size_t)head * (S_LEN * 16);
    const __nv_bfloat16* gk = g_qkv + (size_t)(NH + head) * (S_LEN * 16);
    const __nv_bfloat16* gv = g_qkv + (size_t)(2 * NH + head) * (S_LEN * 16);
    if (tid == 0) {
        for (int i = 0; i < 8; i++) mbar_init(sb + AT_BAR + 8 * i, 1);
        fence_barrier_init();
    }
    {
        uint4 one = make_uint4(0x00003F80u, 0, 0, 0);
#pragma unroll
        for (int i = 0; i < 4; i++) *(uint4*)(smem + AT_ONES + (i * 512 + tid) * 16) = one;
        fence_proxy_async();
    }
    __syncthreads();
    pdl_wait();
    auto load_kv = [&](int i) {
        uint32_t bar = sb + AT_BAR + 8 * i;
        mbar_expect(bar, 16384);
        bulk_g2s(sb + AT_K + i * 4096, gk + i * 2048, 4096, bar);
        bulk_g2s(sb + AT_K + 32768 + i * 4096, gk + 16384 + i * 2048, 4096, bar);
        bulk_g2s(sb + AT_V + i * 4096, gv + i * 2048, 4096, bar);
        bulk_g2s(sb + AT_V + 32768 + i * 4096, gv + 16384 + i * 2048, 4096, bar);
    };
    if (tid == 0) { load_kv(0); load_kv(1); }
    uint32_t q[4], q2[4];
    attn_load_q(q, gq, qq * 512 + wg * 64 + warp * 16, lane);
    attn_load_q(q2, gq, qq * 512 + (4 + wg) * 64 + warp * 16, lane);
    bool fast;
    {
        const float* nq = g_nrm + (0 * NH + head) * 128 + qq * 32;
        const float* nk = g_nrm + (1 * NH + head) * 128;
        const float* nv = g_nrm + (2 * NH + head) * 128;
        float4 k4 = __ldcg((const float4*)nk + lane), v4 = __ldcg((const float4*)nv + lane);
        float qm = warp_max(__ldcg(nq + lane));
        float km = warp_max(fmaxf(fmaxf(k4.x, k4.y), fmaxf(k4.z, k4.w)));
        float vm = warp_max(fmaxf(fmaxf(v4.x, v4.y), fmaxf(v4.z, v4.w)));
        fast = __all_sync(0xffffffffu, (qm * km <= 3500.0f) && (vm <= 1.0e24f));
    }
    const uint64_t kdesc0 = make_desc(sb + AT_K, 32768, 128, 0);
    const uint64_t vdesc0 = make_desc(sb + AT_V, 128, 32768, 0);
    if (!fast) {
        if (tid == 0) for (int i = 2; i < 8; i++) load_kv(i);
        for (int i = 0; i < 8; i++) mbar_wait(sb + AT_BAR + 8 * i, 0);
#pragma unroll 1
        for (int tile = 0; tile < 2; tile++) {
            const int row0 = qq * 512 + (tile * 4 + wg) * 64 + warp * 16;
            attn_tile_safe(q, kdesc0, vdesc0, row0, head, lane);
#pragma unroll
            for (int i = 0; i < 4; i++) q[i] = q2[i];
        }
        return;
    }
#pragma unroll 1
    for (int tile = 0; tile < 2; tile++) {
        const int row0 = qq * 512 + (tile * 4 + wg) * 64 + warp * 16;
        float o[12];
#pragma unroll
        for (int i = 0; i < 12; i++) o[i] = 0.f;
        fence_regs(o);
        float sa[32];
        uint32_t pa[16];
        uint64_t kd = kdesc0, vd = vdesc0;
        if (tile == 0) { mbar_wait(sb + AT_BAR, 0); }
        WG_FENCE();
        qk_wgmma_n64(sa, q, kd); kd += 64;
        WG_COMMIT();
#pragma unroll 1
        for (int jj = 0; jj < 8; jj++) {
            if (tile == 0 && jj < 7) {
                if (tid == 0 && jj < 6) load_kv(jj + 2);
                mbar_wait(sb + AT_BAR + 8 * (jj + 1), 0);
            }
#pragma unroll
            for (int j = 0; j < 4; j++) {
                wg_wait<0>();
                fence_regs(sa);
                if (j & 1) exp_blocks<(POLY_MASK >> 8)>(sa, pa); else exp_blocks<(POLY_MASK & 255)>(sa, pa);
                WG_FENCE();
                PV4(pa);
                qk_wgmma_n64(sa, q, kd); kd += 64;
                WG_COMMIT();
            }
        }
        wg_wait<0>();
        fence_regs(o);
        fence_regs(sa);
        attn_store(o, row0, head, lane);
#pragma unroll
        for (int i = 0; i < 4; i++) q[i] = q2[i];
    }
}

constexpr int F_R2 = 131072, F_X = 196608, F_BAR = 229376;
constexpr int F_RS = F_BAR + 256, F_CS = F_RS + 1024, F_SMEM = F_CS + 1792;
enum { B_FA = 0, B_HF = 4, B_BF = 8, B_BE = 11, B_CF = 14, B_CE = 20, B_ADONE = 26, B_BDONE = 27, B_XC = 28, B_PRDY = 29, B_AUX = 30, B_NUM = 31 };

__device__ __forceinline__ void st_async4(uint32_t dst, float a, float b, float c, float d, uint32_t bar) {
    asm volatile("st.async.weak.shared::cluster.mbarrier::complete_tx::bytes.v4.f32 [%0], {%1,%2,%3,%4}, [%5];"
                 :: "r"(dst), "f"(a), "f"(b), "f"(c), "f"(d), "r"(bar) : "memory");
}
__device__ __forceinline__ void poll_count(const unsigned int* p, unsigned int target) {
    int it = 0;
    while (ld_acquire(p) < target) { if (++it > (1 << 22)) __trap(); }
    asm volatile("fence.proxy.async.global;" ::: "memory");
}
__device__ __forceinline__ void tma2d_store(const CUtensorMap* m, uint32_t src, int c0, int c1) {
    asm volatile("cp.async.bulk.tensor.2d.global.shared::cta.bulk_group [%0, {%2, %3}], [%1];" :: "l"(m), "r"(src), "r"(c0), "r"(c1) : "memory");
}
__device__ __forceinline__ float2 h_row_stats(int row) {
    const float4* hp = (const float4*)(g_hstat + (size_t)row * 8);
    float4 a = __ldcg(hp), b = __ldcg(hp + 1), c = __ldcg(hp + 2), d = __ldcg(hp + 3);
    float mean = 0.125f * (a.x + a.z + b.x + b.z + c.x + c.z + d.x + d.z);
    float m2 = a.y + a.w + b.y + b.w + c.y + c.w + d.y + d.w;
    float e;
    e = a.x - mean; m2 = fmaf(64.f * e, e, m2); e = a.z - mean; m2 = fmaf(64.f * e, e, m2);
    e = b.x - mean; m2 = fmaf(64.f * e, e, m2); e = b.z - mean; m2 = fmaf(64.f * e, e, m2);
    e = c.x - mean; m2 = fmaf(64.f * e, e, m2); e = c.z - mean; m2 = fmaf(64.f * e, e, m2);
    e = d.x - mean; m2 = fmaf(64.f * e, e, m2); e = d.z - mean; m2 = fmaf(64.f * e, e, m2);
    return make_float2(rsqrtf(m2 * (1.0f / DM) + 1e-5f), -mean);
}
__device__ __forceinline__ int c_kblock(int i, int r) {
    if (i < 6) { const int e = 2 * i + r, m = e / 3, k = e - 3 * m; return 7 * m + (k == 2 ? 4 : k); }
    const int l = 2 * (i - 6) + r, m = l >> 2, k = l & 3;
    return 7 * m + (k < 2 ? 2 + k : 3 + k);
}
__device__ __forceinline__ uint32_t c_stage_a(int s, int ntB) { return s < 4 ? ((ntB + 2 * s) & 7) * 16384 : F_R2 + (s - 4) * 32768; }
__device__ __forceinline__ uint32_t c_stage_b(int s, int ntB) { return s < 4 ? ((ntB + 2 * s + 1) & 7) * 16384 : F_R2 + (s - 4) * 32768 + 16384; }
template <int R>
__device__ __forceinline__ void xchg(float (&acc)[64], float (&o)[32], uint32_t sb, unsigned char* smem, int bar, int ctid) {
    const uint32_t dst = mapa(sb + F_X + ctid * 16, 1 - R), rb = mapa(sb + F_BAR + 8 * bar, 1 - R);
#pragma unroll
    for (int q = 0; q < 8; q++) {
        const int j = (1 - R) * 32 + 4 * q;
        st_async4(dst + q * 4096, acc[j], acc[j + 1], acc[j + 2], acc[j + 3], rb);
    }
    mbar_wait_cluster(sb + F_BAR + 8 * bar, 0);
#pragma unroll
    for (int q = 0; q < 8; q++) {
        float4 v = *(const float4*)(smem + F_X + q * 4096 + ctid * 16);
        const int j = R * 32 + 4 * q;
        o[4 * q] = acc[j] + v.x; o[4 * q + 1] = acc[j + 1] + v.y; o[4 * q + 2] = acc[j + 2] + v.z; o[4 * q + 3] = acc[j + 3] + v.w;
    }
}

template <int NB, bool STAGE>
__device__ __forceinline__ void ffn_epilogue(const float* ag, const float* au, const float* s_cs, int cs_off, uint32_t* gp, uint32_t stg,
                                             float2 st0, float2 st1, int lane) {
    const int t = lane & 3;
    const float C1 = 0.7978845608028654f, C2 = 0.044715f * 0.7978845608028654f;
#pragma unroll
    for (int j2 = 0; j2 < NB / 2; j2++) {
        uint32_t pk[4];
#pragma unroll
        for (int jj = 0; jj < 2; jj++) {
            const int j = 2 * j2 + jj;
            const float2 cg = *(const float2*)(s_cs + cs_off + 8 * j + 2 * t);
            const float2 cu = *(const float2*)(s_cs + 224 + cs_off + 8 * j + 2 * t);
            float r[4];
#pragma unroll
            for (int e = 0; e < 4; e++) {
                const float nm = (e < 2) ? st0.y : st1.y, rs = (e < 2) ? st0.x : st1.x;
                const float gt = rs * fmaf(nm, (e & 1) ? cg.y : cg.x, ag[4 * j + e]);
                const float tu = fmaf(nm, (e & 1) ? cu.y : cu.x, au[4 * j + e]);
                const float th = tanh_fast(gt * fmaf(gt * gt, C2, C1));
                const float p = gt * tu;
                r[e] = fmaf(p, th, p);
            }
            pk[2 * jj] = pack_bf16(r[0], r[1]);
            pk[2 * jj + 1] = pack_bf16(r[2], r[3]);
        }
        if (STAGE) {
            stsm4(stg + j2 * 4096, pk[0], pk[1], pk[2], pk[3]);
        } else {
            gp[j2 * 1024] = pk[0]; gp[j2 * 1024 + 32] = pk[1]; gp[j2 * 1024 + 512] = pk[2]; gp[j2 * 1024 + 544] = pk[3];
        }
    }
}

__global__ void __cluster_dims__(2, 1, 1) __launch_bounds__(384, 1)
tail_kernel(const __grid_constant__ CUtensorMap tm_o, const __grid_constant__ CUtensorMap tm_g,
            const __grid_constant__ CUtensorMap tm_u, const __grid_constant__ CUtensorMap tm_d,
            const __grid_constant__ CUtensorMap tm_out, const __nv_bfloat16* __restrict__ x) {
    extern __shared__ __align__(1024) unsigned char smem[];
    const uint32_t sb = smem_u32(smem);
    const uint32_t bars = sb + F_BAR;
    const int tid = threadIdx.x, warp = __shfl_sync(0xffffffffu, tid >> 5, 0), lane = tid & 31;
    const int cl = blockIdx.x >> 1, r = blockIdx.x & 1;
    const int mb = ((cl & 7) >> 1) * 4 + (cl >> 4), ntA = (cl & 1) * 2 + ((cl >> 3) & 1);
    const int nt = ntA * 2 + r;
    const int mbB = (mb & ~1) + r, ntB = (mb & 1) * 4 + ntA;
    if (tid == 0) {
#pragma unroll
        for (int i = 0; i < B_NUM; i++) {
            const int cnt = (i >= B_BE && i < B_BE + 3) ? 16 : (i == B_BDONE) ? 9 : ((i >= B_CE && i < B_CE + 6) || i == B_PRDY) ? 8 : (i == B_AUX || i == B_ADONE) ? 2 : 1;
            mbar_init(bars + 8 * i, cnt);
        }
        mbar_expect(bars + 8 * B_XC, 32768);
        fence_barrier_init();
        for (int i = 0; i < 8; i++) {
            const uint32_t bar = bars + 8 * (B_FA + (i >> 1));
            if (!(i & 1)) mbar_expect(bar, 49152);
            tma2d(sb + F_R2 + 32768 + i * 8192, &tm_o, nt * 64, i * 64, bar);
        }
    }
    __syncthreads();
    asm volatile("barrier.cluster.arrive.relaxed.aligned;" ::: "memory");
    if (warp < 4) {
        asm volatile("setmaxnreg.dec.sync.aligned.u32 56;");
        if (warp == 0) {
            if (lane == 0) {
                auto load_b = [&](int it) {
                    const int s = it % 3, pass = it >> 3, kb = (ntB + it) & 7;
                    const int ng = pass ? 3 : 4, c0 = ntB * 224 + pass * 128;
                    const uint32_t bar = bars + 8 * (B_BF + s), dst = sb + F_R2 + s * 32768 + r * ng * 4096;
                    mbar_expect(bar, ng * 8192);
                    for (int i = 0; i < ng; i++) tma2d_mc(dst + i * 4096, r ? &tm_u : &tm_g, c0 + i * 32, kb * 64, bar);
                };
                asm volatile("barrier.cluster.wait.acquire;" ::: "memory");
                pdl_wait();
                for (int i = 0; i < 4; i++)
                    bulk_g2s_mc(sb + (2 * i + r) * 16384, g_ao + (size_t)(mb * 8 + 2 * i + r) * 8192, 16384, bars + 8 * (B_FA + i));
                load_b(0);
                if (blockIdx.x == 0)
                    for (int i = 0; i < 32; i++) g_cnt[i] = 0;
                mbar_wait_cluster(bars + 8 * B_ADONE, 0);
                load_b(1); load_b(2);
                auto load_c = [&](int i) {
                    const int s = i % 6, kb = c_kblock(i, r);
                    const uint32_t bar = bars + 8 * (B_CF + s), da = sb + c_stage_a(s, ntB), db = sb + c_stage_b(s, ntB);
                    mbar_expect(bar, 32768);
                    tma2d(db, &tm_d, ntA * 128, kb * 64, bar);
                    tma2d(db + 8192, &tm_d, ntA * 128 + 64, kb * 64, bar);
                    bulk_g2s(da, g_g + (size_t)(mb * 28 + kb) * 8192, 16384, bar);
                };
                for (int it = 3; it < 16; it++) {
                    mbar_wait_cluster(bars + 8 * (B_BE + it % 3), (it / 3 - 1) & 1);
                    load_b(it);
                    if (it == 12) { poll_count(&g_cnt2[mb], 8); load_c(0); }
                    if (it == 14) load_c(1);
                }
                mbar_wait_cluster(bars + 8 * (B_BE + 1), 0);
                load_c(2);
                mbar_wait(bars + 8 * B_BDONE, 0);
                for (int i = 3; i < 14; i++) {
                    if (i >= 6) mbar_wait(bars + 8 * (B_CE + i % 6), ((i / 6) - 1) & 1);
                    if (i == 6) { poll_count(&g_cnt2[16 + mb], 8); }
                    load_c(i);
                }
            }
            else asm volatile("barrier.cluster.wait.acquire;" ::: "memory");
        } else if (warp == 1) {
            asm volatile("barrier.cluster.wait.acquire.aligned;" ::: "memory");
            bar_sync(5, 288);
            if (lane == 0) { red_release(&g_cnt2[32 + (mb * 8 + nt)]); }
            __syncwarp();
            bar_sync(6, 288);
            if (lane == 0) red_release(&g_cnt2[32 + (mb * 8 + nt)]);
            __syncwarp();
            bar_sync(1, 288);
            if (lane == 0) red_release(&g_cnt2[mbB]);
            __syncwarp();
            bar_sync(2, 288);
            if (lane == 0) {
                red_release(&g_cnt2[16 + mbB]);
                mbar_arrive(bars + 8 * B_BDONE);
            }
            __syncwarp();
            bar_sync(3, 288);
            if (lane == 0) {
                tma2d_store(&tm_out, sb, nt * 64, mb * 128);
                bulk_commit();
                bulk_wait_all();
            }
        } else {
            asm volatile("barrier.cluster.wait.acquire.aligned;" ::: "memory");
            pdl_wait();
            float2* s_rs = (float2*)(smem + F_RS);
            float* s_cs = (float*)(smem + F_CS);
            for (int c = tid - 64; c < 448; c += 64)
                s_cs[c] = __ldcg(&g_cs2[(c >= 224 ? FF - 224 : 0) + ntB * 224 + c]);
            if (tid == 96) {
                mbar_wait_cluster(bars + 8 * B_ADONE, 0);
                for (int i = 0; i < 8; i++) {
                    const int kb = (ntB + i) & 7;
                    const uint32_t bar = bars + 8 * (i < 4 ? B_HF + i : B_FA + i - 4);
                    poll_count(&g_cnt2[32 + (mbB * 8 + kb)], 1);
                    mbar_expect(bar, 16384);
                    bulk_g2s(sb + kb * 16384, g_h + (size_t)(mbB * 8 + kb) * 8192, 16384, bar);
                }
            }
            __syncwarp();
            for (int i = 0; i < 8; i++) mbar_wait(bars + 8 * (i < 4 ? B_HF + i : B_FA + i - 4), i < 4 ? 0 : 1);
            if (lane < 8) poll_count(&g_cnt2[32 + (mbB * 8 + lane)], 2);
            __syncwarp();
            __syncwarp();
            for (int rr = tid - 64; rr < 128; rr += 64) {
                s_rs[rr] = h_row_stats(mbB * 128 + rr);
            }
            __syncwarp();
            if (lane == 0) mbar_arrive(bars + 8 * B_AUX);
        }
    } else {
        asm volatile("setmaxnreg.inc.sync.aligned.u32 216;");
        const int wgi = (warp >> 2) - 1, ww = warp & 3, ctid = tid - 128;
        const int g = lane >> 2, t = lane & 3;
        const int rl = wgi * 64 + ww * 16 + g, row = mb * 128 + rl;
        const int rgl = wgi * 8 + ww * 2;
        const float2* s_rs = (const float2*)(smem + F_RS);
        const float* s_cs = (const float*)(smem + F_CS);
        uint32_t* hp = (uint32_t*)g_h + ((size_t)(mb * 8 + nt) * 8 * 16 + rgl) * 32 + lane;
        const uint32_t rbars = mapa(bars, 1 - r);
        {
            uint32_t xr[16];
            const uint32_t* xp = (const uint32_t*)(x + (size_t)row * DM + nt * 64) + t;
#pragma unroll
            for (int j = 0; j < 8; j++) { xr[2 * j] = __ldg(xp + 4 * j); xr[2 * j + 1] = __ldg(xp + 8 * (DM / 2) + 4 * j); }
            float acc[32];
#pragma unroll 1
            for (int i = 0; i < 8; i++) {
                if (!(i & 1)) { mbar_wait(bars + 8 * (B_FA + (i >> 1)), 0); }
                uint64_t ad = make_desc(sb + i * 16384 + wgi * 1024, 2048, 128, 0);
                uint64_t bd = make_desc(sb + F_R2 + 32768 + i * 8192, 8192, 1024, 1);
                WG_FENCE();
#pragma unroll
                for (int k = 0; k < 4; k++) wgmma_ss_n64(acc, ad + k * 256, bd + k * 128, (i | k) != 0);
                WG_COMMIT();
            }
            wg_wait<0>();
            fence_regs(acc);
            asm volatile("barrier.cluster.wait.acquire.aligned;" ::: "memory");
            bar_sync(4, 256);
            if (tid == 128) { mbar_arrive(bars + 8 * B_ADONE); mbar_arrive_remote(mapa(bars + 8 * B_ADONE, 1 - r)); }
            float v0[16], v1[16];
            float s0 = 0.f, s1 = 0.f;
#pragma unroll
            for (int j2 = 0; j2 < 4; j2++) {
                uint32_t u[4];
#pragma unroll
                for (int jj = 0; jj < 2; jj++) {
                    const int j = 2 * j2 + jj;
                    u[2 * jj] = pack_bf16(bf_lo(xr[2 * j]) + acc[4 * j], bf_hi(xr[2 * j]) + acc[4 * j + 1]);
                    u[2 * jj + 1] = pack_bf16(bf_lo(xr[2 * j + 1]) + acc[4 * j + 2], bf_hi(xr[2 * j + 1]) + acc[4 * j + 3]);
                    v0[2 * j] = bf_lo(u[2 * jj]); v0[2 * j + 1] = bf_hi(u[2 * jj]);
                    v1[2 * j] = bf_lo(u[2 * jj + 1]); v1[2 * j + 1] = bf_hi(u[2 * jj + 1]);
                    s0 += v0[2 * j] + v0[2 * j + 1];
                    s1 += v1[2 * j] + v1[2 * j + 1];
                }
                hp[j2 * 1024] = u[0]; hp[j2 * 1024 + 32] = u[1]; hp[j2 * 1024 + 512] = u[2]; hp[j2 * 1024 + 544] = u[3];
            }
            bar_arrive(5, 288);
            float m0 = s0 * (1.0f / 16), m1 = s1 * (1.0f / 16), q0 = 0.f, q1 = 0.f;
#pragma unroll
            for (int i = 0; i < 16; i++) {
                float d0 = v0[i] - m0, d1 = v1[i] - m1;
                q0 = fmaf(d0, d0, q0); q1 = fmaf(d1, d1, q1);
            }
#pragma unroll
            for (int st = 0; st < 2; st++) {
                float hn = st ? 16.f : 8.f;
                float om0 = __shfl_xor_sync(0xffffffffu, m0, 1 << st), oq0 = __shfl_xor_sync(0xffffffffu, q0, 1 << st);
                float om1 = __shfl_xor_sync(0xffffffffu, m1, 1 << st), oq1 = __shfl_xor_sync(0xffffffffu, q1, 1 << st);
                float d0 = om0 - m0, d1 = om1 - m1;
                q0 = q0 + oq0 + d0 * d0 * hn; q1 = q1 + oq1 + d1 * d1 * hn;
                m0 = 0.5f * (m0 + om0); m1 = 0.5f * (m1 + om1);
            }
            if (t == 0) {
                g_hstat[row * 8 + nt] = make_float2(m0, q0);
                g_hstat[(row + 8) * 8 + nt] = make_float2(m1, q1);
            }
            bar_arrive(6, 288);
        }
        uint32_t* gp = (uint32_t*)g_g + (((size_t)mbB * 224 + ntB * 28) * 16 + rgl) * 32 + lane;
        {
            float ag[128];
#pragma unroll 1
            for (int kb = 0; kb < 8; kb++) {
                const int s = kb % 3;
                mbar_wait(bars + 8 * (kb < 4 ? B_HF + kb : B_FA + kb - 4), kb < 4 ? 0 : 1);
                mbar_wait(bars + 8 * (B_BF + s), (kb / 3) & 1);
                uint64_t ad = make_desc(sb + ((ntB + kb) & 7) * 16384 + wgi * 1024, 2048, 128, 0);
                uint64_t bd = make_desc(sb + F_R2 + s * 32768, 4096, 512, 2);
                WG_FENCE();
#pragma unroll
                for (int k = 0; k < 4; k++) wgmma_ss_n256(ag, ad + k * 256, bd + k * 64, (kb | k) != 0);
                WG_COMMIT();
                if (kb > 0) {
                    wg_wait<1>();
                    if (lane == 0) { mbar_arrive(bars + 8 * (B_BE + (kb - 1) % 3)); mbar_arrive_remote(rbars + 8 * (B_BE + (kb - 1) % 3)); }
                }
            }
            wg_wait<0>();
            if (lane == 0) { mbar_arrive(bars + 8 * (B_BE + 7 % 3)); mbar_arrive_remote(rbars + 8 * (B_BE + 7 % 3)); }
            fence_regs(ag);
            mbar_wait(bars + 8 * B_AUX, 0);
            ffn_epilogue<16, false>(ag, ag + 64, s_cs, 0, gp, 0, s_rs[rl], s_rs[rl + 8], lane);
            bar_arrive(1, 288);
        }
        {
            float ag[96];
#pragma unroll 1
            for (int kb = 0; kb < 8; kb++) {
                const int it = 8 + kb, s = it % 3;
                mbar_wait(bars + 8 * (B_BF + s), (it / 3) & 1);
                uint64_t ad = make_desc(sb + ((ntB + kb) & 7) * 16384 + wgi * 1024, 2048, 128, 0);
                uint64_t bd = make_desc(sb + F_R2 + s * 32768, 4096, 512, 2);
                WG_FENCE();
#pragma unroll
                for (int k = 0; k < 4; k++) wgmma_ss_n192(ag, ad + k * 256, bd + k * 64, (kb | k) != 0);
                WG_COMMIT();
                if (kb > 0) {
                    wg_wait<1>();
                    if (lane == 0 && it < 15) { mbar_arrive(bars + 8 * (B_BE + (it - 1) % 3)); mbar_arrive_remote(rbars + 8 * (B_BE + (it - 1) % 3)); }
                }
            }
            wg_wait<0>();
            if (lane == 0) {
                mbar_arrive(bars + 8 * B_BDONE);
                mbar_arrive_remote(rbars + 8 * B_PRDY);
            }
            fence_regs(ag);
            ffn_epilogue<12, false>(ag, ag + 48, s_cs, 128, gp + 16 * 512, 0, s_rs[rl], s_rs[rl + 8], lane);
            bar_arrive(2, 288);
        }
        {
            uint32_t hr[16];
#pragma unroll
            for (int j = 0; j < 8; j++) { hr[2 * j] = __ldcg(hp + j * 512); hr[2 * j + 1] = __ldcg(hp + j * 512 + 32); }
            mbar_wait(bars + 8 * (B_CF + 0), 0);
            const float a0 = h_row_stats(row).x, a1 = h_row_stats(row + 8).x;
            float acc[64];
#pragma unroll 1
            for (int kb = 0; kb < 14; kb++) {
                const int s = kb % 6;
                mbar_wait(bars + 8 * (B_CF + s), (kb / 6) & 1);
                uint64_t ad = make_desc(sb + c_stage_a(s, ntB) + wgi * 1024, 2048, 128, 0);
                uint64_t bd = make_desc(sb + c_stage_b(s, ntB), 8192, 1024, 1);
                WG_FENCE();
#pragma unroll
                for (int k = 0; k < 4; k++) wgmma_ss_n128(acc, ad + k * 256, bd + k * 128, (kb | k) != 0);
                WG_COMMIT();
                if (kb > 0) {
                    wg_wait<1>();
                    if (lane == 0) mbar_arrive(bars + 8 * (B_CE + (kb - 1) % 6));
                }
            }
            wg_wait<0>();
            fence_regs(acc);
            mbar_wait_cluster(bars + 8 * B_PRDY, 0);
            float o[32];
            if (r == 0) xchg<0>(acc, o, sb, smem, B_XC, ctid); else xchg<1>(acc, o, sb, smem, B_XC, ctid);
            bar_sync(4, 256);
            const float k0 = 0.5f * a0, k1 = 0.5f * a1;
            const int srow = wgi * 64 + ww * 16 + ((lane >> 3) & 1) * 8 + (lane & 7);
#pragma unroll
            for (int j2 = 0; j2 < 4; j2++) {
                uint32_t u[4];
#pragma unroll
                for (int jj = 0; jj < 2; jj++) {
                    const int j = 2 * j2 + jj;
                    u[2 * jj] = pack_bf16(fmaf(k0, o[4 * j], bf_lo(hr[2 * j])), fmaf(k0, o[4 * j + 1], bf_hi(hr[2 * j])));
                    u[2 * jj + 1] = pack_bf16(fmaf(k1, o[4 * j + 2], bf_lo(hr[2 * j + 1])), fmaf(k1, o[4 * j + 3], bf_hi(hr[2 * j + 1])));
                }
                const int chunk = 2 * j2 + (lane >> 4);
                stsm4(sb + srow * 128 + ((chunk ^ (lane & 7)) * 16), u[0], u[1], u[2], u[3]);
            }
            fence_proxy_async();
            bar_arrive(3, 288);
        }
    }
}


static_assert(K1_SMEM <= F_SMEM && AT_SMEM <= F_SMEM && F_SMEM <= 232448, "shared memory budget");

typedef CUresult (*EncodeFn)(CUtensorMap*, CUtensorMapDataType, cuuint32_t, void*, const cuuint64_t*, const cuuint64_t*,
                             const cuuint32_t*, const cuuint32_t*, CUtensorMapInterleave, CUtensorMapSwizzle,
                             CUtensorMapL2promotion, CUtensorMapFloatOOBfill);

void encode(EncodeFn fn, CUtensorMap* m, const void* ptr, int rank, const cuuint64_t* dims, const cuuint64_t* strides,
            const cuuint32_t* box, CUtensorMapSwizzle swz) {
    cuuint32_t es[3] = {1, 1, 1};
    fn(m, CU_TENSOR_MAP_DATA_TYPE_BFLOAT16, rank, (void*)ptr, dims, strides, box, es, CU_TENSOR_MAP_INTERLEAVE_NONE, swz,
       CU_TENSOR_MAP_L2_PROMOTION_L2_256B, CU_TENSOR_MAP_FLOAT_OOB_FILL_NONE);
}

template <typename... KArgs, typename... Args>
void launch(void (*kern)(KArgs...), int grid, int block, int smem, bool pdl, Args... args) {
    cudaLaunchConfig_t cfg = {};
    cfg.gridDim = dim3(grid); cfg.blockDim = dim3(block); cfg.dynamicSmemBytes = smem;
    cfg.stream = cudaStreamPerThread;
    cudaLaunchAttribute at[1];
    at[0].id = cudaLaunchAttributeProgrammaticStreamSerialization;
    at[0].val.programmaticStreamSerializationAllowed = 1;
    cfg.attrs = at; cfg.numAttrs = pdl ? 1 : 0;
    cudaLaunchKernelEx(&cfg, kern, KArgs(args)...);
}

}

extern "C" void kernel_launch(void* const* d_in, const int* in_sizes, int n_in, void* d_out, int out_size) {
    const __nv_bfloat16* x = (const __nv_bfloat16*)d_in[0];
    const __nv_bfloat16* wqkv = (const __nv_bfloat16*)d_in[1];
    const __nv_bfloat16* wo = (const __nv_bfloat16*)d_in[2];
    const __nv_bfloat16* wgate = (const __nv_bfloat16*)d_in[4];
    const __nv_bfloat16* wup = (const __nv_bfloat16*)d_in[5];
    const __nv_bfloat16* wdown = (const __nv_bfloat16*)d_in[6];
    __nv_bfloat16* out = (__nv_bfloat16*)d_out;

    static CUtensorMap tm_x, tm_wqkv, tm_wo, tm_wg, tm_wu, tm_wd, tm_out;
    static const void* cached[7] = {nullptr, nullptr, nullptr, nullptr, nullptr, nullptr, nullptr};
    if (cached[0] != x || cached[1] != wqkv || cached[2] != wo || cached[3] != wgate || cached[4] != wup || cached[5] != wdown || cached[6] != out) {
        void* fp = nullptr;
        cudaDriverEntryPointQueryResult qr;
        cudaGetDriverEntryPoint("cuTensorMapEncodeTiled", &fp, cudaEnableDefault, &qr);
        EncodeFn fn = (EncodeFn)fp;
        { cuuint64_t d[2] = {512, 2048}, s[1] = {1024}; cuuint32_t b[2] = {64, 128};
          encode(fn, &tm_x, x, 2, d, s, b, CU_TENSOR_MAP_SWIZZLE_128B);
          encode(fn, &tm_out, out, 2, d, s, b, CU_TENSOR_MAP_SWIZZLE_128B); }
        { cuuint64_t d[3] = {64, 512, 24}, s[2] = {3072, 128}; cuuint32_t b[3] = {64, 64, 3};
          encode(fn, &tm_wqkv, wqkv, 3, d, s, b, CU_TENSOR_MAP_SWIZZLE_128B); }
        { cuuint64_t d[2] = {512, 512}, s[1] = {1024}; cuuint32_t b[2] = {64, 64};
          encode(fn, &tm_wo, wo, 2, d, s, b, CU_TENSOR_MAP_SWIZZLE_128B); }
        { cuuint64_t d[2] = {1792, 512}, s[1] = {3584}; cuuint32_t b[2] = {32, 64};
          encode(fn, &tm_wg, wgate, 2, d, s, b, CU_TENSOR_MAP_SWIZZLE_64B);
          encode(fn, &tm_wu, wup, 2, d, s, b, CU_TENSOR_MAP_SWIZZLE_64B); }
        { cuuint64_t d[2] = {512, 1792}, s[1] = {1024}; cuuint32_t b[2] = {64, 64};
          encode(fn, &tm_wd, wdown, 2, d, s, b, CU_TENSOR_MAP_SWIZZLE_128B); }
        cudaFuncSetAttribute(qkv_kernel, cudaFuncAttributeMaxDynamicSharedMemorySize, F_SMEM);
        cudaFuncSetAttribute(qkv_kernel, cudaFuncAttributePreferredSharedMemoryCarveout, 100);
        cudaFuncSetAttribute(attn_kernel, cudaFuncAttributeMaxDynamicSharedMemorySize, F_SMEM);
        cudaFuncSetAttribute(attn_kernel, cudaFuncAttributePreferredSharedMemoryCarveout, 100);
        cudaFuncSetAttribute(tail_kernel, cudaFuncAttributeMaxDynamicSharedMemorySize, F_SMEM);
        cudaFuncSetAttribute(tail_kernel, cudaFuncAttributePreferredSharedMemoryCarveout, 100);
        cached[0] = x; cached[1] = wqkv; cached[2] = wo; cached[3] = wgate; cached[4] = wup; cached[5] = wdown; cached[6] = out;
    }
    launch(qkv_kernel, 128, 384, F_SMEM, false, tm_x, tm_wqkv, x, wqkv);
    launch(attn_kernel, 132, 512, F_SMEM, true, wgate, wup, wo, wdown);
    launch(tail_kernel, 128, 384, F_SMEM, true, tm_wo, tm_wg, tm_wu, tm_wd, tm_out, x);
}
```

```cpp
#include <cuda_runtime.h>
#include <cuda_bf16.h>
#include <cuda.h>
#include <stdint.h>

namespace {

constexpr int S_LEN = 2048, DM = 512, NH = 32, FF = 1792;

__device__ __align__(1024) __nv_bfloat16 g_qkv[3 * NH * S_LEN * 16];
__device__ __align__(1024) __nv_bfloat16 g_ao[S_LEN * DM];
__device__ __align__(1024) __nv_bfloat16 g_h[S_LEN * DM];
__device__ __align__(1024) __nv_bfloat16 g_g[S_LEN * FF];
__device__ __align__(16) float2 g_rowstat1[S_LEN];
__device__ __align__(16) float g_cs1_part[16 * 1536];
__device__ unsigned int g_cnt[32];
__device__ unsigned int g_cnt2[160];
__device__ __align__(16) float g_nrm[3 * NH * 128];
__device__ __align__(16) float2 g_hstat[S_LEN * 8];
__device__ float g_cs2[2 * FF];

__device__ __forceinline__ uint32_t smem_u32(const void* p) { return (uint32_t)__cvta_generic_to_shared(p); }
__device__ __forceinline__ void mbar_init(uint32_t a, int c) { asm volatile("mbarrier.init.shared.b64 [%0], %1;" :: "r"(a), "r"(c)); }
__device__ __forceinline__ void mbar_expect(uint32_t a, int bytes) { asm volatile("mbarrier.arrive.expect_tx.shared.b64 _, [%0], %1;" :: "r"(a), "r"(bytes) : "memory"); }
__device__ __forceinline__ void mbar_arrive(uint32_t a) { asm volatile("mbarrier.arrive.shared.b64 _, [%0];" :: "r"(a) : "memory"); }
__device__ __forceinline__ void mbar_wait(uint32_t a, int parity) {
    uint32_t done;
    int it = 0;
    do {
        asm volatile("{\n.reg .pred p;\nmbarrier.try_wait.parity.shared.b64 p, [%1], %2;\nselp.u32 %0, 1, 0, p;\n}"
                     : "=r"(done) : "r"(a), "r"(parity) : "memory");
        if (++it > (1 << 24)) __trap();
    } while (!done);
}
__device__ __forceinline__ void bulk_g2s(uint32_t dst, const void* src, int bytes, uint32_t bar) {
    asm volatile("cp.async.bulk.shared::cluster.global.mbarrier::complete_tx::bytes [%0], [%1], %2, [%3];"
                 :: "r"(dst), "l"(src), "r"(bytes), "r"(bar) : "memory");
}
__device__ __forceinline__ void tma2d(uint32_t dst, const CUtensorMap* m, int c0, int c1, uint32_t bar) {
    asm volatile("cp.async.bulk.tensor.2d.shared::cluster.global.mbarrier::complete_tx::bytes [%0], [%1, {%3, %4}], [%2];"
                 :: "r"(dst), "l"(m), "r"(bar), "r"(c0), "r"(c1) : "memory");
}
__device__ __forceinline__ void tma3d(uint32_t dst, const CUtensorMap* m, int c0, int c1, int c2, uint32_t bar) {
    asm volatile("cp.async.bulk.tensor.3d.shared::cluster.global.mbarrier::complete_tx::bytes [%0], [%1, {%3, %4, %5}], [%2];"
                 :: "r"(dst), "l"(m), "r"(bar), "r"(c0), "r"(c1), "r"(c2) : "memory");
}
__device__ __forceinline__ void pdl_wait() { asm volatile("griddepcontrol.wait;" ::: "memory"); }
__device__ __forceinline__ void pdl_launch() { asm volatile("griddepcontrol.launch_dependents;" ::: "memory"); }
__device__ __forceinline__ void fence_barrier_init() { asm volatile("fence.mbarrier_init.release.cluster;" ::: "memory"); }
__device__ __forceinline__ void fence_proxy_async() { asm volatile("fence.proxy.async.shared::cta;" ::: "memory"); }
__device__ __forceinline__ uint64_t make_desc(uint32_t saddr, uint32_t lbo, uint32_t sbo, uint32_t swz) {
    return (uint64_t)((saddr & 0x3FFFF) >> 4) | ((uint64_t)((lbo & 0x3FFFF) >> 4) << 16) |
           ((uint64_t)((sbo & 0x3FFFF) >> 4) << 32) | ((uint64_t)swz << 62);
}
#define WG_FENCE() asm volatile("wgmma.fence.sync.aligned;" ::: "memory")
#define WG_COMMIT() asm volatile("wgmma.commit_group.sync.aligned;" ::: "memory")
template <int N> __device__ __forceinline__ void wg_wait() { asm volatile("wgmma.wait_group.sync.aligned %0;" :: "n"(N) : "memory"); }
template <int N> __device__ __forceinline__ void fence_regs(float (&d)[N]) {
#pragma unroll
    for (int i = 0; i < N; i++) asm volatile("" : "+f"(d[i]) :: "memory");
}
__device__ __forceinline__ float ex2f(float x) { float y; asm("ex2.approx.ftz.f32 %0, %1;" : "=f"(y) : "f"(x)); return y; }
__device__ __forceinline__ float tanh_fast(float x) { float y; asm("tanh.approx.f32 %0, %1;" : "=f"(y) : "f"(x)); return y; }
__device__ __forceinline__ uint32_t pack_bf16(float lo, float hi) { uint32_t r; asm("cvt.rn.bf16x2.f32 %0, %1, %2;" : "=r"(r) : "f"(hi), "f"(lo)); return r; }
__device__ __forceinline__ float bf_lo(uint32_t u) { return __uint_as_float(u << 16); }
__device__ __forceinline__ float bf_hi(uint32_t u) { return __uint_as_float(u & 0xFFFF0000u); }
__device__ __forceinline__ uint32_t hfma2(uint32_t a, uint32_t b, uint32_t c) { uint32_t r; asm("fma.rn.f16x2 %0, %1, %2, %3;" : "=r"(r) : "r"(a), "r"(b), "r"(c)); return r; }
__device__ __forceinline__ uint32_t hmul2(uint32_t a, uint32_t b) { uint32_t r; asm("mul.rn.f16x2 %0, %1, %2;" : "=r"(r) : "r"(a), "r"(b)); return r; }
__device__ __forceinline__ unsigned int ld_acquire(const unsigned int* p) { unsigned int v; asm volatile("ld.acquire.gpu.u32 %0, [%1];" : "=r"(v) : "l"(p) : "memory"); return v; }
__device__ __forceinline__ void red_release(unsigned int* p) { asm volatile("red.release.gpu.global.add.u32 [%0], 1;" :: "l"(p) : "memory"); }
__device__ __forceinline__ void stsm4(uint32_t addr, uint32_t a, uint32_t b, uint32_t c, uint32_t d) {
    asm volatile("stmatrix.sync.aligned.m8n8.x4.shared.b16 [%0], {%1,%2,%3,%4};" :: "r"(addr), "r"(a), "r"(b), "r"(c), "r"(d) : "memory");
}
__device__ __forceinline__ void bulk_commit() { asm volatile("cp.async.bulk.commit_group;" ::: "memory"); }
__device__ __forceinline__ void bulk_wait_all() { asm volatile("cp.async.bulk.wait_group 0;" ::: "memory"); }
__device__ __forceinline__ void bar_sync(int id, int n) { asm volatile("bar.sync %0, %1;" :: "r"(id), "r"(n) : "memory"); }
__device__ __forceinline__ void bar_arrive(int id, int n) { asm volatile("bar.arrive %0, %1;" :: "r"(id), "r"(n) : "memory"); }
__device__ __forceinline__ float warp_sum(float v) {
#pragma unroll
    for (int o = 16; o; o >>= 1) v += __shfl_xor_sync(0xffffffffu, v, o);
    return v;
}
__device__ __forceinline__ float warp_max(float v) {
#pragma unroll
    for (int o = 16; o; o >>= 1) v = fmaxf(v, __shfl_xor_sync(0xffffffffu, v, o));
    return v;
}

__device__ __forceinline__ void wgmma_ss_n64(float (&d)[32], uint64_t adesc, uint64_t bdesc, int scale_d) {
    asm volatile("{\n.reg .pred p;\nsetp.ne.b32 p, %34, 0;\n"
      "wgmma.mma_async.sync.aligned.m64n64k16.f32.bf16.bf16 {%0,%1,%2,%3,%4,%5,%6,%7,%8,%9,%10,%11,%12,%13,%14,%15,%16,%17,%18,%19,%20,%21,%22,%23,%24,%25,%26,%27,%28,%29,%30,%31}, %32, %33, p, 1, 1, 0, 1;\n}"
      : "+f"(d[0]), "+f"(d[1]), "+f"(d[2]), "+f"(d[3]), "+f"(d[4]), "+f"(d[5]), "+f"(d[6]), "+f"(d[7]), "+f"(d[8]), "+f"(d[9]), "+f"(d[10]), "+f"(d[11]), "+f"(d[12]), "+f"(d[13]), "+f"(d[14]), "+f"(d[15]), "+f"(d[16]), "+f"(d[17]), "+f"(d[18]), "+f"(d[19]), "+f"(d[20]), "+f"(d[21]), "+f"(d[22]), "+f"(d[23]), "+f"(d[24]), "+f"(d[25]), "+f"(d[26]), "+f"(d[27]), "+f"(d[28]), "+f"(d[29]), "+f"(d[30]), "+f"(d[31])
      : "l"(adesc), "l"(bdesc), "r"(scale_d));
}
__device__ __forceinline__ void wgmma_ss_n128(float (&d)[64], uint64_t adesc, uint64_t bdesc, int scale_d) {
    asm volatile("{\n.reg .pred p;\nsetp.ne.b32 p, %66, 0;\n"
      "wgmma.mma_async.sync.aligned.m64n128k16.f32.bf16.bf16 {%0,%1,%2,%3,%4,%5,%6,%7,%8,%9,%10,%11,%12,%13,%14,%15,%16,%17,%18,%19,%20,%21,%22,%23,%24,%25,%26,%27,%28,%29,%30,%31,%32,%33,%34,%35,%36,%37,%38,%39,%40,%41,%42,%43,%44,%45,%46,%47,%48,%49,%50,%51,%52,%53,%54,%55,%56,%57,%58,%59,%60,%61,%62,%63}, %64, %65, p, 1, 1, 0, 1;\n}"
      : "+f"(d[0]), "+f"(d[1]), "+f"(d[2]), "+f"(d[3]), "+f"(d[4]), "+f"(d[5]), "+f"(d[6]), "+f"(d[7]), "+f"(d[8]), "+f"(d[9]), "+f"(d[10]), "+f"(d[11]), "+f"(d[12]), "+f"(d[13]), "+f"(d[14]), "+f"(d[15]), "+f"(d[16]), "+f"(d[17]), "+f"(d[18]), "+f"(d[19]), "+f"(d[20]), "+f"(d[21]), "+f"(d[22]), "+f"(d[23]), "+f"(d[24]), "+f"(d[25]), "+f"(d[26]), "+f"(d[27]), "+f"(d[28]), "+f"(d[29]), "+f"(d[30]), "+f"(d[31]), "+f"(d[32]), "+f"(d[33]), "+f"(d[34]), "+f"(d[35]), "+f"(d[36]), "+f"(d[37]), "+f"(d[38]), "+f"(d[39]), "+f"(d[40]), "+f"(d[41]), "+f"(d[42]), "+f"(d[43]), "+f"(d[44]), "+f"(d[45]), "+f"(d[46]), "+f"(d[47]), "+f"(d[48]), "+f"(d[49]), "+f"(d[50]), "+f"(d[51]), "+f"(d[52]), "+f"(d[53]), "+f"(d[54]), "+f"(d[55]), "+f"(d[56]), "+f"(d[57]), "+f"(d[58]), "+f"(d[59]), "+f"(d[60]), "+f"(d[61]), "+f"(d[62]), "+f"(d[63])
      : "l"(adesc), "l"(bdesc), "r"(scale_d));
}
__device__ __forceinline__ void wgmma_ss_n192(float (&d)[96], uint64_t adesc, uint64_t bdesc, int scale_d) {
    asm volatile("{\n.reg .pred p;\nsetp.ne.b32 p, %98, 0;\n"
      "wgmma.mma_async.sync.aligned.m64n192k16.f32.bf16.bf16 {%0,%1,%2,%3,%4,%5,%6,%7,%8,%9,%10,%11,%12,%13,%14,%15,%16,%17,%18,%19,%20,%21,%22,%23,%24,%25,%26,%27,%28,%29,%30,%31,%32,%33,%34,%35,%36,%37,%38,%39,%40,%41,%42,%43,%44,%45,%46,%47,%48,%49,%50,%51,%52,%53,%54,%55,%56,%57,%58,%59,%60,%61,%62,%63,%64,%65,%66,%67,%68,%69,%70,%71,%72,%73,%74,%75,%76,%77,%78,%79,%80,%81,%82,%83,%84,%85,%86,%87,%88,%89,%90,%91,%92,%93,%94,%95}, %96, %97, p, 1, 1, 0, 1;\n}"
      : "+f"(d[0]), "+f"(d[1]), "+f"(d[2]), "+f"(d[3]), "+f"(d[4]), "+f"(d[5]), "+f"(d[6]), "+f"(d[7]), "+f"(d[8]), "+f"(d[9]), "+f"(d[10]), "+f"(d[11]), "+f"(d[12]), "+f"(d[13]), "+f"(d[14]), "+f"(d[15]), "+f"(d[16]), "+f"(d[17]), "+f"(d[18]), "+f"(d[19]), "+f"(d[20]), "+f"(d[21]), "+f"(d[22]), "+f"(d[23]), "+f"(d[24]), "+f"(d[25]), "+f"(d[26]), "+f"(d[27]), "+f"(d[28]), "+f"(d[29]), "+f"(d[30]), "+f"(d[31]), "+f"(d[32]), "+f"(d[33]), "+f"(d[34]), "+f"(d[35]), "+f"(d[36]), "+f"(d[37]), "+f"(d[38]), "+f"(d[39]), "+f"(d[40]), "+f"(d[41]), "+f"(d[42]), "+f"(d[43]), "+f"(d[44]), "+f"(d[45]), "+f"(d[46]), "+f"(d[47]), "+f"(d[48]), "+f"(d[49]), "+f"(d[50]), "+f"(d[51]), "+f"(d[52]), "+f"(d[53]), "+f"(d[54]), "+f"(d[55]), "+f"(d[56]), "+f"(d[57]), "+f"(d[58]), "+f"(d[59]), "+f"(d[60]), "+f"(d[61]), "+f"(d[62]), "+f"(d[63]), "+f"(d[64]), "+f"(d[65]), "+f"(d[66]), "+f"(d[67]), "+f"(d[68]), "+f"(d[69]), "+f"(d[70]), "+f"(d[71]), "+f"(d[72]), "+f"(d[73]), "+f"(d[74]), "+f"(d[75]), "+f"(d[76]), "+f"(d[77]), "+f"(d[78]), "+f"(d[79]), "+f"(d[80]), "+f"(d[81]), "+f"(d[82]), "+f"(d[83]), "+f"(d[84]), "+f"(d[85]), "+f"(d[86]), "+f"(d[87]), "+f"(d[88]), "+f"(d[89]), "+f"(d[90]), "+f"(d[91]), "+f"(d[92]), "+f"(d[93]), "+f"(d[94]), "+f"(d[95])
      : "l"(adesc), "l"(bdesc), "r"(scale_d));
}
__device__ __forceinline__ void wgmma_ss_n256(float (&d)[128], uint64_t adesc, uint64_t bdesc, int scale_d) {
    asm volatile("{\n.reg .pred p;\nsetp.ne.b32 p, %130, 0;\n"
      "wgmma.mma_async.sync.aligned.m64n256k16.f32.bf16.bf16 {%0,%1,%2,%3,%4,%5,%6,%7,%8,%9,%10,%11,%12,%13,%14,%15,%16,%17,%18,%19,%20,%21,%22,%23,%24,%25,%26,%27,%28,%29,%30,%31,%32,%33,%34,%35,%36,%37,%38,%39,%40,%41,%42,%43,%44,%45,%46,%47,%48,%49,%50,%51,%52,%53,%54,%55,%56,%57,%58,%59,%60,%61,%62,%63,%64,%65,%66,%67,%68,%69,%70,%71,%72,%73,%74,%75,%76,%77,%78,%79,%80,%81,%82,%83,%84,%85,%86,%87,%88,%89,%90,%91,%92,%93,%94,%95,%96,%97,%98,%99,%100,%101,%102,%103,%104,%105,%106,%107,%108,%109,%110,%111,%112,%113,%114,%115,%116,%117,%118,%119,%120,%121,%122,%123,%124,%125,%126,%127}, %128, %129, p, 1, 1, 0, 1;\n}"
      : "+f"(d[0]), "+f"(d[1]), "+f"(d[2]), "+f"(d[3]), "+f"(d[4]), "+f"(d[5]), "+f"(d[6]), "+f"(d[7]), "+f"(d[8]), "+f"(d[9]), "+f"(d[10]), "+f"(d[11]), "+f"(d[12]), "+f"(d[13]), "+f"(d[14]), "+f"(d[15]), "+f"(d[16]), "+f"(d[17]), "+f"(d[18]), "+f"(d[19]), "+f"(d[20]), "+f"(d[21]), "+f"(d[22]), "+f"(d[23]), "+f"(d[24]), "+f"(d[25]), "+f"(d[26]), "+f"(d[27]), "+f"(d[28]), "+f"(d[29]), "+f"(d[30]), "+f"(d[31]), "+f"(d[32]), "+f"(d[33]), "+f"(d[34]), "+f"(d[35]), "+f"(d[36]), "+f"(d[37]), "+f"(d[38]), "+f"(d[39]), "+f"(d[40]), "+f"(d[41]), "+f"(d[42]), "+f"(d[43]), "+f"(d[44]), "+f"(d[45]), "+f"(d[46]), "+f"(d[47]), "+f"(d[48]), "+f"(d[49]), "+f"(d[50]), "+f"(d[51]), "+f"(d[52]), "+f"(d[53]), "+f"(d[54]), "+f"(d[55]), "+f"(d[56]), "+f"(d[57]), "+f"(d[58]), "+f"(d[59]), "+f"(d[60]), "+f"(d[61]), "+f"(d[62]), "+f"(d[63]), "+f"(d[64]), "+f"(d[65]), "+f"(d[66]), "+f"(d[67]), "+f"(d[68]), "+f"(d[69]), "+f"(d[70]), "+f"(d[71]), "+f"(d[72]), "+f"(d[73]), "+f"(d[74]), "+f"(d[75]), "+f"(d[76]), "+f"(d[77]), "+f"(d[78]), "+f"(d[79]), "+f"(d[80]), "+f"(d[81]), "+f"(d[82]), "+f"(d[83]), "+f"(d[84]), "+f"(d[85]), "+f"(d[86]), "+f"(d[87]), "+f"(d[88]), "+f"(d[89]), "+f"(d[90]), "+f"(d[91]), "+f"(d[92]), "+f"(d[93]), "+f"(d[94]), "+f"(d[95]), "+f"(d[96]), "+f"(d[97]), "+f"(d[98]), "+f"(d[99]), "+f"(d[100]), "+f"(d[101]), "+f"(d[102]), "+f"(d[103]), "+f"(d[104]), "+f"(d[105]), "+f"(d[106]), "+f"(d[107]), "+f"(d[108]), "+f"(d[109]), "+f"(d[110]), "+f"(d[111]), "+f"(d[112]), "+f"(d[113]), "+f"(d[114]), "+f"(d[115]), "+f"(d[116]), "+f"(d[117]), "+f"(d[118]), "+f"(d[119]), "+f"(d[120]), "+f"(d[121]), "+f"(d[122]), "+f"(d[123]), "+f"(d[124]), "+f"(d[125]), "+f"(d[126]), "+f"(d[127])
      : "l"(adesc), "l"(bdesc), "r"(scale_d));
}
__device__ __forceinline__ void qk_wgmma_n64(float (&d)[32], const uint32_t (&a)[4], uint64_t desc) {
    asm volatile("wgmma.mma_async.sync.aligned.m64n64k16.f32.bf16.bf16 {%0,%1,%2,%3,%4,%5,%6,%7,%8,%9,%10,%11,%12,%13,%14,%15,%16,%17,%18,%19,%20,%21,%22,%23,%24,%25,%26,%27,%28,%29,%30,%31}, {%32,%33,%34,%35}, %36, 0, 1, 1, 0;"
      : "=f"(d[0]), "=f"(d[1]), "=f"(d[2]), "=f"(d[3]), "=f"(d[4]), "=f"(d[5]), "=f"(d[6]), "=f"(d[7]), "=f"(d[8]), "=f"(d[9]), "=f"(d[10]), "=f"(d[11]), "=f"(d[12]), "=f"(d[13]), "=f"(d[14]), "=f"(d[15]), "=f"(d[16]), "=f"(d[17]), "=f"(d[18]), "=f"(d[19]), "=f"(d[20]), "=f"(d[21]), "=f"(d[22]), "=f"(d[23]), "=f"(d[24]), "=f"(d[25]), "=f"(d[26]), "=f"(d[27]), "=f"(d[28]), "=f"(d[29]), "=f"(d[30]), "=f"(d[31])
      : "r"(a[0]), "r"(a[1]), "r"(a[2]), "r"(a[3]), "l"(desc));
}

__device__ __forceinline__ void pv_wgmma(float (&d)[12], uint32_t a0, uint32_t a1, uint32_t a2, uint32_t a3, uint64_t desc) {
    asm volatile("wgmma.mma_async.sync.aligned.m64n24k16.f32.bf16.bf16 {%0,%1,%2,%3,%4,%5,%6,%7,%8,%9,%10,%11}, {%12,%13,%14,%15}, %16, 1, 1, 1, 1;"
      : "+f"(d[0]), "+f"(d[1]), "+f"(d[2]), "+f"(d[3]), "+f"(d[4]), "+f"(d[5]), "+f"(d[6]), "+f"(d[7]), "+f"(d[8]), "+f"(d[9]), "+f"(d[10]), "+f"(d[11])
      : "r"(a0), "r"(a1), "r"(a2), "r"(a3), "l"(desc));
}

__device__ __forceinline__ uint32_t mapa(uint32_t a, uint32_t rank) { uint32_t r; asm("mapa.shared::cluster.u32 %0, %1, %2;" : "=r"(r) : "r"(a), "r"(rank)); return r; }
__device__ __forceinline__ void mbar_arrive_remote(uint32_t a) { asm volatile("mbarrier.arrive.relaxed.cluster.shared::cluster.b64 _, [%0];" :: "r"(a) : "memory"); }
__device__ __forceinline__ void mbar_wait_cluster(uint32_t a, int parity) {
    uint32_t done;
    int it = 0;
    do {
        asm volatile("{\n.reg .pred p;\nmbarrier.try_wait.parity.acquire.cluster.shared::cta.b64 p, [%1], %2;\nselp.u32 %0, 1, 0, p;\n}"
                     : "=r"(done) : "r"(a), "r"(parity) : "memory");
        if (++it > (1 << 24)) __trap();
    } while (!done);
}
__device__ __forceinline__ void tma2d_mc(uint32_t dst, const CUtensorMap* m, int c0, int c1, uint32_t bar) {
    asm volatile("cp.async.bulk.tensor.2d.shared::cluster.global.mbarrier::complete_tx::bytes.multicast::cluster [%0], [%1, {%3, %4}], [%2], %5;"
                 :: "r"(dst), "l"(m), "r"(bar), "r"(c0), "r"(c1), "h"((uint16_t)3) : "memory");
}
__device__ __forceinline__ void bulk_g2s_mc(uint32_t dst, const void* src, int bytes, uint32_t bar) {
    asm volatile("cp.async.bulk.shared::cluster.global.mbarrier::complete_tx::bytes.multicast::cluster [%0], [%1], %2, [%3], %4;"
                 :: "r"(dst), "l"(src), "r"(bytes), "r"(bar), "h"((uint16_t)3) : "memory");
}
__device__ __forceinline__ void tile_of(int bid, int& mb, int& nt) {
    int grp = bid >> 4, in = bid & 15;
    mb = (grp >> 1) * 4 + (in >> 2);
    nt = (grp & 1) * 4 + (in & 3);
}

constexpr int K1_STAGES = 5, K1_STAGE = 16384 + 24576;
constexpr int K1_BAR = K1_STAGES * K1_STAGE, K1_RS = K1_BAR + 128, K1_CS = K1_RS + 1024, K1_SMEM = K1_CS + 768;

__device__ __forceinline__ float2 row_stats_regs(uint4 a, uint4 b) {
    float v[16];
    v[0] = bf_lo(a.x); v[1] = bf_hi(a.x); v[2] = bf_lo(a.y); v[3] = bf_hi(a.y);
    v[4] = bf_lo(a.z); v[5] = bf_hi(a.z); v[6] = bf_lo(a.w); v[7] = bf_hi(a.w);
    v[8] = bf_lo(b.x); v[9] = bf_hi(b.x); v[10] = bf_lo(b.y); v[11] = bf_hi(b.y);
    v[12] = bf_lo(b.z); v[13] = bf_hi(b.z); v[14] = bf_lo(b.w); v[15] = bf_hi(b.w);
    float s = 0.f;
#pragma unroll
    for (int i = 0; i < 16; i++) s += v[i];
    float mean = warp_sum(s) * (1.0f / DM);
    float q = 0.f;
#pragma unroll
    for (int i = 0; i < 16; i++) { float d = v[i] - mean; q = fmaf(d, d, q); }
    float var = warp_sum(q) * (1.0f / DM);
    float rstd = rsqrtf(var + 1e-5f);
    return make_float2(rstd, -mean * rstd);
}
__device__ __forceinline__ float2 row_stats_x(const __nv_bfloat16* x, int row, int lane) {
    const uint4* p = (const uint4*)(x + (size_t)row * DM);
    return row_stats_regs(__ldg(p + lane), __ldg(p + 32 + lane));
}
__device__ __forceinline__ void colsum8(const __nv_bfloat16* w, int ld, int col, int k0, int nk, float (&s)[8]) {
#pragma unroll
    for (int i = 0; i < 8; i++) s[i] = 0.f;
    for (int k = k0; k < k0 + nk; k += 8) {
        uint4 u[8];
#pragma unroll
        for (int i = 0; i < 8; i++) u[i] = __ldg((const uint4*)(w + (size_t)(k + i) * ld + col));
#pragma unroll
        for (int i = 0; i < 8; i++) {
            s[0] += bf_lo(u[i].x); s[1] += bf_hi(u[i].x); s[2] += bf_lo(u[i].y); s[3] += bf_hi(u[i].y);
            s[4] += bf_lo(u[i].z); s[5] += bf_hi(u[i].z); s[6] += bf_lo(u[i].w); s[7] += bf_hi(u[i].w);
        }
    }
}
__device__ __forceinline__ bool wait_count(const unsigned int* p, unsigned int target, int lane) {
    int ok = 1;
    if (lane == 0) {
        int it = 0;
        while (ld_acquire(p) < target) { if (++it > (1 << 18)) { ok = 0; break; } }
    }
    ok = __shfl_sync(0xffffffffu, ok, 0);
    return ok != 0;
}

__global__ void __launch_bounds__(384, 1)
qkv_kernel(const __grid_constant__ CUtensorMap tm_x, const __grid_constant__ CUtensorMap tm_w,
           const __nv_bfloat16* __restrict__ x, const __nv_bfloat16* __restrict__ wqkv) {
    extern __shared__ __align__(1024) unsigned char smem[];
    const uint32_t sb = smem_u32(smem);
    const int tid = threadIdx.x, warp = __shfl_sync(0xffffffffu, tid >> 5, 0), lane = tid & 31;
    int mb, nt;
    tile_of(blockIdx.x, mb, nt);
    const uint32_t full = sb + K1_BAR, empty = full + 40, auxb = full + 80;
    if (tid == 0) {
#pragma unroll
        for (int i = 0; i < K1_STAGES; i++) { mbar_init(full + 8 * i, 1); mbar_init(empty + 8 * i, 8); }
        mbar_init(auxb, 3);
        fence_barrier_init();
        for (int kb = 0; kb < K1_STAGES; kb++) {
            mbar_expect(full + 8 * kb, K1_STAGE);
            tma2d(sb + kb * K1_STAGE, &tm_x, kb * 64, mb * 128, full + 8 * kb);
            tma3d(sb + kb * K1_STAGE + 16384, &tm_w, 0, kb * 64, nt * 3, full + 8 * kb);
        }
    }
    __syncthreads();
    pdl_launch();
    if (warp == 0) {
        if (blockIdx.x == 0) g_cnt2[lane] = 0;
        if (lane == 0) {
            g_cnt2[32 + blockIdx.x] = 0;
            for (int kb = K1_STAGES; kb < 8; kb++) {
                int s = kb % K1_STAGES;
                mbar_wait(empty + 8 * s, 0);
                mbar_expect(full + 8 * s, K1_STAGE);
                tma2d(sb + s * K1_STAGE, &tm_x, kb * 64, mb * 128, full + 8 * s);
                tma3d(sb + s * K1_STAGE + 16384, &tm_w, 0, kb * 64, nt * 3, full + 8 * s);
            }
        }
    } else if (warp < 4) {
        float2* s_rs = (float2*)(smem + K1_RS);
        float* s_cs = (float*)(smem + K1_CS);
        if (warp < 3) {
            const int r0 = mb * 128 + nt * 16 + (warp - 1) * 8;
            uint4 u[16];
#pragma unroll
            for (int i = 0; i < 8; i++) {
                const uint4* p = (const uint4*)(x + (size_t)(r0 + i) * DM);
                u[2 * i] = __ldg(p + lane); u[2 * i + 1] = __ldg(p + 32 + lane);
            }
            float2 mine = make_float2(0.f, 0.f);
#pragma unroll
            for (int i = 0; i < 8; i++) {
                float2 st = row_stats_regs(u[2 * i], u[2 * i + 1]);
                if (lane == i) mine = st;
            }
            if (lane < 8) g_rowstat1[r0 + lane] = mine;
            __syncwarp();
            if (lane == 0) red_release(&g_cnt[mb]);
        } else {
            uint4 u[24];
#pragma unroll
            for (int c = 0; c < 3; c++)
#pragma unroll
                for (int i = 0; i < 8; i++)
                    u[c * 8 + i] = __ldg((const uint4*)(wqkv + (size_t)(mb * 32 + (lane >> 3) * 8 + i) * 1536 + nt * 192 + (c * 8 + (lane & 7)) * 8));
#pragma unroll
            for (int c = 0; c < 3; c++) {
                float cs[8];
#pragma unroll
                for (int i = 0; i < 8; i++) cs[i] = 0.f;
#pragma unroll
                for (int i = 0; i < 8; i++) {
                    const uint4 w = u[c * 8 + i];
                    cs[0] += bf_lo(w.x); cs[1] += bf_hi(w.x); cs[2] += bf_lo(w.y); cs[3] += bf_hi(w.y);
                    cs[4] += bf_lo(w.z); cs[5] += bf_hi(w.z); cs[6] += bf_lo(w.w); cs[7] += bf_hi(w.w);
                }
#pragma unroll
                for (int i = 0; i < 8; i++) {
                    cs[i] += __shfl_xor_sync(0xffffffffu, cs[i], 8);
                    cs[i] += __shfl_xor_sync(0xffffffffu, cs[i], 16);
                }
                if (lane < 8) {
                    float4* d = (float4*)(g_cs1_part + mb * 1536 + nt * 192 + (c * 8 + lane) * 8);
                    d[0] = make_float4(cs[0], cs[1], cs[2], cs[3]);
                    d[1] = make_float4(cs[4], cs[5], cs[6], cs[7]);
                }
            }
            __syncwarp();
            if (lane == 0) red_release(&g_cnt[16 + nt]);
        }
        if (warp == 1) {
            if (wait_count(&g_cnt[mb], 16, lane)) {
#pragma unroll
                for (int i = 0; i < 4; i++) s_rs[lane + 32 * i] = __ldcg(&g_rowstat1[mb * 128 + lane + 32 * i]);
            } else {
                for (int i = 0; i < 128; i++) {
                    float2 st = row_stats_x(x, mb * 128 + i, lane);
                    if (lane == 0) s_rs[i] = st;
                }
            }
        } else {
            int c0 = (warp - 2) * 96;
            if (wait_count(&g_cnt[16 + nt], 16, lane)) {
#pragma unroll
                for (int i = 0; i < 3; i++) {
                    float s = 0.f;
#pragma unroll
                    for (int p = 0; p < 16; p++) s += __ldcg(&g_cs1_part[p * 1536 + nt * 192 + c0 + lane + 32 * i]);
                    s_cs[c0 + lane + 32 * i] = s;
                }
            } else if (lane < 12) {
                float s[8];
                colsum8(wqkv, 1536, nt * 192 + c0 + lane * 8, 0, 512, s);
#pragma unroll
                for (int i = 0; i < 8; i++) s_cs[c0 + lane * 8 + i] = s[i];
            }
        }
        __syncwarp();
        if (lane == 0) mbar_arrive(auxb);
        bar_sync(2, 256 + 96);
        const int a = tid - 32;
        {
            const int hh = a >> 3, w = a & 7;
            const float4* p = (const float4*)(smem + 49152) + (hh * 256 + w * 32) / 2;
            float m = 0.f;
#pragma unroll
            for (int i = 0; i < 8; i++) {
                const int ii = (i + a) & 7;
                float4 u = p[2 * ii], v = p[2 * ii + 1];
                float n0 = u.x + u.z + v.x + v.z, n1 = u.y + u.w + v.y + v.w;
                if (!(n0 <= 3.0e38f) || !(n1 <= 3.0e38f)) m = __int_as_float(0x7f800000);
                m = fmaxf(m, fmaxf(n0, n1));
            }
            const int col0 = nt * 192 + hh * 16;
            g_nrm[((col0 >> 9) * NH + ((col0 & 511) >> 4)) * 128 + mb * 8 + w] = m;
        }
    } else {
        const int wgi = (warp >> 2) - 1, ww = warp & 3;
        float acc[96];
#pragma unroll 1
        for (int kb = 0; kb < 8; kb++) {
            int s = kb % K1_STAGES;
            mbar_wait(full + 8 * s, (kb / K1_STAGES) & 1);
            uint64_t ad = make_desc(sb + s * K1_STAGE + wgi * 8192, 16, 1024, 1);
            uint64_t bd = make_desc(sb + s * K1_STAGE + 16384, 8192, 1024, 1);
            WG_FENCE();
#pragma unroll
            for (int k = 0; k < 4; k++) wgmma_ss_n192(acc, ad + k * 2, bd + k * 128, (kb | k) != 0);
            WG_COMMIT();
            if (kb > 0) {
                wg_wait<1>();
                if (lane == 0) mbar_arrive(empty + 8 * ((kb - 1) % K1_STAGES));
            }
        }
        wg_wait<0>();
        fence_regs(acc);
        mbar_wait(auxb, 0);
        bar_sync(1, 256);
        const float2* s_rs = (const float2*)(smem + K1_RS);
        const float* s_cs = (const float*)(smem + K1_CS);
        const int g = lane >> 2, t = lane & 3;
        const int rl = wgi * 64 + ww * 16 + g;
        const float2 st0 = s_rs[rl], st1 = s_rs[rl + 8];
        const float QS = 0.25f * 1.4426950408889634f;
        float2* s_np = (float2*)(smem + 49152) + (warp - 4) * 32 + lane;
#pragma unroll
        for (int hh = 0; hh < 12; hh++) {
            const int which = (nt * 192 + hh * 16) >> 9;
            const float sc = (which == 0) ? QS : 1.0f;
            const float a0 = st0.x * sc, b0 = st0.y * sc, a1 = st1.x * sc, b1 = st1.y * sc;
            const float2 c0 = *(const float2*)(s_cs + 16 * hh + 2 * t), c1 = *(const float2*)(s_cs + 16 * hh + 8 + 2 * t);
            const float* a = acc + 8 * hh;
            float v0 = fmaf(a0, a[0], b0 * c0.x), v1 = fmaf(a0, a[1], b0 * c0.y), v2 = fmaf(a1, a[2], b1 * c0.x), v3 = fmaf(a1, a[3], b1 * c0.y);
            float v4 = fmaf(a0, a[4], b0 * c1.x), v5 = fmaf(a0, a[5], b0 * c1.y), v6 = fmaf(a1, a[6], b1 * c1.x), v7 = fmaf(a1, a[7], b1 * c1.y);
            {
                const int head = ((nt * 192 + hh * 16) & 511) >> 4;
                uint32_t* o = (uint32_t*)g_qkv + ((size_t)((which * NH + head) * 2) * 256 + mb * 16 + wgi * 8 + ww * 2) * 32 + lane;
                o[0] = pack_bf16(v0, v1); o[32] = pack_bf16(v2, v3); o[8192] = pack_bf16(v4, v5); o[8192 + 32] = pack_bf16(v6, v7);
            }
            s_np[hh * 256] = make_float2(fmaf(v0, v0, fmaf(v1, v1, fmaf(v4, v4, v5 * v5))), fmaf(v2, v2, fmaf(v3, v3, fmaf(v6, v6, v7 * v7))));
        }
        bar_arrive(2, 256 + 96);
    }
}

constexpr int AT_K = 0, AT_V = 65536, AT_ONES = 131072, AT_BAR = 163840, AT_SMEM = AT_BAR + 128;
constexpr uint32_t POLY_MASK = 0x7B5A;

__device__ __forceinline__ uint32_t exp2_pair_poly(float x0, float x1) {
    uint32_t t0 = __float_as_uint(x0 + 32895.0f);
    uint32_t t1 = __float_as_uint(x1 + 32895.0f);
    uint32_t gd = __byte_perm(t0, t1, 0x6420);
    uint32_t wm = __byte_perm(t0, t1, 0x5612);
    uint32_t v = hfma2(gd, 0x712d712du, 0x355c355cu);
    uint32_t z = hmul2(v, gd);
    return (wm >> 1) + z;
}
__device__ __forceinline__ uint32_t exp2_pair_mufu(float x0, float x1) { return pack_bf16(ex2f(x0), ex2f(x1)); }
template <uint32_t MASK>
__device__ __forceinline__ void exp_blocks(const float (&s)[32], uint32_t (&p)[16]) {
#pragma unroll
    for (int b = 0; b < 8; b++) {
        if ((MASK >> b) & 1) {
            p[2 * b] = exp2_pair_poly(s[4 * b], s[4 * b + 1]);
            p[2 * b + 1] = exp2_pair_poly(s[4 * b + 2], s[4 * b + 3]);
        } else {
            p[2 * b] = exp2_pair_mufu(s[4 * b], s[4 * b + 1]);
            p[2 * b + 1] = exp2_pair_mufu(s[4 * b + 2], s[4 * b + 3]);
        }
    }
}
#define PV4(P) _Pragma("unroll") for (int i = 0; i < 4; i++) { pv_wgmma(o, P[4 * i], P[4 * i + 1], P[4 * i + 2], P[4 * i + 3], vd); vd += 16; }

__device__ __forceinline__ void attn_store(float (&o)[12], int row0, int head, int lane) {
    float l0 = __shfl_sync(0xffffffffu, o[8], lane & 28);
    float l1 = __shfl_sync(0xffffffffu, o[10], lane & 28);
    float r0 = 1.0f / l0, r1 = 1.0f / l1;
    uint32_t* op = (uint32_t*)g_ao;
    int mb = row0 >> 7, rg = (row0 & 127) >> 3;
    int kb = head >> 2, kc = (head & 3) * 2;
    size_t base = (((size_t)(mb * 8 + kb) * 8 + kc) * 16 + rg) * 32 + lane;
    op[base] = pack_bf16(o[0] * r0, o[1] * r0);
    op[base + 32] = pack_bf16(o[2] * r1, o[3] * r1);
    op[base + 16 * 32] = pack_bf16(o[4] * r0, o[5] * r0);
    op[base + 16 * 32 + 32] = pack_bf16(o[6] * r1, o[7] * r1);
}

__device__ __forceinline__ void attn_load_q(uint32_t (&q)[4], const __nv_bfloat16* gq, int row0, int lane) {
    const uint32_t* qp = (const uint32_t*)gq;
    int j0 = row0 >> 3;
    q[0] = __ldcg(qp + (0 * 256 + j0) * 32 + lane);
    q[1] = __ldcg(qp + (0 * 256 + j0 + 1) * 32 + lane);
    q[2] = __ldcg(qp + (1 * 256 + j0) * 32 + lane);
    q[3] = __ldcg(qp + (1 * 256 + j0 + 1) * 32 + lane);
}

__device__ __forceinline__ void attn_tile_safe(const uint32_t (&q)[4], uint64_t kd, uint64_t vd, int row0, int head, int lane) {
    float o[12];
#pragma unroll
    for (int i = 0; i < 12; i++) o[i] = 0.f;
    float m0 = -INFINITY, m1 = -INFINITY;
    fence_regs(o);
#pragma unroll 1
    for (int j = 0; j < 32; j++) {
        float s[32];
        uint32_t p[16];
        WG_FENCE();
        qk_wgmma_n64(s, q, kd); kd += 64;
        WG_COMMIT();
        wg_wait<0>();
        fence_regs(s);
        fence_regs(o);
        float x0 = m0, x1 = m1;
#pragma unroll
        for (int b = 0; b < 8; b++) {
            x0 = fmaxf(x0, fmaxf(s[4 * b], s[4 * b + 1]));
            x1 = fmaxf(x1, fmaxf(s[4 * b + 2], s[4 * b + 3]));
        }
        x0 = fmaxf(x0, __shfl_xor_sync(0xffffffffu, x0, 1)); x0 = fmaxf(x0, __shfl_xor_sync(0xffffffffu, x0, 2));
        x1 = fmaxf(x1, __shfl_xor_sync(0xffffffffu, x1, 1)); x1 = fmaxf(x1, __shfl_xor_sync(0xffffffffu, x1, 2));
        float al0 = ex2f(m0 - x0), al1 = ex2f(m1 - x1);
        m0 = x0; m1 = x1;
#pragma unroll
        for (int i = 0; i < 3; i++) { o[4 * i] *= al0; o[4 * i + 1] *= al0; o[4 * i + 2] *= al1; o[4 * i + 3] *= al1; }
#pragma unroll
        for (int b = 0; b < 8; b++) {
            p[2 * b] = exp2_pair_mufu(s[4 * b] - m0, s[4 * b + 1] - m0);
            p[2 * b + 1] = exp2_pair_mufu(s[4 * b + 2] - m1, s[4 * b + 3] - m1);
        }
        fence_regs(o);
        WG_FENCE();
        PV4(p);
        WG_COMMIT();
        wg_wait<0>();
        fence_regs(o);
    }
    attn_store(o, row0, head, lane);
}

__global__ void __launch_bounds__(512, 1)
attn_kernel(const __nv_bfloat16* __restrict__ wg_, const __nv_bfloat16* __restrict__ wu_,
            const __nv_bfloat16* __restrict__ wo_, const __nv_bfloat16* __restrict__ wd_) {
    extern __shared__ __align__(1024) unsigned char smem[];
    const uint32_t sb = smem_u32(smem);
    const int tid = threadIdx.x, wg = tid >> 7, warp = (tid >> 5) & 3, lane = tid & 31;
    pdl_launch();
    if (blockIdx.x >= 128) {
        const int e = blockIdx.x - 128;
        const __nv_bfloat16* w = (e < 2) ? wg_ : wu_;
        float* red = (float*)smem;
        const int cgrp = tid & 127, kq = tid >> 7;
        if (cgrp < 112) {
            float s[8];
            colsum8(w, FF, (e & 1) * 896 + cgrp * 8, kq * 128, 128, s);
#pragma unroll
            for (int i = 0; i < 8; i++) red[kq * 896 + cgrp * 8 + i] = s[i];
        }
        __syncthreads();
        for (int c = tid; c < 896; c += 512)
            g_cs2[(e >> 1) * FF + (e & 1) * 896 + c] = red[c] + red[896 + c] + red[1792 + c] + red[2688 + c];
        if (tid < 32) {
            const char* p0 = (const char*)wo_ + e * (DM * DM * 2 / 4);
            for (int i = lane; i < 32; i += 32)
                asm volatile("cp.async.bulk.prefetch.L2.global [%0], %1;" :: "l"(p0 + i * 4096), "r"(4096) : "memory");
            const char* p1 = (const char*)wd_ + e * (FF * DM * 2 / 4);
            for (int i = lane; i < 112; i += 32)
                asm volatile("cp.async.bulk.prefetch.L2.global [%0], %1;" :: "l"(p1 + i * 4096), "r"(4096) : "memory");
        }
        return;
    }
    const int head = blockIdx.x >> 2, qq = blockIdx.x & 3;
    const __nv_bfloat16* gq = g_qkv + (size_t)head * (S_LEN * 16);
    const __nv_bfloat16* gk = g_qkv + (size_t)(NH + head) * (S_LEN * 16);
    const __nv_bfloat16* gv = g_qkv + (size_t)(2 * NH + head) * (S_LEN * 16);
    if (tid == 0) {
        for (int i = 0; i < 8; i++) mbar_init(sb + AT_BAR + 8 * i, 1);
        fence_barrier_init();
    }
    {
        uint4 one = make_uint4(0x00003F80u, 0, 0, 0);
#pragma unroll
        for (int i = 0; i < 4; i++) *(uint4*)(smem + AT_ONES + (i * 512 + tid) * 16) = one;
        fence_proxy_async();
    }
    __syncthreads();
    pdl_wait();
    auto load_kv = [&](int i) {
        uint32_t bar = sb + AT_BAR + 8 * i;
        mbar_expect(bar, 16384);
        bulk_g2s(sb + AT_K + i * 4096, gk + i * 2048, 4096, bar);
        bulk_g2s(sb + AT_K + 32768 + i * 4096, gk + 16384 + i * 2048, 4096, bar);
        bulk_g2s(sb + AT_V + i * 4096, gv + i * 2048, 4096, bar);
        bulk_g2s(sb + AT_V + 32768 + i * 4096, gv + 16384 + i * 2048, 4096, bar);
    };
    if (tid == 0) { load_kv(0); load_kv(1); }
    uint32_t q[4], q2[4];
    attn_load_q(q, gq, qq * 512 + wg * 64 + warp * 16, lane);
    attn_load_q(q2, gq, qq * 512 + (4 + wg) * 64 + warp * 16, lane);
    bool fast;
    {
        const float* nq = g_nrm + (0 * NH + head) * 128 + qq * 32;
        const float* nk = g_nrm + (1 * NH + head) * 128;
        const float* nv = g_nrm + (2 * NH + head) * 128;
        float4 k4 = __ldcg((const float4*)nk + lane), v4 = __ldcg((const float4*)nv + lane);
        float qm = warp_max(__ldcg(nq + lane));
        float km = warp_max(fmaxf(fmaxf(k4.x, k4.y), fmaxf(k4.z, k4.w)));
        float vm = warp_max(fmaxf(fmaxf(v4.x, v4.y), fmaxf(v4.z, v4.w)));
        fast = __all_sync(0xffffffffu, (qm * km <= 3500.0f) && (vm <= 1.0e24f));
    }
    const uint64_t kdesc0 = make_desc(sb + AT_K, 32768, 128, 0);
    const uint64_t vdesc0 = make_desc(sb + AT_V, 128, 32768, 0);
    if (!fast) {
        if (tid == 0) for (int i = 2; i < 8; i++) load_kv(i);
        for (int i = 0; i < 8; i++) mbar_wait(sb + AT_BAR + 8 * i, 0);
#pragma unroll 1
        for (int tile = 0; tile < 2; tile++) {
            const int row0 = qq * 512 + (tile * 4 + wg) * 64 + warp * 16;
            attn_tile_safe(q, kdesc0, vdesc0, row0, head, lane);
#pragma unroll
            for (int i = 0; i < 4; i++) q[i] = q2[i];
        }
        return;
    }
#pragma unroll 1
    for (int tile = 0; tile < 2; tile++) {
        const int row0 = qq * 512 + (tile * 4 + wg) * 64 + warp * 16;
        float o[12];
#pragma unroll
        for (int i = 0; i < 12; i++) o[i] = 0.f;
        fence_regs(o);
        float sa[32];
        uint32_t pa[16];
        uint64_t kd = kdesc0, vd = vdesc0;
        if (tile == 0) { mbar_wait(sb + AT_BAR, 0); }
        WG_FENCE();
        qk_wgmma_n64(sa, q, kd); kd += 64;
        WG_COMMIT();
#pragma unroll 1
        for (int jj = 0; jj < 8; jj++) {
            if (tile == 0 && jj < 7) {
                if (tid == 0 && jj < 6) load_kv(jj + 2);
                mbar_wait(sb + AT_BAR + 8 * (jj + 1), 0);
            }
#pragma unroll
            for (int j = 0; j < 4; j++) {
                wg_wait<0>();
                fence_regs(sa);
                if (j & 1) exp_blocks<(POLY_MASK >> 8)>(sa, pa); else exp_blocks<(POLY_MASK & 255)>(sa, pa);
                WG_FENCE();
                PV4(pa);
                qk_wgmma_n64(sa, q, kd); kd += 64;
                WG_COMMIT();
            }
        }
        wg_wait<0>();
        fence_regs(o);
        fence_regs(sa);
        attn_store(o, row0, head, lane);
#pragma unroll
        for (int i = 0; i < 4; i++) q[i] = q2[i];
    }
}

constexpr int F_R2 = 131072, F_X = 196608, F_BAR = 229376;
constexpr int F_RS = F_BAR + 256, F_CS = F_RS + 1024, F_SMEM = F_CS + 1792;
enum { B_FA = 0, B_HF = 4, B_BF = 8, B_BE = 11, B_CF = 14, B_CE = 20, B_ADONE = 26, B_BDONE = 27, B_XC = 28, B_PRDY = 29, B_AUX = 30, B_NUM = 31 };

__device__ __forceinline__ void st_async4(uint32_t dst, float a, float b, float c, float d, uint32_t bar) {
    asm volatile("st.async.weak.shared::cluster.mbarrier::complete_tx::bytes.v4.f32 [%0], {%1,%2,%3,%4}, [%5];"
                 :: "r"(dst), "f"(a), "f"(b), "f"(c), "f"(d), "r"(bar) : "memory");
}
__device__ __forceinline__ void poll_count(const unsigned int* p, unsigned int target) {
    int it = 0;
    while (ld_acquire(p) < target) { if (++it > (1 << 22)) __trap(); }
    asm volatile("fence.proxy.async.global;" ::: "memory");
}
__device__ __forceinline__ void tma2d_store(const CUtensorMap* m, uint32_t src, int c0, int c1) {
    asm volatile("cp.async.bulk.tensor.2d.global.shared::cta.bulk_group [%0, {%2, %3}], [%1];" :: "l"(m), "r"(src), "r"(c0), "r"(c1) : "memory");
}
__device__ __forceinline__ float2 h_row_stats(int row) {
    const float4* hp = (const float4*)(g_hstat + (size_t)row * 8);
    float4 a = __ldcg(hp), b = __ldcg(hp + 1), c = __ldcg(hp + 2), d = __ldcg(hp + 3);
    float mean = 0.125f * (a.x + a.z + b.x + b.z + c.x + c.z + d.x + d.z);
    float m2 = a.y + a.w + b.y + b.w + c.y + c.w + d.y + d.w;
    float e;
    e = a.x - mean; m2 = fmaf(64.f * e, e, m2); e = a.z - mean; m2 = fmaf(64.f * e, e, m2);
    e = b.x - mean; m2 = fmaf(64.f * e, e, m2); e = b.z - mean; m2 = fmaf(64.f * e, e, m2);
    e = c.x - mean; m2 = fmaf(64.f * e, e, m2); e = c.z - mean; m2 = fmaf(64.f * e, e, m2);
    e = d.x - mean; m2 = fmaf(64.f * e, e, m2); e = d.z - mean; m2 = fmaf(64.f * e, e, m2);
    return make_float2(rsqrtf(m2 * (1.0f / DM) + 1e-5f), -mean);
}
__device__ __forceinline__ int c_kblock(int i, int r) {
    if (i < 6) { const int e = 2 * i + r, m = e / 3, k = e - 3 * m; return 7 * m + (k == 2 ? 4 : k); }
    const int l = 2 * (i - 6) + r, m = l >> 2, k = l & 3;
    return 7 * m + (k < 2 ? 2 + k : 3 + k);
}
__device__ __forceinline__ uint32_t c_stage_a(int s, int ntB) { return s < 4 ? ((ntB + 2 * s) & 7) * 16384 : F_R2 + (s - 4) * 32768; }
__device__ __forceinline__ uint32_t c_stage_b(int s, int ntB) { return s < 4 ? ((ntB + 2 * s + 1) & 7) * 16384 : F_R2 + (s - 4) * 32768 + 16384; }
template <int R>
__device__ __forceinline__ void xchg(float (&acc)[64], float (&o)[32], uint32_t sb, unsigned char* smem, int bar, int ctid) {
    const uint32_t dst = mapa(sb + F_X + ctid * 16, 1 - R), rb = mapa(sb + F_BAR + 8 * bar, 1 - R);
#pragma unroll
    for (int q = 0; q < 8; q++) {
        const int j = (1 - R) * 32 + 4 * q;
        st_async4(dst + q * 4096, acc[j], acc[j + 1], acc[j + 2], acc[j + 3], rb);
    }
    mbar_wait_cluster(sb + F_BAR + 8 * bar, 0);
#pragma unroll
    for (int q = 0; q < 8; q++) {
        float4 v = *(const float4*)(smem + F_X + q * 4096 + ctid * 16);
        const int j = R * 32 + 4 * q;
        o[4 * q] = acc[j] + v.x; o[4 * q + 1] = acc[j + 1] + v.y; o[4 * q + 2] = acc[j + 2] + v.z; o[4 * q + 3] = acc[j + 3] + v.w;
    }
}

template <int NB>
__device__ __forceinline__ void ffn_epilogue(const float* ag, const float* au, const float* s_cs, int cs_off, uint32_t* gp,
                                             float2 st0, float2 st1, int lane) {
    const int t = lane & 3;
    const float C1 = 0.7978845608028654f, C2 = 0.044715f * 0.7978845608028654f;
#pragma unroll
    for (int j2 = 0; j2 < NB / 2; j2++) {
        uint32_t pk[4];
#pragma unroll
        for (int jj = 0; jj < 2; jj++) {
            const int j = 2 * j2 + jj;
            const float2 cg = *(const float2*)(s_cs + cs_off + 8 * j + 2 * t);
            const float2 cu = *(const float2*)(s_cs + 224 + cs_off + 8 * j + 2 * t);
            float r[4];
#pragma unroll
            for (int e = 0; e < 4; e++) {
                const float nm = (e < 2) ? st0.y : st1.y, rs = (e < 2) ? st0.x : st1.x;
                const float gt = rs * fmaf(nm, (e & 1) ? cg.y : cg.x, ag[4 * j + e]);
                const float tu = fmaf(nm, (e & 1) ? cu.y : cu.x, au[4 * j + e]);
                const float th = tanh_fast(gt * fmaf(gt * gt, C2, C1));
                const float p = gt * tu;
                r[e] = fmaf(p, th, p);
            }
            pk[2 * jj] = pack_bf16(r[0], r[1]);
            pk[2 * jj + 1] = pack_bf16(r[2], r[3]);
        }
        gp[j2 * 1024] = pk[0]; gp[j2 * 1024 + 32] = pk[1]; gp[j2 * 1024 + 512] = pk[2]; gp[j2 * 1024 + 544] = pk[3];
    }
}

__global__ void __cluster_dims__(2, 1, 1) __launch_bounds__(384, 1)
tail_kernel(const __grid_constant__ CUtensorMap tm_o, const __grid_constant__ CUtensorMap tm_g,
            const __grid_constant__ CUtensorMap tm_u, const __grid_constant__ CUtensorMap tm_d,
            const __grid_constant__ CUtensorMap tm_out, const __nv_bfloat16* __restrict__ x) {
    extern __shared__ __align__(1024) unsigned char smem[];
    const uint32_t sb = smem_u32(smem);
    const uint32_t bars = sb + F_BAR;
    const int tid = threadIdx.x, warp = __shfl_sync(0xffffffffu, tid >> 5, 0), lane = tid & 31;
    const int cl = blockIdx.x >> 1, r = blockIdx.x & 1;
    const int mb = ((cl & 7) >> 1) * 4 + (cl >> 4), ntA = (cl & 1) * 2 + ((cl >> 3) & 1);
    const int nt = ntA * 2 + r;
    const int mbB = (mb & ~1) + r, ntB = (mb & 1) * 4 + ntA;
    if (tid == 0) {
#pragma unroll
        for (int i = 0; i < B_NUM; i++) {
            const int cnt = (i >= B_BE && i < B_BE + 3) ? 16 : (i == B_BDONE) ? 9 : ((i >= B_CE && i < B_CE + 6) || i == B_PRDY) ? 8 : (i == B_AUX || i == B_ADONE) ? 2 : 1;
            mbar_init(bars + 8 * i, cnt);
        }
        mbar_expect(bars + 8 * B_XC, 32768);
        fence_barrier_init();
        for (int i = 0; i < 8; i++) {
            const uint32_t bar = bars + 8 * (B_FA + (i >> 1));
            if (!(i & 1)) mbar_expect(bar, 49152);
            tma2d(sb + F_R2 + 32768 + i * 8192, &tm_o, nt * 64, i * 64, bar);
        }
    }
    __syncthreads();
    asm volatile("barrier.cluster.arrive.relaxed.aligned;" ::: "memory");
    if (warp < 4) {
        asm volatile("setmaxnreg.dec.sync.aligned.u32 56;");
        if (warp == 0) {
            if (lane == 0) {
                auto load_b = [&](int it) {
                    const int s = it % 3, pass = it >> 3, kb = (ntB + it) & 7;
                    const int ng = pass ? 3 : 4, c0 = ntB * 224 + pass * 128;
                    const uint32_t bar = bars + 8 * (B_BF + s), dst = sb + F_R2 + s * 32768 + r * ng * 4096;
                    mbar_expect(bar, ng * 8192);
                    for (int i = 0; i < ng; i++) tma2d_mc(dst + i * 4096, r ? &tm_u : &tm_g, c0 + i * 32, kb * 64, bar);
                };
                asm volatile("barrier.cluster.wait.acquire;" ::: "memory");
                pdl_wait();
                for (int i = 0; i < 4; i++)
                    bulk_g2s_mc(sb + (2 * i + r) * 16384, g_ao + (size_t)(mb * 8 + 2 * i + r) * 8192, 16384, bars + 8 * (B_FA + i));
                load_b(0);
                if (blockIdx.x == 0)
                    for (int i = 0; i < 32; i++) g_cnt[i] = 0;
                mbar_wait_cluster(bars + 8 * B_ADONE, 0);
                load_b(1); load_b(2);
                auto load_c = [&](int i) {
                    const int s = i % 6, kb = c_kblock(i, r);
                    const uint32_t bar = bars + 8 * (B_CF + s), da = sb + c_stage_a(s, ntB), db = sb + c_stage_b(s, ntB);
                    mbar_expect(bar, 32768);
                    tma2d(db, &tm_d, ntA * 128, kb * 64, bar);
                    tma2d(db + 8192, &tm_d, ntA * 128 + 64, kb * 64, bar);
                    bulk_g2s(da, g_g + (size_t)(mb * 28 + kb) * 8192, 16384, bar);
                };
                for (int it = 3; it < 16; it++) {
                    mbar_wait_cluster(bars + 8 * (B_BE + it % 3), (it / 3 - 1) & 1);
                    load_b(it);
                    if (it == 12) { poll_count(&g_cnt2[mb], 8); load_c(0); }
                    if (it == 14) load_c(1);
                }
                mbar_wait_cluster(bars + 8 * (B_BE + 1), 0);
                load_c(2);
                mbar_wait(bars + 8 * B_BDONE, 0);
                for (int i = 3; i < 14; i++) {
                    if (i >= 6) mbar_wait(bars + 8 * (B_CE + i % 6), ((i / 6) - 1) & 1);
                    if (i == 6) { poll_count(&g_cnt2[16 + mb], 8); }
                    load_c(i);
                }
            }
            else asm volatile("barrier.cluster.wait.acquire;" ::: "memory");
        } else if (warp == 1) {
            asm volatile("barrier.cluster.wait.acquire.aligned;" ::: "memory");
            bar_sync(5, 288);
            if (lane == 0) { red_release(&g_cnt2[32 + (mb * 8 + nt)]); }
            __syncwarp();
            bar_sync(6, 288);
            if (lane == 0) red_release(&g_cnt2[32 + (mb * 8 + nt)]);
            __syncwarp();
            bar_sync(1, 288);
            if (lane == 0) red_release(&g_cnt2[mbB]);
            __syncwarp();
            bar_sync(2, 288);
            if (lane == 0) {
                red_release(&g_cnt2[16 + mbB]);
                mbar_arrive(bars + 8 * B_BDONE);
            }
            __syncwarp();
            bar_sync(3, 288);
            if (lane == 0) {
                tma2d_store(&tm_out, sb, nt * 64, mb * 128);
                bulk_commit();
                bulk_wait_all();
            }
        } else {
            asm volatile("barrier.cluster.wait.acquire.aligned;" ::: "memory");
            pdl_wait();
            float2* s_rs = (float2*)(smem + F_RS);
            float* s_cs = (float*)(smem + F_CS);
            for (int c = tid - 64; c < 448; c += 64)
                s_cs[c] = __ldcg(&g_cs2[(c >= 224 ? FF - 224 : 0) + ntB * 224 + c]);
            if (tid == 96) {
                mbar_wait_cluster(bars + 8 * B_ADONE, 0);
                for (int i = 0; i < 8; i++) {
                    const int kb = (ntB + i) & 7;
                    const uint32_t bar = bars + 8 * (i < 4 ? B_HF + i : B_FA + i - 4);
                    poll_count(&g_cnt2[32 + (mbB * 8 + kb)], 1);
                    mbar_expect(bar, 16384);
                    bulk_g2s(sb + kb * 16384, g_h + (size_t)(mbB * 8 + kb) * 8192, 16384, bar);
                }
            }
            __syncwarp();
            for (int i = 0; i < 8; i++) mbar_wait(bars + 8 * (i < 4 ? B_HF + i : B_FA + i - 4), i < 4 ? 0 : 1);
            if (lane < 8) poll_count(&g_cnt2[32 + (mbB * 8 + lane)], 2);
            __syncwarp();
            for (int rr = tid - 64; rr < 128; rr += 64) {
                s_rs[rr] = h_row_stats(mbB * 128 + rr);
            }
            __syncwarp();
            if (lane == 0) mbar_arrive(bars + 8 * B_AUX);
        }
    } else {
        asm volatile("setmaxnreg.inc.sync.aligned.u32 216;");
        const int wgi = (warp >> 2) - 1, ww = warp & 3, ctid = tid - 128;
        const int g = lane >> 2, t = lane & 3;
        const int rl = wgi * 64 + ww * 16 + g, row = mb * 128 + rl;
        const int rgl = wgi * 8 + ww * 2;
        const float2* s_rs = (const float2*)(smem + F_RS);
        const float* s_cs = (const float*)(smem + F_CS);
        uint32_t* hp = (uint32_t*)g_h + ((size_t)(mb * 8 + nt) * 8 * 16 + rgl) * 32 + lane;
        const uint32_t rbars = mapa(bars, 1 - r);
        {
            uint32_t xr[16];
            const uint32_t* xp = (const uint32_t*)(x + (size_t)row * DM + nt * 64) + t;
#pragma unroll
            for (int j = 0; j < 8; j++) { xr[2 * j] = __ldg(xp + 4 * j); xr[2 * j + 1] = __ldg(xp + 8 * (DM / 2) + 4 * j); }
            float acc[32];
#pragma unroll 1
            for (int i = 0; i < 8; i++) {
                if (!(i & 1)) { mbar_wait(bars + 8 * (B_FA + (i >> 1)), 0); }
                uint64_t ad = make_desc(sb + i * 16384 + wgi * 1024, 2048, 128, 0);
                uint64_t bd = make_desc(sb + F_R2 + 32768 + i * 8192, 8192, 1024, 1);
                WG_FENCE();
#pragma unroll
                for (int k = 0; k < 4; k++) wgmma_ss_n64(acc, ad + k * 256, bd + k * 128, (i | k) != 0);
                WG_COMMIT();
            }
            wg_wait<0>();
            fence_regs(acc);
            asm volatile("barrier.cluster.wait.acquire.aligned;" ::: "memory");
            bar_sync(4, 256);
            if (tid == 128) { mbar_arrive(bars + 8 * B_ADONE); mbar_arrive_remote(mapa(bars + 8 * B_ADONE, 1 - r)); }
            float v0[16], v1[16];
            float s0 = 0.f, s1 = 0.f;
#pragma unroll
            for (int j2 = 0; j2 < 4; j2++) {
                uint32_t u[4];
#pragma unroll
                for (int jj = 0; jj < 2; jj++) {
                    const int j = 2 * j2 + jj;
                    u[2 * jj] = pack_bf16(bf_lo(xr[2 * j]) + acc[4 * j], bf_hi(xr[2 * j]) + acc[4 * j + 1]);
                    u[2 * jj + 1] = pack_bf16(bf_lo(xr[2 * j + 1]) + acc[4 * j + 2], bf_hi(xr[2 * j + 1]) + acc[4 * j + 3]);
                    v0[2 * j] = bf_lo(u[2 * jj]); v0[2 * j + 1] = bf_hi(u[2 * jj]);
                    v1[2 * j] = bf_lo(u[2 * jj + 1]); v1[2 * j + 1] = bf_hi(u[2 * jj + 1]);
                    s0 += v0[2 * j] + v0[2 * j + 1];
                    s1 += v1[2 * j] + v1[2 * j + 1];
                }
                hp[j2 * 1024] = u[0]; hp[j2 * 1024 + 32] = u[1]; hp[j2 * 1024 + 512] = u[2]; hp[j2 * 1024 + 544] = u[3];
            }
            bar_arrive(5, 288);
            float m0 = s0 * (1.0f / 16), m1 = s1 * (1.0f / 16), q0 = 0.f, q1 = 0.f;
#pragma unroll
            for (int i = 0; i < 16; i++) {
                float d0 = v0[i] - m0, d1 = v1[i] - m1;
                q0 = fmaf(d0, d0, q0); q1 = fmaf(d1, d1, q1);
            }
#pragma unroll
            for (int st = 0; st < 2; st++) {
                float hn = st ? 16.f : 8.f;
                float om0 = __shfl_xor_sync(0xffffffffu, m0, 1 << st), oq0 = __shfl_xor_sync(0xffffffffu, q0, 1 << st);
                float om1 = __shfl_xor_sync(0xffffffffu, m1, 1 << st), oq1 = __shfl_xor_sync(0xffffffffu, q1, 1 << st);
                float d0 = om0 - m0, d1 = om1 - m1;
                q0 = q0 + oq0 + d0 * d0 * hn; q1 = q1 + oq1 + d1 * d1 * hn;
                m0 = 0.5f * (m0 + om0); m1 = 0.5f * (m1 + om1);
            }
            if (t == 0) {
                g_hstat[row * 8 + nt] = make_float2(m0, q0);
                g_hstat[(row + 8) * 8 + nt] = make_float2(m1, q1);
            }
            bar_arrive(6, 288);
        }
        uint32_t* gp = (uint32_t*)g_g + (((size_t)mbB * 224 + ntB * 28) * 16 + rgl) * 32 + lane;
        {
            float ag[128];
#pragma unroll 1
            for (int kb = 0; kb < 8; kb++) {
                const int s = kb % 3;
                mbar_wait(bars + 8 * (kb < 4 ? B_HF + kb : B_FA + kb - 4), kb < 4 ? 0 : 1);
                mbar_wait(bars + 8 * (B_BF + s), (kb / 3) & 1);
                uint64_t ad = make_desc(sb + ((ntB + kb) & 7) * 16384 + wgi * 1024, 2048, 128, 0);
                uint64_t bd = make_desc(sb + F_R2 + s * 32768, 4096, 512, 2);
                WG_FENCE();
#pragma unroll
                for (int k = 0; k < 4; k++) wgmma_ss_n256(ag, ad + k * 256, bd + k * 64, (kb | k) != 0);
                WG_COMMIT();
                if (kb > 0) {
                    wg_wait<1>();
                    if (lane == 0) { mbar_arrive(bars + 8 * (B_BE + (kb - 1) % 3)); mbar_arrive_remote(rbars + 8 * (B_BE + (kb - 1) % 3)); }
                }
            }
            wg_wait<0>();
            if (lane == 0) { mbar_arrive(bars + 8 * (B_BE + 7 % 3)); mbar_arrive_remote(rbars + 8 * (B_BE + 7 % 3)); }
            fence_regs(ag);
            mbar_wait(bars + 8 * B_AUX, 0);
            ffn_epilogue<16>(ag, ag + 64, s_cs, 0, gp, s_rs[rl], s_rs[rl + 8], lane);
            bar_arrive(1, 288);
        }
        {
            float ag[96];
#pragma unroll 1
            for (int kb = 0; kb < 8; kb++) {
                const int it = 8 + kb, s = it % 3;
                mbar_wait(bars + 8 * (B_BF + s), (it / 3) & 1);
                uint64_t ad = make_desc(sb + ((ntB + kb) & 7) * 16384 + wgi * 1024, 2048, 128, 0);
                uint64_t bd = make_desc(sb + F_R2 + s * 32768, 4096, 512, 2);
                WG_FENCE();
#pragma unroll
                for (int k = 0; k < 4; k++) wgmma_ss_n192(ag, ad + k * 256, bd + k * 64, (kb | k) != 0);
                WG_COMMIT();
                if (kb > 0) {
                    wg_wait<1>();
                    if (lane == 0 && it < 15) { mbar_arrive(bars + 8 * (B_BE + (it - 1) % 3)); mbar_arrive_remote(rbars + 8 * (B_BE + (it - 1) % 3)); }
                }
            }
            wg_wait<0>();
            if (lane == 0) {
                mbar_arrive(bars + 8 * B_BDONE);
                mbar_arrive_remote(rbars + 8 * B_PRDY);
            }
            fence_regs(ag);
            ffn_epilogue<12>(ag, ag + 48, s_cs, 128, gp + 16 * 512, s_rs[rl], s_rs[rl + 8], lane);
            bar_arrive(2, 288);
        }
        {
            uint32_t hr[16];
#pragma unroll
            for (int j = 0; j < 8; j++) { hr[2 * j] = __ldcg(hp + j * 512); hr[2 * j + 1] = __ldcg(hp + j * 512 + 32); }
            mbar_wait(bars + 8 * (B_CF + 0), 0);
            const float a0 = h_row_stats(row).x, a1 = h_row_stats(row + 8).x;
            float acc[64];
#pragma unroll 1
            for (int kb = 0; kb < 14; kb++) {
                const int s = kb % 6;
                mbar_wait(bars + 8 * (B_CF + s), (kb / 6) & 1);
                uint64_t ad = make_desc(sb + c_stage_a(s, ntB) + wgi * 1024, 2048, 128, 0);
                uint64_t bd = make_desc(sb + c_stage_b(s, ntB), 8192, 1024, 1);
                WG_FENCE();
#pragma unroll
                for (int k = 0; k < 4; k++) wgmma_ss_n128(acc, ad + k * 256, bd + k * 128, (kb | k) != 0);
                WG_COMMIT();
                if (kb > 0) {
                    wg_wait<1>();
                    if (lane == 0) mbar_arrive(bars + 8 * (B_CE + (kb - 1) % 6));
                }
            }
            wg_wait<0>();
            fence_regs(acc);
            mbar_wait_cluster(bars + 8 * B_PRDY, 0);
            float o[32];
            if (r == 0) xchg<0>(acc, o, sb, smem, B_XC, ctid); else xchg<1>(acc, o, sb, smem, B_XC, ctid);
            bar_sync(4, 256);
            const float k0 = 0.5f * a0, k1 = 0.5f * a1;
            const int srow = wgi * 64 + ww * 16 + ((lane >> 3) & 1) * 8 + (lane & 7);
#pragma unroll
            for (int j2 = 0; j2 < 4; j2++) {
                uint32_t u[4];
#pragma unroll
                for (int jj = 0; jj < 2; jj++) {
                    const int j = 2 * j2 + jj;
                    u[2 * jj] = pack_bf16(fmaf(k0, o[4 * j], bf_lo(hr[2 * j])), fmaf(k0, o[4 * j + 1], bf_hi(hr[2 * j])));
                    u[2 * jj + 1] = pack_bf16(fmaf(k1, o[4 * j + 2], bf_lo(hr[2 * j + 1])), fmaf(k1, o[4 * j + 3], bf_hi(hr[2 * j + 1])));
                }
                const int chunk = 2 * j2 + (lane >> 4);
                stsm4(sb + srow * 128 + ((chunk ^ (lane & 7)) * 16), u[0], u[1], u[2], u[3]);
            }
            fence_proxy_async();
            bar_arrive(3, 288);
        }
    }
}


static_assert(K1_SMEM <= F_SMEM && AT_SMEM <= F_SMEM && F_SMEM <= 232448, "shared memory budget");

typedef CUresult (*EncodeFn)(CUtensorMap*, CUtensorMapDataType, cuuint32_t, void*, const cuuint64_t*, const cuuint64_t*,
                             const cuuint32_t*, const cuuint32_t*, CUtensorMapInterleave, CUtensorMapSwizzle,
                             CUtensorMapL2promotion, CUtensorMapFloatOOBfill);

void encode(EncodeFn fn, CUtensorMap* m, const void* ptr, int rank, const cuuint64_t* dims, const cuuint64_t* strides,
            const cuuint32_t* box, CUtensorMapSwizzle swz) {
    cuuint32_t es[3] = {1, 1, 1};
    fn(m, CU_TENSOR_MAP_DATA_TYPE_BFLOAT16, rank, (void*)ptr, dims, strides, box, es, CU_TENSOR_MAP_INTERLEAVE_NONE, swz,
       CU_TENSOR_MAP_L2_PROMOTION_L2_256B, CU_TENSOR_MAP_FLOAT_OOB_FILL_NONE);
}

template <typename... KArgs, typename... Args>
void launch(void (*kern)(KArgs...), int grid, int block, int smem, bool pdl, Args... args) {
    cudaLaunchConfig_t cfg = {};
    cfg.gridDim = dim3(grid); cfg.blockDim = dim3(block); cfg.dynamicSmemBytes = smem;
    cfg.stream = cudaStreamPerThread;
    cudaLaunchAttribute at[1];
    at[0].id = cudaLaunchAttributeProgrammaticStreamSerialization;
    at[0].val.programmaticStreamSerializationAllowed = 1;
    cfg.attrs = at; cfg.numAttrs = pdl ? 1 : 0;
    cudaLaunchKernelEx(&cfg, kern, KArgs(args)...);
}

}

extern "C" void kernel_launch(void* const* d_in, const int* in_sizes, int n_in, void* d_out, int out_size) {
    const __nv_bfloat16* x = (const __nv_bfloat16*)d_in[0];
    const __nv_bfloat16* wqkv = (const __nv_bfloat16*)d_in[1];
    const __nv_bfloat16* wo = (const __nv_bfloat16*)d_in[2];
    const __nv_bfloat16* wgate = (const __nv_bfloat16*)d_in[4];
    const __nv_bfloat16* wup = (const __nv_bfloat16*)d_in[5];
    const __nv_bfloat16* wdown = (const __nv_bfloat16*)d_in[6];
    __nv_bfloat16* out = (__nv_bfloat16*)d_out;

    static CUtensorMap tm_x, tm_wqkv, tm_wo, tm_wg, tm_wu, tm_wd, tm_out;
    static const void* cached[7] = {nullptr, nullptr, nullptr, nullptr, nullptr, nullptr, nullptr};
    if (cached[0] != x || cached[1] != wqkv || cached[2] != wo || cached[3] != wgate || cached[4] != wup || cached[5] != wdown || cached[6] != out) {
        void* fp = nullptr;
        cudaDriverEntryPointQueryResult qr;
        cudaGetDriverEntryPoint("cuTensorMapEncodeTiled", &fp, cudaEnableDefault, &qr);
        EncodeFn fn = (EncodeFn)fp;
        { cuuint64_t d[2] = {512, 2048}, s[1] = {1024}; cuuint32_t b[2] = {64, 128};
          encode(fn, &tm_x, x, 2, d, s, b, CU_TENSOR_MAP_SWIZZLE_128B);
          encode(fn, &tm_out, out, 2, d, s, b, CU_TENSOR_MAP_SWIZZLE_128B); }
        { cuuint64_t d[3] = {64, 512, 24}, s[2] = {3072, 128}; cuuint32_t b[3] = {64, 64, 3};
          encode(fn, &tm_wqkv, wqkv, 3, d, s, b, CU_TENSOR_MAP_SWIZZLE_128B); }
        { cuuint64_t d[2] = {512, 512}, s[1] = {1024}; cuuint32_t b[2] = {64, 64};
          encode(fn, &tm_wo, wo, 2, d, s, b, CU_TENSOR_MAP_SWIZZLE_128B); }
        { cuuint64_t d[2] = {1792, 512}, s[1] = {3584}; cuuint32_t b[2] = {32, 64};
          encode(fn, &tm_wg, wgate, 2, d, s, b, CU_TENSOR_MAP_SWIZZLE_64B);
          encode(fn, &tm_wu, wup, 2, d, s, b, CU_TENSOR_MAP_SWIZZLE_64B); }
        { cuuint64_t d[2] = {512, 1792}, s[1] = {1024}; cuuint32_t b[2] = {64, 64};
          encode(fn, &tm_wd, wdown, 2, d, s, b, CU_TENSOR_MAP_SWIZZLE_128B); }
        cudaFuncSetAttribute(qkv_kernel, cudaFuncAttributeMaxDynamicSharedMemorySize, F_SMEM);
        cudaFuncSetAttribute(qkv_kernel, cudaFuncAttributePreferredSharedMemoryCarveout, 100);
        cudaFuncSetAttribute(attn_kernel, cudaFuncAttributeMaxDynamicSharedMemorySize, F_SMEM);
        cudaFuncSetAttribute(attn_kernel, cudaFuncAttributePreferredSharedMemoryCarveout, 100);
        cudaFuncSetAttribute(tail_kernel, cudaFuncAttributeMaxDynamicSharedMemorySize, F_SMEM);
        cudaFuncSetAttribute(tail_kernel, cudaFuncAttributePreferredSharedMemoryCarveout, 100);
        cached[0] = x; cached[1] = wqkv; cached[2] = wo; cached[3] = wgate; cached[4] = wup; cached[5] = wdown; cached[6] = out;
    }
    launch(qkv_kernel, 128, 384, F_SMEM, false, tm_x, tm_wqkv, x, wqkv);
    launch(attn_kernel, 132, 512, F_SMEM, true, wgate, wup, wo, wdown);
    launch(tail_kernel, 128, 384, F_SMEM, true, tm_wo, tm_wg, tm_wu, tm_wd, tm_out, x);
}
```

```cpp
#include <cuda_runtime.h>
#include <cuda_bf16.h>
#include <cuda.h>
#include <stdint.h>

namespace {

constexpr int S_LEN = 2048, DM = 512, NH = 32, FF = 1792;

__device__ __align__(1024) __nv_bfloat16 g_qkv[3 * NH * S_LEN * 16];
__device__ __align__(1024) __nv_bfloat16 g_ao[S_LEN * DM];
__device__ __align__(1024) __nv_bfloat16 g_h[S_LEN * DM];
__device__ __align__(1024) __nv_bfloat16 g_g[S_LEN * FF];
__device__ __align__(16) float2 g_rowstat1[S_LEN];
__device__ __align__(16) float g_cs1_part[16 * 1536];
__device__ unsigned int g_cnt[32];
__device__ unsigned int g_cnt2[160];
__device__ __align__(16) float g_nrm[3 * NH * 128];
__device__ __align__(16) float2 g_hstat[S_LEN * 8];
__device__ float g_cs2[2 * FF];

__device__ __forceinline__ uint32_t smem_u32(const void* p) { return (uint32_t)__cvta_generic_to_shared(p); }
__device__ __forceinline__ void mbar_init(uint32_t a, int c) { asm volatile("mbarrier.init.shared.b64 [%0], %1;" :: "r"(a), "r"(c)); }
__device__ __forceinline__ void mbar_expect(uint32_t a, int bytes) { asm volatile("mbarrier.arrive.expect_tx.shared.b64 _, [%0], %1;" :: "r"(a), "r"(bytes) : "memory"); }
__device__ __forceinline__ void mbar_arrive(uint32_t a) { asm volatile("mbarrier.arrive.shared.b64 _, [%0];" :: "r"(a) : "memory"); }
__device__ __forceinline__ void mbar_wait(uint32_t a, int parity) {
    uint32_t done;
    int it = 0;
    do {
        asm volatile("{\n.reg .pred p;\nmbarrier.try_wait.parity.shared.b64 p, [%1], %2;\nselp.u32 %0, 1, 0, p;\n}"
                     : "=r"(done) : "r"(a), "r"(parity) : "memory");
        if (++it > (1 << 24)) __trap();
    } while (!done);
}
__device__ __forceinline__ void bulk_g2s(uint32_t dst, const void* src, int bytes, uint32_t bar) {
    asm volatile("cp.async.bulk.shared::cluster.global.mbarrier::complete_tx::bytes [%0], [%1], %2, [%3];"
                 :: "r"(dst), "l"(src), "r"(bytes), "r"(bar) : "memory");
}
__device__ __forceinline__ void tma2d(uint32_t dst, const CUtensorMap* m, int c0, int c1, uint32_t bar) {
    asm volatile("cp.async.bulk.tensor.2d.shared::cluster.global.mbarrier::complete_tx::bytes [%0], [%1, {%3, %4}], [%2];"
                 :: "r"(dst), "l"(m), "r"(bar), "r"(c0), "r"(c1) : "memory");
}
__device__ __forceinline__ void tma3d(uint32_t dst, const CUtensorMap* m, int c0, int c1, int c2, uint32_t bar) {
    asm volatile("cp.async.bulk.tensor.3d.shared::cluster.global.mbarrier::complete_tx::bytes [%0], [%1, {%3, %4, %5}], [%2];"
                 :: "r"(dst), "l"(m), "r"(bar), "r"(c0), "r"(c1), "r"(c2) : "memory");
}
__device__ __forceinline__ void pdl_wait() { asm volatile("griddepcontrol.wait;" ::: "memory"); }
__device__ __forceinline__ void pdl_launch() { asm volatile("griddepcontrol.launch_dependents;" ::: "memory"); }
__device__ __forceinline__ void fence_barrier_init() { asm volatile("fence.mbarrier_init.release.cluster;" ::: "memory"); }
__device__ __forceinline__ void fence_proxy_async() { asm volatile("fence.proxy.async.shared::cta;" ::: "memory"); }
__device__ __forceinline__ uint64_t make_desc(uint32_t saddr, uint32_t lbo, uint32_t sbo, uint32_t swz) {
    return (uint64_t)((saddr & 0x3FFFF) >> 4) | ((uint64_t)((lbo & 0x3FFFF) >> 4) << 16) |
           ((uint64_t)((sbo & 0x3FFFF) >> 4) << 32) | ((uint64_t)swz << 62);
}
#define WG_FENCE() asm volatile("wgmma.fence.sync.aligned;" ::: "memory")
#define WG_COMMIT() asm volatile("wgmma.commit_group.sync.aligned;" ::: "memory")
template <int N> __device__ __forceinline__ void wg_wait() { asm volatile("wgmma.wait_group.sync.aligned %0;" :: "n"(N) : "memory"); }
template <int N> __device__ __forceinline__ void fence_regs(float (&d)[N]) {
#pragma unroll
    for (int i = 0; i < N; i++) asm volatile("" : "+f"(d[i]) :: "memory");
}
__device__ __forceinline__ float ex2f(float x) { float y; asm("ex2.approx.ftz.f32 %0, %1;" : "=f"(y) : "f"(x)); return y; }
__device__ __forceinline__ float tanh_fast(float x) { float y; asm("tanh.approx.f32 %0, %1;" : "=f"(y) : "f"(x)); return y; }
__device__ __forceinline__ uint32_t pack_bf16(float lo, float hi) { uint32_t r; asm("cvt.rn.bf16x2.f32 %0, %1, %2;" : "=r"(r) : "f"(hi), "f"(lo)); return r; }
__device__ __forceinline__ float bf_lo(uint32_t u) { return __uint_as_float(u << 16); }
__device__ __forceinline__ float bf_hi(uint32_t u) { return __uint_as_float(u & 0xFFFF0000u); }
__device__ __forceinline__ uint32_t hfma2(uint32_t a, uint32_t b, uint32_t c) { uint32_t r; asm("fma.rn.f16x2 %0, %1, %2, %3;" : "=r"(r) : "r"(a), "r"(b), "r"(c)); return r; }
__device__ __forceinline__ uint32_t hmul2(uint32_t a, uint32_t b) { uint32_t r; asm("mul.rn.f16x2 %0, %1, %2;" : "=r"(r) : "r"(a), "r"(b)); return r; }
__device__ __forceinline__ unsigned int ld_acquire(const unsigned int* p) { unsigned int v; asm volatile("ld.acquire.gpu.u32 %0, [%1];" : "=r"(v) : "l"(p) : "memory"); return v; }
__device__ __forceinline__ void red_release(unsigned int* p) { asm volatile("red.release.gpu.global.add.u32 [%0], 1;" :: "l"(p) : "memory"); }
__device__ __forceinline__ void stsm4(uint32_t addr, uint32_t a, uint32_t b, uint32_t c, uint32_t d) {
    asm volatile("stmatrix.sync.aligned.m8n8.x4.shared.b16 [%0], {%1,%2,%3,%4};" :: "r"(addr), "r"(a), "r"(b), "r"(c), "r"(d) : "memory");
}
__device__ __forceinline__ void bulk_commit() { asm volatile("cp.async.bulk.commit_group;" ::: "memory"); }
__device__ __forceinline__ void bulk_wait_all() { asm volatile("cp.async.bulk.wait_group 0;" ::: "memory"); }
__device__ __forceinline__ void bar_sync(int id, int n) { asm volatile("bar.sync %0, %1;" :: "r"(id), "r"(n) : "memory"); }
__device__ __forceinline__ void bar_arrive(int id, int n) { asm volatile("bar.arrive %0, %1;" :: "r"(id), "r"(n) : "memory"); }
__device__ __forceinline__ float warp_sum(float v) {
#pragma unroll
    for (int o = 16; o; o >>= 1) v += __shfl_xor_sync(0xffffffffu, v, o);
    return v;
}
__device__ __forceinline__ float warp_max(float v) {
#pragma unroll
    for (int o = 16; o; o >>= 1) v = fmaxf(v, __shfl_xor_sync(0xffffffffu, v, o));
    return v;
}

__device__ __forceinline__ void wgmma_ss_n64(float (&d)[32], uint64_t adesc, uint64_t bdesc, int scale_d) {
    asm volatile("{\n.reg .pred p;\nsetp.ne.b32 p, %34, 0;\n"
      "wgmma.mma_async.sync.aligned.m64n64k16.f32.bf16.bf16 {%0,%1,%2,%3,%4,%5,%6,%7,%8,%9,%10,%11,%12,%13,%14,%15,%16,%17,%18,%19,%20,%21,%22,%23,%24,%25,%26,%27,%28,%29,%30,%31}, %32, %33, p, 1, 1, 0, 1;\n}"
      : "+f"(d[0]), "+f"(d[1]), "+f"(d[2]), "+f"(d[3]), "+f"(d[4]), "+f"(d[5]), "+f"(d[6]), "+f"(d[7]), "+f"(d[8]), "+f"(d[9]), "+f"(d[10]), "+f"(d[11]), "+f"(d[12]), "+f"(d[13]), "+f"(d[14]), "+f"(d[15]), "+f"(d[16]), "+f"(d[17]), "+f"(d[18]), "+f"(d[19]), "+f"(d[20]), "+f"(d[21]), "+f"(d[22]), "+f"(d[23]), "+f"(d[24]), "+f"(d[25]), "+f"(d[26]), "+f"(d[27]), "+f"(d[28]), "+f"(d[29]), "+f"(d[30]), "+f"(d[31])
      : "l"(adesc), "l"(bdesc), "r"(scale_d));
}
__device__ __forceinline__ void wgmma_ss_n128(float (&d)[64], uint64_t adesc, uint64_t bdesc, int scale_d) {
    asm volatile("{\n.reg .pred p;\nsetp.ne.b32 p, %66, 0;\n"
      "wgmma.mma_async.sync.aligned.m64n128k16.f32.bf16.bf16 {%0,%1,%2,%3,%4,%5,%6,%7,%8,%9,%10,%11,%12,%13,%14,%15,%16,%17,%18,%19,%20,%21,%22,%23,%24,%25,%26,%27,%28,%29,%30,%31,%32,%33,%34,%35,%36,%37,%38,%39,%40,%41,%42,%43,%44,%45,%46,%47,%48,%49,%50,%51,%52,%53,%54,%55,%56,%57,%58,%59,%60,%61,%62,%63}, %64, %65, p, 1, 1, 0, 1;\n}"
      : "+f"(d[0]), "+f"(d[1]), "+f"(d[2]), "+f"(d[3]), "+f"(d[4]), "+f"(d[5]), "+f"(d[6]), "+f"(d[7]), "+f"(d[8]), "+f"(d[9]), "+f"(d[10]), "+f"(d[11]), "+f"(d[12]), "+f"(d[13]), "+f"(d[14]), "+f"(d[15]), "+f"(d[16]), "+f"(d[17]), "+f"(d[18]), "+f"(d[19]), "+f"(d[20]), "+f"(d[21]), "+f"(d[22]), "+f"(d[23]), "+f"(d[24]), "+f"(d[25]), "+f"(d[26]), "+f"(d[27]), "+f"(d[28]), "+f"(d[29]), "+f"(d[30]), "+f"(d[31]), "+f"(d[32]), "+f"(d[33]), "+f"(d[34]), "+f"(d[35]), "+f"(d[36]), "+f"(d[37]), "+f"(d[38]), "+f"(d[39]), "+f"(d[40]), "+f"(d[41]), "+f"(d[42]), "+f"(d[43]), "+f"(d[44]), "+f"(d[45]), "+f"(d[46]), "+f"(d[47]), "+f"(d[48]), "+f"(d[49]), "+f"(d[50]), "+f"(d[51]), "+f"(d[52]), "+f"(d[53]), "+f"(d[54]), "+f"(d[55]), "+f"(d[56]), "+f"(d[57]), "+f"(d[58]), "+f"(d[59]), "+f"(d[60]), "+f"(d[61]), "+f"(d[62]), "+f"(d[63])
      : "l"(adesc), "l"(bdesc), "r"(scale_d));
}
__device__ __forceinline__ void wgmma_ss_n192(float (&d)[96], uint64_t adesc, uint64_t bdesc, int scale_d) {
    asm volatile("{\n.reg .pred p;\nsetp.ne.b32 p, %98, 0;\n"
      "wgmma.mma_async.sync.aligned.m64n192k16.f32.bf16.bf16 {%0,%1,%2,%3,%4,%5,%6,%7,%8,%9,%10,%11,%12,%13,%14,%15,%16,%17,%18,%19,%20,%21,%22,%23,%24,%25,%26,%27,%28,%29,%30,%31,%32,%33,%34,%35,%36,%37,%38,%39,%40,%41,%42,%43,%44,%45,%46,%47,%48,%49,%50,%51,%52,%53,%54,%55,%56,%57,%58,%59,%60,%61,%62,%63,%64,%65,%66,%67,%68,%69,%70,%71,%72,%73,%74,%75,%76,%77,%78,%79,%80,%81,%82,%83,%84,%85,%86,%87,%88,%89,%90,%91,%92,%93,%94,%95}, %96, %97, p, 1, 1, 0, 1;\n}"
      : "+f"(d[0]), "+f"(d[1]), "+f"(d[2]), "+f"(d[3]), "+f"(d[4]), "+f"(d[5]), "+f"(d[6]), "+f"(d[7]), "+f"(d[8]), "+f"(d[9]), "+f"(d[10]), "+f"(d[11]), "+f"(d[12]), "+f"(d[13]), "+f"(d[14]), "+f"(d[15]), "+f"(d[16]), "+f"(d[17]), "+f"(d[18]), "+f"(d[19]), "+f"(d[20]), "+f"(d[21]), "+f"(d[22]), "+f"(d[23]), "+f"(d[24]), "+f"(d[25]), "+f"(d[26]), "+f"(d[27]), "+f"(d[28]), "+f"(d[29]), "+f"(d[30]), "+f"(d[31]), "+f"(d[32]), "+f"(d[33]), "+f"(d[34]), "+f"(d[35]), "+f"(d[36]), "+f"(d[37]), "+f"(d[38]), "+f"(d[39]), "+f"(d[40]), "+f"(d[41]), "+f"(d[42]), "+f"(d[43]), "+f"(d[44]), "+f"(d[45]), "+f"(d[46]), "+f"(d[47]), "+f"(d[48]), "+f"(d[49]), "+f"(d[50]), "+f"(d[51]), "+f"(d[52]), "+f"(d[53]), "+f"(d[54]), "+f"(d[55]), "+f"(d[56]), "+f"(d[57]), "+f"(d[58]), "+f"(d[59]), "+f"(d[60]), "+f"(d[61]), "+f"(d[62]), "+f"(d[63]), "+f"(d[64]), "+f"(d[65]), "+f"(d[66]), "+f"(d[67]), "+f"(d[68]), "+f"(d[69]), "+f"(d[70]), "+f"(d[71]), "+f"(d[72]), "+f"(d[73]), "+f"(d[74]), "+f"(d[75]), "+f"(d[76]), "+f"(d[77]), "+f"(d[78]), "+f"(d[79]), "+f"(d[80]), "+f"(d[81]), "+f"(d[82]), "+f"(d[83]), "+f"(d[84]), "+f"(d[85]), "+f"(d[86]), "+f"(d[87]), "+f"(d[88]), "+f"(d[89]), "+f"(d[90]), "+f"(d[91]), "+f"(d[92]), "+f"(d[93]), "+f"(d[94]), "+f"(d[95])
      : "l"(adesc), "l"(bdesc), "r"(scale_d));
}
__device__ __forceinline__ void wgmma_ss_n256(float (&d)[128], uint64_t adesc, uint64_t bdesc, int scale_d) {
    asm volatile("{\n.reg .pred p;\nsetp.ne.b32 p, %130, 0;\n"
      "wgmma.mma_async.sync.aligned.m64n256k16.f32.bf16.bf16 {%0,%1,%2,%3,%4,%5,%6,%7,%8,%9,%10,%11,%12,%13,%14,%15,%16,%17,%18,%19,%20,%21,%22,%23,%24,%25,%26,%27,%28,%29,%30,%31,%32,%33,%34,%35,%36,%37,%38,%39,%40,%41,%42,%43,%44,%45,%46,%47,%48,%49,%50,%51,%52,%53,%54,%55,%56,%57,%58,%59,%60,%61,%62,%63,%64,%65,%66,%67,%68,%69,%70,%71,%72,%73,%74,%75,%76,%77,%78,%79,%80,%81,%82,%83,%84,%85,%86,%87,%88,%89,%90,%91,%92,%93,%94,%95,%96,%97,%98,%99,%100,%101,%102,%103,%104,%105,%106,%107,%108,%109,%110,%111,%112,%113,%114,%115,%116,%117,%118,%119,%120,%121,%122,%123,%124,%125,%126,%127}, %128, %129, p, 1, 1, 0, 1;\n}"
      : "+f"(d[0]), "+f"(d[1]), "+f"(d[2]), "+f"(d[3]), "+f"(d[4]), "+f"(d[5]), "+f"(d[6]), "+f"(d[7]), "+f"(d[8]), "+f"(d[9]), "+f"(d[10]), "+f"(d[11]), "+f"(d[12]), "+f"(d[13]), "+f"(d[14]), "+f"(d[15]), "+f"(d[16]), "+f"(d[17]), "+f"(d[18]), "+f"(d[19]), "+f"(d[20]), "+f"(d[21]), "+f"(d[22]), "+f"(d[23]), "+f"(d[24]), "+f"(d[25]), "+f"(d[26]), "+f"(d[27]), "+f"(d[28]), "+f"(d[29]), "+f"(d[30]), "+f"(d[31]), "+f"(d[32]), "+f"(d[33]), "+f"(d[34]), "+f"(d[35]), "+f"(d[36]), "+f"(d[37]), "+f"(d[38]), "+f"(d[39]), "+f"(d[40]), "+f"(d[41]), "+f"(d[42]), "+f"(d[43]), "+f"(d[44]), "+f"(d[45]), "+f"(d[46]), "+f"(d[47]), "+f"(d[48]), "+f"(d[49]), "+f"(d[50]), "+f"(d[51]), "+f"(d[52]), "+f"(d[53]), "+f"(d[54]), "+f"(d[55]), "+f"(d[56]), "+f"(d[57]), "+f"(d[58]), "+f"(d[59]), "+f"(d[60]), "+f"(d[61]), "+f"(d[62]), "+f"(d[63]), "+f"(d[64]), "+f"(d[65]), "+f"(d[66]), "+f"(d[67]), "+f"(d[68]), "+f"(d[69]), "+f"(d[70]), "+f"(d[71]), "+f"(d[72]), "+f"(d[73]), "+f"(d[74]), "+f"(d[75]), "+f"(d[76]), "+f"(d[77]), "+f"(d[78]), "+f"(d[79]), "+f"(d[80]), "+f"(d[81]), "+f"(d[82]), "+f"(d[83]), "+f"(d[84]), "+f"(d[85]), "+f"(d[86]), "+f"(d[87]), "+f"(d[88]), "+f"(d[89]), "+f"(d[90]), "+f"(d[91]), "+f"(d[92]), "+f"(d[93]), "+f"(d[94]), "+f"(d[95]), "+f"(d[96]), "+f"(d[97]), "+f"(d[98]), "+f"(d[99]), "+f"(d[100]), "+f"(d[101]), "+f"(d[102]), "+f"(d[103]), "+f"(d[104]), "+f"(d[105]), "+f"(d[106]), "+f"(d[107]), "+f"(d[108]), "+f"(d[109]), "+f"(d[110]), "+f"(d[111]), "+f"(d[112]), "+f"(d[113]), "+f"(d[114]), "+f"(d[115]), "+f"(d[116]), "+f"(d[117]), "+f"(d[118]), "+f"(d[119]), "+f"(d[120]), "+f"(d[121]), "+f"(d[122]), "+f"(d[123]), "+f"(d[124]), "+f"(d[125]), "+f"(d[126]), "+f"(d[127])
      : "l"(adesc), "l"(bdesc), "r"(scale_d));
}
__device__ __forceinline__ void qk_wgmma_n64(float (&d)[32], const uint32_t (&a)[4], uint64_t desc) {
    asm volatile("wgmma.mma_async.sync.aligned.m64n64k16.f32.bf16.bf16 {%0,%1,%2,%3,%4,%5,%6,%7,%8,%9,%10,%11,%12,%13,%14,%15,%16,%17,%18,%19,%20,%21,%22,%23,%24,%25,%26,%27,%28,%29,%30,%31}, {%32,%33,%34,%35}, %36, 0, 1, 1, 0;"
      : "=f"(d[0]), "=f"(d[1]), "=f"(d[2]), "=f"(d[3]), "=f"(d[4]), "=f"(d[5]), "=f"(d[6]), "=f"(d[7]), "=f"(d[8]), "=f"(d[9]), "=f"(d[10]), "=f"(d[11]), "=f"(d[12]), "=f"(d[13]), "=f"(d[14]), "=f"(d[15]), "=f"(d[16]), "=f"(d[17]), "=f"(d[18]), "=f"(d[19]), "=f"(d[20]), "=f"(d[21]), "=f"(d[22]), "=f"(d[23]), "=f"(d[24]), "=f"(d[25]), "=f"(d[26]), "=f"(d[27]), "=f"(d[28]), "=f"(d[29]), "=f"(d[30]), "=f"(d[31])
      : "r"(a[0]), "r"(a[1]), "r"(a[2]), "r"(a[3]), "l"(desc));
}

__device__ __forceinline__ void pv_wgmma(float (&d)[12], uint32_t a0, uint32_t a1, uint32_t a2, uint32_t a3, uint64_t desc) {
    asm volatile("wgmma.mma_async.sync.aligned.m64n24k16.f32.bf16.bf16 {%0,%1,%2,%3,%4,%5,%6,%7,%8,%9,%10,%11}, {%12,%13,%14,%15}, %16, 1, 1, 1, 1;"
      : "+f"(d[0]), "+f"(d[1]), "+f"(d[2]), "+f"(d[3]), "+f"(d[4]), "+f"(d[5]), "+f"(d[6]), "+f"(d[7]), "+f"(d[8]), "+f"(d[9]), "+f"(d[10]), "+f"(d[11])
      : "r"(a0), "r"(a1), "r"(a2), "r"(a3), "l"(desc));
}

__device__ __forceinline__ uint32_t mapa(uint32_t a, uint32_t rank) { uint32_t r; asm("mapa.shared::cluster.u32 %0, %1, %2;" : "=r"(r) : "r"(a), "r"(rank)); return r; }
__device__ __forceinline__ void mbar_arrive_remote(uint32_t a) { asm volatile("mbarrier.arrive.relaxed.cluster.shared::cluster.b64 _, [%0];" :: "r"(a) : "memory"); }
__device__ __forceinline__ void mbar_wait_cluster(uint32_t a, int parity) {
    uint32_t done;
    int it = 0;
    do {
        asm volatile("{\n.reg .pred p;\nmbarrier.try_wait.parity.acquire.cluster.shared::cta.b64 p, [%1], %2;\nselp.u32 %0, 1, 0, p;\n}"
                     : "=r"(done) : "r"(a), "r"(parity) : "memory");
        if (++it > (1 << 24)) __trap();
    } while (!done);
}
__device__ __forceinline__ void tma2d_mc(uint32_t dst, const CUtensorMap* m, int c0, int c1, uint32_t bar) {
    asm volatile("cp.async.bulk.tensor.2d.shared::cluster.global.mbarrier::complete_tx::bytes.multicast::cluster [%0], [%1, {%3, %4}], [%2], %5;"
                 :: "r"(dst), "l"(m), "r"(bar), "r"(c0), "r"(c1), "h"((uint16_t)3) : "memory");
}
__device__ __forceinline__ void bulk_g2s_mc(uint32_t dst, const void* src, int bytes, uint32_t bar) {
    asm volatile("cp.async.bulk.shared::cluster.global.mbarrier::complete_tx::bytes.multicast::cluster [%0], [%1], %2, [%3], %4;"
                 :: "r"(dst), "l"(src), "r"(bytes), "r"(bar), "h"((uint16_t)3) : "memory");
}
__device__ __forceinline__ void tile_of(int bid, int& mb, int& nt) {
    int grp = bid >> 4, in = bid & 15;
    mb = (grp >> 1) * 4 + (in >> 2);
    nt = (grp & 1) * 4 + (in & 3);
}

constexpr int K1_STAGES = 5, K1_STAGE = 16384 + 24576;
constexpr int K1_BAR = K1_STAGES * K1_STAGE, K1_RS = K1_BAR + 128, K1_CS = K1_RS + 1024, K1_SMEM = K1_CS + 768;

__device__ __forceinline__ float2 row_stats_regs(uint4 a, uint4 b) {
    float v[16];
    v[0] = bf_lo(a.x); v[1] = bf_hi(a.x); v[2] = bf_lo(a.y); v[3] = bf_hi(a.y);
    v[4] = bf_lo(a.z); v[5] = bf_hi(a.z); v[6] = bf_lo(a.w); v[7] = bf_hi(a.w);
    v[8] = bf_lo(b.x); v[9] = bf_hi(b.x); v[10] = bf_lo(b.y); v[11] = bf_hi(b.y);
    v[12] = bf_lo(b.z); v[13] = bf_hi(b.z); v[14] = bf_lo(b.w); v[15] = bf_hi(b.w);
    float s = 0.f;
#pragma unroll
    for (int i = 0; i < 16; i++) s += v[i];
    float mean = warp_sum(s) * (1.0f / DM);
    float q = 0.f;
#pragma unroll
    for (int i = 0; i < 16; i++) { float d = v[i] - mean; q = fmaf(d, d, q); }
    float var = warp_sum(q) * (1.0f / DM);
    float rstd = rsqrtf(var + 1e-5f);
    return make_float2(rstd, -mean * rstd);
}
__device__ __forceinline__ float2 row_stats_x(const __nv_bfloat16* x, int row, int lane) {
    const uint4* p = (const uint4*)(x + (size_t)row * DM);
    return row_stats_regs(__ldg(p + lane), __ldg(p + 32 + lane));
}
__device__ __forceinline__ void colsum8(const __nv_bfloat16* w, int ld, int col, int k0, int nk, float (&s)[8]) {
#pragma unroll
    for (int i = 0; i < 8; i++) s[i] = 0.f;
    for (int k = k0; k < k0 + nk; k += 8) {
        uint4 u[8];
#pragma unroll
        for (int i = 0; i < 8; i++) u[i] = __ldg((const uint4*)(w + (size_t)(k + i) * ld + col));
#pragma unroll
        for (int i = 0; i < 8; i++) {
            s[0] += bf_lo(u[i].x); s[1] += bf_hi(u[i].x); s[2] += bf_lo(u[i].y); s[3] += bf_hi(u[i].y);
            s[4] += bf_lo(u[i].z); s[5] += bf_hi(u[i].z); s[6] += bf_lo(u[i].w); s[7] += bf_hi(u[i].w);
        }
    }
}
__device__ __forceinline__ bool wait_count(const unsigned int* p, unsigned int target, int lane) {
    int ok = 1;
    if (lane == 0) {
        int it = 0;
        while (ld_acquire(p) < target) { if (++it > (1 << 18)) { ok = 0; break; } }
    }
    ok = __shfl_sync(0xffffffffu, ok, 0);
    return ok != 0;
}

__global__ void __launch_bounds__(384, 1)
qkv_kernel(const __grid_constant__ CUtensorMap tm_x, const __grid_constant__ CUtensorMap tm_w,
           const __nv_bfloat16* __restrict__ x, const __nv_bfloat16* __restrict__ wqkv) {
    extern __shared__ __align__(1024) unsigned char smem[];
    const uint32_t sb = smem_u32(smem);
    const int tid = threadIdx.x, warp = __shfl_sync(0xffffffffu, tid >> 5, 0), lane = tid & 31;
    int mb, nt;
    tile_of(blockIdx.x, mb, nt);
    const uint32_t full = sb + K1_BAR, empty = full + 40, auxb = full + 80;
    if (tid == 0) {
#pragma unroll
        for (int i = 0; i < K1_STAGES; i++) { mbar_init(full + 8 * i, 1); mbar_init(empty + 8 * i, 8); }
        mbar_init(auxb, 3);
        fence_barrier_init();
        for (int kb = 0; kb < K1_STAGES; kb++) {
            mbar_expect(full + 8 * kb, K1_STAGE);
            tma2d(sb + kb * K1_STAGE, &tm_x, kb * 64, mb * 128, full + 8 * kb);
            tma3d(sb + kb * K1_STAGE + 16384, &tm_w, 0, kb * 64, nt * 3, full + 8 * kb);
        }
    }
    __syncthreads();
    pdl_launch();
    if (warp == 0) {
        if (blockIdx.x == 0) g_cnt2[lane] = 0;
        if (lane == 0) {
            g_cnt2[32 + blockIdx.x] = 0;
            for (int kb = K1_STAGES; kb < 8; kb++) {
                int s = kb % K1_STAGES;
                mbar_wait(empty + 8 * s, 0);
                mbar_expect(full + 8 * s, K1_STAGE);
                tma2d(sb + s * K1_STAGE, &tm_x, kb * 64, mb * 128, full + 8 * s);
                tma3d(sb + s * K1_STAGE + 16384, &tm_w, 0, kb * 64, nt * 3, full + 8 * s);
            }
        }
    } else if (warp < 4) {
        float2* s_rs = (float2*)(smem + K1_RS);
        float* s_cs = (float*)(smem + K1_CS);
        if (warp < 3) {
            const int r0 = mb * 128 + nt * 16 + (warp - 1) * 8;
            uint4 u[16];
#pragma unroll
            for (int i = 0; i < 8; i++) {
                const uint4* p = (const uint4*)(x + (size_t)(r0 + i) * DM);
                u[2 * i] = __ldg(p + lane); u[2 * i + 1] = __ldg(p + 32 + lane);
            }
            float2 mine = make_float2(0.f, 0.f);
#pragma unroll
            for (int i = 0; i < 8; i++) {
                float2 st = row_stats_regs(u[2 * i], u[2 * i + 1]);
                if (lane == i) mine = st;
            }
            if (lane < 8) g_rowstat1[r0 + lane] = mine;
            __syncwarp();
            if (lane == 0) red_release(&g_cnt[mb]);
        } else {
            uint4 u[24];
#pragma unroll
            for (int c = 0; c < 3; c++)
#pragma unroll
                for (int i = 0; i < 8; i++)
                    u[c * 8 + i] = __ldg((const uint4*)(wqkv + (size_t)(mb * 32 + (lane >> 3) * 8 + i) * 1536 + nt * 192 + (c * 8 + (lane & 7)) * 8));
#pragma unroll
            for (int c = 0; c < 3; c++) {
                float cs[8];
#pragma unroll
                for (int i = 0; i < 8; i++) cs[i] = 0.f;
#pragma unroll
                for (int i = 0; i < 8; i++) {
                    const uint4 w = u[c * 8 + i];
                    cs[0] += bf_lo(w.x); cs[1] += bf_hi(w.x); cs[2] += bf_lo(w.y); cs[3] += bf_hi(w.y);
                    cs[4] += bf_lo(w.z); cs[5] += bf_hi(w.z); cs[6] += bf_lo(w.w); cs[7] += bf_hi(w.w);
                }
#pragma unroll
                for (int i = 0; i < 8; i++) {
                    cs[i] += __shfl_xor_sync(0xffffffffu, cs[i], 8);
                    cs[i] += __shfl_xor_sync(0xffffffffu, cs[i], 16);
                }
                if (lane < 8) {
                    float4* d = (float4*)(g_cs1_part + mb * 1536 + nt * 192 + (c * 8 + lane) * 8);
                    d[0] = make_float4(cs[0], cs[1], cs[2], cs[3]);
                    d[1] = make_float4(cs[4], cs[5], cs[6], cs[7]);
                }
            }
            __syncwarp();
            if (lane == 0) red_release(&g_cnt[16 + nt]);
        }
        if (warp == 1) {
            if (wait_count(&g_cnt[mb], 16, lane)) {
#pragma unroll
                for (int i = 0; i < 4; i++) s_rs[lane + 32 * i] = __ldcg(&g_rowstat1[mb * 128 + lane + 32 * i]);
            } else {
                for (int i = 0; i < 128; i++) {
                    float2 st = row_stats_x(x, mb * 128 + i, lane);
                    if (lane == 0) s_rs[i] = st;
                }
            }
        } else {
            int c0 = (warp - 2) * 96;
            if (wait_count(&g_cnt[16 + nt], 16, lane)) {
#pragma unroll
                for (int i = 0; i < 3; i++) {
                    float s = 0.f;
#pragma unroll
                    for (int p = 0; p < 16; p++) s += __ldcg(&g_cs1_part[p * 1536 + nt * 192 + c0 + lane + 32 * i]);
                    s_cs[c0 + lane + 32 * i] = s;
                }
            } else if (lane < 12) {
                float s[8];
                colsum8(wqkv, 1536, nt * 192 + c0 + lane * 8, 0, 512, s);
#pragma unroll
                for (int i = 0; i < 8; i++) s_cs[c0 + lane * 8 + i] = s[i];
            }
        }
        __syncwarp();
        if (lane == 0) mbar_arrive(auxb);
        bar_sync(2, 256 + 96);
        const int a = tid - 32;
        {
            const int hh = a >> 3, w = a & 7;
            const float4* p = (const float4*)(smem + 49152) + (hh * 256 + w * 32) / 2;
            float m = 0.f;
#pragma unroll
            for (int i = 0; i < 8; i++) {
                const int ii = (i + a) & 7;
                float4 u = p[2 * ii], v = p[2 * ii + 1];
                float n0 = u.x + u.z + v.x + v.z, n1 = u.y + u.w + v.y + v.w;
                if (!(n0 <= 3.0e38f) || !(n1 <= 3.0e38f)) m = __int_as_float(0x7f800000);
                m = fmaxf(m, fmaxf(n0, n1));
            }
            const int col0 = nt * 192 + hh * 16;
            g_nrm[((col0 >> 9) * NH + ((col0 & 511) >> 4)) * 128 + mb * 8 + w] = m;
        }
    } else {
        const int wgi = (warp >> 2) - 1, ww = warp & 3;
        float acc[96];
#pragma unroll 1
        for (int kb = 0; kb < 8; kb++) {
            int s = kb % K1_STAGES;
            mbar_wait(full + 8 * s, (kb / K1_STAGES) & 1);
            uint64_t ad = make_desc(sb + s * K1_STAGE + wgi * 8192, 16, 1024, 1);
            uint64_t bd = make_desc(sb + s * K1_STAGE + 16384, 8192, 1024, 1);
            WG_FENCE();
#pragma unroll
            for (int k = 0; k < 4; k++) wgmma_ss_n192(acc, ad + k * 2, bd + k * 128, (kb | k) != 0);
            WG_COMMIT();
            if (kb > 0) {
                wg_wait<1>();
                if (lane == 0) mbar_arrive(empty + 8 * ((kb - 1) % K1_STAGES));
            }
        }
        wg_wait<0>();
        fence_regs(acc);
        mbar_wait(auxb, 0);
        bar_sync(1, 256);
        const float2* s_rs = (const float2*)(smem + K1_RS);
        const float* s_cs = (const float*)(smem + K1_CS);
        const int g = lane >> 2, t = lane & 3;
        const int rl = wgi * 64 + ww * 16 + g;
        const float2 st0 = s_rs[rl], st1 = s_rs[rl + 8];
        const float QS = 0.25f * 1.4426950408889634f;
        float2* s_np = (float2*)(smem + 49152) + (warp - 4) * 32 + lane;
#pragma unroll
        for (int hh = 0; hh < 12; hh++) {
            const int which = (nt * 192 + hh * 16) >> 9;
            const float sc = (which == 0) ? QS : 1.0f;
            const float a0 = st0.x * sc, b0 = st0.y * sc, a1 = st1.x * sc, b1 = st1.y * sc;
            const float2 c0 = *(const float2*)(s_cs + 16 * hh + 2 * t), c1 = *(const float2*)(s_cs + 16 * hh + 8 + 2 * t);
            const float* a = acc + 8 * hh;
            float v0 = fmaf(a0, a[0], b0 * c0.x), v1 = fmaf(a0, a[1], b0 * c0.y), v2 = fmaf(a1, a[2], b1 * c0.x), v3 = fmaf(a1, a[3], b1 * c0.y);
            float v4 = fmaf(a0, a[4], b0 * c1.x), v5 = fmaf(a0, a[5], b0 * c1.y), v6 = fmaf(a1, a[6], b1 * c1.x), v7 = fmaf(a1, a[7], b1 * c1.y);
            {
                const int head = ((nt * 192 + hh * 16) & 511) >> 4;
                uint32_t* o = (uint32_t*)g_qkv + ((size_t)((which * NH + head) * 2) * 256 + mb * 16 + wgi * 8 + ww * 2) * 32 + lane;
                o[0] = pack_bf16(v0, v1); o[32] = pack_bf16(v2, v3); o[8192] = pack_bf16(v4, v5); o[8192 + 32] = pack_bf16(v6, v7);
            }
            s_np[hh * 256] = make_float2(fmaf(v0, v0, fmaf(v1, v1, fmaf(v4, v4, v5 * v5))), fmaf(v2, v2, fmaf(v3, v3, fmaf(v6, v6, v7 * v7))));
        }
        bar_arrive(2, 256 + 96);
    }
}

constexpr int AT_K = 0, AT_V = 65536, AT_ONES = 131072, AT_BAR = 163840, AT_SMEM = AT_BAR + 128;
constexpr uint32_t POLY_MASK = 0x7B5A;

__device__ __forceinline__ uint32_t exp2_pair_poly(float x0, float x1) {
    uint32_t t0 = __float_as_uint(x0 + 32895.0f);
    uint32_t t1 = __float_as_uint(x1 + 32895.0f);
    uint32_t gd = __byte_perm(t0, t1, 0x6420);
    uint32_t wm = __byte_perm(t0, t1, 0x5612);
    uint32_t v = hfma2(gd, 0x712d712du, 0x355c355cu);
    uint32_t z = hmul2(v, gd);
    return (wm >> 1) + z;
}
__device__ __forceinline__ uint32_t exp2_pair_mufu(float x0, float x1) { return pack_bf16(ex2f(x0), ex2f(x1)); }
template <uint32_t MASK>
__device__ __forceinline__ void exp_blocks(const float (&s)[32], uint32_t (&p)[16]) {
#pragma unroll
    for (int b = 0; b < 8; b++) {
        if ((MASK >> b) & 1) {
            p[2 * b] = exp2_pair_poly(s[4 * b], s[4 * b + 1]);
            p[2 * b + 1] = exp2_pair_poly(s[4 * b + 2], s[4 * b + 3]);
        } else {
            p[2 * b] = exp2_pair_mufu(s[4 * b], s[4 * b + 1]);
            p[2 * b + 1] = exp2_pair_mufu(s[4 * b + 2], s[4 * b + 3]);
        }
    }
}
#define PV4(P) _Pragma("unroll") for (int i = 0; i < 4; i++) { pv_wgmma(o, P[4 * i], P[4 * i + 1], P[4 * i + 2], P[4 * i + 3], vd); vd += 16; }

__device__ __forceinline__ void attn_store(float (&o)[12], int row0, int head, int lane) {
    float l0 = __shfl_sync(0xffffffffu, o[8], lane & 28);
    float l1 = __shfl_sync(0xffffffffu, o[10], lane & 28);
    float r0 = 1.0f / l0, r1 = 1.0f / l1;
    uint32_t* op = (uint32_t*)g_ao;
    int mb = row0 >> 7, rg = (row0 & 127) >> 3;
    int kb = head >> 2, kc = (head & 3) * 2;
    size_t base = (((size_t)(mb * 8 + kb) * 8 + kc) * 16 + rg) * 32 + lane;
    op[base] = pack_bf16(o[0] * r0, o[1] * r0);
    op[base + 32] = pack_bf16(o[2] * r1, o[3] * r1);
    op[base + 16 * 32] = pack_bf16(o[4] * r0, o[5] * r0);
    op[base + 16 * 32 + 32] = pack_bf16(o[6] * r1, o[7] * r1);
}

__device__ __forceinline__ void attn_load_q(uint32_t (&q)[4], const __nv_bfloat16* gq, int row0, int lane) {
    const uint32_t* qp = (const uint32_t*)gq;
    int j0 = row0 >> 3;
    q[0] = __ldcg(qp + (0 * 256 + j0) * 32 + lane);
    q[1] = __ldcg(qp + (0 * 256 + j0 + 1) * 32 + lane);
    q[2] = __ldcg(qp + (1 * 256 + j0) * 32 + lane);
    q[3] = __ldcg(qp + (1 * 256 + j0 + 1) * 32 + lane);
}

__device__ __forceinline__ void attn_tile_safe(const uint32_t (&q)[4], uint64_t kd, uint64_t vd, int row0, int head, int lane) {
    float o[12];
#pragma unroll
    for (int i = 0; i < 12; i++) o[i] = 0.f;
    float m0 = -INFINITY, m1 = -INFINITY;
    fence_regs(o);
#pragma unroll 1
    for (int j = 0; j < 32; j++) {
        float s[32];
        uint32_t p[16];
        WG_FENCE();
        qk_wgmma_n64(s, q, kd); kd += 64;
        WG_COMMIT();
        wg_wait<0>();
        fence_regs(s);
        fence_regs(o);
        float x0 = m0, x1 = m1;
#pragma unroll
        for (int b = 0; b < 8; b++) {
            x0 = fmaxf(x0, fmaxf(s[4 * b], s[4 * b + 1]));
            x1 = fmaxf(x1, fmaxf(s[4 * b + 2], s[4 * b + 3]));
        }
        x0 = fmaxf(x0, __shfl_xor_sync(0xffffffffu, x0, 1)); x0 = fmaxf(x0, __shfl_xor_sync(0xffffffffu, x0, 2));
        x1 = fmaxf(x1, __shfl_xor_sync(0xffffffffu, x1, 1)); x1 = fmaxf(x1, __shfl_xor_sync(0xffffffffu, x1, 2));
        float al0 = ex2f(m0 - x0), al1 = ex2f(m1 - x1);
        m0 = x0; m1 = x1;
#pragma unroll
        for (int i = 0; i < 3; i++) { o[4 * i] *= al0; o[4 * i + 1] *= al0; o[4 * i + 2] *= al1; o[4 * i + 3] *= al1; }
#pragma unroll
        for (int b = 0; b < 8; b++) {
            p[2 * b] = exp2_pair_mufu(s[4 * b] - m0, s[4 * b + 1] - m0);
            p[2 * b + 1] = exp2_pair_mufu(s[4 * b + 2] - m1, s[4 * b + 3] - m1);
        }
        fence_regs(o);
        WG_FENCE();
        PV4(p);
        WG_COMMIT();
        wg_wait<0>();
        fence_regs(o);
    }
    attn_store(o, row0, head, lane);
}

__global__ void __launch_bounds__(512, 1)
attn_kernel(const __nv_bfloat16* __restrict__ wg_, const __nv_bfloat16* __restrict__ wu_,
            const __nv_bfloat16* __restrict__ wo_, const __nv_bfloat16* __restrict__ wd_) {
    extern __shared__ __align__(1024) unsigned char smem[];
    const uint32_t sb = smem_u32(smem);
    const int tid = threadIdx.x, wg = tid >> 7, warp = (tid >> 5) & 3, lane = tid & 31;
    pdl_launch();
    if (blockIdx.x >= 128) {
        const int e = blockIdx.x - 128;
        const __nv_bfloat16* w = (e < 2) ? wg_ : wu_;
        float* red = (float*)smem;
        const int cgrp = tid & 127, kq = tid >> 7;
        if (cgrp < 112) {
            float s[8];
            colsum8(w, FF, (e & 1) * 896 + cgrp * 8, kq * 128, 128, s);
#pragma unroll
            for (int i = 0; i < 8; i++) red[kq * 896 + cgrp * 8 + i] = s[i];
        }
        __syncthreads();
        for (int c = tid; c < 896; c += 512)
            g_cs2[(e >> 1) * FF + (e & 1) * 896 + c] = red[c] + red[896 + c] + red[1792 + c] + red[2688 + c];
        if (tid < 32) {
            const char* p0 = (const char*)wo_ + e * (DM * DM * 2 / 4);
            for (int i = lane; i < 32; i += 32)
                asm volatile("cp.async.bulk.prefetch.L2.global [%0], %1;" :: "l"(p0 + i * 4096), "r"(4096) : "memory");
            const char* p1 = (const char*)wd_ + e * (FF * DM * 2 / 4);
            for (int i = lane; i < 112; i += 32)
                asm volatile("cp.async.bulk.prefetch.L2.global [%0], %1;" :: "l"(p1 + i * 4096), "r"(4096) : "memory");
        }
        return;
    }
    const int head = blockIdx.x >> 2, qq = blockIdx.x & 3;
    const __nv_bfloat16* gq = g_qkv + (size_t)head * (S_LEN * 16);
    const __nv_bfloat16* gk = g_qkv + (size_t)(NH + head) * (S_LEN * 16);
    const __nv_bfloat16* gv = g_qkv + (size_t)(2 * NH + head) * (S_LEN * 16);
    if (tid == 0) {
        for (int i = 0; i < 8; i++) mbar_init(sb + AT_BAR + 8 * i, 1);
        fence_barrier_init();
    }
    {
        uint4 one = make_uint4(0x00003F80u, 0, 0, 0);
#pragma unroll
        for (int i = 0; i < 4; i++) *(uint4*)(smem + AT_ONES + (i * 512 + tid) * 16) = one;
        fence_proxy_async();
    }
    __syncthreads();
    pdl_wait();
    auto load_kv = [&](int i) {
        uint32_t bar = sb + AT_BAR + 8 * i;
        mbar_expect(bar, 16384);
        bulk_g2s(sb + AT_K + i * 4096, gk + i * 2048, 4096, bar);
        bulk_g2s(sb + AT_K + 32768 + i * 4096, gk + 16384 + i * 2048, 4096, bar);
        bulk_g2s(sb + AT_V + i * 4096, gv + i * 2048, 4096, bar);
        bulk_g2s(sb + AT_V + 32768 + i * 4096, gv + 16384 + i * 2048, 4096, bar);
    };
    if (tid == 0) load_kv(0);
    if (tid == 128) load_kv(1);
    uint32_t q[4], q2[4];
    attn_load_q(q, gq, qq * 512 + wg * 64 + warp * 16, lane);
    attn_load_q(q2, gq, qq * 512 + (4 + wg) * 64 + warp * 16, lane);
    bool fast;
    {
        const float* nq = g_nrm + (0 * NH + head) * 128 + qq * 32;
        const float* nk = g_nrm + (1 * NH + head) * 128;
        const float* nv = g_nrm + (2 * NH + head) * 128;
        float4 k4 = __ldcg((const float4*)nk + lane), v4 = __ldcg((const float4*)nv + lane);
        float qm = warp_max(__ldcg(nq + lane));
        float km = warp_max(fmaxf(fmaxf(k4.x, k4.y), fmaxf(k4.z, k4.w)));
        float vm = warp_max(fmaxf(fmaxf(v4.x, v4.y), fmaxf(v4.z, v4.w)));
        fast = __all_sync(0xffffffffu, 1.01f * sqrtf(qm * km) + 0.5f * log2f(fmaxf(vm, 1.0f)) <= 100.0f);
    }
    const uint64_t kdesc0 = make_desc(sb + AT_K, 32768, 128, 0);
    const uint64_t vdesc0 = make_desc(sb + AT_V, 128, 32768, 0);
    if (!fast) {
        if (tid == 0) for (int i = 2; i < 8; i++) load_kv(i);
        for (int i = 0; i < 8; i++) mbar_wait(sb + AT_BAR + 8 * i, 0);
#pragma unroll 1
        for (int tile = 0; tile < 2; tile++) {
            const int row0 = qq * 512 + (tile * 4 + wg) * 64 + warp * 16;
            attn_tile_safe(q, kdesc0, vdesc0, row0, head, lane);
#pragma unroll
            for (int i = 0; i < 4; i++) q[i] = q2[i];
        }
        return;
    }
#pragma unroll 1
    for (int tile = 0; tile < 2; tile++) {
        const int row0 = qq * 512 + (tile * 4 + wg) * 64 + warp * 16;
        float o[12];
#pragma unroll
        for (int i = 0; i < 12; i++) o[i] = 0.f;
        fence_regs(o);
        float sa[32];
        uint32_t pa[16];
        uint64_t kd = kdesc0, vd = vdesc0;
        if (tile == 0) {
            mbar_wait(sb + AT_BAR, 0);
            if (wg) __nanosleep(wg * 100);
        }
        WG_FENCE();
        qk_wgmma_n64(sa, q, kd); kd += 64;
        WG_COMMIT();
#pragma unroll 1
        for (int jj = 0; jj < 8; jj++) {
            if (tile == 0 && jj < 7) {
                if ((tid & 127) == 0 && jj < 6 && ((jj + 2) & 3) == wg) load_kv(jj + 2);
                mbar_wait(sb + AT_BAR + 8 * (jj + 1), 0);
            }
#pragma unroll
            for (int j = 0; j < 4; j++) {
                wg_wait<0>();
                fence_regs(sa);
                if (j & 1) exp_blocks<(POLY_MASK >> 8)>(sa, pa); else exp_blocks<(POLY_MASK & 255)>(sa, pa);
                WG_FENCE();
                PV4(pa);
                qk_wgmma_n64(sa, q, kd); kd += 64;
                WG_COMMIT();
            }
        }
        wg_wait<0>();
        fence_regs(o);
        fence_regs(sa);
        attn_store(o, row0, head, lane);
#pragma unroll
        for (int i = 0; i < 4; i++) q[i] = q2[i];
    }
}

constexpr int F_R2 = 131072, F_X = 196608, F_BAR = 229376;
constexpr int F_RS = F_BAR + 256, F_CS = F_RS + 1024, F_SMEM = F_CS + 1792;
enum { B_FA = 0, B_HF = 4, B_BF = 8, B_BE = 11, B_CF = 14, B_CE = 20, B_ADONE = 26, B_BDONE = 27, B_XC = 28, B_PRDY = 29, B_AUX = 30, B_NUM = 31 };

__device__ __forceinline__ void st_async4(uint32_t dst, float a, float b, float c, float d, uint32_t bar) {
    asm volatile("st.async.weak.shared::cluster.mbarrier::complete_tx::bytes.v4.f32 [%0], {%1,%2,%3,%4}, [%5];"
                 :: "r"(dst), "f"(a), "f"(b), "f"(c), "f"(d), "r"(bar) : "memory");
}
__device__ __forceinline__ void poll_count(const unsigned int* p, unsigned int target) {
    int it = 0;
    while (ld_acquire(p) < target) { if (++it > (1 << 22)) __trap(); }
    asm volatile("fence.proxy.async.global;" ::: "memory");
}
__device__ __forceinline__ void tma2d_store(const CUtensorMap* m, uint32_t src, int c0, int c1) {
    asm volatile("cp.async.bulk.tensor.2d.global.shared::cta.bulk_group [%0, {%2, %3}], [%1];" :: "l"(m), "r"(src), "r"(c0), "r"(c1) : "memory");
}
__device__ __forceinline__ float2 h_row_stats(int row) {
    const float4* hp = (const float4*)(g_hstat + (size_t)row * 8);
    float4 a = __ldcg(hp), b = __ldcg(hp + 1), c = __ldcg(hp + 2), d = __ldcg(hp + 3);
    float mean = 0.125f * (a.x + a.z + b.x + b.z + c.x + c.z + d.x + d.z);
    float m2 = a.y + a.w + b.y + b.w + c.y + c.w + d.y + d.w;
    float e;
    e = a.x - mean; m2 = fmaf(64.f * e, e, m2); e = a.z - mean; m2 = fmaf(64.f * e, e, m2);
    e = b.x - mean; m2 = fmaf(64.f * e, e, m2); e = b.z - mean; m2 = fmaf(64.f * e, e, m2);
    e = c.x - mean; m2 = fmaf(64.f * e, e, m2); e = c.z - mean; m2 = fmaf(64.f * e, e, m2);
    e = d.x - mean; m2 = fmaf(64.f * e, e, m2); e = d.z - mean; m2 = fmaf(64.f * e, e, m2);
    return make_float2(rsqrtf(m2 * (1.0f / DM) + 1e-5f), -mean);
}
__device__ __forceinline__ int c_kblock(int i, int r) {
    if (i < 6) { const int e = 2 * i + r, m = e / 3, k = e - 3 * m; return 7 * m + (k == 2 ? 4 : k); }
    const int l = 2 * (i - 6) + r, m = l >> 2, k = l & 3;
    return 7 * m + (k < 2 ? 2 + k : 3 + k);
}
__device__ __forceinline__ uint32_t c_stage_a(int s, int ntB) { return s < 4 ? ((ntB + 2 * s) & 7) * 16384 : F_R2 + (s - 4) * 32768; }
__device__ __forceinline__ uint32_t c_stage_b(int s, int ntB) { return s < 4 ? ((ntB + 2 * s + 1) & 7) * 16384 : F_R2 + (s - 4) * 32768 + 16384; }
template <int R>
__device__ __forceinline__ void xchg(float (&acc)[64], float (&o)[32], uint32_t sb, unsigned char* smem, int bar, int ctid) {
    const uint32_t dst = mapa(sb + F_X + ctid * 16, 1 - R), rb = mapa(sb + F_BAR + 8 * bar, 1 - R);
#pragma unroll
    for (int q = 0; q < 8; q++) {
        const int j = (1 - R) * 32 + 4 * q;
        st_async4(dst + q * 4096, acc[j], acc[j + 1], acc[j + 2], acc[j + 3], rb);
    }
    mbar_wait_cluster(sb + F_BAR + 8 * bar, 0);
#pragma unroll
    for (int q = 0; q < 8; q++) {
        float4 v = *(const float4*)(smem + F_X + q * 4096 + ctid * 16);
        const int j = R * 32 + 4 * q;
        o[4 * q] = acc[j] + v.x; o[4 * q + 1] = acc[j + 1] + v.y; o[4 * q + 2] = acc[j + 2] + v.z; o[4 * q + 3] = acc[j + 3] + v.w;
    }
}

template <int NB>
__device__ __forceinline__ void ffn_epilogue(const float* ag, const float* au, const float* s_cs, int cs_off, uint32_t* gp,
                                             float2 st0, float2 st1, int lane) {
    const int t = lane & 3;
    const float C1 = 0.7978845608028654f, C2 = 0.044715f * 0.7978845608028654f;
#pragma unroll
    for (int j2 = 0; j2 < NB / 2; j2++) {
        uint32_t pk[4];
#pragma unroll
        for (int jj = 0; jj < 2; jj++) {
            const int j = 2 * j2 + jj;
            const float2 cg = *(const float2*)(s_cs + cs_off + 8 * j + 2 * t);
            const float2 cu = *(const float2*)(s_cs + 224 + cs_off + 8 * j + 2 * t);
            float r[4];
#pragma unroll
            for (int e = 0; e < 4; e++) {
                const float nm = (e < 2) ? st0.y : st1.y, rs = (e < 2) ? st0.x : st1.x;
                const float gt = rs * fmaf(nm, (e & 1) ? cg.y : cg.x, ag[4 * j + e]);
                const float tu = fmaf(nm, (e & 1) ? cu.y : cu.x, au[4 * j + e]);
                const float th = tanh_fast(gt * fmaf(gt * gt, C2, C1));
                const float p = gt * tu;
                r[e] = fmaf(p, th, p);
            }
            pk[2 * jj] = pack_bf16(r[0], r[1]);
            pk[2 * jj + 1] = pack_bf16(r[2], r[3]);
        }
        gp[j2 * 1024] = pk[0]; gp[j2 * 1024 + 32] = pk[1]; gp[j2 * 1024 + 512] = pk[2]; gp[j2 * 1024 + 544] = pk[3];
    }
}

__global__ void __cluster_dims__(2, 1, 1) __launch_bounds__(384, 1)
tail_kernel(const __grid_constant__ CUtensorMap tm_o, const __grid_constant__ CUtensorMap tm_g,
            const __grid_constant__ CUtensorMap tm_u, const __grid_constant__ CUtensorMap tm_d,
            const __grid_constant__ CUtensorMap tm_out, const __nv_bfloat16* __restrict__ x) {
    extern __shared__ __align__(1024) unsigned char smem[];
    const uint32_t sb = smem_u32(smem);
    const uint32_t bars = sb + F_BAR;
    const int tid = threadIdx.x, warp = __shfl_sync(0xffffffffu, tid >> 5, 0), lane = tid & 31;
    const int cl = blockIdx.x >> 1, r = blockIdx.x & 1;
    const int mb = cl & 15, ntA = cl >> 4;
    const int nt = ntA * 2 + r;
    const int mbB = (mb & ~1) + r, ntB = (mb & 1) * 4 + ntA;
    if (tid == 0) {
#pragma unroll
        for (int i = 0; i < B_NUM; i++) {
            const int cnt = (i >= B_BE && i < B_BE + 3) ? 16 : (i == B_BDONE) ? 9 : ((i >= B_CE && i < B_CE + 6) || i == B_PRDY) ? 8 : (i == B_AUX || i == B_ADONE) ? 2 : 1;
            mbar_init(bars + 8 * i, cnt);
        }
        mbar_expect(bars + 8 * B_XC, 32768);
        fence_barrier_init();
        for (int i = 0; i < 8; i++) {
            const uint32_t bar = bars + 8 * (B_FA + (i >> 1));
            if (!(i & 1)) mbar_expect(bar, 49152);
            tma2d(sb + F_R2 + 32768 + i * 8192, &tm_o, nt * 64, i * 64, bar);
        }
    }
    __syncthreads();
    asm volatile("barrier.cluster.arrive.relaxed.aligned;" ::: "memory");
    if (warp < 4) {
        asm volatile("setmaxnreg.dec.sync.aligned.u32 56;");
        if (warp == 0) {
            if (lane == 0) {
                auto load_b = [&](int it) {
                    const int s = it % 3, pass = it >> 3, kb = (ntB + it) & 7;
                    const int ng = pass ? 3 : 4, c0 = ntB * 224 + pass * 128;
                    const uint32_t bar = bars + 8 * (B_BF + s), dst = sb + F_R2 + s * 32768 + r * ng * 4096;
                    mbar_expect(bar, ng * 8192);
                    for (int i = 0; i < ng; i++) tma2d_mc(dst + i * 4096, r ? &tm_u : &tm_g, c0 + i * 32, kb * 64, bar);
                };
                asm volatile("barrier.cluster.wait.acquire;" ::: "memory");
                pdl_wait();
                for (int i = 0; i < 4; i++)
                    bulk_g2s_mc(sb + (2 * i + r) * 16384, g_ao + (size_t)(mb * 8 + 2 * i + r) * 8192, 16384, bars + 8 * (B_FA + i));
                load_b(0);
                if (blockIdx.x == 0)
                    for (int i = 0; i < 32; i++) g_cnt[i] = 0;
                mbar_wait_cluster(bars + 8 * B_ADONE, 0);
                load_b(1); load_b(2);
                auto load_c = [&](int i) {
                    const int s = i % 6, kb = c_kblock(i, r);
                    const uint32_t bar = bars + 8 * (B_CF + s), da = sb + c_stage_a(s, ntB), db = sb + c_stage_b(s, ntB);
                    mbar_expect(bar, 32768);
                    tma2d(db, &tm_d, ntA * 128, kb * 64, bar);
                    tma2d(db + 8192, &tm_d, ntA * 128 + 64, kb * 64, bar);
                    bulk_g2s(da, g_g + (size_t)(mb * 28 + kb) * 8192, 16384, bar);
                };
                for (int it = 3; it < 16; it++) {
                    mbar_wait_cluster(bars + 8 * (B_BE + it % 3), (it / 3 - 1) & 1);
                    load_b(it);
                    if (it == 12) { poll_count(&g_cnt2[mb], 8); load_c(0); }
                    if (it == 14) load_c(1);
                }
                mbar_wait_cluster(bars + 8 * (B_BE + 1), 0);
                load_c(2);
                mbar_wait(bars + 8 * B_BDONE, 0);
                for (int i = 3; i < 14; i++) {
                    if (i >= 6) mbar_wait(bars + 8 * (B_CE + i % 6), ((i / 6) - 1) & 1);
                    if (i == 6) { poll_count(&g_cnt2[16 + mb], 8); }
                    load_c(i);
                }
            }
            else asm volatile("barrier.cluster.wait.acquire;" ::: "memory");
        } else if (warp == 1) {
            asm volatile("barrier.cluster.wait.acquire.aligned;" ::: "memory");
            bar_sync(5, 288);
            if (lane == 0) { red_release(&g_cnt2[32 + (mb * 8 + nt)]); }
            __syncwarp();
            bar_sync(6, 288);
            if (lane == 0) red_release(&g_cnt2[32 + (mb * 8 + nt)]);
            __syncwarp();
            bar_sync(1, 288);
            if (lane == 0) red_release(&g_cnt2[mbB]);
            __syncwarp();
            bar_sync(2, 288);
            if (lane == 0) {
                red_release(&g_cnt2[16 + mbB]);
                mbar_arrive(bars + 8 * B_BDONE);
            }
            __syncwarp();
            bar_sync(3, 288);
            if (lane == 0) {
                tma2d_store(&tm_out, sb, nt * 64, mb * 128);
                bulk_commit();
                bulk_wait_all();
            }
        } else {
            asm volatile("barrier.cluster.wait.acquire.aligned;" ::: "memory");
            pdl_wait();
            float2* s_rs = (float2*)(smem + F_RS);
            float* s_cs = (float*)(smem + F_CS);
            for (int c = tid - 64; c < 448; c += 64)
                s_cs[c] = __ldcg(&g_cs2[(c >= 224 ? FF - 224 : 0) + ntB * 224 + c]);
            if (tid == 96) {
                mbar_wait_cluster(bars + 8 * B_ADONE, 0);
                for (int i = 0; i < 8; i++) {
                    const int kb = (ntB + i) & 7;
                    const uint32_t bar = bars + 8 * (i < 4 ? B_HF + i : B_FA + i - 4);
                    poll_count(&g_cnt2[32 + (mbB * 8 + kb)], 1);
                    mbar_expect(bar, 16384);
                    bulk_g2s(sb + kb * 16384, g_h + (size_t)(mbB * 8 + kb) * 8192, 16384, bar);
                }
            }
            __syncwarp();
            for (int i = 0; i < 8; i++) mbar_wait(bars + 8 * (i < 4 ? B_HF + i : B_FA + i - 4), i < 4 ? 0 : 1);
            if (lane < 8) poll_count(&g_cnt2[32 + (mbB * 8 + lane)], 2);
            __syncwarp();
            for (int rr = tid - 64; rr < 128; rr += 64) {
                s_rs[rr] = h_row_stats(mbB * 128 + rr);
            }
            __syncwarp();
            if (lane == 0) mbar_arrive(bars + 8 * B_AUX);
        }
    } else {
        asm volatile("setmaxnreg.inc.sync.aligned.u32 216;");
        const int wgi = (warp >> 2) - 1, ww = warp & 3, ctid = tid - 128;
        const int g = lane >> 2, t = lane & 3;
        const int rl = wgi * 64 + ww * 16 + g, row = mb * 128 + rl;
        const int rgl = wgi * 8 + ww * 2;
        const float2* s_rs = (const float2*)(smem + F_RS);
        const float* s_cs = (const float*)(smem + F_CS);
        uint32_t* hp = (uint32_t*)g_h + ((size_t)(mb * 8 + nt) * 8 * 16 + rgl) * 32 + lane;
        const uint32_t rbars = mapa(bars, 1 - r);
        {
            uint32_t xr[16];
            const uint32_t* xp = (const uint32_t*)(x + (size_t)row * DM + nt * 64) + t;
#pragma unroll
            for (int j = 0; j < 8; j++) { xr[2 * j] = __ldg(xp + 4 * j); xr[2 * j + 1] = __ldg(xp + 8 * (DM / 2) + 4 * j); }
            float acc[32];
#pragma unroll 1
            for (int i = 0; i < 8; i++) {
                if (!(i & 1)) { mbar_wait(bars + 8 * (B_FA + (i >> 1)), 0); }
                uint64_t ad = make_desc(sb + i * 16384 + wgi * 1024, 2048, 128, 0);
                uint64_t bd = make_desc(sb + F_R2 + 32768 + i * 8192, 8192, 1024, 1);
                WG_FENCE();
#pragma unroll
                for (int k = 0; k < 4; k++) wgmma_ss_n64(acc, ad + k * 256, bd + k * 128, (i | k) != 0);
                WG_COMMIT();
            }
            wg_wait<0>();
            fence_regs(acc);
            asm volatile("barrier.cluster.wait.acquire.aligned;" ::: "memory");
            bar_sync(4, 256);
            if (tid == 128) { mbar_arrive(bars + 8 * B_ADONE); mbar_arrive_remote(mapa(bars + 8 * B_ADONE, 1 - r)); }
            float v0[16], v1[16];
            float s0 = 0.f, s1 = 0.f;
#pragma unroll
            for (int j2 = 0; j2 < 4; j2++) {
                uint32_t u[4];
#pragma unroll
                for (int jj = 0; jj < 2; jj++) {
                    const int j = 2 * j2 + jj;
                    u[2 * jj] = pack_bf16(bf_lo(xr[2 * j]) + acc[4 * j], bf_hi(xr[2 * j]) + acc[4 * j + 1]);
                    u[2 * jj + 1] = pack_bf16(bf_lo(xr[2 * j + 1]) + acc[4 * j + 2], bf_hi(xr[2 * j + 1]) + acc[4 * j + 3]);
                    v0[2 * j] = bf_lo(u[2 * jj]); v0[2 * j + 1] = bf_hi(u[2 * jj]);
                    v1[2 * j] = bf_lo(u[2 * jj + 1]); v1[2 * j + 1] = bf_hi(u[2 * jj + 1]);
                    s0 += v0[2 * j] + v0[2 * j + 1];
                    s1 += v1[2 * j] + v1[2 * j + 1];
                }
                hp[j2 * 1024] = u[0]; hp[j2 * 1024 + 32] = u[1]; hp[j2 * 1024 + 512] = u[2]; hp[j2 * 1024 + 544] = u[3];
            }
            bar_arrive(5, 288);
            float m0 = s0 * (1.0f / 16), m1 = s1 * (1.0f / 16), q0 = 0.f, q1 = 0.f;
#pragma unroll
            for (int i = 0; i < 16; i++) {
                float d0 = v0[i] - m0, d1 = v1[i] - m1;
                q0 = fmaf(d0, d0, q0); q1 = fmaf(d1, d1, q1);
            }
#pragma unroll
            for (int st = 0; st < 2; st++) {
                float hn = st ? 16.f : 8.f;
                float om0 = __shfl_xor_sync(0xffffffffu, m0, 1 << st), oq0 = __shfl_xor_sync(0xffffffffu, q0, 1 << st);
                float om1 = __shfl_xor_sync(0xffffffffu, m1, 1 << st), oq1 = __shfl_xor_sync(0xffffffffu, q1, 1 << st);
                float d0 = om0 - m0, d1 = om1 - m1;
                q0 = q0 + oq0 + d0 * d0 * hn; q1 = q1 + oq1 + d1 * d1 * hn;
                m0 = 0.5f * (m0 + om0); m1 = 0.5f * (m1 + om1);
            }
            if (t == 0) {
                g_hstat[row * 8 + nt] = make_float2(m0, q0);
                g_hstat[(row + 8) * 8 + nt] = make_float2(m1, q1);
            }
            bar_arrive(6, 288);
        }
        uint32_t* gp = (uint32_t*)g_g + (((size_t)mbB * 224 + ntB * 28) * 16 + rgl) * 32 + lane;
        {
            float ag[128];
#pragma unroll 1
            for (int kb = 0; kb < 8; kb++) {
                const int s = kb % 3;
                mbar_wait(bars + 8 * (kb < 4 ? B_HF + kb : B_FA + kb - 4), kb < 4 ? 0 : 1);
                mbar_wait(bars + 8 * (B_BF + s), (kb / 3) & 1);
                uint64_t ad = make_desc(sb + ((ntB + kb) & 7) * 16384 + wgi * 1024, 2048, 128, 0);
                uint64_t bd = make_desc(sb + F_R2 + s * 32768, 4096, 512, 2);
                WG_FENCE();
#pragma unroll
                for (int k = 0; k < 4; k++) wgmma_ss_n256(ag, ad + k * 256, bd + k * 64, (kb | k) != 0);
                WG_COMMIT();
                if (kb > 0) {
                    wg_wait<1>();
                    if (lane == 0) { mbar_arrive(bars + 8 * (B_BE + (kb - 1) % 3)); mbar_arrive_remote(rbars + 8 * (B_BE + (kb - 1) % 3)); }
                }
            }
            wg_wait<0>();
            if (lane == 0) { mbar_arrive(bars + 8 * (B_BE + 7 % 3)); mbar_arrive_remote(rbars + 8 * (B_BE + 7 % 3)); }
            fence_regs(ag);
            mbar_wait(bars + 8 * B_AUX, 0);
            ffn_epilogue<16>(ag, ag + 64, s_cs, 0, gp, s_rs[rl], s_rs[rl + 8], lane);
            bar_arrive(1, 288);
        }
        {
            float ag[96];
#pragma unroll 1
            for (int kb = 0; kb < 8; kb++) {
                const int it = 8 + kb, s = it % 3;
                mbar_wait(bars + 8 * (B_BF + s), (it / 3) & 1);
                uint64_t ad = make_desc(sb + ((ntB + kb) & 7) * 16384 + wgi * 1024, 2048, 128, 0);
                uint64_t bd = make_desc(sb + F_R2 + s * 32768, 4096, 512, 2);
                WG_FENCE();
#pragma unroll
                for (int k = 0; k < 4; k++) wgmma_ss_n192(ag, ad + k * 256, bd + k * 64, (kb | k) != 0);
                WG_COMMIT();
                if (kb > 0) {
                    wg_wait<1>();
                    if (lane == 0 && it < 15) { mbar_arrive(bars + 8 * (B_BE + (it - 1) % 3)); mbar_arrive_remote(rbars + 8 * (B_BE + (it - 1) % 3)); }
                }
            }
            wg_wait<0>();
            if (lane == 0) {
                mbar_arrive(bars + 8 * B_BDONE);
                mbar_arrive_remote(rbars + 8 * B_PRDY);
            }
            fence_regs(ag);
            ffn_epilogue<12>(ag, ag + 48, s_cs, 128, gp + 16 * 512, s_rs[rl], s_rs[rl + 8], lane);
            bar_arrive(2, 288);
        }
        {
            uint32_t hr[16];
#pragma unroll
            for (int j = 0; j < 8; j++) { hr[2 * j] = __ldcg(hp + j * 512); hr[2 * j + 1] = __ldcg(hp + j * 512 + 32); }
            mbar_wait(bars + 8 * (B_CF + 0), 0);
            const float a0 = h_row_stats(row).x, a1 = h_row_stats(row + 8).x;
            float acc[64];
#pragma unroll 1
            for (int kb = 0; kb < 14; kb++) {
                const int s = kb % 6;
                mbar_wait(bars + 8 * (B_CF + s), (kb / 6) & 1);
                uint64_t ad = make_desc(sb + c_stage_a(s, ntB) + wgi * 1024, 2048, 128, 0);
                uint64_t bd = make_desc(sb + c_stage_b(s, ntB), 8192, 1024, 1);
                WG_FENCE();
#pragma unroll
                for (int k = 0; k < 4; k++) wgmma_ss_n128(acc, ad + k * 256, bd + k * 128, (kb | k) != 0);
                WG_COMMIT();
                if (kb > 0) {
                    wg_wait<1>();
                    if (lane == 0) mbar_arrive(bars + 8 * (B_CE + (kb - 1) % 6));
                }
            }
            wg_wait<0>();
            fence_regs(acc);
            mbar_wait_cluster(bars + 8 * B_PRDY, 0);
            float o[32];
            if (r == 0) xchg<0>(acc, o, sb, smem, B_XC, ctid); else xchg<1>(acc, o, sb, smem, B_XC, ctid);
            bar_sync(4, 256);
            const float k0 = 0.5f * a0, k1 = 0.5f * a1;
            const int srow = wgi * 64 + ww * 16 + ((lane >> 3) & 1) * 8 + (lane & 7);
#pragma unroll
            for (int j2 = 0; j2 < 4; j2++) {
                uint32_t u[4];
#pragma unroll
                for (int jj = 0; jj < 2; jj++) {
                    const int j = 2 * j2 + jj;
                    u[2 * jj] = pack_bf16(fmaf(k0, o[4 * j], bf_lo(hr[2 * j])), fmaf(k0, o[4 * j + 1], bf_hi(hr[2 * j])));
                    u[2 * jj + 1] = pack_bf16(fmaf(k1, o[4 * j + 2], bf_lo(hr[2 * j + 1])), fmaf(k1, o[4 * j + 3], bf_hi(hr[2 * j + 1])));
                }
                const int chunk = 2 * j2 + (lane >> 4);
                stsm4(sb + srow * 128 + ((chunk ^ (lane & 7)) * 16), u[0], u[1], u[2], u[3]);
            }
            fence_proxy_async();
            bar_arrive(3, 288);
        }
    }
}


static_assert(K1_SMEM <= F_SMEM && AT_SMEM <= F_SMEM && F_SMEM <= 232448, "shared memory budget");

typedef CUresult (*EncodeFn)(CUtensorMap*, CUtensorMapDataType, cuuint32_t, void*, const cuuint64_t*, const cuuint64_t*,
                             const cuuint32_t*, const cuuint32_t*, CUtensorMapInterleave, CUtensorMapSwizzle,
                             CUtensorMapL2promotion, CUtensorMapFloatOOBfill);

void encode(EncodeFn fn, CUtensorMap* m, const void* ptr, int rank, const cuuint64_t* dims, const cuuint64_t* strides,
            const cuuint32_t* box, CUtensorMapSwizzle swz) {
    cuuint32_t es[3] = {1, 1, 1};
    fn(m, CU_TENSOR_MAP_DATA_TYPE_BFLOAT16, rank, (void*)ptr, dims, strides, box, es, CU_TENSOR_MAP_INTERLEAVE_NONE, swz,
       CU_TENSOR_MAP_L2_PROMOTION_L2_256B, CU_TENSOR_MAP_FLOAT_OOB_FILL_NONE);
}

template <typename... KArgs, typename... Args>
void launch(void (*kern)(KArgs...), int grid, int block, int smem, bool pdl, Args... args) {
    cudaLaunchConfig_t cfg = {};
    cfg.gridDim = dim3(grid); cfg.blockDim = dim3(block); cfg.dynamicSmemBytes = smem;
    cfg.stream = cudaStreamPerThread;
    cudaLaunchAttribute at[1];
    at[0].id = cudaLaunchAttributeProgrammaticStreamSerialization;
    at[0].val.programmaticStreamSerializationAllowed = 1;
    cfg.attrs = at; cfg.numAttrs = pdl ? 1 : 0;
    cudaLaunchKernelEx(&cfg, kern, KArgs(args)...);
}

}

extern "C" void kernel_launch(void* const* d_in, const int* in_sizes, int n_in, void* d_out, int out_size) {
    const __nv_bfloat16* x = (const __nv_bfloat16*)d_in[0];
    const __nv_bfloat16* wqkv = (const __nv_bfloat16*)d_in[1];
    const __nv_bfloat16* wo = (const __nv_bfloat16*)d_in[2];
    const __nv_bfloat16* wgate = (const __nv_bfloat16*)d_in[4];
    const __nv_bfloat16* wup = (const __nv_bfloat16*)d_in[5];
    const __nv_bfloat16* wdown = (const __nv_bfloat16*)d_in[6];
    __nv_bfloat16* out = (__nv_bfloat16*)d_out;

    static CUtensorMap tm_x, tm_wqkv, tm_wo, tm_wg, tm_wu, tm_wd, tm_out;
    static const void* cached[7] = {nullptr, nullptr, nullptr, nullptr, nullptr, nullptr, nullptr};
    if (cached[0] != x || cached[1] != wqkv || cached[2] != wo || cached[3] != wgate || cached[4] != wup || cached[5] != wdown || cached[6] != out) {
        void* fp = nullptr;
        cudaDriverEntryPointQueryResult qr;
        cudaGetDriverEntryPoint("cuTensorMapEncodeTiled", &fp, cudaEnableDefault, &qr);
        EncodeFn fn = (EncodeFn)fp;
        { cuuint64_t d[2] = {512, 2048}, s[1] = {1024}; cuuint32_t b[2] = {64, 128};
          encode(fn, &tm_x, x, 2, d, s, b, CU_TENSOR_MAP_SWIZZLE_128B);
          encode(fn, &tm_out, out, 2, d, s, b, CU_TENSOR_MAP_SWIZZLE_128B); }
        { cuuint64_t d[3] = {64, 512, 24}, s[2] = {3072, 128}; cuuint32_t b[3] = {64, 64, 3};
          encode(fn, &tm_wqkv, wqkv, 3, d, s, b, CU_TENSOR_MAP_SWIZZLE_128B); }
        { cuuint64_t d[2] = {512, 512}, s[1] = {1024}; cuuint32_t b[2] = {64, 64};
          encode(fn, &tm_wo, wo, 2, d, s, b, CU_TENSOR_MAP_SWIZZLE_128B); }
        { cuuint64_t d[2] = {1792, 512}, s[1] = {3584}; cuuint32_t b[2] = {32, 64};
          encode(fn, &tm_wg, wgate, 2, d, s, b, CU_TENSOR_MAP_SWIZZLE_64B);
          encode(fn, &tm_wu, wup, 2, d, s, b, CU_TENSOR_MAP_SWIZZLE_64B); }
        { cuuint64_t d[2] = {512, 1792}, s[1] = {1024}; cuuint32_t b[2] = {64, 64};
          encode(fn, &tm_wd, wdown, 2, d, s, b, CU_TENSOR_MAP_SWIZZLE_128B); }
        cudaFuncSetAttribute(qkv_kernel, cudaFuncAttributeMaxDynamicSharedMemorySize, F_SMEM);
        cudaFuncSetAttribute(qkv_kernel, cudaFuncAttributePreferredSharedMemoryCarveout, 100);
        cudaFuncSetAttribute(attn_kernel, cudaFuncAttributeMaxDynamicSharedMemorySize, F_SMEM);
        cudaFuncSetAttribute(attn_kernel, cudaFuncAttributePreferredSharedMemoryCarveout, 100);
        cudaFuncSetAttribute(tail_kernel, cudaFuncAttributeMaxDynamicSharedMemorySize, F_SMEM);
        cudaFuncSetAttribute(tail_kernel, cudaFuncAttributePreferredSharedMemoryCarveout, 100);
        cached[0] = x; cached[1] = wqkv; cached[2] = wo; cached[3] = wgate; cached[4] = wup; cached[5] = wdown; cached[6] = out;
    }
    launch(qkv_kernel, 128, 384, F_SMEM, false, tm_x, tm_wqkv, x, wqkv);
    launch(attn_kernel, 132, 512, F_SMEM, true, wgate, wup, wo, wdown);
    launch(tail_kernel, 128, 384, F_SMEM, true, tm_wo, tm_wg, tm_wu, tm_wd, tm_out, x);
}
```
